```python
import torch

def _softmax(x, axis=-1):
    return torch.softmax(x, dim=axis)
def _gelu(x):
    return torch.nn.functional.gelu(x, approximate="tanh")
def _silu(x):
    return torch.nn.functional.silu(x)
def _sigmoid(x):
    return torch.sigmoid(x)
def _layernorm(x, axis=-1, eps=1e-5):
    m = x.mean(dim=axis, keepdim=True)
    v = x.var(dim=axis, keepdim=True, unbiased=False)
    return (x - m) / torch.sqrt(v + eps)
def _scatter_add(tgt, idx, src, axis=0):
    return tgt.clone().index_add_(axis, idx, src)
def _segment_sum(src, seg, n):
    out = torch.zeros((n,) + src.shape[1:], dtype=src.dtype)
    return out.index_add_(0, seg, src)
def _pad(x, pw):
    flat = tuple(v for pair in reversed(pw) for v in pair)
    return torch.nn.functional.pad(x, flat)

kernel_name = 'recurrent_scan__ssm_conv_s4__geglu_ffn__prompt'

def setup_inputs():

    _w = (lambda a: (lambda t: t.to(torch.bfloat16) if t.is_floating_point() else t)(torch.as_tensor(a)))
    def _A_setup():
        B, L, D, N = 1, 2048, 512, 128
        A_re = -(lambda _x: torch.exp(torch.as_tensor(_x)))((lambda *s: torch.randn(*s, dtype=torch.bfloat16) * 6.4)(D, N))
        A_im = torch.pi * (lambda *s: torch.randn(*s, dtype=torch.bfloat16) * 0.05)(D, N)
        B_re = (lambda *s: torch.randn(*s, dtype=torch.bfloat16) * 0.1)(D, N)
        B_im = (lambda *s: torch.randn(*s, dtype=torch.bfloat16) * 0.1)(D, N)
        C_re = (lambda *s: torch.randn(*s, dtype=torch.bfloat16) * 0.1)(D, N)
        C_im = (lambda *s: torch.randn(*s, dtype=torch.bfloat16) * 0.1)(D, N)
        log_dt = (lambda *s: torch.randn(*s, dtype=torch.bfloat16) * 0.05)(D) * 0.5 - 4.0
        Dskip = (lambda *s: torch.randn(*s, dtype=torch.bfloat16) * 0.05)(D)
        return {
            "u": _w((lambda *s: torch.randn(*s, dtype=torch.bfloat16) * 0.05)(B, L, D)),
            "A_re": _w(A_re),
            "A_im": _w(A_im),
            "B_re": _w(B_re),
            "B_im": _w(B_im),
            "C_re": _w(C_re),
            "C_im": _w(C_im),
            "log_dt": _w(log_dt),
            "Dskip": _w(Dskip),
        }
    _A_in = _A_setup()

    def _B_setup():
        B, S, D, F = 1, 2048, 512, 1792
        return {
            "x": _w((lambda *s: torch.randn(*s, dtype=torch.bfloat16) * 0.05)(B, S, D)),
            "w_gate": _w((lambda *s: torch.randn(*s, dtype=torch.bfloat16) * 0.05)(D, F)),
            "w_up": _w((lambda *s: torch.randn(*s, dtype=torch.bfloat16) * 0.05)(D, F)),
            "w_down": _w((lambda *s: torch.randn(*s, dtype=torch.bfloat16) * 0.05)(F, D)),
        }
    _B_in = _B_setup()

    return {
        "A_u": _A_in["u"],
        "A_A_re": _A_in["A_re"],
        "A_A_im": _A_in["A_im"],
        "A_B_re": _A_in["B_re"],
        "A_B_im": _A_in["B_im"],
        "A_C_re": _A_in["C_re"],
        "A_C_im": _A_in["C_im"],
        "A_log_dt": _A_in["log_dt"],
        "A_Dskip": _A_in["Dskip"],
        "B_x": _B_in["x"],
        "B_w_gate": _B_in["w_gate"],
        "B_w_up": _B_in["w_up"],
        "B_w_down": _B_in["w_down"],
    }

def reference(A_u, A_A_re, A_A_im, A_B_re, A_B_im, A_C_re, A_C_im, A_log_dt, A_Dskip, B_x, B_w_gate, B_w_up, B_w_down):
    def _A_ref(u, A_re, A_im, B_re, B_im, C_re, C_im, log_dt, Dskip):
        Bsz, L, D = u.shape
        dt = torch.exp(log_dt)[:, None]
        A = A_re + 1j * A_im
        Bc = B_re + 1j * B_im
        Cc = C_re + 1j * C_im
        logdA = dt * A
        dB = dt * Bc
        l = (lambda x, dt: x.to(dt))(torch.arange(L), A_re.dtype)
        P = torch.exp(logdA[:, :, None] * l[None, None, :])
        K = torch.einsum("dn,dnl,dn->dl", Cc, P, dB).real
        L2 = 2 * L
        Kp = _pad(K, ((0, 0), (0, L)))
        up = (lambda x, *d: x.permute(*d))(u, 0, 2, 1)
        up = _pad(up, ((0, 0), (0, 0), (0, L)))
        Kf = (lambda x, axes=(-2,-1): torch.fft.rfft2(x.float(), dim=axes))(Kp[:, None, :], axes=(-2, -1))
        Uf = (lambda x, axes=(-2,-1): torch.fft.rfft2(x.float(), dim=axes))(up[:, :, None, :], axes=(-2, -1))
        Yf = Uf * Kf[None, :, :, :]
        y = (lambda x, s, axes=(-2,-1): torch.fft.irfft2(x, s=s, dim=axes).to(torch.bfloat16))(Yf, (1, L2), axes=(-2, -1))[:, :, 0, :L]
        y = (lambda x, *d: x.permute(*d))(y, 0, 2, 1) + u * Dskip[None, None, :]
        return y

    def _B_ref(x, w_gate, w_up, w_down):
        return (_gelu(x @ w_gate) * (x @ w_up)) @ w_down

    x = A_u
    xn = _layernorm(x, axis=-1)
    s = _A_ref(xn, A_A_re, A_A_im, A_B_re, A_B_im, A_C_re, A_C_im, A_log_dt, A_Dskip)
    g = _silu(_B_ref(xn, B_w_gate, B_w_up, B_w_down))
    return x + s * g
```

```cpp
#include <cuda_runtime.h>
#include <cuda_bf16.h>
#include <cuda.h>
#include <stdint.h>

namespace {

constexpr int L_ = 2048, D_ = 512, NS_ = 128, F_ = 1792;

__device__ __align__(1024) __nv_bfloat16 g_xn[L_ * D_];
__device__ __align__(1024) __nv_bfloat16 g_xnT[D_ * L_];
__device__ __align__(1024) __nv_bfloat16 g_sT[D_ * L_];
__device__ __align__(1024) __nv_bfloat16 g_h[L_ * F_];

__device__ __forceinline__ uint32_t smem_u32(const void* p) { return (uint32_t)__cvta_generic_to_shared(p); }
__device__ __forceinline__ void pdl_wait() { asm volatile("griddepcontrol.wait;" ::: "memory"); }
__device__ __forceinline__ void pdl_launch() { asm volatile("griddepcontrol.launch_dependents;" ::: "memory"); }

__device__ __forceinline__ void mbar_init(uint32_t bar, uint32_t cnt) {
    asm volatile("mbarrier.init.shared::cta.b64 [%0], %1;" ::"r"(bar), "r"(cnt) : "memory");
}
__device__ __forceinline__ void mbar_expect_tx(uint32_t bar, uint32_t bytes) {
    asm volatile("mbarrier.arrive.expect_tx.shared::cta.b64 _, [%0], %1;" ::"r"(bar), "r"(bytes) : "memory");
}
__device__ __forceinline__ void mbar_arrive(uint32_t bar) {
    asm volatile("mbarrier.arrive.shared::cta.b64 _, [%0];" ::"r"(bar) : "memory");
}
__device__ __forceinline__ void mbar_wait(uint32_t bar, uint32_t parity) {
    asm volatile(
        "{\n.reg .pred p;\n"
        "WAIT_LOOP:\n"
        "mbarrier.try_wait.parity.shared::cta.b64 p, [%0], %1;\n"
        "@p bra WAIT_DONE;\n"
        "bra WAIT_LOOP;\n"
        "WAIT_DONE:\n}\n" ::"r"(bar), "r"(parity) : "memory");
}
__device__ __forceinline__ void tma_load_2d(uint32_t dst, const CUtensorMap* tm, int c0, int c1, uint32_t bar) {
    asm volatile(
        "cp.async.bulk.tensor.2d.shared::cluster.global.mbarrier::complete_tx::bytes [%0], [%1, {%3, %4}], [%2];"
        ::"r"(dst), "l"((uint64_t)tm), "r"(bar), "r"(c0), "r"(c1) : "memory");
}
__device__ __forceinline__ void prefetch_tmap(const CUtensorMap* tm) {
    asm volatile("prefetch.tensormap [%0];" ::"l"((uint64_t)tm) : "memory");
}
__device__ __forceinline__ uint64_t make_desc(uint32_t addr, uint32_t lbo, uint32_t sbo) {
    uint64_t d = 0;
    d |= (uint64_t)((addr & 0x3FFFF) >> 4);
    d |= (uint64_t)((lbo >> 4) & 0x3FFF) << 16;
    d |= (uint64_t)((sbo >> 4) & 0x3FFF) << 32;
    d |= (uint64_t)1 << 62;
    return d;
}
__device__ __forceinline__ void wgmma_fence() { asm volatile("wgmma.fence.sync.aligned;" ::: "memory"); }
__device__ __forceinline__ void wgmma_commit() { asm volatile("wgmma.commit_group.sync.aligned;" ::: "memory"); }
template <int N> __device__ __forceinline__ void wgmma_wait() {
    asm volatile("wgmma.wait_group.sync.aligned %0;" ::"n"(N) : "memory");
}

#define R8(a, i) "+f"(a[i + 0]), "+f"(a[i + 1]), "+f"(a[i + 2]), "+f"(a[i + 3]), "+f"(a[i + 4]), "+f"(a[i + 5]), "+f"(a[i + 6]), "+f"(a[i + 7])

__device__ __forceinline__ void wgmma_n112(float* a, uint64_t da, uint64_t db, int scale_d) {
    asm volatile(
        "{\n.reg .pred p;\nsetp.ne.b32 p, %58, 0;\n"
        "wgmma.mma_async.sync.aligned.m64n112k16.f32.bf16.bf16 "
        "{%0,%1,%2,%3,%4,%5,%6,%7,%8,%9,%10,%11,%12,%13,%14,%15,%16,%17,%18,%19,%20,%21,%22,%23,%24,%25,%26,%27,"
        "%28,%29,%30,%31,%32,%33,%34,%35,%36,%37,%38,%39,%40,%41,%42,%43,%44,%45,%46,%47,%48,%49,%50,%51,%52,%53,%54,%55},"
        " %56, %57, p, 1, 1, 0, 1;\n}\n"
        : R8(a, 0), R8(a, 8), R8(a, 16), R8(a, 24), R8(a, 32), R8(a, 40), R8(a, 48)
        : "l"(da), "l"(db), "r"(scale_d));
}
__device__ __forceinline__ void wgmma_n64(float* a, uint64_t da, uint64_t db, int scale_d) {
    asm volatile(
        "{\n.reg .pred p;\nsetp.ne.b32 p, %34, 0;\n"
        "wgmma.mma_async.sync.aligned.m64n64k16.f32.bf16.bf16 "
        "{%0,%1,%2,%3,%4,%5,%6,%7,%8,%9,%10,%11,%12,%13,%14,%15,%16,%17,%18,%19,%20,%21,%22,%23,%24,%25,%26,%27,"
        "%28,%29,%30,%31}, %32, %33, p, 1, 1, 0, 1;\n}\n"
        : R8(a, 0), R8(a, 8), R8(a, 16), R8(a, 24)
        : "l"(da), "l"(db), "r"(scale_d));
}

__device__ __forceinline__ float bf16_round(float x) { return __bfloat162float(__float2bfloat16_rn(x)); }
__device__ __forceinline__ uint32_t pack_bf16(float lo, float hi) {
    __nv_bfloat162 v = __floats2bfloat162_rn(lo, hi);
    return *reinterpret_cast<uint32_t*>(&v);
}
__device__ __forceinline__ float bf_lo(uint32_t v) { return __uint_as_float(v << 16); }
__device__ __forceinline__ float bf_hi(uint32_t v) { return __uint_as_float(v & 0xFFFF0000u); }

constexpr int LN_ROWS = 16;
__global__ void __launch_bounds__(256) ln_kernel(const __nv_bfloat16* __restrict__ x,
                                                  const __nv_bfloat16* __restrict__ wg,
                                                  const __nv_bfloat16* __restrict__ wu,
                                                  const __nv_bfloat16* __restrict__ wd) {
    pdl_launch();
    __shared__ __align__(16) __nv_bfloat16 tile[LN_ROWS][D_ + 8];
    const int warp = threadIdx.x >> 5, lane = threadIdx.x & 31;
    const int row0 = blockIdx.x * LN_ROWS;
    {
        const int lines_per = (D_ * F_ * 2) / 128 / 128;
        if (threadIdx.x < lines_per) {
            size_t off = ((size_t)blockIdx.x * lines_per + threadIdx.x) * 128;
            asm volatile("prefetch.global.L2 [%0];" ::"l"((const char*)wg + off));
            asm volatile("prefetch.global.L2 [%0];" ::"l"((const char*)wu + off));
            asm volatile("prefetch.global.L2 [%0];" ::"l"((const char*)wd + off));
        }
    }
    uint4 v[2][2];
#pragma unroll
    for (int r = 0; r < 2; r++) {
        const __nv_bfloat16* xr = x + (size_t)(row0 + warp * 2 + r) * D_;
        v[r][0] = *reinterpret_cast<const uint4*>(xr + lane * 8);
        v[r][1] = *reinterpret_cast<const uint4*>(xr + 256 + lane * 8);
    }
#pragma unroll
    for (int r = 0; r < 2; r++) {
        float f[16];
        const uint32_t* w = reinterpret_cast<const uint32_t*>(&v[r][0]);
#pragma unroll
        for (int i = 0; i < 8; i++) { f[2 * i] = bf_lo(w[i]); f[2 * i + 1] = bf_hi(w[i]); }
        float s = 0.f;
#pragma unroll
        for (int i = 0; i < 16; i++) s += f[i];
#pragma unroll
        for (int o = 16; o > 0; o >>= 1) s += __shfl_xor_sync(0xffffffffu, s, o);
        const float mean = s * (1.0f / D_);
        float q = 0.f;
#pragma unroll
        for (int i = 0; i < 16; i++) { float d = f[i] - mean; q += d * d; }
#pragma unroll
        for (int o = 16; o > 0; o >>= 1) q += __shfl_xor_sync(0xffffffffu, q, o);
        const float mb = bf16_round(mean);
        const float vb = bf16_round(q * (1.0f / D_));
        const float den = bf16_round(sqrtf(bf16_round(vb + 1e-5f)));
        uint32_t o[8];
#pragma unroll
        for (int i = 0; i < 8; i++) {
            float a = __fdiv_rn(bf16_round(f[2 * i] - mb), den);
            float b = __fdiv_rn(bf16_round(f[2 * i + 1] - mb), den);
            o[i] = pack_bf16(a, b);
        }
        const int rr = warp * 2 + r;
        __nv_bfloat16* dst = g_xn + (size_t)(row0 + rr) * D_;
        *reinterpret_cast<uint4*>(dst + lane * 8) = make_uint4(o[0], o[1], o[2], o[3]);
        *reinterpret_cast<uint4*>(dst + 256 + lane * 8) = make_uint4(o[4], o[5], o[6], o[7]);
        *reinterpret_cast<uint4*>(&tile[rr][lane * 8]) = make_uint4(o[0], o[1], o[2], o[3]);
        *reinterpret_cast<uint4*>(&tile[rr][256 + lane * 8]) = make_uint4(o[4], o[5], o[6], o[7]);
    }
    __syncthreads();
#pragma unroll
    for (int cc = 0; cc < 2; cc++) {
        const int c = threadIdx.x + cc * 256;
        uint32_t o[8];
#pragma unroll
        for (int i = 0; i < 8; i++) {
            uint32_t lo = *reinterpret_cast<const uint16_t*>(&tile[2 * i][c]);
            uint32_t hi = *reinterpret_cast<const uint16_t*>(&tile[2 * i + 1][c]);
            o[i] = lo | (hi << 16);
        }
        __nv_bfloat16* dst = g_xnT + (size_t)c * L_ + row0;
        *reinterpret_cast<uint4*>(dst) = make_uint4(o[0], o[1], o[2], o[3]);
        *reinterpret_cast<uint4*>(dst + 8) = make_uint4(o[4], o[5], o[6], o[7]);
    }
}

struct cplx { float r, i; };
__device__ __forceinline__ cplx cmul(cplx a, cplx b) {
    cplx c; c.r = a.r * b.r - a.i * b.i; c.i = a.r * b.i + a.i * b.r; return c;
}
__device__ __forceinline__ cplx csq(cplx a) {
    cplx c; c.r = a.r * a.r - a.i * a.i; c.i = 2.0f * a.r * a.i; return c;
}
__device__ __forceinline__ cplx cexp_m(float ar, float ai, float m) {
    float mag;
    float e = (ar * m) * 1.4426950408889634f;
    asm("ex2.approx.ftz.f32 %0, %1;" : "=f"(mag) : "f"(e));
    float rr = (ai * m) * 0.15915494309189535f;
    rr -= rintf(rr);
    float th = rr * 6.283185307179586f;
    cplx c; c.r = mag * __cosf(th); c.i = mag * __sinf(th);
    return c;
}
__device__ __forceinline__ uint32_t to_tf32(float x) {
    uint32_t r; asm("cvt.rna.tf32.f32 %0, %1;" : "=r"(r) : "f"(x)); return r;
}
__device__ __forceinline__ void mma_tf32(float* c, uint32_t a0, uint32_t a1, uint32_t a2, uint32_t a3, uint32_t b0, uint32_t b1) {
    asm volatile("mma.sync.aligned.m16n8k8.row.col.f32.tf32.tf32.f32 {%0,%1,%2,%3}, {%4,%5,%6,%7}, {%8,%9}, {%0,%1,%2,%3};"
                 : "+f"(c[0]), "+f"(c[1]), "+f"(c[2]), "+f"(c[3])
                 : "r"(a0), "r"(a1), "r"(a2), "r"(a3), "r"(b0), "r"(b1));
}
__device__ __forceinline__ void mma_bf16(float* c, uint32_t a0, uint32_t a1, uint32_t a2, uint32_t a3, uint32_t b0, uint32_t b1) {
    asm volatile("mma.sync.aligned.m16n8k16.row.col.f32.bf16.bf16.f32 {%0,%1,%2,%3}, {%4,%5,%6,%7}, {%8,%9}, {%0,%1,%2,%3};"
                 : "+f"(c[0]), "+f"(c[1]), "+f"(c[2]), "+f"(c[3])
                 : "r"(a0), "r"(a1), "r"(a2), "r"(a3), "r"(b0), "r"(b1));
}
__device__ __forceinline__ void named_bar(int id, int n) { asm volatile("bar.sync %0, %1;" ::"r"(id), "r"(n) : "memory"); }

constexpr int CV_CH = 4;
constexpr int CV_CONST_B = NS_ * 12 * 4;
constexpr int CV_KV_B = 648 * 4;
constexpr int CV_Q_B = (L_ + 16) * 4;
constexpr int CV_U_B = (L_ + 128) * 2;
constexpr int CV_PER_CH = CV_CONST_B + 2 * CV_KV_B + CV_Q_B + CV_U_B;
constexpr int CV_SMEM = CV_CH * CV_PER_CH;

__global__ void __launch_bounds__(256) conv_kernel(const __nv_bfloat16* __restrict__ A_re, const __nv_bfloat16* __restrict__ A_im,
                                                    const __nv_bfloat16* __restrict__ B_re, const __nv_bfloat16* __restrict__ B_im,
                                                    const __nv_bfloat16* __restrict__ C_re, const __nv_bfloat16* __restrict__ C_im,
                                                    const __nv_bfloat16* __restrict__ log_dt, const __nv_bfloat16* __restrict__ Dskip) {
    pdl_launch();
    extern __shared__ __align__(16) uint8_t smem[];
    const int warp = threadIdx.x >> 5, lane = threadIdx.x & 31;
    const int ch = warp >> 1, h = warp & 1;
    const int d = blockIdx.x * CV_CH + ch;
    const int g = lane >> 2, t = lane & 3;
    uint8_t* base = smem + ch * CV_PER_CH;
    float4* s_const = reinterpret_cast<float4*>(base);
    float* s_kv = reinterpret_cast<float*>(base + CV_CONST_B);
    uint32_t* s_q = reinterpret_cast<uint32_t*>(base + CV_CONST_B + 2 * CV_KV_B);
    __nv_bfloat16* s_u = reinterpret_cast<__nv_bfloat16*>(base + CV_CONST_B + 2 * CV_KV_B + CV_Q_B);
    const int bar_id = 1 + ch;

    const float dt = bf16_round(expf(__bfloat162float(log_dt[d])));
    float tail = 0.f;
    {
        const int n0 = h * 64 + lane * 2;
        const size_t off = (size_t)d * NS_ + n0;
        uint32_t war = *reinterpret_cast<const uint32_t*>(A_re + off);
        uint32_t wai = *reinterpret_cast<const uint32_t*>(A_im + off);
        uint32_t wbr = *reinterpret_cast<const uint32_t*>(B_re + off);
        uint32_t wbi = *reinterpret_cast<const uint32_t*>(B_im + off);
        uint32_t wcr = *reinterpret_cast<const uint32_t*>(C_re + off);
        uint32_t wci = *reinterpret_cast<const uint32_t*>(C_im + off);
#pragma unroll
        for (int j = 0; j < 2; j++) {
            float ar = dt * (j ? bf_hi(war) : bf_lo(war));
            float ai = dt * (j ? bf_hi(wai) : bf_lo(wai));
            cplx db = {dt * (j ? bf_hi(wbr) : bf_lo(wbr)), dt * (j ? bf_hi(wbi) : bf_lo(wbi))};
            cplx cc = {(j ? bf_hi(wcr) : bf_lo(wcr)), (j ? bf_hi(wci) : bf_lo(wci))};
            cplx cb = cmul(cc, db);
            cplx e128 = cexp_m(ar, ai, 128.f);
            cplx c256 = cmul(cb, cexp_m(ar, ai, 256.f));
            cplx c512 = cmul(cb, cexp_m(ar, ai, 512.f));
            cplx c1024 = cmul(cb, cexp_m(ar, ai, 1024.f));
            cplx c2048 = cmul(cb, cexp_m(ar, ai, 2048.f));
            tail += c2048.r;
            s_const[(n0 + j) * 3 + 0] = make_float4(ar, ai, cb.r, cb.i);
            s_const[(n0 + j) * 3 + 1] = make_float4(e128.r, e128.i, c256.r, c256.i);
            s_const[(n0 + j) * 3 + 2] = make_float4(c512.r, c512.i, c1024.r, c1024.i);
        }
#pragma unroll
        for (int o = 16; o > 0; o >>= 1) tail += __shfl_xor_sync(0xffffffffu, tail, o);
    }
    __syncwarp();
    {
        float acc[5][4];
#pragma unroll
        for (int i = 0; i < 5; i++) { acc[i][0] = acc[i][1] = acc[i][2] = acc[i][3] = 0.f; }
        const float gf = (float)g;
#pragma unroll 2
        for (int s = 0; s < 16; s++) {
            const int n = h * 64 + s * 4 + t;
            const float4 k0 = s_const[n * 3 + 0], k1 = s_const[n * 3 + 1], k2 = s_const[n * 3 + 2];
            const cplx cb = {k0.z, k0.w}, e128 = {k1.x, k1.y}, c256 = {k1.z, k1.w}, c512 = {k2.x, k2.y}, c1024 = {k2.z, k2.w};
            cplx p1 = cexp_m(k0.x, k0.y, gf);
            cplx p1b = cexp_m(k0.x, k0.y, gf + 8.f);
            cplx r16a = cexp_m(k0.x, k0.y, gf * 16.f);
            cplx r16b = cmul(r16a, e128);
            cplx p2 = csq(p1), p4 = csq(p2), p8 = csq(p4);
            cplx r32a = csq(r16a), r32b = csq(r16b), r64a = csq(r32a), r64b = csq(r32b);
            cplx f0a = cmul(cb, p1), f0b = cmul(cb, p1b), f1 = cmul(c256, p2), f2 = cmul(c512, p4), f3 = cmul(c1024, p8);
            {
                uint32_t a0 = to_tf32(r16a.r), a1 = to_tf32(r16b.r), a2 = to_tf32(-r16a.i), a3 = to_tf32(-r16b.i);
                mma_tf32(acc[0], a0, a1, a2, a3, to_tf32(f0a.r), to_tf32(f0a.i));
                mma_tf32(acc[1], a0, a1, a2, a3, to_tf32(f0b.r), to_tf32(f0b.i));
                mma_tf32(acc[2], a0, a1, a2, a3, to_tf32(f1.r), to_tf32(f1.i));
            }
            mma_tf32(acc[3], to_tf32(r32a.r), to_tf32(r32b.r), to_tf32(-r32a.i), to_tf32(-r32b.i), to_tf32(f2.r), to_tf32(f2.i));
            mma_tf32(acc[4], to_tf32(r64a.r), to_tf32(r64b.r), to_tf32(-r64a.i), to_tf32(-r64b.i), to_tf32(f3.r), to_tf32(f3.i));
        }
        float* kv = s_kv + h * 648;
        *reinterpret_cast<float2*>(kv + 16 * g + 2 * t) = make_float2(acc[0][0], acc[0][1]);
        *reinterpret_cast<float2*>(kv + 16 * (g + 8) + 2 * t) = make_float2(acc[0][2], acc[0][3]);
        *reinterpret_cast<float2*>(kv + 16 * g + 8 + 2 * t) = make_float2(acc[1][0], acc[1][1]);
        *reinterpret_cast<float2*>(kv + 16 * (g + 8) + 8 + 2 * t) = make_float2(acc[1][2], acc[1][3]);
#pragma unroll
        for (int sg = 0; sg < 3; sg++) {
            *reinterpret_cast<float2*>(kv + 256 + 128 * sg + 8 * g + 2 * t) = make_float2(acc[2 + sg][0], acc[2 + sg][1]);
            *reinterpret_cast<float2*>(kv + 256 + 128 * sg + 8 * (g + 8) + 2 * t) = make_float2(acc[2 + sg][2], acc[2 + sg][3]);
        }
        if (lane == 0) kv[640] = tail;
    }
    named_bar(bar_id, 64);
    {
        const int tid2 = h * 32 + lane;
        if (tid2 < 16) s_q[tid2] = 0u;
        for (int x = tid2; x < L_; x += 64) {
            float kc, kp;
            {
                int s = (x >= 1024) ? 3 : (x >= 512) ? 2 : (x >= 256) ? 1 : 0;
                int rq = (s == 0) ? x : ((x + (1 << (s - 1)) - 1 + ((x >> s) & 1)) >> s);
                int idx = 128 * s + rq;
                kc = s_kv[idx] + s_kv[648 + idx];
            }
            {
                int y = x - 1;
                if (y < 0) kp = 0.f;
                else {
                    int s = (y >= 1024) ? 3 : (y >= 512) ? 2 : (y >= 256) ? 1 : 0;
                    int rq = (s == 0) ? y : ((y + (1 << (s - 1)) - 1 + ((y >> s) & 1)) >> s);
                    int idx = 128 * s + rq;
                    kp = s_kv[idx] + s_kv[648 + idx];
                }
            }
            s_q[x + 16] = pack_bf16(kc, kp);
        }
    }
    pdl_wait();
    {
        const int tid2 = h * 32 + lane;
        if (tid2 < 16) *reinterpret_cast<uint4*>(s_u + tid2 * 8) = make_uint4(0, 0, 0, 0);
        const uint4* src = reinterpret_cast<const uint4*>(g_xnT + (size_t)d * L_);
#pragma unroll
        for (int i = 0; i < 4; i++) {
            *reinterpret_cast<uint4*>(s_u + 128 + (tid2 + i * 64) * 8) = src[tid2 + i * 64];
        }
    }
    named_bar(bar_id, 64);
    float acc[16][4];
#pragma unroll
    for (int i = 0; i < 16; i++) { acc[i][0] = acc[i][1] = acc[i][2] = acc[i][3] = 0.f; }
    const uint32_t su_addr = smem_u32(s_u);
    for (int rr = 0; rr < 4; rr++) {
        const int r = h * 4 + rr;
        uint32_t ub[16][2];
        {
            const int mi = lane >> 3, rowi = lane & 7;
            uint32_t addr = su_addr + (uint32_t)((128 + 16 * (8 * (mi >> 1) + rowi - r) + 8 * (mi & 1)) * 2);
#pragma unroll
            for (int j = 0; j < 16; j += 2) {
                asm volatile("ldmatrix.sync.aligned.m8n8.x4.shared.b16 {%0,%1,%2,%3}, [%4];"
                             : "=r"(ub[j][0]), "=r"(ub[j][1]), "=r"(ub[j + 1][0]), "=r"(ub[j + 1][1])
                             : "r"(addr + (uint32_t)(j * 8 * 16 * 2)));
            }
        }
        const uint32_t* qp = s_q + 16 + 16 * r + g - 2 * t;
#pragma unroll
        for (int q = 0; q < 16; q++) {
            const uint32_t a0 = qp[128 * q], a1 = qp[128 * q + 8], a2 = qp[128 * q - 8];
#pragma unroll
            for (int nt = q; nt < 16; nt++) mma_bf16(acc[nt], a0, a1, a2, a0, ub[nt - q][0], ub[nt - q][1]);
        }
    }
    named_bar(bar_id, 64);
    {
        float4* xch = reinterpret_cast<float4*>(base) + h * 256;
#pragma unroll
        for (int i = 0; i < 8; i++) {
            const int nt = (h ? i : 8 + i);
            xch[i * 32 + lane] = make_float4(acc[nt][0], acc[nt][1], acc[nt][2], acc[nt][3]);
        }
    }
    named_bar(bar_id, 64);
    {
        const float4* xch = reinterpret_cast<const float4*>(base) + (h ^ 1) * 256;
        const float dsk = __bfloat162float(Dskip[d]);
        __nv_bfloat16* stg = reinterpret_cast<__nv_bfloat16*>(s_q);
#pragma unroll
        for (int i = 0; i < 8; i++) {
            float4 o = xch[i * 32 + lane];
            float y[4];
            if (h) { y[0] = acc[8 + i][0] + o.x; y[1] = acc[8 + i][1] + o.y; y[2] = acc[8 + i][2] + o.z; y[3] = acc[8 + i][3] + o.w; }
            else   { y[0] = acc[i][0] + o.x; y[1] = acc[i][1] + o.y; y[2] = acc[i][2] + o.z; y[3] = acc[i][3] + o.w; }
            const int nt = h * 8 + i;
#pragma unroll
            for (int e = 0; e < 4; e++) {
                const int tau = 16 * (8 * nt + 2 * t + (e & 1)) + g + 8 * (e >> 1);
                float u = __bfloat162float(s_u[128 + tau]);
                float sv = bf16_round(y[e]) + bf16_round(u * dsk);
                stg[tau] = __float2bfloat16_rn(sv);
            }
        }
        __syncwarp();
        uint4* dst = reinterpret_cast<uint4*>(g_sT + (size_t)d * L_ + h * 1024);
        const uint4* srcp = reinterpret_cast<const uint4*>(stg + h * 1024);
#pragma unroll
        for (int i = 0; i < 4; i++) dst[i * 32 + lane] = srcp[i * 32 + lane];
    }
}

constexpr int G1_STAGES = 3;
constexpr int G1_A_BYTES = 8 * 16384;
constexpr int G1_B_STAGE = 4 * 8192;
constexpr int G1_SMEM = G1_A_BYTES + G1_STAGES * G1_B_STAGE + 1024 + 256;

__device__ __forceinline__ float gelu_tanh(float x) {
    float u = x * (0.7978845608028654f + 0.035677408136300125f * x * x);
    float t; asm("tanh.approx.f32 %0, %1;" : "=f"(t) : "f"(u));
    float hx = 0.5f * x;
    return fmaf(hx, t, hx);
}
__device__ __forceinline__ uint32_t geglu_pair(uint32_t p0, uint32_t p1) {
    float a = bf16_round(gelu_tanh(bf_lo(p0))) * bf_hi(p0);
    float b = bf16_round(gelu_tanh(bf_lo(p1))) * bf_hi(p1);
    return pack_bf16(a, b);
}

__global__ void __launch_bounds__(288, 1) gemm1_kernel(const __grid_constant__ CUtensorMap tm_xn,
                                                        const __grid_constant__ CUtensorMap tm_wg,
                                                        const __grid_constant__ CUtensorMap tm_wu) {
    pdl_launch();
    extern __shared__ uint8_t smem_raw[];
    const uint32_t sbase = (smem_u32(smem_raw) + 1023) & ~1023u;
    const uint32_t sA = sbase, sB = sbase + G1_A_BYTES, sBar = sB + G1_STAGES * G1_B_STAGE;
    const uint32_t bar_a = sBar, bar_full = sBar + 64, bar_empty = sBar + 64 + 8 * G1_STAGES;
    const int rb = blockIdx.x >> 3, cj = blockIdx.x & 7;
    const int warp = threadIdx.x >> 5, lane = threadIdx.x & 31;

    if (threadIdx.x == 0) {
        for (int i = 0; i < 8; i++) mbar_init(bar_a + 8 * i, 1);
        for (int i = 0; i < G1_STAGES; i++) { mbar_init(bar_full + 8 * i, 1); mbar_init(bar_empty + 8 * i, 8); }
        asm volatile("fence.mbarrier_init.release.cluster;" ::: "memory");
    }
    __syncthreads();

    if (warp == 8) {
        if (lane == 0) {
            prefetch_tmap(&tm_xn); prefetch_tmap(&tm_wg); prefetch_tmap(&tm_wu);
            for (int it = 0; it < 16; it++) {
                const int s = it % G1_STAGES, tile = it >> 3, kb = it & 7;
                if (it == G1_STAGES) {
                    pdl_wait();
                    for (int k = 0; k < 8; k++) {
                        mbar_expect_tx(bar_a + 8 * k, 16384);
                        tma_load_2d(sA + k * 16384, &tm_xn, k * 64, rb * 128, bar_a + 8 * k);
                    }
                }
                if (it >= G1_STAGES) mbar_wait(bar_empty + 8 * s, ((it / G1_STAGES) - 1) & 1);
                const int n0 = (cj * 2 + tile) * 112;
                const uint32_t dst = sB + s * G1_B_STAGE;
                mbar_expect_tx(bar_full + 8 * s, G1_B_STAGE);
                tma_load_2d(dst, &tm_wg, n0, kb * 64, bar_full + 8 * s);
                tma_load_2d(dst + 8192, &tm_wg, n0 + 64, kb * 64, bar_full + 8 * s);
                tma_load_2d(dst + 16384, &tm_wu, n0, kb * 64, bar_full + 8 * s);
                tma_load_2d(dst + 24576, &tm_wu, n0 + 64, kb * 64, bar_full + 8 * s);
            }
        }
    } else {
        const int wg = warp >> 2;
        const int g = lane >> 2, t = lane & 3;
        float accg[56], accu[56];
        uint32_t pk[56];
        const int row = rb * 128 + wg * 64 + (warp & 3) * 16 + g;
        __nv_bfloat16* hrow0 = g_h + (size_t)row * F_ + cj * 224 + 2 * t;
        __nv_bfloat16* hrow1 = hrow0 + 8 * F_;
#pragma unroll
        for (int tile = 0; tile < 2; tile++) {
#pragma unroll
            for (int kb = 0; kb < 8; kb++) {
                const int it = tile * 8 + kb, s = it % G1_STAGES;
                if (tile == 0) mbar_wait(bar_a + 8 * kb, 0);
                mbar_wait(bar_full + 8 * s, (it / G1_STAGES) & 1);
                wgmma_fence();
                const uint32_t a_addr = sA + kb * 16384 + wg * 8192;
                const uint32_t b_addr = sB + s * G1_B_STAGE;
#pragma unroll
                for (int k = 0; k < 4; k++) {
                    const uint64_t da = make_desc(a_addr + k * 32, 16, 1024);
                    wgmma_n112(accg, da, make_desc(b_addr + k * 2048, 8192, 1024), (kb | k) != 0);
                    wgmma_n112(accu, da, make_desc(b_addr + 16384 + k * 2048, 8192, 1024), (kb | k) != 0);
                }
                wgmma_commit();
                if (tile == 1 && kb < 7) {
#pragma unroll
                    for (int j = 2 * kb; j < 2 * kb + 2; j++) {
                        *reinterpret_cast<uint32_t*>(hrow0 + 8 * j) = geglu_pair(pk[4 * j], pk[4 * j + 1]);
                        *reinterpret_cast<uint32_t*>(hrow1 + 8 * j) = geglu_pair(pk[4 * j + 2], pk[4 * j + 3]);
                    }
                }
                if (kb > 0) {
                    wgmma_wait<1>();
                    if (lane == 0) mbar_arrive(bar_empty + 8 * ((it - 1) % G1_STAGES));
                }
            }
            wgmma_wait<0>();
            if (lane == 0) mbar_arrive(bar_empty + 8 * ((tile * 8 + 7) % G1_STAGES));
#pragma unroll
            for (int i = 0; i < 56; i++) pk[i] = pack_bf16(accg[i], accu[i]);
        }
#pragma unroll
        for (int j = 0; j < 14; j++) {
            *reinterpret_cast<uint32_t*>(hrow0 + 112 + 8 * j) = geglu_pair(pk[4 * j], pk[4 * j + 1]);
            *reinterpret_cast<uint32_t*>(hrow1 + 112 + 8 * j) = geglu_pair(pk[4 * j + 2], pk[4 * j + 3]);
        }
    }
}

constexpr int G2_STAGES = 8;
constexpr int G2_STAGE = 16384 + 8192;
constexpr int G2_SMEM = G2_STAGES * G2_STAGE + 1024 + 256;
constexpr int G2_KB = F_ / 64;

__global__ void __launch_bounds__(288, 1) gemm2_kernel(const __grid_constant__ CUtensorMap tm_h,
                                                        const __grid_constant__ CUtensorMap tm_wd,
                                                        const __nv_bfloat16* __restrict__ x,
                                                        __nv_bfloat16* __restrict__ out) {
    extern __shared__ uint8_t smem_raw[];
    const uint32_t sbase = (smem_u32(smem_raw) + 1023) & ~1023u;
    const uint32_t sBar = sbase + G2_STAGES * G2_STAGE;
    const uint32_t bar_full = sBar, bar_empty = sBar + 8 * G2_STAGES;
    const int rb = blockIdx.x >> 3, cj = blockIdx.x & 7;
    const int warp = threadIdx.x >> 5, lane = threadIdx.x & 31;

    if (threadIdx.x == 0) {
        for (int i = 0; i < G2_STAGES; i++) { mbar_init(bar_full + 8 * i, 1); mbar_init(bar_empty + 8 * i, 8); }
        asm volatile("fence.mbarrier_init.release.cluster;" ::: "memory");
    }
    __syncthreads();

    if (warp == 8) {
        if (lane == 0) {
            prefetch_tmap(&tm_h); prefetch_tmap(&tm_wd);
            for (int it = 0; it < G2_STAGES; it++) {
                mbar_expect_tx(bar_full + 8 * it, G2_STAGE);
                tma_load_2d(sbase + it * G2_STAGE + 16384, &tm_wd, cj * 64, it * 64, bar_full + 8 * it);
            }
            pdl_wait();
            for (int it = 0; it < G2_STAGES; it++)
                tma_load_2d(sbase + it * G2_STAGE, &tm_h, it * 64, rb * 128, bar_full + 8 * it);
            for (int it = G2_STAGES; it < G2_KB; it++) {
                const int s = it % G2_STAGES;
                mbar_wait(bar_empty + 8 * s, ((it / G2_STAGES) - 1) & 1);
                mbar_expect_tx(bar_full + 8 * s, G2_STAGE);
                tma_load_2d(sbase + s * G2_STAGE, &tm_h, it * 64, rb * 128, bar_full + 8 * s);
                tma_load_2d(sbase + s * G2_STAGE + 16384, &tm_wd, cj * 64, it * 64, bar_full + 8 * s);
            }
        }
    } else {
        const int wg = warp >> 2;
        const int g = lane >> 2, t = lane & 3;
        float acc[32];
        for (int it = 0; it < G2_KB; it++) {
            const int s = it % G2_STAGES;
            mbar_wait(bar_full + 8 * s, (it / G2_STAGES) & 1);
            wgmma_fence();
            const uint32_t a_addr = sbase + s * G2_STAGE + wg * 8192;
            const uint32_t b_addr = sbase + s * G2_STAGE + 16384;
#pragma unroll
            for (int k = 0; k < 4; k++)
                wgmma_n64(acc, make_desc(a_addr + k * 32, 16, 1024), make_desc(b_addr + k * 2048, 8192, 1024), (it | k) != 0);
            wgmma_commit();
            if (it > 0) {
                wgmma_wait<1>();
                if (lane == 0) mbar_arrive(bar_empty + 8 * ((it - 1) % G2_STAGES));
            }
        }
        wgmma_wait<0>();
        pdl_wait();
        const int row = rb * 128 + wg * 64 + (warp & 3) * 16 + g;
#pragma unroll
        for (int j = 0; j < 8; j++) {
            const int col = cj * 64 + 8 * j + 2 * t;
#pragma unroll
            for (int hh = 0; hh < 2; hh++) {
                const int r = row + 8 * hh;
                uint32_t xv = *reinterpret_cast<const uint32_t*>(x + (size_t)r * D_ + col);
                float s0 = __bfloat162float(g_sT[(size_t)col * L_ + r]);
                float s1 = __bfloat162float(g_sT[(size_t)(col + 1) * L_ + r]);
                float f0 = bf16_round(acc[4 * j + 2 * hh]), f1 = bf16_round(acc[4 * j + 2 * hh + 1]);
                float g0 = bf16_round(f0 / (1.0f + __expf(-f0)));
                float g1 = bf16_round(f1 / (1.0f + __expf(-f1)));
                float o0 = bf_lo(xv) + bf16_round(s0 * g0);
                float o1 = bf_hi(xv) + bf16_round(s1 * g1);
                *reinterpret_cast<uint32_t*>(out + (size_t)r * D_ + col) = pack_bf16(o0, o1);
            }
        }
    }
}

typedef CUresult (*EncodeFn)(CUtensorMap*, CUtensorMapDataType, cuuint32_t, void*, const cuuint64_t*, const cuuint64_t*,
                             const cuuint32_t*, const cuuint32_t*, CUtensorMapInterleave, CUtensorMapSwizzle,
                             CUtensorMapL2promotion, CUtensorMapFloatOOBfill);

void make_map(EncodeFn fn, CUtensorMap* m, const void* ptr, uint64_t inner, uint64_t outer, uint32_t box_in, uint32_t box_out) {
    cuuint64_t dims[2] = {inner, outer};
    cuuint64_t strides[1] = {inner * 2};
    cuuint32_t box[2] = {box_in, box_out};
    cuuint32_t es[2] = {1, 1};
    fn(m, CU_TENSOR_MAP_DATA_TYPE_BFLOAT16, 2, const_cast<void*>(ptr), dims, strides, box, es, CU_TENSOR_MAP_INTERLEAVE_NONE,
       CU_TENSOR_MAP_SWIZZLE_128B, CU_TENSOR_MAP_L2_PROMOTION_L2_256B, CU_TENSOR_MAP_FLOAT_OOB_FILL_NONE);
}

template <typename... Args>
void launch_pdl(void (*kern)(Args...), int grid, int block, int smem, bool pdl, Args... args) {
    cudaLaunchConfig_t cfg = {};
    cfg.gridDim = dim3(grid); cfg.blockDim = dim3(block); cfg.dynamicSmemBytes = smem; cfg.stream = cudaStreamPerThread;
    cudaLaunchAttribute at[1];
    at[0].id = cudaLaunchAttributeProgrammaticStreamSerialization;
    at[0].val.programmaticStreamSerializationAllowed = 1;
    cfg.attrs = at; cfg.numAttrs = pdl ? 1 : 0;
    cudaLaunchKernelEx(&cfg, kern, args...);
}

}

extern "C" void kernel_launch(void* const* d_in, const int* in_sizes, int n_in, void* d_out, int out_size) {
    const __nv_bfloat16* x = (const __nv_bfloat16*)d_in[0];
    const __nv_bfloat16* A_re = (const __nv_bfloat16*)d_in[1];
    const __nv_bfloat16* A_im = (const __nv_bfloat16*)d_in[2];
    const __nv_bfloat16* B_re = (const __nv_bfloat16*)d_in[3];
    const __nv_bfloat16* B_im = (const __nv_bfloat16*)d_in[4];
    const __nv_bfloat16* C_re = (const __nv_bfloat16*)d_in[5];
    const __nv_bfloat16* C_im = (const __nv_bfloat16*)d_in[6];
    const __nv_bfloat16* log_dt = (const __nv_bfloat16*)d_in[7];
    const __nv_bfloat16* Dskip = (const __nv_bfloat16*)d_in[8];
    const __nv_bfloat16* wg = (const __nv_bfloat16*)d_in[10];
    const __nv_bfloat16* wu = (const __nv_bfloat16*)d_in[11];
    const __nv_bfloat16* wd = (const __nv_bfloat16*)d_in[12];
    __nv_bfloat16* out = (__nv_bfloat16*)d_out;

    static bool init = false;
    static CUtensorMap tm_xn, tm_wg, tm_wu, tm_h, tm_wd;
    static const void* last_ptrs[3] = {nullptr, nullptr, nullptr};
    if (!init || last_ptrs[0] != wg || last_ptrs[1] != wu || last_ptrs[2] != wd) {
        void* fnp = nullptr;
        cudaDriverEntryPointQueryResult qres;
        cudaGetDriverEntryPoint("cuTensorMapEncodeTiled", &fnp, cudaEnableDefault, &qres);
        EncodeFn fn = (EncodeFn)fnp;
        void *p_xn, *p_h;
        cudaGetSymbolAddress(&p_xn, g_xn);
        cudaGetSymbolAddress(&p_h, g_h);
        make_map(fn, &tm_xn, p_xn, D_, L_, 64, 128);
        make_map(fn, &tm_wg, wg, F_, D_, 64, 64);
        make_map(fn, &tm_wu, wu, F_, D_, 64, 64);
        make_map(fn, &tm_h, p_h, F_, L_, 64, 128);
        make_map(fn, &tm_wd, wd, D_, F_, 64, 64);
        cudaFuncSetAttribute(conv_kernel, cudaFuncAttributeMaxDynamicSharedMemorySize, CV_SMEM);
        cudaFuncSetAttribute(gemm1_kernel, cudaFuncAttributeMaxDynamicSharedMemorySize, G1_SMEM);
        cudaFuncSetAttribute(gemm2_kernel, cudaFuncAttributeMaxDynamicSharedMemorySize, G2_SMEM);
        last_ptrs[0] = wg; last_ptrs[1] = wu; last_ptrs[2] = wd;
        init = true;
    }
    launch_pdl(ln_kernel, L_ / LN_ROWS, 256, 0, false, x, wg, wu, wd);
    launch_pdl(conv_kernel, D_ / CV_CH, 256, CV_SMEM, true, A_re, A_im, B_re, B_im, C_re, C_im, log_dt, Dskip);
    launch_pdl(gemm1_kernel, 128, 288, G1_SMEM, true, tm_xn, tm_wg, tm_wu);
    launch_pdl(gemm2_kernel, 128, 288, G2_SMEM, true, tm_h, tm_wd, x, out);
}
```

```cpp
#include <cuda_runtime.h>
#include <cuda_bf16.h>
#include <cuda.h>
#include <stdint.h>

namespace {

constexpr int L_ = 2048, D_ = 512, NS_ = 128, F_ = 1792;

__device__ __align__(1024) __nv_bfloat16 g_xn[L_ * D_];
__device__ __align__(1024) __nv_bfloat16 g_xnT[D_ * L_];
__device__ __align__(1024) __nv_bfloat16 g_sT[D_ * L_];
__device__ __align__(1024) __nv_bfloat16 g_h[L_ * F_];

__device__ __forceinline__ uint32_t smem_u32(const void* p) { return (uint32_t)__cvta_generic_to_shared(p); }
__device__ __forceinline__ void pdl_wait() { asm volatile("griddepcontrol.wait;" ::: "memory"); }
__device__ __forceinline__ void pdl_launch() { asm volatile("griddepcontrol.launch_dependents;" ::: "memory"); }

__device__ __forceinline__ void mbar_init(uint32_t bar, uint32_t cnt) {
    asm volatile("mbarrier.init.shared::cta.b64 [%0], %1;" ::"r"(bar), "r"(cnt) : "memory");
}
__device__ __forceinline__ void mbar_expect_tx(uint32_t bar, uint32_t bytes) {
    asm volatile("mbarrier.arrive.expect_tx.shared::cta.b64 _, [%0], %1;" ::"r"(bar), "r"(bytes) : "memory");
}
__device__ __forceinline__ void mbar_arrive(uint32_t bar) {
    asm volatile("mbarrier.arrive.shared::cta.b64 _, [%0];" ::"r"(bar) : "memory");
}
__device__ __forceinline__ void mbar_wait(uint32_t bar, uint32_t parity) {
    asm volatile(
        "{\n.reg .pred p;\n"
        "WAIT_LOOP:\n"
        "mbarrier.try_wait.parity.shared::cta.b64 p, [%0], %1;\n"
        "@p bra WAIT_DONE;\n"
        "bra WAIT_LOOP;\n"
        "WAIT_DONE:\n}\n" ::"r"(bar), "r"(parity) : "memory");
}
__device__ __forceinline__ void tma_load_2d(uint32_t dst, const CUtensorMap* tm, int c0, int c1, uint32_t bar) {
    asm volatile(
        "cp.async.bulk.tensor.2d.shared::cluster.global.mbarrier::complete_tx::bytes [%0], [%1, {%3, %4}], [%2];"
        ::"r"(dst), "l"((uint64_t)tm), "r"(bar), "r"(c0), "r"(c1) : "memory");
}
__device__ __forceinline__ void prefetch_tmap(const CUtensorMap* tm) {
    asm volatile("prefetch.tensormap [%0];" ::"l"((uint64_t)tm) : "memory");
}
__device__ __forceinline__ uint64_t make_desc(uint32_t addr, uint32_t lbo, uint32_t sbo) {
    uint64_t d = 0;
    d |= (uint64_t)((addr & 0x3FFFF) >> 4);
    d |= (uint64_t)((lbo >> 4) & 0x3FFF) << 16;
    d |= (uint64_t)((sbo >> 4) & 0x3FFF) << 32;
    d |= (uint64_t)1 << 62;
    return d;
}
__device__ __forceinline__ void wgmma_fence() { asm volatile("wgmma.fence.sync.aligned;" ::: "memory"); }
__device__ __forceinline__ void wgmma_commit() { asm volatile("wgmma.commit_group.sync.aligned;" ::: "memory"); }
template <int N> __device__ __forceinline__ void wgmma_wait() {
    asm volatile("wgmma.wait_group.sync.aligned %0;" ::"n"(N) : "memory");
}

#define R8(a, i) "+f"(a[i + 0]), "+f"(a[i + 1]), "+f"(a[i + 2]), "+f"(a[i + 3]), "+f"(a[i + 4]), "+f"(a[i + 5]), "+f"(a[i + 6]), "+f"(a[i + 7])

__device__ __forceinline__ void wgmma_n112(float* a, uint64_t da, uint64_t db, int scale_d) {
    asm volatile(
        "{\n.reg .pred p;\nsetp.ne.b32 p, %58, 0;\n"
        "wgmma.mma_async.sync.aligned.m64n112k16.f32.bf16.bf16 "
        "{%0,%1,%2,%3,%4,%5,%6,%7,%8,%9,%10,%11,%12,%13,%14,%15,%16,%17,%18,%19,%20,%21,%22,%23,%24,%25,%26,%27,"
        "%28,%29,%30,%31,%32,%33,%34,%35,%36,%37,%38,%39,%40,%41,%42,%43,%44,%45,%46,%47,%48,%49,%50,%51,%52,%53,%54,%55},"
        " %56, %57, p, 1, 1, 0, 1;\n}\n"
        : R8(a, 0), R8(a, 8), R8(a, 16), R8(a, 24), R8(a, 32), R8(a, 40), R8(a, 48)
        : "l"(da), "l"(db), "r"(scale_d));
}
__device__ __forceinline__ void wgmma_n64(float* a, uint64_t da, uint64_t db, int scale_d) {
    asm volatile(
        "{\n.reg .pred p;\nsetp.ne.b32 p, %34, 0;\n"
        "wgmma.mma_async.sync.aligned.m64n64k16.f32.bf16.bf16 "
        "{%0,%1,%2,%3,%4,%5,%6,%7,%8,%9,%10,%11,%12,%13,%14,%15,%16,%17,%18,%19,%20,%21,%22,%23,%24,%25,%26,%27,"
        "%28,%29,%30,%31}, %32, %33, p, 1, 1, 0, 1;\n}\n"
        : R8(a, 0), R8(a, 8), R8(a, 16), R8(a, 24)
        : "l"(da), "l"(db), "r"(scale_d));
}

__device__ __forceinline__ float bf16_round(float x) { return __bfloat162float(__float2bfloat16_rn(x)); }
__device__ __forceinline__ uint32_t pack_bf16(float lo, float hi) {
    __nv_bfloat162 v = __floats2bfloat162_rn(lo, hi);
    return *reinterpret_cast<uint32_t*>(&v);
}
__device__ __forceinline__ float bf_lo(uint32_t v) { return __uint_as_float(v << 16); }
__device__ __forceinline__ float bf_hi(uint32_t v) { return __uint_as_float(v & 0xFFFF0000u); }

constexpr int LN_ROWS = 16;
__global__ void __launch_bounds__(256) ln_kernel(const __nv_bfloat16* __restrict__ x,
                                                  const __nv_bfloat16* __restrict__ wg,
                                                  const __nv_bfloat16* __restrict__ wu,
                                                  const __nv_bfloat16* __restrict__ wd) {
    pdl_launch();
    __shared__ __align__(16) __nv_bfloat16 tile[LN_ROWS][D_ + 8];
    const int warp = threadIdx.x >> 5, lane = threadIdx.x & 31;
    const int row0 = blockIdx.x * LN_ROWS;
    {
        const int lines_per = (D_ * F_ * 2) / 128 / 128;
        if (threadIdx.x < lines_per) {
            size_t off = ((size_t)blockIdx.x * lines_per + threadIdx.x) * 128;
            asm volatile("prefetch.global.L2 [%0];" ::"l"((const char*)wg + off));
            asm volatile("prefetch.global.L2 [%0];" ::"l"((const char*)wu + off));
            asm volatile("prefetch.global.L2 [%0];" ::"l"((const char*)wd + off));
        }
    }
    uint4 v[2][2];
#pragma unroll
    for (int r = 0; r < 2; r++) {
        const __nv_bfloat16* xr = x + (size_t)(row0 + warp * 2 + r) * D_;
        v[r][0] = *reinterpret_cast<const uint4*>(xr + lane * 8);
        v[r][1] = *reinterpret_cast<const uint4*>(xr + 256 + lane * 8);
    }
#pragma unroll
    for (int r = 0; r < 2; r++) {
        float f[16];
        const uint32_t* w = reinterpret_cast<const uint32_t*>(&v[r][0]);
#pragma unroll
        for (int i = 0; i < 8; i++) { f[2 * i] = bf_lo(w[i]); f[2 * i + 1] = bf_hi(w[i]); }
        float s = 0.f;
#pragma unroll
        for (int i = 0; i < 16; i++) s += f[i];
#pragma unroll
        for (int o = 16; o > 0; o >>= 1) s += __shfl_xor_sync(0xffffffffu, s, o);
        const float mean = s * (1.0f / D_);
        float q = 0.f;
#pragma unroll
        for (int i = 0; i < 16; i++) { float d = f[i] - mean; q += d * d; }
#pragma unroll
        for (int o = 16; o > 0; o >>= 1) q += __shfl_xor_sync(0xffffffffu, q, o);
        const float mb = bf16_round(mean);
        const float vb = bf16_round(q * (1.0f / D_));
        const float den = bf16_round(sqrtf(bf16_round(vb + 1e-5f)));
        uint32_t o[8];
#pragma unroll
        for (int i = 0; i < 8; i++) {
            float a = __fdiv_rn(bf16_round(f[2 * i] - mb), den);
            float b = __fdiv_rn(bf16_round(f[2 * i + 1] - mb), den);
            o[i] = pack_bf16(a, b);
        }
        const int rr = warp * 2 + r;
        __nv_bfloat16* dst = g_xn + (size_t)(row0 + rr) * D_;
        *reinterpret_cast<uint4*>(dst + lane * 8) = make_uint4(o[0], o[1], o[2], o[3]);
        *reinterpret_cast<uint4*>(dst + 256 + lane * 8) = make_uint4(o[4], o[5], o[6], o[7]);
        *reinterpret_cast<uint4*>(&tile[rr][lane * 8]) = make_uint4(o[0], o[1], o[2], o[3]);
        *reinterpret_cast<uint4*>(&tile[rr][256 + lane * 8]) = make_uint4(o[4], o[5], o[6], o[7]);
    }
    __syncthreads();
#pragma unroll
    for (int cc = 0; cc < 2; cc++) {
        const int c = threadIdx.x + cc * 256;
        uint32_t o[8];
#pragma unroll
        for (int i = 0; i < 8; i++) {
            uint32_t lo = *reinterpret_cast<const uint16_t*>(&tile[2 * i][c]);
            uint32_t hi = *reinterpret_cast<const uint16_t*>(&tile[2 * i + 1][c]);
            o[i] = lo | (hi << 16);
        }
        __nv_bfloat16* dst = g_xnT + (size_t)c * L_ + row0;
        *reinterpret_cast<uint4*>(dst) = make_uint4(o[0], o[1], o[2], o[3]);
        *reinterpret_cast<uint4*>(dst + 8) = make_uint4(o[4], o[5], o[6], o[7]);
    }
}

struct cplx { float r, i; };
__device__ __forceinline__ cplx cmul(cplx a, cplx b) {
    cplx c; c.r = a.r * b.r - a.i * b.i; c.i = a.r * b.i + a.i * b.r; return c;
}
__device__ __forceinline__ cplx csq(cplx a) {
    cplx c; c.r = a.r * a.r - a.i * a.i; c.i = 2.0f * a.r * a.i; return c;
}
__device__ __forceinline__ cplx cexp_m(float ar, float ai, float m) {
    float mag;
    float e = (ar * m) * 1.4426950408889634f;
    asm("ex2.approx.ftz.f32 %0, %1;" : "=f"(mag) : "f"(e));
    float rr = (ai * m) * 0.15915494309189535f;
    rr -= rintf(rr);
    float th = rr * 6.283185307179586f;
    cplx c; c.r = mag * __cosf(th); c.i = mag * __sinf(th);
    return c;
}
__device__ __forceinline__ uint32_t to_tf32(float x) {
    uint32_t r; asm("cvt.rna.tf32.f32 %0, %1;" : "=r"(r) : "f"(x)); return r;
}
__device__ __forceinline__ void mma_tf32(float* c, uint32_t a0, uint32_t a1, uint32_t a2, uint32_t a3, uint32_t b0, uint32_t b1) {
    asm volatile("mma.sync.aligned.m16n8k8.row.col.f32.tf32.tf32.f32 {%0,%1,%2,%3}, {%4,%5,%6,%7}, {%8,%9}, {%0,%1,%2,%3};"
                 : "+f"(c[0]), "+f"(c[1]), "+f"(c[2]), "+f"(c[3])
                 : "r"(a0), "r"(a1), "r"(a2), "r"(a3), "r"(b0), "r"(b1));
}
__device__ __forceinline__ void mma_bf16(float* c, uint32_t a0, uint32_t a1, uint32_t a2, uint32_t a3, uint32_t b0, uint32_t b1) {
    asm volatile("mma.sync.aligned.m16n8k16.row.col.f32.bf16.bf16.f32 {%0,%1,%2,%3}, {%4,%5,%6,%7}, {%8,%9}, {%0,%1,%2,%3};"
                 : "+f"(c[0]), "+f"(c[1]), "+f"(c[2]), "+f"(c[3])
                 : "r"(a0), "r"(a1), "r"(a2), "r"(a3), "r"(b0), "r"(b1));
}
__device__ __forceinline__ void named_bar(int id, int n) { asm volatile("bar.sync %0, %1;" ::"r"(id), "r"(n) : "memory"); }

constexpr int CV_CH = 4;
constexpr int CV_CONST_B = NS_ * 12 * 4;
constexpr int CV_KV_B = 648 * 4;
constexpr int CV_Q_B = (L_ + 16) * 4;
constexpr int CV_U_B = (L_ + 128) * 2;
constexpr int CV_PER_CH = CV_CONST_B + 2 * CV_KV_B + CV_Q_B + CV_U_B;
constexpr int CV_SMEM = CV_CH * CV_PER_CH;

__global__ void __launch_bounds__(256) conv_kernel(const __nv_bfloat16* __restrict__ A_re, const __nv_bfloat16* __restrict__ A_im,
                                                    const __nv_bfloat16* __restrict__ B_re, const __nv_bfloat16* __restrict__ B_im,
                                                    const __nv_bfloat16* __restrict__ C_re, const __nv_bfloat16* __restrict__ C_im,
                                                    const __nv_bfloat16* __restrict__ log_dt, const __nv_bfloat16* __restrict__ Dskip) {
    pdl_launch();
    extern __shared__ __align__(16) uint8_t smem[];
    const int warp = threadIdx.x >> 5, lane = threadIdx.x & 31;
    const int ch = warp >> 1, h = warp & 1;
    const int d = blockIdx.x * CV_CH + ch;
    const int g = lane >> 2, t = lane & 3;
    uint8_t* base = smem + ch * CV_PER_CH;
    float4* s_const = reinterpret_cast<float4*>(base);
    float* s_kv = reinterpret_cast<float*>(base + CV_CONST_B);
    uint32_t* s_q = reinterpret_cast<uint32_t*>(base + CV_CONST_B + 2 * CV_KV_B);
    __nv_bfloat16* s_u = reinterpret_cast<__nv_bfloat16*>(base + CV_CONST_B + 2 * CV_KV_B + CV_Q_B);
    const int bar_id = 1 + ch;

    const float dt = bf16_round(expf(__bfloat162float(log_dt[d])));
    float tail = 0.f;
    {
        const int n0 = h * 64 + lane * 2;
        const size_t off = (size_t)d * NS_ + n0;
        uint32_t war = *reinterpret_cast<const uint32_t*>(A_re + off);
        uint32_t wai = *reinterpret_cast<const uint32_t*>(A_im + off);
        uint32_t wbr = *reinterpret_cast<const uint32_t*>(B_re + off);
        uint32_t wbi = *reinterpret_cast<const uint32_t*>(B_im + off);
        uint32_t wcr = *reinterpret_cast<const uint32_t*>(C_re + off);
        uint32_t wci = *reinterpret_cast<const uint32_t*>(C_im + off);
#pragma unroll
        for (int j = 0; j < 2; j++) {
            float ar = dt * (j ? bf_hi(war) : bf_lo(war));
            float ai = dt * (j ? bf_hi(wai) : bf_lo(wai));
            cplx db = {dt * (j ? bf_hi(wbr) : bf_lo(wbr)), dt * (j ? bf_hi(wbi) : bf_lo(wbi))};
            cplx cc = {(j ? bf_hi(wcr) : bf_lo(wcr)), (j ? bf_hi(wci) : bf_lo(wci))};
            cplx cb = cmul(cc, db);
            cplx e128 = cexp_m(ar, ai, 128.f);
            cplx c256 = cmul(cb, cexp_m(ar, ai, 256.f));
            cplx c512 = cmul(cb, cexp_m(ar, ai, 512.f));
            cplx c1024 = cmul(cb, cexp_m(ar, ai, 1024.f));
            cplx c2048 = cmul(cb, cexp_m(ar, ai, 2048.f));
            tail += c2048.r;
            s_const[(n0 + j) * 3 + 0] = make_float4(ar, ai, cb.r, cb.i);
            s_const[(n0 + j) * 3 + 1] = make_float4(e128.r, e128.i, c256.r, c256.i);
            s_const[(n0 + j) * 3 + 2] = make_float4(c512.r, c512.i, c1024.r, c1024.i);
        }
#pragma unroll
        for (int o = 16; o > 0; o >>= 1) tail += __shfl_xor_sync(0xffffffffu, tail, o);
    }
    __syncwarp();
    {
        float acc[5][4];
#pragma unroll
        for (int i = 0; i < 5; i++) { acc[i][0] = acc[i][1] = acc[i][2] = acc[i][3] = 0.f; }
        const float gf = (float)g;
#pragma unroll 2
        for (int s = 0; s < 16; s++) {
            const int n = h * 64 + s * 4 + t;
            const float4 k0 = s_const[n * 3 + 0], k1 = s_const[n * 3 + 1], k2 = s_const[n * 3 + 2];
            const cplx cb = {k0.z, k0.w}, e128 = {k1.x, k1.y}, c256 = {k1.z, k1.w}, c512 = {k2.x, k2.y}, c1024 = {k2.z, k2.w};
            cplx p1 = cexp_m(k0.x, k0.y, gf);
            cplx p1b = cexp_m(k0.x, k0.y, gf + 8.f);
            cplx r16a = cexp_m(k0.x, k0.y, gf * 16.f);
            cplx r16b = cmul(r16a, e128);
            cplx p2 = csq(p1), p4 = csq(p2), p8 = csq(p4);
            cplx r32a = csq(r16a), r32b = csq(r16b), r64a = csq(r32a), r64b = csq(r32b);
            cplx f0a = cmul(cb, p1), f0b = cmul(cb, p1b), f1 = cmul(c256, p2), f2 = cmul(c512, p4), f3 = cmul(c1024, p8);
            {
                uint32_t a0 = to_tf32(r16a.r), a1 = to_tf32(r16b.r), a2 = to_tf32(-r16a.i), a3 = to_tf32(-r16b.i);
                mma_tf32(acc[0], a0, a1, a2, a3, to_tf32(f0a.r), to_tf32(f0a.i));
                mma_tf32(acc[1], a0, a1, a2, a3, to_tf32(f0b.r), to_tf32(f0b.i));
                mma_tf32(acc[2], a0, a1, a2, a3, to_tf32(f1.r), to_tf32(f1.i));
            }
            mma_tf32(acc[3], to_tf32(r32a.r), to_tf32(r32b.r), to_tf32(-r32a.i), to_tf32(-r32b.i), to_tf32(f2.r), to_tf32(f2.i));
            mma_tf32(acc[4], to_tf32(r64a.r), to_tf32(r64b.r), to_tf32(-r64a.i), to_tf32(-r64b.i), to_tf32(f3.r), to_tf32(f3.i));
        }
        float* kv = s_kv + h * 648;
        *reinterpret_cast<float2*>(kv + 16 * g + 2 * t) = make_float2(acc[0][0], acc[0][1]);
        *reinterpret_cast<float2*>(kv + 16 * (g + 8) + 2 * t) = make_float2(acc[0][2], acc[0][3]);
        *reinterpret_cast<float2*>(kv + 16 * g + 8 + 2 * t) = make_float2(acc[1][0], acc[1][1]);
        *reinterpret_cast<float2*>(kv + 16 * (g + 8) + 8 + 2 * t) = make_float2(acc[1][2], acc[1][3]);
#pragma unroll
        for (int sg = 0; sg < 3; sg++) {
            *reinterpret_cast<float2*>(kv + 256 + 128 * sg + 8 * g + 2 * t) = make_float2(acc[2 + sg][0], acc[2 + sg][1]);
            *reinterpret_cast<float2*>(kv + 256 + 128 * sg + 8 * (g + 8) + 2 * t) = make_float2(acc[2 + sg][2], acc[2 + sg][3]);
        }
        if (lane == 0) kv[640] = tail;
    }
    named_bar(bar_id, 64);
    {
        const int tid2 = h * 32 + lane;
        if (tid2 < 16) s_q[tid2] = 0u;
        for (int x = tid2; x < L_; x += 64) {
            float kc, kp;
            {
                int s = (x >= 1024) ? 3 : (x >= 512) ? 2 : (x >= 256) ? 1 : 0;
                int rq = (s == 0) ? x : ((x + (1 << (s - 1)) - 1 + ((x >> s) & 1)) >> s);
                int idx = 128 * s + rq;
                kc = s_kv[idx] + s_kv[648 + idx];
            }
            {
                int y = x - 1;
                if (y < 0) kp = 0.f;
                else {
                    int s = (y >= 1024) ? 3 : (y >= 512) ? 2 : (y >= 256) ? 1 : 0;
                    int rq = (s == 0) ? y : ((y + (1 << (s - 1)) - 1 + ((y >> s) & 1)) >> s);
                    int idx = 128 * s + rq;
                    kp = s_kv[idx] + s_kv[648 + idx];
                }
            }
            s_q[x + 16] = pack_bf16(kc, kp);
        }
    }
    pdl_wait();
    {
        const int tid2 = h * 32 + lane;
        if (tid2 < 16) *reinterpret_cast<uint4*>(s_u + tid2 * 8) = make_uint4(0, 0, 0, 0);
        const uint4* src = reinterpret_cast<const uint4*>(g_xnT + (size_t)d * L_);
#pragma unroll
        for (int i = 0; i < 4; i++) {
            *reinterpret_cast<uint4*>(s_u + 128 + (tid2 + i * 64) * 8) = src[tid2 + i * 64];
        }
    }
    named_bar(bar_id, 64);
    float acc[16][4];
#pragma unroll
    for (int i = 0; i < 16; i++) { acc[i][0] = acc[i][1] = acc[i][2] = acc[i][3] = 0.f; }
    const uint32_t su_addr = smem_u32(s_u);
    for (int rr = 0; rr < 4; rr++) {
        const int r = h * 4 + rr;
        uint32_t ub[16][2];
        {
            const int mi = lane >> 3, rowi = lane & 7;
            uint32_t addr = su_addr + (uint32_t)((128 + 16 * (8 * (mi >> 1) + rowi - r) + 8 * (mi & 1)) * 2);
#pragma unroll
            for (int j = 0; j < 16; j += 2) {
                asm volatile("ldmatrix.sync.aligned.m8n8.x4.shared.b16 {%0,%1,%2,%3}, [%4];"
                             : "=r"(ub[j][0]), "=r"(ub[j][1]), "=r"(ub[j + 1][0]), "=r"(ub[j + 1][1])
                             : "r"(addr + (uint32_t)(j * 8 * 16 * 2)));
            }
        }
        const uint32_t* qp = s_q + 16 + 16 * r + g - 2 * t;
#pragma unroll
        for (int q = 0; q < 16; q++) {
            const uint32_t a0 = qp[128 * q], a1 = qp[128 * q + 8], a2 = qp[128 * q - 8];
#pragma unroll
            for (int nt = q; nt < 16; nt++) mma_bf16(acc[nt], a0, a1, a2, a0, ub[nt - q][0], ub[nt - q][1]);
        }
    }
    named_bar(bar_id, 64);
    {
        float4* xch = reinterpret_cast<float4*>(base) + h * 256;
        if (h) {
#pragma unroll
            for (int i = 0; i < 8; i++) xch[i * 32 + lane] = make_float4(acc[i][0], acc[i][1], acc[i][2], acc[i][3]);
        } else {
#pragma unroll
            for (int i = 0; i < 8; i++) xch[i * 32 + lane] = make_float4(acc[8 + i][0], acc[8 + i][1], acc[8 + i][2], acc[8 + i][3]);
        }
    }
    named_bar(bar_id, 64);
    {
        const float4* xch = reinterpret_cast<const float4*>(base) + (h ^ 1) * 256;
        const float dsk = __bfloat162float(Dskip[d]);
        __nv_bfloat16* stg = reinterpret_cast<__nv_bfloat16*>(s_q);
#pragma unroll
        for (int i = 0; i < 8; i++) {
            float4 o = xch[i * 32 + lane];
            float y[4];
            if (h) { y[0] = acc[8 + i][0] + o.x; y[1] = acc[8 + i][1] + o.y; y[2] = acc[8 + i][2] + o.z; y[3] = acc[8 + i][3] + o.w; }
            else   { y[0] = acc[i][0] + o.x; y[1] = acc[i][1] + o.y; y[2] = acc[i][2] + o.z; y[3] = acc[i][3] + o.w; }
            const int nt = h * 8 + i;
#pragma unroll
            for (int e = 0; e < 4; e++) {
                const int tau = 16 * (8 * nt + 2 * t + (e & 1)) + g + 8 * (e >> 1);
                float u = __bfloat162float(s_u[128 + tau]);
                float sv = bf16_round(y[e]) + bf16_round(u * dsk);
                stg[tau] = __float2bfloat16_rn(sv);
            }
        }
        __syncwarp();
        uint4* dst = reinterpret_cast<uint4*>(g_sT + (size_t)d * L_ + h * 1024);
        const uint4* srcp = reinterpret_cast<const uint4*>(stg + h * 1024);
#pragma unroll
        for (int i = 0; i < 4; i++) dst[i * 32 + lane] = srcp[i * 32 + lane];
    }
}

constexpr int G1_STAGES = 3;
constexpr int G1_A_BYTES = 8 * 16384;
constexpr int G1_B_STAGE = 4 * 8192;
constexpr int G1_SMEM = G1_A_BYTES + G1_STAGES * G1_B_STAGE + 1024 + 256;

__device__ __forceinline__ float gelu_tanh(float x) {
    float u = x * (0.7978845608028654f + 0.035677408136300125f * x * x);
    float t; asm("tanh.approx.f32 %0, %1;" : "=f"(t) : "f"(u));
    float hx = 0.5f * x;
    return fmaf(hx, t, hx);
}
__device__ __forceinline__ uint32_t geglu_pair(uint32_t p0, uint32_t p1) {
    float a = bf16_round(gelu_tanh(bf_lo(p0))) * bf_hi(p0);
    float b = bf16_round(gelu_tanh(bf_lo(p1))) * bf_hi(p1);
    return pack_bf16(a, b);
}

__global__ void __launch_bounds__(384, 1) gemm1_kernel(const __grid_constant__ CUtensorMap tm_xn,
                                                        const __grid_constant__ CUtensorMap tm_wg,
                                                        const __grid_constant__ CUtensorMap tm_wu) {
    pdl_launch();
    extern __shared__ uint8_t smem_raw[];
    const uint32_t sbase = (smem_u32(smem_raw) + 1023) & ~1023u;
    const uint32_t sA = sbase, sB = sbase + G1_A_BYTES, sBar = sB + G1_STAGES * G1_B_STAGE;
    const uint32_t bar_a = sBar, bar_full = sBar + 64, bar_empty = sBar + 64 + 8 * G1_STAGES;
    const int rb = blockIdx.x >> 3, cj = blockIdx.x & 7;
    const int warp = threadIdx.x >> 5, lane = threadIdx.x & 31;

    if (threadIdx.x == 0) {
        for (int i = 0; i < 8; i++) mbar_init(bar_a + 8 * i, 1);
        for (int i = 0; i < G1_STAGES; i++) { mbar_init(bar_full + 8 * i, 1); mbar_init(bar_empty + 8 * i, 8); }
        asm volatile("fence.mbarrier_init.release.cluster;" ::: "memory");
    }
    __syncthreads();

    if (warp >= 8) {
        asm volatile("setmaxnreg.dec.sync.aligned.u32 40;");
        if (warp == 8 && lane == 0) {
            prefetch_tmap(&tm_xn); prefetch_tmap(&tm_wg); prefetch_tmap(&tm_wu);
            for (int it = 0; it < 16; it++) {
                const int s = it % G1_STAGES, tile = it >> 3, kb = it & 7;
                if (it == G1_STAGES) {
                    pdl_wait();
                    for (int k = 0; k < 8; k++) {
                        mbar_expect_tx(bar_a + 8 * k, 16384);
                        tma_load_2d(sA + k * 16384, &tm_xn, k * 64, rb * 128, bar_a + 8 * k);
                    }
                }
                if (it >= G1_STAGES) mbar_wait(bar_empty + 8 * s, ((it / G1_STAGES) - 1) & 1);
                const int n0 = (cj * 2 + tile) * 112;
                const uint32_t dst = sB + s * G1_B_STAGE;
                mbar_expect_tx(bar_full + 8 * s, G1_B_STAGE);
                tma_load_2d(dst, &tm_wg, n0, kb * 64, bar_full + 8 * s);
                tma_load_2d(dst + 8192, &tm_wg, n0 + 64, kb * 64, bar_full + 8 * s);
                tma_load_2d(dst + 16384, &tm_wu, n0, kb * 64, bar_full + 8 * s);
                tma_load_2d(dst + 24576, &tm_wu, n0 + 64, kb * 64, bar_full + 8 * s);
            }
        }
    } else {
        asm volatile("setmaxnreg.inc.sync.aligned.u32 232;");
        const int wg = warp >> 2;
        const int g = lane >> 2, t = lane & 3;
        float accg[56], accu[56];
        uint32_t pk[56];
        const int row = rb * 128 + wg * 64 + (warp & 3) * 16 + g;
        __nv_bfloat16* hrow0 = g_h + (size_t)row * F_ + cj * 224 + 2 * t;
        __nv_bfloat16* hrow1 = hrow0 + 8 * F_;
#pragma unroll
        for (int tile = 0; tile < 2; tile++) {
#pragma unroll
            for (int kb = 0; kb < 8; kb++) {
                const int it = tile * 8 + kb, s = it % G1_STAGES;
                if (tile == 0) mbar_wait(bar_a + 8 * kb, 0);
                mbar_wait(bar_full + 8 * s, (it / G1_STAGES) & 1);
                wgmma_fence();
                const uint32_t a_addr = sA + kb * 16384 + wg * 8192;
                const uint32_t b_addr = sB + s * G1_B_STAGE;
#pragma unroll
                for (int k = 0; k < 4; k++) {
                    const uint64_t da = make_desc(a_addr + k * 32, 16, 1024);
                    wgmma_n112(accg, da, make_desc(b_addr + k * 2048, 8192, 1024), (kb | k) != 0);
                    wgmma_n112(accu, da, make_desc(b_addr + 16384 + k * 2048, 8192, 1024), (kb | k) != 0);
                }
                wgmma_commit();
                if (tile == 1 && kb < 7) {
#pragma unroll
                    for (int j = 2 * kb; j < 2 * kb + 2; j++) {
                        *reinterpret_cast<uint32_t*>(hrow0 + 8 * j) = geglu_pair(pk[4 * j], pk[4 * j + 1]);
                        *reinterpret_cast<uint32_t*>(hrow1 + 8 * j) = geglu_pair(pk[4 * j + 2], pk[4 * j + 3]);
                    }
                }
                if (kb > 0) {
                    wgmma_wait<1>();
                    if (lane == 0) mbar_arrive(bar_empty + 8 * ((it - 1) % G1_STAGES));
                }
            }
            wgmma_wait<0>();
            if (lane == 0) mbar_arrive(bar_empty + 8 * ((tile * 8 + 7) % G1_STAGES));
#pragma unroll
            for (int i = 0; i < 56; i++) pk[i] = pack_bf16(accg[i], accu[i]);
        }
#pragma unroll
        for (int j = 0; j < 14; j++) {
            *reinterpret_cast<uint32_t*>(hrow0 + 112 + 8 * j) = geglu_pair(pk[4 * j], pk[4 * j + 1]);
            *reinterpret_cast<uint32_t*>(hrow1 + 112 + 8 * j) = geglu_pair(pk[4 * j + 2], pk[4 * j + 3]);
        }
    }
}

constexpr int G2_STAGES = 8;
constexpr int G2_STAGE = 16384 + 8192;
constexpr int G2_SMEM = G2_STAGES * G2_STAGE + 1024 + 256;
constexpr int G2_KB = F_ / 64;

__global__ void __launch_bounds__(288, 1) gemm2_kernel(const __grid_constant__ CUtensorMap tm_h,
                                                        const __grid_constant__ CUtensorMap tm_wd,
                                                        const __nv_bfloat16* __restrict__ x,
                                                        __nv_bfloat16* __restrict__ out) {
    extern __shared__ uint8_t smem_raw[];
    const uint32_t sbase = (smem_u32(smem_raw) + 1023) & ~1023u;
    const uint32_t sBar = sbase + G2_STAGES * G2_STAGE;
    const uint32_t bar_full = sBar, bar_empty = sBar + 8 * G2_STAGES;
    const int rb = blockIdx.x >> 3, cj = blockIdx.x & 7;
    const int warp = threadIdx.x >> 5, lane = threadIdx.x & 31;

    if (threadIdx.x == 0) {
        for (int i = 0; i < G2_STAGES; i++) { mbar_init(bar_full + 8 * i, 1); mbar_init(bar_empty + 8 * i, 8); }
        asm volatile("fence.mbarrier_init.release.cluster;" ::: "memory");
    }
    __syncthreads();

    if (warp == 8) {
        if (lane == 0) {
            prefetch_tmap(&tm_h); prefetch_tmap(&tm_wd);
            for (int it = 0; it < G2_STAGES; it++) {
                mbar_expect_tx(bar_full + 8 * it, G2_STAGE);
                tma_load_2d(sbase + it * G2_STAGE + 16384, &tm_wd, cj * 64, it * 64, bar_full + 8 * it);
            }
            pdl_wait();
            for (int it = 0; it < G2_STAGES; it++)
                tma_load_2d(sbase + it * G2_STAGE, &tm_h, it * 64, rb * 128, bar_full + 8 * it);
            for (int it = G2_STAGES; it < G2_KB; it++) {
                const int s = it % G2_STAGES;
                mbar_wait(bar_empty + 8 * s, ((it / G2_STAGES) - 1) & 1);
                mbar_expect_tx(bar_full + 8 * s, G2_STAGE);
                tma_load_2d(sbase + s * G2_STAGE, &tm_h, it * 64, rb * 128, bar_full + 8 * s);
                tma_load_2d(sbase + s * G2_STAGE + 16384, &tm_wd, cj * 64, it * 64, bar_full + 8 * s);
            }
        }
    } else {
        const int wg = warp >> 2;
        const int g = lane >> 2, t = lane & 3;
        float acc[32];
        for (int it = 0; it < G2_KB; it++) {
            const int s = it % G2_STAGES;
            mbar_wait(bar_full + 8 * s, (it / G2_STAGES) & 1);
            wgmma_fence();
            const uint32_t a_addr = sbase + s * G2_STAGE + wg * 8192;
            const uint32_t b_addr = sbase + s * G2_STAGE + 16384;
#pragma unroll
            for (int k = 0; k < 4; k++)
                wgmma_n64(acc, make_desc(a_addr + k * 32, 16, 1024), make_desc(b_addr + k * 2048, 8192, 1024), (it | k) != 0);
            wgmma_commit();
            if (it > 0) {
                wgmma_wait<1>();
                if (lane == 0) mbar_arrive(bar_empty + 8 * ((it - 1) % G2_STAGES));
            }
        }
        wgmma_wait<0>();
        pdl_wait();
        const int row = rb * 128 + wg * 64 + (warp & 3) * 16 + g;
#pragma unroll
        for (int j = 0; j < 8; j++) {
            const int col = cj * 64 + 8 * j + 2 * t;
#pragma unroll
            for (int hh = 0; hh < 2; hh++) {
                const int r = row + 8 * hh;
                uint32_t xv = *reinterpret_cast<const uint32_t*>(x + (size_t)r * D_ + col);
                float s0 = __bfloat162float(g_sT[(size_t)col * L_ + r]);
                float s1 = __bfloat162float(g_sT[(size_t)(col + 1) * L_ + r]);
                float f0 = bf16_round(acc[4 * j + 2 * hh]), f1 = bf16_round(acc[4 * j + 2 * hh + 1]);
                float g0 = bf16_round(f0 / (1.0f + __expf(-f0)));
                float g1 = bf16_round(f1 / (1.0f + __expf(-f1)));
                float o0 = bf_lo(xv) + bf16_round(s0 * g0);
                float o1 = bf_hi(xv) + bf16_round(s1 * g1);
                *reinterpret_cast<uint32_t*>(out + (size_t)r * D_ + col) = pack_bf16(o0, o1);
            }
        }
    }
}

typedef CUresult (*EncodeFn)(CUtensorMap*, CUtensorMapDataType, cuuint32_t, void*, const cuuint64_t*, const cuuint64_t*,
                             const cuuint32_t*, const cuuint32_t*, CUtensorMapInterleave, CUtensorMapSwizzle,
                             CUtensorMapL2promotion, CUtensorMapFloatOOBfill);

void make_map(EncodeFn fn, CUtensorMap* m, const void* ptr, uint64_t inner, uint64_t outer, uint32_t box_in, uint32_t box_out) {
    cuuint64_t dims[2] = {inner, outer};
    cuuint64_t strides[1] = {inner * 2};
    cuuint32_t box[2] = {box_in, box_out};
    cuuint32_t es[2] = {1, 1};
    fn(m, CU_TENSOR_MAP_DATA_TYPE_BFLOAT16, 2, const_cast<void*>(ptr), dims, strides, box, es, CU_TENSOR_MAP_INTERLEAVE_NONE,
       CU_TENSOR_MAP_SWIZZLE_128B, CU_TENSOR_MAP_L2_PROMOTION_L2_256B, CU_TENSOR_MAP_FLOAT_OOB_FILL_NONE);
}

template <typename... Args>
void launch_pdl(void (*kern)(Args...), int grid, int block, int smem, bool pdl, Args... args) {
    cudaLaunchConfig_t cfg = {};
    cfg.gridDim = dim3(grid); cfg.blockDim = dim3(block); cfg.dynamicSmemBytes = smem; cfg.stream = cudaStreamPerThread;
    cudaLaunchAttribute at[1];
    at[0].id = cudaLaunchAttributeProgrammaticStreamSerialization;
    at[0].val.programmaticStreamSerializationAllowed = 1;
    cfg.attrs = at; cfg.numAttrs = pdl ? 1 : 0;
    cudaLaunchKernelEx(&cfg, kern, args...);
}

}

extern "C" void kernel_launch(void* const* d_in, const int* in_sizes, int n_in, void* d_out, int out_size) {
    const __nv_bfloat16* x = (const __nv_bfloat16*)d_in[0];
    const __nv_bfloat16* A_re = (const __nv_bfloat16*)d_in[1];
    const __nv_bfloat16* A_im = (const __nv_bfloat16*)d_in[2];
    const __nv_bfloat16* B_re = (const __nv_bfloat16*)d_in[3];
    const __nv_bfloat16* B_im = (const __nv_bfloat16*)d_in[4];
    const __nv_bfloat16* C_re = (const __nv_bfloat16*)d_in[5];
    const __nv_bfloat16* C_im = (const __nv_bfloat16*)d_in[6];
    const __nv_bfloat16* log_dt = (const __nv_bfloat16*)d_in[7];
    const __nv_bfloat16* Dskip = (const __nv_bfloat16*)d_in[8];
    const __nv_bfloat16* wg = (const __nv_bfloat16*)d_in[10];
    const __nv_bfloat16* wu = (const __nv_bfloat16*)d_in[11];
    const __nv_bfloat16* wd = (const __nv_bfloat16*)d_in[12];
    __nv_bfloat16* out = (__nv_bfloat16*)d_out;

    static bool init = false;
    static CUtensorMap tm_xn, tm_wg, tm_wu, tm_h, tm_wd;
    static const void* last_ptrs[3] = {nullptr, nullptr, nullptr};
    if (!init || last_ptrs[0] != wg || last_ptrs[1] != wu || last_ptrs[2] != wd) {
        void* fnp = nullptr;
        cudaDriverEntryPointQueryResult qres;
        cudaGetDriverEntryPoint("cuTensorMapEncodeTiled", &fnp, cudaEnableDefault, &qres);
        EncodeFn fn = (EncodeFn)fnp;
        void *p_xn, *p_h;
        cudaGetSymbolAddress(&p_xn, g_xn);
        cudaGetSymbolAddress(&p_h, g_h);
        make_map(fn, &tm_xn, p_xn, D_, L_, 64, 128);
        make_map(fn, &tm_wg, wg, F_, D_, 64, 64);
        make_map(fn, &tm_wu, wu, F_, D_, 64, 64);
        make_map(fn, &tm_h, p_h, F_, L_, 64, 128);
        make_map(fn, &tm_wd, wd, D_, F_, 64, 64);
        cudaFuncSetAttribute(conv_kernel, cudaFuncAttributeMaxDynamicSharedMemorySize, CV_SMEM);
        cudaFuncSetAttribute(gemm1_kernel, cudaFuncAttributeMaxDynamicSharedMemorySize, G1_SMEM);
        cudaFuncSetAttribute(gemm2_kernel, cudaFuncAttributeMaxDynamicSharedMemorySize, G2_SMEM);
        last_ptrs[0] = wg; last_ptrs[1] = wu; last_ptrs[2] = wd;
        init = true;
    }
    launch_pdl(ln_kernel, L_ / LN_ROWS, 256, 0, false, x, wg, wu, wd);
    launch_pdl(conv_kernel, D_ / CV_CH, 256, CV_SMEM, true, A_re, A_im, B_re, B_im, C_re, C_im, log_dt, Dskip);
    launch_pdl(gemm1_kernel, 128, 384, G1_SMEM, true, tm_xn, tm_wg, tm_wu);
    launch_pdl(gemm2_kernel, 128, 288, G2_SMEM, true, tm_h, tm_wd, x, out);
}
```

```cpp
#include <cuda_runtime.h>
#include <cuda_bf16.h>
#include <cuda.h>
#include <stdint.h>

namespace {

constexpr int L_ = 2048, D_ = 512, NS_ = 128, F_ = 1792;

__device__ __align__(1024) __nv_bfloat16 g_xn[L_ * D_];
__device__ __align__(1024) __nv_bfloat16 g_xnT[D_ * L_];
__device__ __align__(1024) __nv_bfloat16 g_sT[D_ * L_];
__device__ __align__(1024) __nv_bfloat16 g_h[L_ * F_];

#define STAMP(k, i)

__device__ __forceinline__ uint32_t smem_u32(const void* p) { return (uint32_t)__cvta_generic_to_shared(p); }
__device__ __forceinline__ void pdl_wait() { asm volatile("griddepcontrol.wait;" ::: "memory"); }
__device__ __forceinline__ void pdl_launch() { asm volatile("griddepcontrol.launch_dependents;" ::: "memory"); }

__device__ __forceinline__ void mbar_init(uint32_t bar, uint32_t cnt) {
    asm volatile("mbarrier.init.shared::cta.b64 [%0], %1;" ::"r"(bar), "r"(cnt) : "memory");
}
__device__ __forceinline__ void mbar_expect_tx(uint32_t bar, uint32_t bytes) {
    asm volatile("mbarrier.arrive.expect_tx.shared::cta.b64 _, [%0], %1;" ::"r"(bar), "r"(bytes) : "memory");
}
__device__ __forceinline__ void mbar_arrive(uint32_t bar) {
    asm volatile("mbarrier.arrive.shared::cta.b64 _, [%0];" ::"r"(bar) : "memory");
}
__device__ __forceinline__ void mbar_wait(uint32_t bar, uint32_t parity) {
    asm volatile(
        "{\n.reg .pred p;\n"
        "WAIT_LOOP:\n"
        "mbarrier.try_wait.parity.shared::cta.b64 p, [%0], %1;\n"
        "@p bra WAIT_DONE;\n"
        "bra WAIT_LOOP;\n"
        "WAIT_DONE:\n}\n" ::"r"(bar), "r"(parity) : "memory");
}
__device__ __forceinline__ void tma_load_2d(uint32_t dst, const CUtensorMap* tm, int c0, int c1, uint32_t bar) {
    asm volatile(
        "cp.async.bulk.tensor.2d.shared::cluster.global.mbarrier::complete_tx::bytes [%0], [%1, {%3, %4}], [%2];"
        ::"r"(dst), "l"((uint64_t)tm), "r"(bar), "r"(c0), "r"(c1) : "memory");
}
__device__ __forceinline__ void prefetch_tmap(const CUtensorMap* tm) {
    asm volatile("prefetch.tensormap [%0];" ::"l"((uint64_t)tm) : "memory");
}
__device__ __forceinline__ uint64_t make_desc(uint32_t addr, uint32_t lbo, uint32_t sbo) {
    uint64_t d = 0;
    d |= (uint64_t)((addr & 0x3FFFF) >> 4);
    d |= (uint64_t)((lbo >> 4) & 0x3FFF) << 16;
    d |= (uint64_t)((sbo >> 4) & 0x3FFF) << 32;
    d |= (uint64_t)1 << 62;
    return d;
}
__device__ __forceinline__ void wgmma_fence() { asm volatile("wgmma.fence.sync.aligned;" ::: "memory"); }
__device__ __forceinline__ void wgmma_commit() { asm volatile("wgmma.commit_group.sync.aligned;" ::: "memory"); }
template <int N> __device__ __forceinline__ void wgmma_wait() {
    asm volatile("wgmma.wait_group.sync.aligned %0;" ::"n"(N) : "memory");
}

#define R8(a, i) "+f"(a[i + 0]), "+f"(a[i + 1]), "+f"(a[i + 2]), "+f"(a[i + 3]), "+f"(a[i + 4]), "+f"(a[i + 5]), "+f"(a[i + 6]), "+f"(a[i + 7])

__device__ __forceinline__ void wgmma_n112(float* a, uint64_t da, uint64_t db, int scale_d) {
    asm volatile(
        "{\n.reg .pred p;\nsetp.ne.b32 p, %58, 0;\n"
        "wgmma.mma_async.sync.aligned.m64n112k16.f32.bf16.bf16 "
        "{%0,%1,%2,%3,%4,%5,%6,%7,%8,%9,%10,%11,%12,%13,%14,%15,%16,%17,%18,%19,%20,%21,%22,%23,%24,%25,%26,%27,"
        "%28,%29,%30,%31,%32,%33,%34,%35,%36,%37,%38,%39,%40,%41,%42,%43,%44,%45,%46,%47,%48,%49,%50,%51,%52,%53,%54,%55},"
        " %56, %57, p, 1, 1, 0, 1;\n}\n"
        : R8(a, 0), R8(a, 8), R8(a, 16), R8(a, 24), R8(a, 32), R8(a, 40), R8(a, 48)
        : "l"(da), "l"(db), "r"(scale_d));
}
__device__ __forceinline__ void wgmma_n64(float* a, uint64_t da, uint64_t db, int scale_d) {
    asm volatile(
        "{\n.reg .pred p;\nsetp.ne.b32 p, %34, 0;\n"
        "wgmma.mma_async.sync.aligned.m64n64k16.f32.bf16.bf16 "
        "{%0,%1,%2,%3,%4,%5,%6,%7,%8,%9,%10,%11,%12,%13,%14,%15,%16,%17,%18,%19,%20,%21,%22,%23,%24,%25,%26,%27,"
        "%28,%29,%30,%31}, %32, %33, p, 1, 1, 0, 1;\n}\n"
        : R8(a, 0), R8(a, 8), R8(a, 16), R8(a, 24)
        : "l"(da), "l"(db), "r"(scale_d));
}

__device__ __forceinline__ float bf16_round(float x) { return __bfloat162float(__float2bfloat16_rn(x)); }
__device__ __forceinline__ uint32_t pack_bf16(float lo, float hi) {
    __nv_bfloat162 v = __floats2bfloat162_rn(lo, hi);
    return *reinterpret_cast<uint32_t*>(&v);
}
__device__ __forceinline__ float bf_lo(uint32_t v) { return __uint_as_float(v << 16); }
__device__ __forceinline__ float bf_hi(uint32_t v) { return __uint_as_float(v & 0xFFFF0000u); }

constexpr int LN_ROWS = 16;
__global__ void __launch_bounds__(256) ln_kernel(const __nv_bfloat16* __restrict__ x,
                                                  const __nv_bfloat16* __restrict__ wg,
                                                  const __nv_bfloat16* __restrict__ wu,
                                                  const __nv_bfloat16* __restrict__ wd) {
    pdl_launch();
    if (threadIdx.x == 0) STAMP(0, 0);
    __shared__ __align__(16) __nv_bfloat16 tile[LN_ROWS][D_ + 8];
    const int warp = threadIdx.x >> 5, lane = threadIdx.x & 31;
    const int row0 = blockIdx.x * LN_ROWS;
    {
        const int lines_per = (D_ * F_ * 2) / 128 / 128;
        if (threadIdx.x < lines_per) {
            size_t off = ((size_t)blockIdx.x * lines_per + threadIdx.x) * 128;
            asm volatile("prefetch.global.L2 [%0];" ::"l"((const char*)wg + off));
            asm volatile("prefetch.global.L2 [%0];" ::"l"((const char*)wu + off));
            asm volatile("prefetch.global.L2 [%0];" ::"l"((const char*)wd + off));
        }
    }
    uint4 v[2][2];
#pragma unroll
    for (int r = 0; r < 2; r++) {
        const __nv_bfloat16* xr = x + (size_t)(row0 + warp * 2 + r) * D_;
        v[r][0] = *reinterpret_cast<const uint4*>(xr + lane * 8);
        v[r][1] = *reinterpret_cast<const uint4*>(xr + 256 + lane * 8);
    }
#pragma unroll
    for (int r = 0; r < 2; r++) {
        float f[16];
        const uint32_t* w = reinterpret_cast<const uint32_t*>(&v[r][0]);
#pragma unroll
        for (int i = 0; i < 8; i++) { f[2 * i] = bf_lo(w[i]); f[2 * i + 1] = bf_hi(w[i]); }
        float s = 0.f;
#pragma unroll
        for (int i = 0; i < 16; i++) s += f[i];
#pragma unroll
        for (int o = 16; o > 0; o >>= 1) s += __shfl_xor_sync(0xffffffffu, s, o);
        const float mean = s * (1.0f / D_);
        float q = 0.f;
#pragma unroll
        for (int i = 0; i < 16; i++) { float d = f[i] - mean; q += d * d; }
#pragma unroll
        for (int o = 16; o > 0; o >>= 1) q += __shfl_xor_sync(0xffffffffu, q, o);
        const float mb = bf16_round(mean);
        const float vb = bf16_round(q * (1.0f / D_));
        const float den = bf16_round(sqrtf(bf16_round(vb + 1e-5f)));
        uint32_t o[8];
#pragma unroll
        for (int i = 0; i < 8; i++) {
            float a = __fdiv_rn(bf16_round(f[2 * i] - mb), den);
            float b = __fdiv_rn(bf16_round(f[2 * i + 1] - mb), den);
            o[i] = pack_bf16(a, b);
        }
        const int rr = warp * 2 + r;
        __nv_bfloat16* dst = g_xn + (size_t)(row0 + rr) * D_;
        *reinterpret_cast<uint4*>(dst + lane * 8) = make_uint4(o[0], o[1], o[2], o[3]);
        *reinterpret_cast<uint4*>(dst + 256 + lane * 8) = make_uint4(o[4], o[5], o[6], o[7]);
        *reinterpret_cast<uint4*>(&tile[rr][lane * 8]) = make_uint4(o[0], o[1], o[2], o[3]);
        *reinterpret_cast<uint4*>(&tile[rr][256 + lane * 8]) = make_uint4(o[4], o[5], o[6], o[7]);
    }
    __syncthreads();
    if (threadIdx.x == 0) STAMP(0, 1);
#pragma unroll
    for (int cc = 0; cc < 2; cc++) {
        const int c = threadIdx.x + cc * 256;
        uint32_t o[8];
#pragma unroll
        for (int i = 0; i < 8; i++) {
            uint32_t lo = *reinterpret_cast<const uint16_t*>(&tile[2 * i][c]);
            uint32_t hi = *reinterpret_cast<const uint16_t*>(&tile[2 * i + 1][c]);
            o[i] = lo | (hi << 16);
        }
        __nv_bfloat16* dst = g_xnT + (size_t)c * L_ + row0;
        *reinterpret_cast<uint4*>(dst) = make_uint4(o[0], o[1], o[2], o[3]);
        *reinterpret_cast<uint4*>(dst + 8) = make_uint4(o[4], o[5], o[6], o[7]);
    }
    if (threadIdx.x == 0) STAMP(0, 2);
}

struct cplx { float r, i; };
__device__ __forceinline__ cplx cmul(cplx a, cplx b) {
    cplx c; c.r = a.r * b.r - a.i * b.i; c.i = a.r * b.i + a.i * b.r; return c;
}
__device__ __forceinline__ cplx csq(cplx a) {
    cplx c; c.r = a.r * a.r - a.i * a.i; c.i = 2.0f * a.r * a.i; return c;
}
__device__ __forceinline__ cplx cexp_m(float ar, float ai, float m) {
    float mag;
    float e = (ar * m) * 1.4426950408889634f;
    asm("ex2.approx.ftz.f32 %0, %1;" : "=f"(mag) : "f"(e));
    float rr = (ai * m) * 0.15915494309189535f;
    rr -= rintf(rr);
    float th = rr * 6.283185307179586f;
    cplx c; c.r = mag * __cosf(th); c.i = mag * __sinf(th);
    return c;
}
__device__ __forceinline__ uint32_t to_tf32(float x) {
    uint32_t r; asm("cvt.rna.tf32.f32 %0, %1;" : "=r"(r) : "f"(x)); return r;
}
__device__ __forceinline__ void mma_tf32(float* c, uint32_t a0, uint32_t a1, uint32_t a2, uint32_t a3, uint32_t b0, uint32_t b1) {
    asm volatile("mma.sync.aligned.m16n8k8.row.col.f32.tf32.tf32.f32 {%0,%1,%2,%3}, {%4,%5,%6,%7}, {%8,%9}, {%0,%1,%2,%3};"
                 : "+f"(c[0]), "+f"(c[1]), "+f"(c[2]), "+f"(c[3])
                 : "r"(a0), "r"(a1), "r"(a2), "r"(a3), "r"(b0), "r"(b1));
}
__device__ __forceinline__ void mma_bf16(float* c, uint32_t a0, uint32_t a1, uint32_t a2, uint32_t a3, uint32_t b0, uint32_t b1) {
    asm volatile("mma.sync.aligned.m16n8k16.row.col.f32.bf16.bf16.f32 {%0,%1,%2,%3}, {%4,%5,%6,%7}, {%8,%9}, {%0,%1,%2,%3};"
                 : "+f"(c[0]), "+f"(c[1]), "+f"(c[2]), "+f"(c[3])
                 : "r"(a0), "r"(a1), "r"(a2), "r"(a3), "r"(b0), "r"(b1));
}
__device__ __forceinline__ void named_bar(int id, int n) { asm volatile("bar.sync %0, %1;" ::"r"(id), "r"(n) : "memory"); }

constexpr int CV_CH = 4;
constexpr int CV_CONST_B = NS_ * 12 * 4;
constexpr int CV_KV_B = 648 * 4;
constexpr int CV_Q_B = (L_ + 16) * 4;
constexpr int CV_U_B = (L_ + 128) * 2;
constexpr int CV_PER_CH = CV_CONST_B + 2 * CV_KV_B + CV_Q_B + CV_U_B;
constexpr int CV_SMEM = CV_CH * CV_PER_CH;

__global__ void __launch_bounds__(256) conv_kernel(const __nv_bfloat16* __restrict__ A_re, const __nv_bfloat16* __restrict__ A_im,
                                                    const __nv_bfloat16* __restrict__ B_re, const __nv_bfloat16* __restrict__ B_im,
                                                    const __nv_bfloat16* __restrict__ C_re, const __nv_bfloat16* __restrict__ C_im,
                                                    const __nv_bfloat16* __restrict__ log_dt, const __nv_bfloat16* __restrict__ Dskip) {
    pdl_launch();
    if (threadIdx.x == 0) STAMP(1, 0);
    extern __shared__ __align__(16) uint8_t smem[];
    const int warp = threadIdx.x >> 5, lane = threadIdx.x & 31;
    const int ch = warp >> 1, h = warp & 1;
    const int d = blockIdx.x * CV_CH + ch;
    const int g = lane >> 2, t = lane & 3;
    uint8_t* base = smem + ch * CV_PER_CH;
    float4* s_const = reinterpret_cast<float4*>(base);
    float* s_kv = reinterpret_cast<float*>(base + CV_CONST_B);
    uint32_t* s_q = reinterpret_cast<uint32_t*>(base + CV_CONST_B + 2 * CV_KV_B);
    __nv_bfloat16* s_u = reinterpret_cast<__nv_bfloat16*>(base + CV_CONST_B + 2 * CV_KV_B + CV_Q_B);
    const int bar_id = 1 + ch;

    const float dt = bf16_round(expf(__bfloat162float(log_dt[d])));
    float tail = 0.f;
    {
        const int n0 = h * 64 + lane * 2;
        const size_t off = (size_t)d * NS_ + n0;
        uint32_t war = *reinterpret_cast<const uint32_t*>(A_re + off);
        uint32_t wai = *reinterpret_cast<const uint32_t*>(A_im + off);
        uint32_t wbr = *reinterpret_cast<const uint32_t*>(B_re + off);
        uint32_t wbi = *reinterpret_cast<const uint32_t*>(B_im + off);
        uint32_t wcr = *reinterpret_cast<const uint32_t*>(C_re + off);
        uint32_t wci = *reinterpret_cast<const uint32_t*>(C_im + off);
#pragma unroll
        for (int j = 0; j < 2; j++) {
            float ar = dt * (j ? bf_hi(war) : bf_lo(war));
            float ai = dt * (j ? bf_hi(wai) : bf_lo(wai));
            cplx db = {dt * (j ? bf_hi(wbr) : bf_lo(wbr)), dt * (j ? bf_hi(wbi) : bf_lo(wbi))};
            cplx cc = {(j ? bf_hi(wcr) : bf_lo(wcr)), (j ? bf_hi(wci) : bf_lo(wci))};
            cplx cb = cmul(cc, db);
            cplx e128 = cexp_m(ar, ai, 128.f);
            cplx c256 = cmul(cb, cexp_m(ar, ai, 256.f));
            cplx c512 = cmul(cb, cexp_m(ar, ai, 512.f));
            cplx c1024 = cmul(cb, cexp_m(ar, ai, 1024.f));
            cplx c2048 = cmul(cb, cexp_m(ar, ai, 2048.f));
            tail += c2048.r;
            s_const[(n0 + j) * 3 + 0] = make_float4(ar, ai, cb.r, cb.i);
            s_const[(n0 + j) * 3 + 1] = make_float4(e128.r, e128.i, c256.r, c256.i);
            s_const[(n0 + j) * 3 + 2] = make_float4(c512.r, c512.i, c1024.r, c1024.i);
        }
#pragma unroll
        for (int o = 16; o > 0; o >>= 1) tail += __shfl_xor_sync(0xffffffffu, tail, o);
    }
    __syncwarp();
    if (threadIdx.x == 0) STAMP(1, 1);
    {
        float acc[5][4];
#pragma unroll
        for (int i = 0; i < 5; i++) { acc[i][0] = acc[i][1] = acc[i][2] = acc[i][3] = 0.f; }
        const float gf = (float)g;
#pragma unroll 2
        for (int s = 0; s < 16; s++) {
            const int n = h * 64 + s * 4 + t;
            const float4 k0 = s_const[n * 3 + 0], k1 = s_const[n * 3 + 1], k2 = s_const[n * 3 + 2];
            const cplx cb = {k0.z, k0.w}, e128 = {k1.x, k1.y}, c256 = {k1.z, k1.w}, c512 = {k2.x, k2.y}, c1024 = {k2.z, k2.w};
            cplx p1 = cexp_m(k0.x, k0.y, gf);
            cplx p1b = cexp_m(k0.x, k0.y, gf + 8.f);
            cplx r16a = cexp_m(k0.x, k0.y, gf * 16.f);
            cplx r16b = cmul(r16a, e128);
            cplx p2 = csq(p1), p4 = csq(p2), p8 = csq(p4);
            cplx r32a = csq(r16a), r32b = csq(r16b), r64a = csq(r32a), r64b = csq(r32b);
            cplx f0a = cmul(cb, p1), f0b = cmul(cb, p1b), f1 = cmul(c256, p2), f2 = cmul(c512, p4), f3 = cmul(c1024, p8);
            {
                uint32_t a0 = to_tf32(r16a.r), a1 = to_tf32(r16b.r), a2 = to_tf32(-r16a.i), a3 = to_tf32(-r16b.i);
                mma_tf32(acc[0], a0, a1, a2, a3, to_tf32(f0a.r), to_tf32(f0a.i));
                mma_tf32(acc[1], a0, a1, a2, a3, to_tf32(f0b.r), to_tf32(f0b.i));
                mma_tf32(acc[2], a0, a1, a2, a3, to_tf32(f1.r), to_tf32(f1.i));
            }
            mma_tf32(acc[3], to_tf32(r32a.r), to_tf32(r32b.r), to_tf32(-r32a.i), to_tf32(-r32b.i), to_tf32(f2.r), to_tf32(f2.i));
            mma_tf32(acc[4], to_tf32(r64a.r), to_tf32(r64b.r), to_tf32(-r64a.i), to_tf32(-r64b.i), to_tf32(f3.r), to_tf32(f3.i));
        }
        float* kv = s_kv + h * 648;
        *reinterpret_cast<float2*>(kv + 16 * g + 2 * t) = make_float2(acc[0][0], acc[0][1]);
        *reinterpret_cast<float2*>(kv + 16 * (g + 8) + 2 * t) = make_float2(acc[0][2], acc[0][3]);
        *reinterpret_cast<float2*>(kv + 16 * g + 8 + 2 * t) = make_float2(acc[1][0], acc[1][1]);
        *reinterpret_cast<float2*>(kv + 16 * (g + 8) + 8 + 2 * t) = make_float2(acc[1][2], acc[1][3]);
#pragma unroll
        for (int sg = 0; sg < 3; sg++) {
            *reinterpret_cast<float2*>(kv + 256 + 128 * sg + 8 * g + 2 * t) = make_float2(acc[2 + sg][0], acc[2 + sg][1]);
            *reinterpret_cast<float2*>(kv + 256 + 128 * sg + 8 * (g + 8) + 2 * t) = make_float2(acc[2 + sg][2], acc[2 + sg][3]);
        }
        if (lane == 0) kv[640] = tail;
    }
    named_bar(bar_id, 64);
    if (threadIdx.x == 0) STAMP(1, 2);
    {
        const int tid2 = h * 32 + lane;
        if (tid2 < 16) s_q[tid2] = 0u;
        for (int x = tid2; x < L_; x += 64) {
            float kc, kp;
            {
                int s = (x >= 1024) ? 3 : (x >= 512) ? 2 : (x >= 256) ? 1 : 0;
                int rq = (s == 0) ? x : ((x + (1 << (s - 1)) - 1 + ((x >> s) & 1)) >> s);
                int idx = 128 * s + rq;
                kc = s_kv[idx] + s_kv[648 + idx];
            }
            {
                int y = x - 1;
                if (y < 0) kp = 0.f;
                else {
                    int s = (y >= 1024) ? 3 : (y >= 512) ? 2 : (y >= 256) ? 1 : 0;
                    int rq = (s == 0) ? y : ((y + (1 << (s - 1)) - 1 + ((y >> s) & 1)) >> s);
                    int idx = 128 * s + rq;
                    kp = s_kv[idx] + s_kv[648 + idx];
                }
            }
            s_q[x + 16] = pack_bf16(kc, kp);
        }
    }
    if (threadIdx.x == 0) STAMP(1, 3);
    pdl_wait();
    if (threadIdx.x == 0) STAMP(1, 4);
    {
        const int tid2 = h * 32 + lane;
        if (tid2 < 16) *reinterpret_cast<uint4*>(s_u + tid2 * 8) = make_uint4(0, 0, 0, 0);
        const uint4* src = reinterpret_cast<const uint4*>(g_xnT + (size_t)d * L_);
#pragma unroll
        for (int i = 0; i < 4; i++) {
            *reinterpret_cast<uint4*>(s_u + 128 + (tid2 + i * 64) * 8) = src[tid2 + i * 64];
        }
    }
    named_bar(bar_id, 64);
    if (threadIdx.x == 0) STAMP(1, 5);
    float acc[16][4];
#pragma unroll
    for (int i = 0; i < 16; i++) { acc[i][0] = acc[i][1] = acc[i][2] = acc[i][3] = 0.f; }
    const uint32_t su_addr = smem_u32(s_u);
    for (int rr = 0; rr < 4; rr++) {
        const int r = h * 4 + rr;
        uint32_t ub[16][2];
        {
            const int mi = lane >> 3, rowi = lane & 7;
            uint32_t addr = su_addr + (uint32_t)((128 + 16 * (8 * (mi >> 1) + rowi - r) + 8 * (mi & 1)) * 2);
#pragma unroll
            for (int j = 0; j < 16; j += 2) {
                asm volatile("ldmatrix.sync.aligned.m8n8.x4.shared.b16 {%0,%1,%2,%3}, [%4];"
                             : "=r"(ub[j][0]), "=r"(ub[j][1]), "=r"(ub[j + 1][0]), "=r"(ub[j + 1][1])
                             : "r"(addr + (uint32_t)(j * 8 * 16 * 2)));
            }
        }
        const uint32_t* qp = s_q + 16 + 16 * r + g - 2 * t;
#pragma unroll
        for (int q = 0; q < 16; q++) {
            const uint32_t a0 = qp[128 * q], a1 = qp[128 * q + 8], a2 = qp[128 * q - 8];
#pragma unroll
            for (int nt = q; nt < 16; nt++) mma_bf16(acc[nt], a0, a1, a2, a0, ub[nt - q][0], ub[nt - q][1]);
        }
    }
    if (threadIdx.x == 0) STAMP(1, 6);
    named_bar(bar_id, 64);
    {
        float4* xch = reinterpret_cast<float4*>(base) + h * 256;
        if (h) {
#pragma unroll
            for (int i = 0; i < 8; i++) xch[i * 32 + lane] = make_float4(acc[i][0], acc[i][1], acc[i][2], acc[i][3]);
        } else {
#pragma unroll
            for (int i = 0; i < 8; i++) xch[i * 32 + lane] = make_float4(acc[8 + i][0], acc[8 + i][1], acc[8 + i][2], acc[8 + i][3]);
        }
    }
    named_bar(bar_id, 64);
    {
        const float4* xch = reinterpret_cast<const float4*>(base) + (h ^ 1) * 256;
        const float dsk = __bfloat162float(Dskip[d]);
        __nv_bfloat16* stg = reinterpret_cast<__nv_bfloat16*>(s_q);
#pragma unroll
        for (int i = 0; i < 8; i++) {
            float4 o = xch[i * 32 + lane];
            float y[4];
            if (h) { y[0] = acc[8 + i][0] + o.x; y[1] = acc[8 + i][1] + o.y; y[2] = acc[8 + i][2] + o.z; y[3] = acc[8 + i][3] + o.w; }
            else   { y[0] = acc[i][0] + o.x; y[1] = acc[i][1] + o.y; y[2] = acc[i][2] + o.z; y[3] = acc[i][3] + o.w; }
            const int nt = h * 8 + i;
#pragma unroll
            for (int e = 0; e < 4; e++) {
                const int tau = 16 * (8 * nt + 2 * t + (e & 1)) + g + 8 * (e >> 1);
                float u = __bfloat162float(s_u[128 + tau]);
                float sv = bf16_round(y[e]) + bf16_round(u * dsk);
                stg[tau] = __float2bfloat16_rn(sv);
            }
        }
        __syncwarp();
        uint4* dst = reinterpret_cast<uint4*>(g_sT + (size_t)d * L_ + h * 1024);
        const uint4* srcp = reinterpret_cast<const uint4*>(stg + h * 1024);
#pragma unroll
        for (int i = 0; i < 4; i++) dst[i * 32 + lane] = srcp[i * 32 + lane];
    }
    if (threadIdx.x == 0) STAMP(1, 7);
}

__device__ __forceinline__ uint32_t cluster_rank() { uint32_t r; asm volatile("mov.u32 %0, %%cluster_ctarank;" : "=r"(r)); return r; }
__device__ __forceinline__ void cluster_sync_all() {
    asm volatile("barrier.cluster.arrive.release.aligned;\nbarrier.cluster.wait.acquire.aligned;" ::: "memory");
}
__device__ __forceinline__ void mbar_arrive_remote(uint32_t bar, uint32_t cta) {
    asm volatile("{\n.reg .b32 ra;\nmapa.shared::cluster.u32 ra, %0, %1;\n"
                 "mbarrier.arrive.release.cluster.shared::cluster.b64 _, [ra];\n}\n" ::"r"(bar), "r"(cta) : "memory");
}
__device__ __forceinline__ void tma_load_2d_mc(uint32_t dst, const CUtensorMap* tm, int c0, int c1, uint32_t bar, uint16_t mask) {
    asm volatile(
        "cp.async.bulk.tensor.2d.shared::cluster.global.mbarrier::complete_tx::bytes.multicast::cluster [%0], [%1, {%3, %4}], [%2], %5;"
        ::"r"(dst), "l"((uint64_t)tm), "r"(bar), "r"(c0), "r"(c1), "h"(mask) : "memory");
}
__device__ __forceinline__ void tma_store_2d(const CUtensorMap* tm, uint32_t src, int c0, int c1) {
    asm volatile("cp.async.bulk.tensor.2d.global.shared::cta.bulk_group [%0, {%2, %3}], [%1];"
                 ::"l"((uint64_t)tm), "r"(src), "r"(c0), "r"(c1) : "memory");
}
__device__ __forceinline__ void bulk_commit() { asm volatile("cp.async.bulk.commit_group;" ::: "memory"); }
template <int N> __device__ __forceinline__ void bulk_wait_read() { asm volatile("cp.async.bulk.wait_group.read %0;" ::"n"(N) : "memory"); }
template <int N> __device__ __forceinline__ void bulk_wait() { asm volatile("cp.async.bulk.wait_group %0;" ::"n"(N) : "memory"); }
__device__ __forceinline__ void fence_async_smem() { asm volatile("fence.proxy.async.shared::cta;" ::: "memory"); }
__device__ __forceinline__ void stmatrix_x4(uint32_t addr, uint32_t r0, uint32_t r1, uint32_t r2, uint32_t r3) {
    asm volatile("stmatrix.sync.aligned.m8n8.x4.shared.b16 [%0], {%1,%2,%3,%4};" ::"r"(addr), "r"(r0), "r"(r1), "r"(r2), "r"(r3) : "memory");
}

constexpr int G1_CM = 2;
constexpr int G1_STAGES = 5;
constexpr int G1_A_BYTES = 8 * 16384;
constexpr int G1_B_STAGE = 4 * 4096;
constexpr int G1_STG = 8 * 1024;
constexpr int G1_SMEM = G1_A_BYTES + G1_STAGES * G1_B_STAGE + G1_STG + 1024 + 256;
constexpr int G1_ITERS = 32;

__device__ __forceinline__ float gelu_tanh(float x) {
    float u = x * (0.7978845608028654f + 0.035677408136300125f * x * x);
    float t; asm("tanh.approx.f32 %0, %1;" : "=f"(t) : "f"(u));
    float hx = 0.5f * x;
    return fmaf(hx, t, hx);
}
__device__ __forceinline__ uint32_t geglu_pair(uint32_t p0, uint32_t p1) {
    float a = bf16_round(gelu_tanh(bf_lo(p0))) * bf_hi(p0);
    float b = bf16_round(gelu_tanh(bf_lo(p1))) * bf_hi(p1);
    return pack_bf16(a, b);
}

__global__ void __launch_bounds__(384, 1) gemm1_kernel(const __grid_constant__ CUtensorMap tm_xn,
                                                        const __grid_constant__ CUtensorMap tm_wg,
                                                        const __grid_constant__ CUtensorMap tm_wu,
                                                        const __grid_constant__ CUtensorMap tm_hst) {
    pdl_launch();
    if (threadIdx.x == 0) STAMP(2, 0);
    extern __shared__ uint8_t smem_raw[];
    const uint32_t sbase = (smem_u32(smem_raw) + 1023) & ~1023u;
    const uint32_t sA = sbase, sB = sbase + G1_A_BYTES, sStg = sB + G1_STAGES * G1_B_STAGE, sBar = sStg + G1_STG;
    const uint32_t bar_a = sBar, bar_full = sBar + 64, bar_empty = sBar + 64 + 8 * G1_STAGES;
    const uint32_t rank = cluster_rank();
    const int cid = blockIdx.x / G1_CM;
    const int rb = (cid >> 3) * G1_CM + rank, cj = cid & 7;
    const int warp = threadIdx.x >> 5, lane = threadIdx.x & 31;

    if (threadIdx.x == 0) {
        for (int i = 0; i < 8; i++) mbar_init(bar_a + 8 * i, 1);
        for (int i = 0; i < G1_STAGES; i++) { mbar_init(bar_full + 8 * i, 1); mbar_init(bar_empty + 8 * i, 8 * G1_CM); }
        asm volatile("fence.mbarrier_init.release.cluster;" ::: "memory");
    }
    cluster_sync_all();

    if (warp >= 8) {
        asm volatile("setmaxnreg.dec.sync.aligned.u32 40;");
        if (warp == 8 && lane == 0) {
            prefetch_tmap(&tm_xn); prefetch_tmap(&tm_wg); prefetch_tmap(&tm_wu); prefetch_tmap(&tm_hst);
            for (int it = 0; it < G1_ITERS; it++) {
                const int s = it % G1_STAGES, tile = it >> 4, kb = it & 15;
                if (it == G1_STAGES) {
                    pdl_wait();
                    STAMP(2, 1);
                    for (int k = 0; k < 8; k++) {
                        mbar_expect_tx(bar_a + 8 * k, 16384);
                        tma_load_2d(sA + k * 16384, &tm_xn, k * 64, rb * 128, bar_a + 8 * k);
                    }
                }
                if (it >= G1_STAGES) mbar_wait(bar_empty + 8 * s, ((it / G1_STAGES) - 1) & 1);
                const int n0 = (cj * 2 + tile) * 112;
                const uint32_t dst = sB + s * G1_B_STAGE;
                mbar_expect_tx(bar_full + 8 * s, G1_B_STAGE);
#pragma unroll
                for (int b = 0; b < 4 / G1_CM; b++) {
                    const int box = rank * (4 / G1_CM) + b;
                    tma_load_2d_mc(dst + box * 4096, (box & 2) ? &tm_wu : &tm_wg, n0 + (box & 1) * 64, kb * 32, bar_full + 8 * s,
                                   (uint16_t)((1 << G1_CM) - 1));
                }
            }
        }
    } else {
        asm volatile("setmaxnreg.inc.sync.aligned.u32 232;");
        const int wg = warp >> 2;
        float accg[56], accu[56];
        uint32_t pk[56];
        const int row0 = rb * 128 + wg * 64 + (warp & 3) * 16;
        const uint32_t stg = sStg + warp * 1024;
        const uint32_t st_off = (uint32_t)(((lane & 7) + ((lane >> 3) & 1) * 8) * 32 + (lane >> 4) * 16);
        auto store_group = [&](int jj, int col) {
            const uint32_t buf = stg + (jj & 1) * 512;
            uint32_t r0 = geglu_pair(pk[8 * jj + 0], pk[8 * jj + 1]);
            uint32_t r1 = geglu_pair(pk[8 * jj + 2], pk[8 * jj + 3]);
            uint32_t r2 = geglu_pair(pk[8 * jj + 4], pk[8 * jj + 5]);
            uint32_t r3 = geglu_pair(pk[8 * jj + 6], pk[8 * jj + 7]);
            if (lane == 0) bulk_wait_read<1>();
            __syncwarp();
            stmatrix_x4(buf + st_off, r0, r1, r2, r3);
            fence_async_smem();
            __syncwarp();
            if (lane == 0) { tma_store_2d(&tm_hst, buf, col, row0); bulk_commit(); }
        };
#pragma unroll
        for (int tile = 0; tile < 2; tile++) {
#pragma unroll
            for (int kb = 0; kb < 16; kb++) {
                const int it = tile * 16 + kb, s = it % G1_STAGES;
                if (tile == 0 && (kb & 1) == 0) mbar_wait(bar_a + 8 * (kb >> 1), 0);
                mbar_wait(bar_full + 8 * s, (it / G1_STAGES) & 1);
                if (threadIdx.x == 0 && (it & 7) == 0) STAMP(2, 2 + it / 8);
                wgmma_fence();
                const uint32_t a_addr = sA + (kb >> 1) * 16384 + wg * 8192 + (kb & 1) * 64;
                const uint32_t b_addr = sB + s * G1_B_STAGE;
#pragma unroll
                for (int k = 0; k < 2; k++) {
                    const uint64_t da = make_desc(a_addr + k * 32, 16, 1024);
                    wgmma_n112(accg, da, make_desc(b_addr + k * 2048, 4096, 1024), (kb | k) != 0);
                    wgmma_n112(accu, da, make_desc(b_addr + 8192 + k * 2048, 4096, 1024), (kb | k) != 0);
                }
                wgmma_commit();
                if (tile == 1 && (kb & 1) == 0 && kb < 14) store_group(kb >> 1, cj * 224 + (kb >> 1) * 16);
                if (kb > 0) {
                    wgmma_wait<1>();
                    if (lane < G1_CM) mbar_arrive_remote(bar_empty + 8 * ((it - 1) % G1_STAGES), lane);
                }
            }
            wgmma_wait<0>();
            if (lane < G1_CM) mbar_arrive_remote(bar_empty + 8 * ((tile * 16 + 15) % G1_STAGES), lane);
#pragma unroll
            for (int i = 0; i < 56; i++) pk[i] = pack_bf16(accg[i], accu[i]);
        }
        if (threadIdx.x == 0) STAMP(2, 6);
#pragma unroll
        for (int jj = 0; jj < 7; jj++) store_group(jj, cj * 224 + 112 + jj * 16);
        if (lane == 0) bulk_wait<0>();
        if (threadIdx.x == 0) STAMP(2, 7);
    }
    cluster_sync_all();
}

constexpr int G2_CM = 2, G2_CN = 4;
constexpr int G2_STAGES = 7;
constexpr int G2_STAGE = 16384 + 8192;
constexpr int G2_EPI = 16384 + 16384;
constexpr int G2_SMEM = G2_STAGES * G2_STAGE + G2_EPI + 1024 + 256;
constexpr int G2_KB = F_ / 64;

__global__ void __launch_bounds__(288, 1) gemm2_kernel(const __grid_constant__ CUtensorMap tm_h,
                                                        const __grid_constant__ CUtensorMap tm_wd,
                                                        const __grid_constant__ CUtensorMap tm_x,
                                                        const __grid_constant__ CUtensorMap tm_sT,
                                                        const __grid_constant__ CUtensorMap tm_out) {
    if (threadIdx.x == 0) STAMP(3, 0);
    extern __shared__ uint8_t smem_raw[];
    const uint32_t sbase = (smem_u32(smem_raw) + 1023) & ~1023u;
    const uint32_t sX = sbase + G2_STAGES * G2_STAGE, sS = sX + 16384, sBar = sX + G2_EPI;
    const uint32_t bar_full = sBar, bar_empty = sBar + 8 * G2_STAGES, bar_epi = sBar + 16 * G2_STAGES;
    const uint32_t rank = cluster_rank();
    const int cm = rank / G2_CN, cn = rank % G2_CN;
    const int cid = blockIdx.x / (G2_CM * G2_CN);
    constexpr int NCL_N = 8 / G2_CN;
    const int rb = (cid / NCL_N) * G2_CM + cm, cj = (cid % NCL_N) * G2_CN + cn;
    const int warp = threadIdx.x >> 5, lane = threadIdx.x & 31;
    uint16_t mask_a = 0, mask_b = 0;
#pragma unroll
    for (int i = 0; i < G2_CN; i++) mask_a |= (uint16_t)(1 << (cm * G2_CN + i));
#pragma unroll
    for (int i = 0; i < G2_CM; i++) mask_b |= (uint16_t)(1 << (i * G2_CN + cn));

    if (threadIdx.x == 0) {
        for (int i = 0; i < G2_STAGES; i++) { mbar_init(bar_full + 8 * i, 1); mbar_init(bar_empty + 8 * i, 8 * (G2_CM + G2_CN - 1)); }
        mbar_init(bar_epi, 1);
        asm volatile("fence.mbarrier_init.release.cluster;" ::: "memory");
    }
    cluster_sync_all();

    constexpr int AR = 128 / G2_CN;
    constexpr int BK = 64 / G2_CM;
    if (warp == 8) {
        if (lane == 0) {
            prefetch_tmap(&tm_h); prefetch_tmap(&tm_wd); prefetch_tmap(&tm_x); prefetch_tmap(&tm_sT); prefetch_tmap(&tm_out);
            for (int it = 0; it < G2_STAGES; it++) {
                mbar_expect_tx(bar_full + 8 * it, G2_STAGE);
                tma_load_2d_mc(sbase + it * G2_STAGE + 16384 + cm * BK * 128, &tm_wd, cj * 64, it * 64 + cm * BK, bar_full + 8 * it, mask_b);
            }
            mbar_expect_tx(bar_epi, G2_EPI);
            tma_load_2d(sX, &tm_x, cj * 64, rb * 128, bar_epi);
            pdl_wait();
            STAMP(3, 1);
            for (int it = 0; it < G2_STAGES; it++)
                tma_load_2d_mc(sbase + it * G2_STAGE + cn * AR * 128, &tm_h, it * 64, rb * 128 + cn * AR, bar_full + 8 * it, mask_a);
            tma_load_2d(sS, &tm_sT, rb * 128, cj * 64, bar_epi);
            tma_load_2d(sS + 8192, &tm_sT, rb * 128 + 64, cj * 64, bar_epi);
            for (int it = G2_STAGES; it < G2_KB; it++) {
                const int s = it % G2_STAGES;
                mbar_wait(bar_empty + 8 * s, ((it / G2_STAGES) - 1) & 1);
                mbar_expect_tx(bar_full + 8 * s, G2_STAGE);
                tma_load_2d_mc(sbase + s * G2_STAGE + cn * AR * 128, &tm_h, it * 64, rb * 128 + cn * AR, bar_full + 8 * s, mask_a);
                tma_load_2d_mc(sbase + s * G2_STAGE + 16384 + cm * BK * 128, &tm_wd, cj * 64, it * 64 + cm * BK, bar_full + 8 * s, mask_b);
            }
        }
    } else {
        const int wg = warp >> 2;
        const int g = lane >> 2, t = lane & 3;
        int tgt = -1;
        if (lane < G2_CN) tgt = cm * G2_CN + lane;
        else if (lane < G2_CN + G2_CM - 1) { int i = lane - G2_CN; if (i >= cm) i++; tgt = i * G2_CN + cn; }
        float acc[32];
        for (int it = 0; it < G2_KB; it++) {
            const int s = it % G2_STAGES;
            mbar_wait(bar_full + 8 * s, (it / G2_STAGES) & 1);
            if (threadIdx.x == 0 && (it == 0 || it == 14)) STAMP(3, 2 + it / 14);
            wgmma_fence();
            const uint32_t a_addr = sbase + s * G2_STAGE + wg * 8192;
            const uint32_t b_addr = sbase + s * G2_STAGE + 16384;
#pragma unroll
            for (int k = 0; k < 4; k++)
                wgmma_n64(acc, make_desc(a_addr + k * 32, 16, 1024), make_desc(b_addr + k * 2048, 8192, 1024), (it | k) != 0);
            wgmma_commit();
            if (it > 0 && it - 1 + G2_STAGES < G2_KB) {
                wgmma_wait<1>();
                if (tgt >= 0) mbar_arrive_remote(bar_empty + 8 * ((it - 1) % G2_STAGES), (uint32_t)tgt);
            }
        }
        wgmma_wait<0>();
        if (threadIdx.x == 0) STAMP(3, 4);
        mbar_wait(bar_epi, 0);
        const int lr = wg * 64 + (warp & 3) * 16 + g;
#pragma unroll
        for (int j = 0; j < 8; j++) {
#pragma unroll
            for (int hh = 0; hh < 2; hh++) {
                const int r = lr + 8 * hh;
                const uint32_t xaddr = sX + r * 128 + ((j ^ (r & 7)) << 4) + 4 * t;
                uint32_t xv; asm volatile("ld.shared.u32 %0, [%1];" : "=r"(xv) : "r"(xaddr));
                const int c0 = 8 * j + 2 * t;
                const uint32_t sa = sS + (r >> 6) * 8192 + (((r & 63) >> 3) << 4) + (r & 7) * 2;
                uint16_t s0r, s1r;
                asm volatile("ld.shared.u16 %0, [%1];" : "=h"(s0r) : "r"((sa + c0 * 128) ^ ((c0 & 7) << 4)));
                asm volatile("ld.shared.u16 %0, [%1];" : "=h"(s1r) : "r"((sa + (c0 + 1) * 128) ^ (((c0 + 1) & 7) << 4)));
                float s0 = __uint_as_float((uint32_t)s0r << 16), s1 = __uint_as_float((uint32_t)s1r << 16);
                float f0 = bf16_round(acc[4 * j + 2 * hh]), f1 = bf16_round(acc[4 * j + 2 * hh + 1]);
                float g0 = bf16_round(__fdividef(f0, 1.0f + __expf(-f0)));
                float g1 = bf16_round(__fdividef(f1, 1.0f + __expf(-f1)));
                float o0 = bf_lo(xv) + bf16_round(s0 * g0);
                float o1 = bf_hi(xv) + bf16_round(s1 * g1);
                asm volatile("st.shared.u32 [%0], %1;" ::"r"(xaddr), "r"(pack_bf16(o0, o1)) : "memory");
            }
        }
        fence_async_smem();
        __syncwarp();
        if (lane == 0) {
            tma_store_2d(&tm_out, sX + (wg * 64 + (warp & 3) * 16) * 128, cj * 64, rb * 128 + wg * 64 + (warp & 3) * 16);
            bulk_commit();
            bulk_wait<0>();
        }
        if (threadIdx.x == 0) STAMP(3, 5);
    }
    cluster_sync_all();
}

typedef CUresult (*EncodeFn)(CUtensorMap*, CUtensorMapDataType, cuuint32_t, void*, const cuuint64_t*, const cuuint64_t*,
                             const cuuint32_t*, const cuuint32_t*, CUtensorMapInterleave, CUtensorMapSwizzle,
                             CUtensorMapL2promotion, CUtensorMapFloatOOBfill);

void make_map(EncodeFn fn, CUtensorMap* m, const void* ptr, uint64_t inner, uint64_t outer, uint32_t box_in, uint32_t box_out,
              CUtensorMapSwizzle swz = CU_TENSOR_MAP_SWIZZLE_128B) {
    cuuint64_t dims[2] = {inner, outer};
    cuuint64_t strides[1] = {inner * 2};
    cuuint32_t box[2] = {box_in, box_out};
    cuuint32_t es[2] = {1, 1};
    fn(m, CU_TENSOR_MAP_DATA_TYPE_BFLOAT16, 2, const_cast<void*>(ptr), dims, strides, box, es, CU_TENSOR_MAP_INTERLEAVE_NONE,
       swz, CU_TENSOR_MAP_L2_PROMOTION_L2_256B, CU_TENSOR_MAP_FLOAT_OOB_FILL_NONE);
}

template <typename... Args>
void launch_pdl(void (*kern)(Args...), int grid, int block, int smem, bool pdl, int cluster, Args... args) {
    cudaLaunchConfig_t cfg = {};
    cfg.gridDim = dim3(grid); cfg.blockDim = dim3(block); cfg.dynamicSmemBytes = smem; cfg.stream = cudaStreamPerThread;
    cudaLaunchAttribute at[2];
    int n = 0;
    if (pdl) {
        at[n].id = cudaLaunchAttributeProgrammaticStreamSerialization;
        at[n].val.programmaticStreamSerializationAllowed = 1;
        n++;
    }
    if (cluster > 1) {
        at[n].id = cudaLaunchAttributeClusterDimension;
        at[n].val.clusterDim.x = cluster; at[n].val.clusterDim.y = 1; at[n].val.clusterDim.z = 1;
        n++;
    }
    cfg.attrs = at; cfg.numAttrs = n;
    cudaLaunchKernelEx(&cfg, kern, args...);
}

}

extern "C" void kernel_launch(void* const* d_in, const int* in_sizes, int n_in, void* d_out, int out_size) {
    const __nv_bfloat16* x = (const __nv_bfloat16*)d_in[0];
    const __nv_bfloat16* A_re = (const __nv_bfloat16*)d_in[1];
    const __nv_bfloat16* A_im = (const __nv_bfloat16*)d_in[2];
    const __nv_bfloat16* B_re = (const __nv_bfloat16*)d_in[3];
    const __nv_bfloat16* B_im = (const __nv_bfloat16*)d_in[4];
    const __nv_bfloat16* C_re = (const __nv_bfloat16*)d_in[5];
    const __nv_bfloat16* C_im = (const __nv_bfloat16*)d_in[6];
    const __nv_bfloat16* log_dt = (const __nv_bfloat16*)d_in[7];
    const __nv_bfloat16* Dskip = (const __nv_bfloat16*)d_in[8];
    const __nv_bfloat16* wg = (const __nv_bfloat16*)d_in[10];
    const __nv_bfloat16* wu = (const __nv_bfloat16*)d_in[11];
    const __nv_bfloat16* wd = (const __nv_bfloat16*)d_in[12];
    __nv_bfloat16* out = (__nv_bfloat16*)d_out;

    static bool init = false;
    static CUtensorMap tm_xn, tm_wg, tm_wu, tm_hst, tm_h, tm_wd, tm_x, tm_sT, tm_out;
    static const void* last_ptrs[5] = {nullptr, nullptr, nullptr, nullptr, nullptr};
    if (!init || last_ptrs[0] != wg || last_ptrs[1] != wu || last_ptrs[2] != wd || last_ptrs[3] != x || last_ptrs[4] != out) {
        void* fnp = nullptr;
        cudaDriverEntryPointQueryResult qres;
        cudaGetDriverEntryPoint("cuTensorMapEncodeTiled", &fnp, cudaEnableDefault, &qres);
        EncodeFn fn = (EncodeFn)fnp;
        void *p_xn, *p_h, *p_sT;
        cudaGetSymbolAddress(&p_xn, g_xn);
        cudaGetSymbolAddress(&p_h, g_h);
        cudaGetSymbolAddress(&p_sT, g_sT);
        make_map(fn, &tm_xn, p_xn, D_, L_, 64, 128);
        make_map(fn, &tm_wg, wg, F_, D_, 64, 32);
        make_map(fn, &tm_wu, wu, F_, D_, 64, 32);
        make_map(fn, &tm_hst, p_h, F_, L_, 16, 16, CU_TENSOR_MAP_SWIZZLE_NONE);
        make_map(fn, &tm_h, p_h, F_, L_, 64, 128 / G2_CN);
        make_map(fn, &tm_wd, wd, D_, F_, 64, 64 / G2_CM);
        make_map(fn, &tm_x, x, D_, L_, 64, 128);
        make_map(fn, &tm_sT, p_sT, L_, D_, 64, 64);
        make_map(fn, &tm_out, out, D_, L_, 64, 16);
        cudaFuncSetAttribute(ln_kernel, cudaFuncAttributePreferredSharedMemoryCarveout, 100);
        cudaFuncSetAttribute(conv_kernel, cudaFuncAttributeMaxDynamicSharedMemorySize, CV_SMEM);
        cudaFuncSetAttribute(conv_kernel, cudaFuncAttributePreferredSharedMemoryCarveout, 100);
        cudaFuncSetAttribute(gemm1_kernel, cudaFuncAttributeMaxDynamicSharedMemorySize, G1_SMEM);
        cudaFuncSetAttribute(gemm2_kernel, cudaFuncAttributeMaxDynamicSharedMemorySize, G2_SMEM);
        last_ptrs[0] = wg; last_ptrs[1] = wu; last_ptrs[2] = wd; last_ptrs[3] = x; last_ptrs[4] = out;
        init = true;
    }
    launch_pdl(ln_kernel, L_ / LN_ROWS, 256, 0, false, 1, x, wg, wu, wd);
    launch_pdl(conv_kernel, D_ / CV_CH, 256, CV_SMEM, true, 1, A_re, A_im, B_re, B_im, C_re, C_im, log_dt, Dskip);
    launch_pdl(gemm1_kernel, 128, 384, G1_SMEM, true, G1_CM, tm_xn, tm_wg, tm_wu, tm_hst);
    launch_pdl(gemm2_kernel, 128, 288, G2_SMEM, true, G2_CM * G2_CN, tm_h, tm_wd, tm_x, tm_sT, tm_out);
}
```

```cpp
#include <cuda_runtime.h>
#include <cuda_bf16.h>
#include <cuda.h>
#include <stdint.h>

namespace {

constexpr int L_ = 2048, D_ = 512, NS_ = 128, F_ = 1792;

__device__ __align__(1024) __nv_bfloat16 g_xn[L_ * D_];
__device__ __align__(1024) __nv_bfloat16 g_xnT[D_ * L_];
__device__ __align__(1024) __nv_bfloat16 g_sT[D_ * L_];
__device__ __align__(1024) __nv_bfloat16 g_h[L_ * F_];

#define STAMP(k, i)

__device__ __forceinline__ uint32_t smem_u32(const void* p) { return (uint32_t)__cvta_generic_to_shared(p); }
__device__ __forceinline__ void pdl_wait() { asm volatile("griddepcontrol.wait;" ::: "memory"); }
__device__ __forceinline__ void pdl_launch() { asm volatile("griddepcontrol.launch_dependents;" ::: "memory"); }

__device__ __forceinline__ void mbar_init(uint32_t bar, uint32_t cnt) {
    asm volatile("mbarrier.init.shared::cta.b64 [%0], %1;" ::"r"(bar), "r"(cnt) : "memory");
}
__device__ __forceinline__ void mbar_expect_tx(uint32_t bar, uint32_t bytes) {
    asm volatile("mbarrier.arrive.expect_tx.shared::cta.b64 _, [%0], %1;" ::"r"(bar), "r"(bytes) : "memory");
}
__device__ __forceinline__ void mbar_arrive(uint32_t bar) {
    asm volatile("mbarrier.arrive.shared::cta.b64 _, [%0];" ::"r"(bar) : "memory");
}
__device__ __forceinline__ void mbar_wait(uint32_t bar, uint32_t parity) {
    asm volatile(
        "{\n.reg .pred p;\n"
        "WAIT_LOOP:\n"
        "mbarrier.try_wait.parity.shared::cta.b64 p, [%0], %1;\n"
        "@p bra WAIT_DONE;\n"
        "bra WAIT_LOOP;\n"
        "WAIT_DONE:\n}\n" ::"r"(bar), "r"(parity) : "memory");
}
__device__ __forceinline__ void tma_load_2d(uint32_t dst, const CUtensorMap* tm, int c0, int c1, uint32_t bar) {
    asm volatile(
        "cp.async.bulk.tensor.2d.shared::cluster.global.mbarrier::complete_tx::bytes [%0], [%1, {%3, %4}], [%2];"
        ::"r"(dst), "l"((uint64_t)tm), "r"(bar), "r"(c0), "r"(c1) : "memory");
}
__device__ __forceinline__ void prefetch_tmap(const CUtensorMap* tm) {
    asm volatile("prefetch.tensormap [%0];" ::"l"((uint64_t)tm) : "memory");
}
__device__ __forceinline__ uint64_t make_desc(uint32_t addr, uint32_t lbo, uint32_t sbo, uint64_t mode = 1) {
    uint64_t d = 0;
    d |= (uint64_t)((addr & 0x3FFFF) >> 4);
    d |= (uint64_t)((lbo >> 4) & 0x3FFF) << 16;
    d |= (uint64_t)((sbo >> 4) & 0x3FFF) << 32;
    d |= mode << 62;
    return d;
}
__device__ __forceinline__ void wgmma_fence() { asm volatile("wgmma.fence.sync.aligned;" ::: "memory"); }
__device__ __forceinline__ void wgmma_commit() { asm volatile("wgmma.commit_group.sync.aligned;" ::: "memory"); }
template <int N> __device__ __forceinline__ void wgmma_wait() {
    asm volatile("wgmma.wait_group.sync.aligned %0;" ::"n"(N) : "memory");
}

#define R8(a, i) "+f"(a[i + 0]), "+f"(a[i + 1]), "+f"(a[i + 2]), "+f"(a[i + 3]), "+f"(a[i + 4]), "+f"(a[i + 5]), "+f"(a[i + 6]), "+f"(a[i + 7])

__device__ __forceinline__ void wgmma_n256_k32(float* a, uint64_t da0, uint64_t da1, uint64_t db0, uint64_t db1, int scale_d) {
    asm volatile(
        "{\n.reg .pred p;\nsetp.ne.b32 p, %132, 0;\n"
        "wgmma.mma_async.sync.aligned.m64n256k16.f32.bf16.bf16 {%0,%1,%2,%3,%4,%5,%6,%7,%8,%9,%10,%11,%12,%13,%14,%15,%16,%17,%18,%19,%20,%21,%22,%23,%24,%25,%26,%27,%28,%29,%30,%31,%32,%33,%34,%35,%36,%37,%38,%39,%40,%41,%42,%43,%44,%45,%46,%47,%48,%49,%50,%51,%52,%53,%54,%55,%56,%57,%58,%59,%60,%61,%62,%63,%64,%65,%66,%67,%68,%69,%70,%71,%72,%73,%74,%75,%76,%77,%78,%79,%80,%81,%82,%83,%84,%85,%86,%87,%88,%89,%90,%91,%92,%93,%94,%95,%96,%97,%98,%99,%100,%101,%102,%103,%104,%105,%106,%107,%108,%109,%110,%111,%112,%113,%114,%115,%116,%117,%118,%119,%120,%121,%122,%123,%124,%125,%126,%127}, %128, %130, p, 1, 1, 0, 1;\n"
        "wgmma.mma_async.sync.aligned.m64n256k16.f32.bf16.bf16 {%0,%1,%2,%3,%4,%5,%6,%7,%8,%9,%10,%11,%12,%13,%14,%15,%16,%17,%18,%19,%20,%21,%22,%23,%24,%25,%26,%27,%28,%29,%30,%31,%32,%33,%34,%35,%36,%37,%38,%39,%40,%41,%42,%43,%44,%45,%46,%47,%48,%49,%50,%51,%52,%53,%54,%55,%56,%57,%58,%59,%60,%61,%62,%63,%64,%65,%66,%67,%68,%69,%70,%71,%72,%73,%74,%75,%76,%77,%78,%79,%80,%81,%82,%83,%84,%85,%86,%87,%88,%89,%90,%91,%92,%93,%94,%95,%96,%97,%98,%99,%100,%101,%102,%103,%104,%105,%106,%107,%108,%109,%110,%111,%112,%113,%114,%115,%116,%117,%118,%119,%120,%121,%122,%123,%124,%125,%126,%127}, %129, %131, 1, 1, 1, 0, 1;\n"
        "}\n"
        : R8(a, 0), R8(a, 8), R8(a, 16), R8(a, 24), R8(a, 32), R8(a, 40), R8(a, 48), R8(a, 56), R8(a, 64), R8(a, 72), R8(a, 80), R8(a, 88), R8(a, 96), R8(a, 104), R8(a, 112), R8(a, 120)
        : "l"(da0), "l"(da1), "l"(db0), "l"(db1), "r"(scale_d));
}
__device__ __forceinline__ void wgmma_n192_k32(float* a, uint64_t da0, uint64_t da1, uint64_t db0, uint64_t db1, int scale_d) {
    asm volatile(
        "{\n.reg .pred p;\nsetp.ne.b32 p, %100, 0;\n"
        "wgmma.mma_async.sync.aligned.m64n192k16.f32.bf16.bf16 {%0,%1,%2,%3,%4,%5,%6,%7,%8,%9,%10,%11,%12,%13,%14,%15,%16,%17,%18,%19,%20,%21,%22,%23,%24,%25,%26,%27,%28,%29,%30,%31,%32,%33,%34,%35,%36,%37,%38,%39,%40,%41,%42,%43,%44,%45,%46,%47,%48,%49,%50,%51,%52,%53,%54,%55,%56,%57,%58,%59,%60,%61,%62,%63,%64,%65,%66,%67,%68,%69,%70,%71,%72,%73,%74,%75,%76,%77,%78,%79,%80,%81,%82,%83,%84,%85,%86,%87,%88,%89,%90,%91,%92,%93,%94,%95}, %96, %98, p, 1, 1, 0, 1;\n"
        "wgmma.mma_async.sync.aligned.m64n192k16.f32.bf16.bf16 {%0,%1,%2,%3,%4,%5,%6,%7,%8,%9,%10,%11,%12,%13,%14,%15,%16,%17,%18,%19,%20,%21,%22,%23,%24,%25,%26,%27,%28,%29,%30,%31,%32,%33,%34,%35,%36,%37,%38,%39,%40,%41,%42,%43,%44,%45,%46,%47,%48,%49,%50,%51,%52,%53,%54,%55,%56,%57,%58,%59,%60,%61,%62,%63,%64,%65,%66,%67,%68,%69,%70,%71,%72,%73,%74,%75,%76,%77,%78,%79,%80,%81,%82,%83,%84,%85,%86,%87,%88,%89,%90,%91,%92,%93,%94,%95}, %97, %99, 1, 1, 1, 0, 1;\n"
        "}\n"
        : R8(a, 0), R8(a, 8), R8(a, 16), R8(a, 24), R8(a, 32), R8(a, 40), R8(a, 48), R8(a, 56), R8(a, 64), R8(a, 72), R8(a, 80), R8(a, 88)
        : "l"(da0), "l"(da1), "l"(db0), "l"(db1), "r"(scale_d));
}
__device__ __forceinline__ void wgmma_n128_k64(float* a, uint64_t da0, uint64_t da1, uint64_t da2, uint64_t da3,
                                               uint64_t db0, uint64_t db1, uint64_t db2, uint64_t db3, int scale_d) {
    asm volatile(
        "{\n.reg .pred p;\nsetp.ne.b32 p, %72, 0;\n"
        "wgmma.mma_async.sync.aligned.m64n128k16.f32.bf16.bf16 {%0,%1,%2,%3,%4,%5,%6,%7,%8,%9,%10,%11,%12,%13,%14,%15,%16,%17,%18,%19,%20,%21,%22,%23,%24,%25,%26,%27,%28,%29,%30,%31,%32,%33,%34,%35,%36,%37,%38,%39,%40,%41,%42,%43,%44,%45,%46,%47,%48,%49,%50,%51,%52,%53,%54,%55,%56,%57,%58,%59,%60,%61,%62,%63}, %64, %68, p, 1, 1, 0, 1;\n"
        "wgmma.mma_async.sync.aligned.m64n128k16.f32.bf16.bf16 {%0,%1,%2,%3,%4,%5,%6,%7,%8,%9,%10,%11,%12,%13,%14,%15,%16,%17,%18,%19,%20,%21,%22,%23,%24,%25,%26,%27,%28,%29,%30,%31,%32,%33,%34,%35,%36,%37,%38,%39,%40,%41,%42,%43,%44,%45,%46,%47,%48,%49,%50,%51,%52,%53,%54,%55,%56,%57,%58,%59,%60,%61,%62,%63}, %65, %69, 1, 1, 1, 0, 1;\n"
        "wgmma.mma_async.sync.aligned.m64n128k16.f32.bf16.bf16 {%0,%1,%2,%3,%4,%5,%6,%7,%8,%9,%10,%11,%12,%13,%14,%15,%16,%17,%18,%19,%20,%21,%22,%23,%24,%25,%26,%27,%28,%29,%30,%31,%32,%33,%34,%35,%36,%37,%38,%39,%40,%41,%42,%43,%44,%45,%46,%47,%48,%49,%50,%51,%52,%53,%54,%55,%56,%57,%58,%59,%60,%61,%62,%63}, %66, %70, 1, 1, 1, 0, 1;\n"
        "wgmma.mma_async.sync.aligned.m64n128k16.f32.bf16.bf16 {%0,%1,%2,%3,%4,%5,%6,%7,%8,%9,%10,%11,%12,%13,%14,%15,%16,%17,%18,%19,%20,%21,%22,%23,%24,%25,%26,%27,%28,%29,%30,%31,%32,%33,%34,%35,%36,%37,%38,%39,%40,%41,%42,%43,%44,%45,%46,%47,%48,%49,%50,%51,%52,%53,%54,%55,%56,%57,%58,%59,%60,%61,%62,%63}, %67, %71, 1, 1, 1, 0, 1;\n"
        "}\n"
        : R8(a, 0), R8(a, 8), R8(a, 16), R8(a, 24), R8(a, 32), R8(a, 40), R8(a, 48), R8(a, 56)
        : "l"(da0), "l"(da1), "l"(da2), "l"(da3), "l"(db0), "l"(db1), "l"(db2), "l"(db3), "r"(scale_d));
}

__device__ __forceinline__ float bf16_round(float x) { return __bfloat162float(__float2bfloat16_rn(x)); }
__device__ __forceinline__ uint32_t pack_bf16(float lo, float hi) {
    __nv_bfloat162 v = __floats2bfloat162_rn(lo, hi);
    return *reinterpret_cast<uint32_t*>(&v);
}
__device__ __forceinline__ float bf_lo(uint32_t v) { return __uint_as_float(v << 16); }
__device__ __forceinline__ float bf_hi(uint32_t v) { return __uint_as_float(v & 0xFFFF0000u); }

constexpr int LN_ROWS = 16;
__global__ void __launch_bounds__(256) ln_kernel(const __nv_bfloat16* __restrict__ x,
                                                  const __nv_bfloat16* __restrict__ wg,
                                                  const __nv_bfloat16* __restrict__ wu,
                                                  const __nv_bfloat16* __restrict__ wd) {
    pdl_launch();
    if (threadIdx.x == 0) STAMP(0, 0);
    __shared__ __align__(16) __nv_bfloat16 tile[LN_ROWS][D_ + 8];
    const int warp = threadIdx.x >> 5, lane = threadIdx.x & 31;
    const int row0 = blockIdx.x * LN_ROWS;
    {
        const int lines_per = (D_ * F_ * 2) / 128 / 128;
        if (threadIdx.x < lines_per) {
            size_t off = ((size_t)blockIdx.x * lines_per + threadIdx.x) * 128;
            asm volatile("prefetch.global.L2 [%0];" ::"l"((const char*)wg + off));
            asm volatile("prefetch.global.L2 [%0];" ::"l"((const char*)wu + off));
            asm volatile("prefetch.global.L2 [%0];" ::"l"((const char*)wd + off));
        }
    }
    uint4 v[2][2];
#pragma unroll
    for (int r = 0; r < 2; r++) {
        const __nv_bfloat16* xr = x + (size_t)(row0 + warp * 2 + r) * D_;
        v[r][0] = *reinterpret_cast<const uint4*>(xr + lane * 8);
        v[r][1] = *reinterpret_cast<const uint4*>(xr + 256 + lane * 8);
    }
#pragma unroll
    for (int r = 0; r < 2; r++) {
        float f[16];
        const uint32_t* w = reinterpret_cast<const uint32_t*>(&v[r][0]);
#pragma unroll
        for (int i = 0; i < 8; i++) { f[2 * i] = bf_lo(w[i]); f[2 * i + 1] = bf_hi(w[i]); }
        float s = 0.f;
#pragma unroll
        for (int i = 0; i < 16; i++) s += f[i];
#pragma unroll
        for (int o = 16; o > 0; o >>= 1) s += __shfl_xor_sync(0xffffffffu, s, o);
        const float mean = s * (1.0f / D_);
        float q = 0.f;
#pragma unroll
        for (int i = 0; i < 16; i++) { float d = f[i] - mean; q += d * d; }
#pragma unroll
        for (int o = 16; o > 0; o >>= 1) q += __shfl_xor_sync(0xffffffffu, q, o);
        const float mb = bf16_round(mean);
        const float vb = bf16_round(q * (1.0f / D_));
        const float den = bf16_round(sqrtf(bf16_round(vb + 1e-5f)));
        uint32_t o[8];
#pragma unroll
        for (int i = 0; i < 8; i++) {
            float a = __fdiv_rn(bf16_round(f[2 * i] - mb), den);
            float b = __fdiv_rn(bf16_round(f[2 * i + 1] - mb), den);
            o[i] = pack_bf16(a, b);
        }
        const int rr = warp * 2 + r;
        __nv_bfloat16* dst = g_xn + (size_t)(row0 + rr) * D_;
        *reinterpret_cast<uint4*>(dst + lane * 8) = make_uint4(o[0], o[1], o[2], o[3]);
        *reinterpret_cast<uint4*>(dst + 256 + lane * 8) = make_uint4(o[4], o[5], o[6], o[7]);
        *reinterpret_cast<uint4*>(&tile[rr][lane * 8]) = make_uint4(o[0], o[1], o[2], o[3]);
        *reinterpret_cast<uint4*>(&tile[rr][256 + lane * 8]) = make_uint4(o[4], o[5], o[6], o[7]);
    }
    __syncthreads();
    if (threadIdx.x == 0) STAMP(0, 1);
#pragma unroll
    for (int cc = 0; cc < 2; cc++) {
        const int c = threadIdx.x + cc * 256;
        uint32_t o[8];
#pragma unroll
        for (int i = 0; i < 8; i++) {
            uint32_t lo = *reinterpret_cast<const uint16_t*>(&tile[2 * i][c]);
            uint32_t hi = *reinterpret_cast<const uint16_t*>(&tile[2 * i + 1][c]);
            o[i] = lo | (hi << 16);
        }
        __nv_bfloat16* dst = g_xnT + (size_t)c * L_ + row0;
        *reinterpret_cast<uint4*>(dst) = make_uint4(o[0], o[1], o[2], o[3]);
        *reinterpret_cast<uint4*>(dst + 8) = make_uint4(o[4], o[5], o[6], o[7]);
    }
    if (threadIdx.x == 0) STAMP(0, 2);
}

struct cplx { float r, i; };
__device__ __forceinline__ cplx cmul(cplx a, cplx b) {
    cplx c; c.r = a.r * b.r - a.i * b.i; c.i = a.r * b.i + a.i * b.r; return c;
}
__device__ __forceinline__ cplx csq(cplx a) {
    cplx c; c.r = a.r * a.r - a.i * a.i; c.i = 2.0f * a.r * a.i; return c;
}
__device__ __forceinline__ cplx cexp_m(float ar, float ai, float m) {
    float mag;
    float e = (ar * m) * 1.4426950408889634f;
    asm("ex2.approx.ftz.f32 %0, %1;" : "=f"(mag) : "f"(e));
    float rr = (ai * m) * 0.15915494309189535f;
    rr -= rintf(rr);
    float th = rr * 6.283185307179586f;
    cplx c; c.r = mag * __cosf(th); c.i = mag * __sinf(th);
    return c;
}
__device__ __forceinline__ uint32_t to_tf32(float x) {
    uint32_t r; asm("cvt.rna.tf32.f32 %0, %1;" : "=r"(r) : "f"(x)); return r;
}
__device__ __forceinline__ void mma_tf32(float* c, uint32_t a0, uint32_t a1, uint32_t a2, uint32_t a3, uint32_t b0, uint32_t b1) {
    asm volatile("mma.sync.aligned.m16n8k8.row.col.f32.tf32.tf32.f32 {%0,%1,%2,%3}, {%4,%5,%6,%7}, {%8,%9}, {%0,%1,%2,%3};"
                 : "+f"(c[0]), "+f"(c[1]), "+f"(c[2]), "+f"(c[3])
                 : "r"(a0), "r"(a1), "r"(a2), "r"(a3), "r"(b0), "r"(b1));
}
__device__ __forceinline__ void mma_bf16(float* c, uint32_t a0, uint32_t a1, uint32_t a2, uint32_t a3, uint32_t b0, uint32_t b1) {
    asm volatile("mma.sync.aligned.m16n8k16.row.col.f32.bf16.bf16.f32 {%0,%1,%2,%3}, {%4,%5,%6,%7}, {%8,%9}, {%0,%1,%2,%3};"
                 : "+f"(c[0]), "+f"(c[1]), "+f"(c[2]), "+f"(c[3])
                 : "r"(a0), "r"(a1), "r"(a2), "r"(a3), "r"(b0), "r"(b1));
}
__device__ __forceinline__ void named_bar(int id, int n) { asm volatile("bar.sync %0, %1;" ::"r"(id), "r"(n) : "memory"); }

constexpr int CV_CH = 4;
constexpr int CV_CONST_B = NS_ * 12 * 4;
constexpr int CV_KV_B = 648 * 4;
constexpr int CV_Q_B = (L_ + 16) * 4;
constexpr int CV_U_B = (L_ + 128) * 2;
constexpr int CV_PER_CH = CV_CONST_B + 2 * CV_KV_B + CV_Q_B + CV_U_B;
constexpr int CV_SMEM = CV_CH * CV_PER_CH;

__global__ void __launch_bounds__(256) conv_kernel(const __nv_bfloat16* __restrict__ A_re, const __nv_bfloat16* __restrict__ A_im,
                                                    const __nv_bfloat16* __restrict__ B_re, const __nv_bfloat16* __restrict__ B_im,
                                                    const __nv_bfloat16* __restrict__ C_re, const __nv_bfloat16* __restrict__ C_im,
                                                    const __nv_bfloat16* __restrict__ log_dt, const __nv_bfloat16* __restrict__ Dskip) {
    pdl_launch();
    if (threadIdx.x == 0) STAMP(1, 0);
    extern __shared__ __align__(16) uint8_t smem[];
    const int warp = threadIdx.x >> 5, lane = threadIdx.x & 31;
    const int ch = warp >> 1, h = warp & 1;
    const int d = blockIdx.x * CV_CH + ch;
    const int g = lane >> 2, t = lane & 3;
    uint8_t* base = smem + ch * CV_PER_CH;
    float4* s_const = reinterpret_cast<float4*>(base);
    float* s_kv = reinterpret_cast<float*>(base + CV_CONST_B);
    uint32_t* s_q = reinterpret_cast<uint32_t*>(base + CV_CONST_B + 2 * CV_KV_B);
    __nv_bfloat16* s_u = reinterpret_cast<__nv_bfloat16*>(base + CV_CONST_B + 2 * CV_KV_B + CV_Q_B);
    const int bar_id = 1 + ch;

    const float dt = bf16_round(expf(__bfloat162float(log_dt[d])));
    float tail = 0.f;
    {
        const int n0 = h * 64 + lane * 2;
        const size_t off = (size_t)d * NS_ + n0;
        uint32_t war = *reinterpret_cast<const uint32_t*>(A_re + off);
        uint32_t wai = *reinterpret_cast<const uint32_t*>(A_im + off);
        uint32_t wbr = *reinterpret_cast<const uint32_t*>(B_re + off);
        uint32_t wbi = *reinterpret_cast<const uint32_t*>(B_im + off);
        uint32_t wcr = *reinterpret_cast<const uint32_t*>(C_re + off);
        uint32_t wci = *reinterpret_cast<const uint32_t*>(C_im + off);
#pragma unroll
        for (int j = 0; j < 2; j++) {
            float ar = dt * (j ? bf_hi(war) : bf_lo(war));
            float ai = dt * (j ? bf_hi(wai) : bf_lo(wai));
            cplx db = {dt * (j ? bf_hi(wbr) : bf_lo(wbr)), dt * (j ? bf_hi(wbi) : bf_lo(wbi))};
            cplx cc = {(j ? bf_hi(wcr) : bf_lo(wcr)), (j ? bf_hi(wci) : bf_lo(wci))};
            cplx cb = cmul(cc, db);
            cplx e128 = cexp_m(ar, ai, 128.f);
            cplx c256 = cmul(cb, cexp_m(ar, ai, 256.f));
            cplx c512 = cmul(cb, cexp_m(ar, ai, 512.f));
            cplx c1024 = cmul(cb, cexp_m(ar, ai, 1024.f));
            cplx c2048 = cmul(cb, cexp_m(ar, ai, 2048.f));
            tail += c2048.r;
            s_const[(n0 + j) * 3 + 0] = make_float4(ar, ai, cb.r, cb.i);
            s_const[(n0 + j) * 3 + 1] = make_float4(e128.r, e128.i, c256.r, c256.i);
            s_const[(n0 + j) * 3 + 2] = make_float4(c512.r, c512.i, c1024.r, c1024.i);
        }
#pragma unroll
        for (int o = 16; o > 0; o >>= 1) tail += __shfl_xor_sync(0xffffffffu, tail, o);
    }
    __syncwarp();
    if (threadIdx.x == 0) STAMP(1, 1);
    {
        float acc[5][4];
#pragma unroll
        for (int i = 0; i < 5; i++) { acc[i][0] = acc[i][1] = acc[i][2] = acc[i][3] = 0.f; }
        const float gf = (float)g;
#pragma unroll 2
        for (int s = 0; s < 16; s++) {
            const int n = h * 64 + s * 4 + t;
            const float4 k0 = s_const[n * 3 + 0], k1 = s_const[n * 3 + 1], k2 = s_const[n * 3 + 2];
            const cplx cb = {k0.z, k0.w}, e128 = {k1.x, k1.y}, c256 = {k1.z, k1.w}, c512 = {k2.x, k2.y}, c1024 = {k2.z, k2.w};
            cplx p1 = cexp_m(k0.x, k0.y, gf);
            cplx p1b = cexp_m(k0.x, k0.y, gf + 8.f);
            cplx r16a = cexp_m(k0.x, k0.y, gf * 16.f);
            cplx r16b = cmul(r16a, e128);
            cplx p2 = csq(p1), p4 = csq(p2), p8 = csq(p4);
            cplx r32a = csq(r16a), r32b = csq(r16b), r64a = csq(r32a), r64b = csq(r32b);
            cplx f0a = cmul(cb, p1), f0b = cmul(cb, p1b), f1 = cmul(c256, p2), f2 = cmul(c512, p4), f3 = cmul(c1024, p8);
            {
                uint32_t a0 = to_tf32(r16a.r), a1 = to_tf32(r16b.r), a2 = to_tf32(-r16a.i), a3 = to_tf32(-r16b.i);
                mma_tf32(acc[0], a0, a1, a2, a3, to_tf32(f0a.r), to_tf32(f0a.i));
                mma_tf32(acc[1], a0, a1, a2, a3, to_tf32(f0b.r), to_tf32(f0b.i));
                mma_tf32(acc[2], a0, a1, a2, a3, to_tf32(f1.r), to_tf32(f1.i));
            }
            mma_tf32(acc[3], to_tf32(r32a.r), to_tf32(r32b.r), to_tf32(-r32a.i), to_tf32(-r32b.i), to_tf32(f2.r), to_tf32(f2.i));
            mma_tf32(acc[4], to_tf32(r64a.r), to_tf32(r64b.r), to_tf32(-r64a.i), to_tf32(-r64b.i), to_tf32(f3.r), to_tf32(f3.i));
        }
        float* kv = s_kv + h * 648;
        *reinterpret_cast<float2*>(kv + 16 * g + 2 * t) = make_float2(acc[0][0], acc[0][1]);
        *reinterpret_cast<float2*>(kv + 16 * (g + 8) + 2 * t) = make_float2(acc[0][2], acc[0][3]);
        *reinterpret_cast<float2*>(kv + 16 * g + 8 + 2 * t) = make_float2(acc[1][0], acc[1][1]);
        *reinterpret_cast<float2*>(kv + 16 * (g + 8) + 8 + 2 * t) = make_float2(acc[1][2], acc[1][3]);
#pragma unroll
        for (int sg = 0; sg < 3; sg++) {
            *reinterpret_cast<float2*>(kv + 256 + 128 * sg + 8 * g + 2 * t) = make_float2(acc[2 + sg][0], acc[2 + sg][1]);
            *reinterpret_cast<float2*>(kv + 256 + 128 * sg + 8 * (g + 8) + 2 * t) = make_float2(acc[2 + sg][2], acc[2 + sg][3]);
        }
        if (lane == 0) kv[640] = tail;
    }
    named_bar(bar_id, 64);
    if (threadIdx.x == 0) STAMP(1, 2);
    {
        const int tid2 = h * 32 + lane;
        if (tid2 < 16) s_q[tid2] = 0u;
        for (int x = tid2; x < L_; x += 64) {
            float kc, kp;
            {
                int s = (x >= 1024) ? 3 : (x >= 512) ? 2 : (x >= 256) ? 1 : 0;
                int rq = (s == 0) ? x : ((x + (1 << (s - 1)) - 1 + ((x >> s) & 1)) >> s);
                int idx = 128 * s + rq;
                kc = s_kv[idx] + s_kv[648 + idx];
            }
            {
                int y = x - 1;
                if (y < 0) kp = 0.f;
                else {
                    int s = (y >= 1024) ? 3 : (y >= 512) ? 2 : (y >= 256) ? 1 : 0;
                    int rq = (s == 0) ? y : ((y + (1 << (s - 1)) - 1 + ((y >> s) & 1)) >> s);
                    int idx = 128 * s + rq;
                    kp = s_kv[idx] + s_kv[648 + idx];
                }
            }
            s_q[x + 16] = pack_bf16(kc, kp);
        }
    }
    if (threadIdx.x == 0) STAMP(1, 3);
    pdl_wait();
    if (threadIdx.x == 0) STAMP(1, 4);
    {
        const int tid2 = h * 32 + lane;
        if (tid2 < 16) *reinterpret_cast<uint4*>(s_u + tid2 * 8) = make_uint4(0, 0, 0, 0);
        const uint4* src = reinterpret_cast<const uint4*>(g_xnT + (size_t)d * L_);
#pragma unroll
        for (int i = 0; i < 4; i++) {
            *reinterpret_cast<uint4*>(s_u + 128 + (tid2 + i * 64) * 8) = src[tid2 + i * 64];
        }
    }
    named_bar(bar_id, 64);
    if (threadIdx.x == 0) STAMP(1, 5);
    float acc[16][4];
#pragma unroll
    for (int i = 0; i < 16; i++) { acc[i][0] = acc[i][1] = acc[i][2] = acc[i][3] = 0.f; }
    const uint32_t su_addr = smem_u32(s_u);
    for (int rr = 0; rr < 4; rr++) {
        const int r = h * 4 + rr;
        uint32_t ub[16][2];
        {
            const int mi = lane >> 3, rowi = lane & 7;
            uint32_t addr = su_addr + (uint32_t)((128 + 16 * (8 * (mi >> 1) + rowi - r) + 8 * (mi & 1)) * 2);
#pragma unroll
            for (int j = 0; j < 16; j += 2) {
                asm volatile("ldmatrix.sync.aligned.m8n8.x4.shared.b16 {%0,%1,%2,%3}, [%4];"
                             : "=r"(ub[j][0]), "=r"(ub[j][1]), "=r"(ub[j + 1][0]), "=r"(ub[j + 1][1])
                             : "r"(addr + (uint32_t)(j * 8 * 16 * 2)));
            }
        }
        const uint32_t* qp = s_q + 16 + 16 * r + g - 2 * t;
#pragma unroll
        for (int q = 0; q < 16; q++) {
            const uint32_t a0 = qp[128 * q], a1 = qp[128 * q + 8], a2 = qp[128 * q - 8];
#pragma unroll
            for (int nt = q; nt < 16; nt++) mma_bf16(acc[nt], a0, a1, a2, a0, ub[nt - q][0], ub[nt - q][1]);
        }
    }
    if (threadIdx.x == 0) STAMP(1, 6);
    named_bar(bar_id, 64);
    {
        float4* xch = reinterpret_cast<float4*>(base) + h * 256;
        if (h) {
#pragma unroll
            for (int i = 0; i < 8; i++) xch[i * 32 + lane] = make_float4(acc[i][0], acc[i][1], acc[i][2], acc[i][3]);
        } else {
#pragma unroll
            for (int i = 0; i < 8; i++) xch[i * 32 + lane] = make_float4(acc[8 + i][0], acc[8 + i][1], acc[8 + i][2], acc[8 + i][3]);
        }
    }
    named_bar(bar_id, 64);
    {
        const float4* xch = reinterpret_cast<const float4*>(base) + (h ^ 1) * 256;
        const float dsk = __bfloat162float(Dskip[d]);
        __nv_bfloat16* stg = reinterpret_cast<__nv_bfloat16*>(s_q);
#pragma unroll
        for (int i = 0; i < 8; i++) {
            float4 o = xch[i * 32 + lane];
            float y[4];
            if (h) { y[0] = acc[8 + i][0] + o.x; y[1] = acc[8 + i][1] + o.y; y[2] = acc[8 + i][2] + o.z; y[3] = acc[8 + i][3] + o.w; }
            else   { y[0] = acc[i][0] + o.x; y[1] = acc[i][1] + o.y; y[2] = acc[i][2] + o.z; y[3] = acc[i][3] + o.w; }
            const int nt = h * 8 + i;
#pragma unroll
            for (int e = 0; e < 4; e++) {
                const int tau = 16 * (8 * nt + 2 * t + (e & 1)) + g + 8 * (e >> 1);
                float u = __bfloat162float(s_u[128 + tau]);
                float sv = bf16_round(y[e]) + bf16_round(u * dsk);
                stg[tau] = __float2bfloat16_rn(sv);
            }
        }
        __syncwarp();
        uint4* dst = reinterpret_cast<uint4*>(g_sT + (size_t)d * L_ + h * 1024);
        const uint4* srcp = reinterpret_cast<const uint4*>(stg + h * 1024);
#pragma unroll
        for (int i = 0; i < 4; i++) dst[i * 32 + lane] = srcp[i * 32 + lane];
    }
    if (threadIdx.x == 0) STAMP(1, 7);
}

__device__ __forceinline__ uint32_t cluster_rank() { uint32_t r; asm volatile("mov.u32 %0, %%cluster_ctarank;" : "=r"(r)); return r; }
__device__ __forceinline__ void cluster_sync_all() {
    asm volatile("barrier.cluster.arrive.release.aligned;\nbarrier.cluster.wait.acquire.aligned;" ::: "memory");
}
__device__ __forceinline__ void mbar_arrive_remote(uint32_t bar, uint32_t cta) {
    asm volatile("{\n.reg .b32 ra;\nmapa.shared::cluster.u32 ra, %0, %1;\n"
                 "mbarrier.arrive.shared::cluster.b64 _, [ra];\n}\n" ::"r"(bar), "r"(cta) : "memory");
}
__device__ __forceinline__ void tma_load_2d_mc(uint32_t dst, const CUtensorMap* tm, int c0, int c1, uint32_t bar, uint16_t mask) {
    asm volatile(
        "cp.async.bulk.tensor.2d.shared::cluster.global.mbarrier::complete_tx::bytes.multicast::cluster [%0], [%1, {%3, %4}], [%2], %5;"
        ::"r"(dst), "l"((uint64_t)tm), "r"(bar), "r"(c0), "r"(c1), "h"(mask) : "memory");
}
__device__ __forceinline__ void tma_store_2d(const CUtensorMap* tm, uint32_t src, int c0, int c1) {
    asm volatile("cp.async.bulk.tensor.2d.global.shared::cta.bulk_group [%0, {%2, %3}], [%1];"
                 ::"l"((uint64_t)tm), "r"(src), "r"(c0), "r"(c1) : "memory");
}
__device__ __forceinline__ void bulk_commit() { asm volatile("cp.async.bulk.commit_group;" ::: "memory"); }
template <int N> __device__ __forceinline__ void bulk_wait_read() { asm volatile("cp.async.bulk.wait_group.read %0;" ::"n"(N) : "memory"); }
template <int N> __device__ __forceinline__ void bulk_wait() { asm volatile("cp.async.bulk.wait_group %0;" ::"n"(N) : "memory"); }
__device__ __forceinline__ void fence_async_smem() { asm volatile("fence.proxy.async.shared::cta;" ::: "memory"); }
__device__ __forceinline__ void stmatrix_x4(uint32_t addr, uint32_t r0, uint32_t r1, uint32_t r2, uint32_t r3) {
    asm volatile("stmatrix.sync.aligned.m8n8.x4.shared.b16 [%0], {%1,%2,%3,%4};" ::"r"(addr), "r"(r0), "r"(r1), "r"(r2), "r"(r3) : "memory");
}

constexpr int G1_STAGES = 5;
constexpr int G1_A_BYTES = 8 * 16384;
constexpr int G1_B_STAGE = 16384;
constexpr int G1_STG = 8 * 1024;
constexpr int G1_SMEM = G1_A_BYTES + G1_STAGES * G1_B_STAGE + G1_STG + 1024 + 256;
constexpr int G1_ITERS = 32;

__device__ __forceinline__ void tma_load_3d(uint32_t dst, const CUtensorMap* tm, int c0, int c1, int c2, uint32_t bar) {
    asm volatile(
        "cp.async.bulk.tensor.3d.shared::cluster.global.mbarrier::complete_tx::bytes [%0], [%1, {%3, %4, %5}], [%2];"
        ::"r"(dst), "l"((uint64_t)tm), "r"(bar), "r"(c0), "r"(c1), "r"(c2) : "memory");
}

__device__ __forceinline__ float gelu_tanh(float x) {
    float u = x * (0.7978845608028654f + 0.035677408136300125f * x * x);
    float t; asm("tanh.approx.f32 %0, %1;" : "=f"(t) : "f"(u));
    float hx = 0.5f * x;
    return fmaf(hx, t, hx);
}
__device__ __forceinline__ uint32_t geglu_pair(uint32_t p0, uint32_t p1) {
    float a = bf16_round(gelu_tanh(bf_lo(p0))) * bf_hi(p0);
    float b = bf16_round(gelu_tanh(bf_lo(p1))) * bf_hi(p1);
    return pack_bf16(a, b);
}

__global__ void __launch_bounds__(384, 1) gemm1_kernel(const __grid_constant__ CUtensorMap tm_xn,
                                                        const __grid_constant__ CUtensorMap tm_wg4,
                                                        const __grid_constant__ CUtensorMap tm_wu4,
                                                        const __grid_constant__ CUtensorMap tm_wg3,
                                                        const __grid_constant__ CUtensorMap tm_wu3,
                                                        const __grid_constant__ CUtensorMap tm_hst) {
    pdl_launch();
    if (threadIdx.x == 0) STAMP(2, 0);
    extern __shared__ uint8_t smem_raw[];
    const uint32_t sbase = (smem_u32(smem_raw) + 1023) & ~1023u;
    const uint32_t sA = sbase, sB = sbase + G1_A_BYTES, sStg = sB + G1_STAGES * G1_B_STAGE, sBar = sStg + G1_STG;
    const uint32_t bar_a = sBar, bar_full = sBar + 64, bar_empty = sBar + 64 + 8 * G1_STAGES;
    const int rb = blockIdx.x >> 3, cj = blockIdx.x & 7;
    const int warp = threadIdx.x >> 5, lane = threadIdx.x & 31;

    if (threadIdx.x == 0) {
        for (int i = 0; i < 8; i++) mbar_init(bar_a + 8 * i, 1);
        for (int i = 0; i < G1_STAGES; i++) { mbar_init(bar_full + 8 * i, 1); mbar_init(bar_empty + 8 * i, 8); }
        asm volatile("fence.mbarrier_init.release.cluster;" ::: "memory");
    }
    __syncthreads();

    if (warp >= 8) {
        asm volatile("setmaxnreg.dec.sync.aligned.u32 40;");
        if (lane == 0) {
            const int pw = warp - 8;
            if (pw == 0) { prefetch_tmap(&tm_wg4); prefetch_tmap(&tm_wu4); prefetch_tmap(&tm_xn); }
            if (pw == 1) { prefetch_tmap(&tm_wg3); prefetch_tmap(&tm_wu3); prefetch_tmap(&tm_hst); }
            for (int it = pw; it < G1_ITERS; it += 4) {
                const int s = it % G1_STAGES, kb = it & 15;
                if (it >= G1_STAGES) mbar_wait(bar_empty + 8 * s, ((it / G1_STAGES) - 1) & 1);
                const uint32_t dst = sB + s * G1_B_STAGE;
                if (it < 16) {
                    mbar_expect_tx(bar_full + 8 * s, 16384);
                    tma_load_3d(dst, &tm_wg4, 0, kb * 32, cj * 7, bar_full + 8 * s);
                    tma_load_3d(dst + 8192, &tm_wu4, 0, kb * 32, cj * 7, bar_full + 8 * s);
                } else {
                    mbar_expect_tx(bar_full + 8 * s, 12288);
                    tma_load_3d(dst, &tm_wg3, 0, kb * 32, cj * 7 + 4, bar_full + 8 * s);
                    tma_load_3d(dst + 6144, &tm_wu3, 0, kb * 32, cj * 7 + 4, bar_full + 8 * s);
                }
                if (it < 4) {
                    pdl_wait();
                    if (pw == 0) STAMP(2, 1);
                    for (int k = pw; k < 8; k += 4) {
                        mbar_expect_tx(bar_a + 8 * k, 16384);
                        tma_load_2d(sA + k * 16384, &tm_xn, k * 64, rb * 128, bar_a + 8 * k);
                    }
                }
            }
        }
    } else {
        asm volatile("setmaxnreg.inc.sync.aligned.u32 232;");
        const int wg = __shfl_sync(0xffffffffu, (int)(threadIdx.x >> 7), 0);
        float r[160];
        const int row0 = rb * 128 + wg * 64 + (warp & 3) * 16;
        const uint64_t descA = make_desc(sA + wg * 8192, 16, 1024);
        const uint64_t descB = make_desc(sB, 2048, 512, 2);
        const uint32_t stg = sStg + warp * 1024;
        const uint32_t st_off = (uint32_t)(((lane & 7) + ((lane >> 3) & 1) * 8) * 32 + (lane >> 4) * 16);
        auto store_group = [&](const float* pk, int par, int col) {
            const uint32_t buf = stg + par * 512;
            uint32_t r0 = geglu_pair(__float_as_uint(pk[0]), __float_as_uint(pk[1]));
            uint32_t r1 = geglu_pair(__float_as_uint(pk[2]), __float_as_uint(pk[3]));
            uint32_t r2 = geglu_pair(__float_as_uint(pk[4]), __float_as_uint(pk[5]));
            uint32_t r3 = geglu_pair(__float_as_uint(pk[6]), __float_as_uint(pk[7]));
            if (lane == 0) bulk_wait_read<1>();
            __syncwarp();
            stmatrix_x4(buf + st_off, r0, r1, r2, r3);
            fence_async_smem();
            __syncwarp();
            if (lane == 0) { tma_store_2d(&tm_hst, buf, col, row0); bulk_commit(); }
        };
#pragma unroll
        for (int kb = 0; kb < 16; kb++) {
            const int it = kb, s = it % G1_STAGES;
            if ((kb & 1) == 0) mbar_wait(bar_a + 8 * (kb >> 1), 0);
            mbar_wait(bar_full + 8 * s, (it / G1_STAGES) & 1);
            if (threadIdx.x == 0 && (it & 7) == 0) STAMP(2, 2 + it / 8);
            wgmma_fence();
            const uint64_t da = descA + (uint64_t)(((kb >> 1) * 16384 + (kb & 1) * 64) >> 4);
            const uint64_t db = descB + (uint64_t)((s * G1_B_STAGE) >> 4);
            wgmma_n256_k32(r, da, da + 2, db, db + 64, kb != 0);
            wgmma_commit();
            if (kb > 0) {
                wgmma_wait<1>();
                if (lane == 0) mbar_arrive(bar_empty + 8 * ((it - 1) % G1_STAGES));
            }
        }
        wgmma_wait<0>();
        if (lane == 0) mbar_arrive(bar_empty + 8 * (15 % G1_STAGES));
#pragma unroll
        for (int i = 0; i < 32; i++) r[128 + i] = __uint_as_float(pack_bf16(r[i], r[64 + i]));
#pragma unroll
        for (int i = 32; i < 64; i++) r[64 + i] = __uint_as_float(pack_bf16(r[i], r[64 + i]));
#pragma unroll
        for (int kb = 0; kb < 16; kb++) {
            const int it = 16 + kb, s = it % G1_STAGES;
            mbar_wait(bar_full + 8 * s, (it / G1_STAGES) & 1);
            if (threadIdx.x == 0 && (it & 7) == 0) STAMP(2, 2 + it / 8);
            wgmma_fence();
            const uint64_t da = descA + (uint64_t)(((kb >> 1) * 16384 + (kb & 1) * 64) >> 4);
            const uint64_t db = descB + (uint64_t)((s * G1_B_STAGE) >> 4);
            wgmma_n192_k32(r, da, da + 2, db, db + 64, kb != 0);
            wgmma_commit();
            if ((kb & 1) == 0) {
                const int jj = kb >> 1;
                store_group(jj < 4 ? &r[128 + 8 * jj] : &r[64 + 8 * jj], jj & 1, cj * 224 + jj * 16);
            }
            if (kb > 0 && it - 1 + G1_STAGES < G1_ITERS) {
                wgmma_wait<1>();
                if (lane == 0) mbar_arrive(bar_empty + 8 * ((it - 1) % G1_STAGES));
            }
        }
        wgmma_wait<0>();
#pragma unroll
        for (int i = 0; i < 48; i++) r[i] = __uint_as_float(pack_bf16(r[i], r[48 + i]));
        if (threadIdx.x == 0) STAMP(2, 6);
#pragma unroll
        for (int jj = 0; jj < 6; jj++) store_group(&r[8 * jj], jj & 1, cj * 224 + 128 + jj * 16);
        if (lane == 0) bulk_wait_read<0>();
        if (threadIdx.x == 0) STAMP(2, 7);
    }
}

constexpr int G2_STAGES = 5;
constexpr int G2_STAGE = 16384 + 16384;
constexpr int G2_XCH = 32768;
constexpr int G2_EPI = 16384 + 16384;
constexpr int G2_SMEM = G2_STAGES * G2_STAGE + G2_XCH + G2_EPI + 1024 + 256;
constexpr int G2_KB = F_ / 64 / 2;

__global__ void __launch_bounds__(384, 1) gemm2_kernel(const __grid_constant__ CUtensorMap tm_h,
                                                        const __grid_constant__ CUtensorMap tm_wd,
                                                        const __grid_constant__ CUtensorMap tm_x,
                                                        const __grid_constant__ CUtensorMap tm_sT,
                                                        const __grid_constant__ CUtensorMap tm_out) {
    if (threadIdx.x == 0) STAMP(3, 0);
    extern __shared__ uint8_t smem_raw[];
    const uint32_t sbase = (smem_u32(smem_raw) + 1023) & ~1023u;
    const uint32_t sXch = sbase + G2_STAGES * G2_STAGE, sX = sXch + G2_XCH, sS = sX + 16384, sBar = sX + G2_EPI;
    const uint32_t bar_full = sBar, bar_empty = sBar + 8 * G2_STAGES, bar_epi = sBar + 16 * G2_STAGES;
    const uint32_t kh = cluster_rank();
    const int cid = blockIdx.x >> 1;
    const int rb = cid >> 2, nb = cid & 3;
    const int col_fin = nb * 128 + kh * 64;
    const int warp = threadIdx.x >> 5, lane = threadIdx.x & 31;

    if (threadIdx.x == 0) {
        for (int i = 0; i < G2_STAGES; i++) { mbar_init(bar_full + 8 * i, 1); mbar_init(bar_empty + 8 * i, 8); }
        mbar_init(bar_epi, 1);
        asm volatile("fence.mbarrier_init.release.cluster;" ::: "memory");
    }
    __syncthreads();

    if (warp >= 8) {
        if (lane == 0) {
            const int pw = warp - 8;
            const int k0 = kh * G2_KB;
            if (pw == 0) { prefetch_tmap(&tm_wd); prefetch_tmap(&tm_h); }
            if (pw == 1) { prefetch_tmap(&tm_x); prefetch_tmap(&tm_sT); prefetch_tmap(&tm_out); }
            for (int it = pw; it < G2_STAGES; it += 4) {
                mbar_expect_tx(bar_full + 8 * it, G2_STAGE);
                tma_load_3d(sbase + it * G2_STAGE + 16384, &tm_wd, 0, (k0 + it) * 64, nb * 2, bar_full + 8 * it);
            }
            if (pw == 3) {
                mbar_expect_tx(bar_epi, G2_EPI);
                tma_load_2d(sX, &tm_x, col_fin, rb * 128, bar_epi);
            }
            pdl_wait();
            if (pw == 0) STAMP(3, 1);
            for (int it = pw; it < G2_STAGES; it += 4)
                tma_load_2d(sbase + it * G2_STAGE, &tm_h, (k0 + it) * 64, rb * 128, bar_full + 8 * it);
            if (pw == 3) {
                tma_load_2d(sS, &tm_sT, rb * 128, col_fin, bar_epi);
                tma_load_2d(sS + 8192, &tm_sT, rb * 128 + 64, col_fin, bar_epi);
            }
            for (int it = G2_STAGES + ((pw + 4 - (G2_STAGES & 3)) & 3); it < G2_KB; it += 4) {
                const int s = it % G2_STAGES;
                mbar_wait(bar_empty + 8 * s, ((it / G2_STAGES) - 1) & 1);
                mbar_expect_tx(bar_full + 8 * s, G2_STAGE);
                tma_load_2d(sbase + s * G2_STAGE, &tm_h, (k0 + it) * 64, rb * 128, bar_full + 8 * s);
                tma_load_3d(sbase + s * G2_STAGE + 16384, &tm_wd, 0, (k0 + it) * 64, nb * 2, bar_full + 8 * s);
            }
        }
        __syncwarp();
        cluster_sync_all();
    } else {
        const int wg = __shfl_sync(0xffffffffu, (int)(threadIdx.x >> 7), 0);
        const int g = lane >> 2, t = lane & 3;
        float acc[64];
        const uint64_t descA = make_desc(sbase + wg * 8192, 16, 1024);
        const uint64_t descB = make_desc(sbase + 16384, 8192, 1024);
#pragma unroll
        for (int it = 0; it < G2_KB; it++) {
            const int s = it % G2_STAGES;
            mbar_wait(bar_full + 8 * s, (it / G2_STAGES) & 1);
            if (threadIdx.x == 0 && (it == 0 || it == 7)) STAMP(3, 2 + it / 7);
            wgmma_fence();
            {
                const uint64_t da = descA + (uint64_t)((s * G2_STAGE) >> 4);
                const uint64_t db = descB + (uint64_t)((s * G2_STAGE) >> 4);
                wgmma_n128_k64(acc, da, da + 2, da + 4, da + 6, db, db + 128, db + 256, db + 384, it != 0);
            }
            wgmma_commit();
            if (it > 0 && it - 1 + G2_STAGES < G2_KB) {
                wgmma_wait<1>();
                if (lane == 0) mbar_arrive(bar_empty + 8 * ((it - 1) % G2_STAGES));
            }
        }
        wgmma_wait<0>();
        if (threadIdx.x == 0) STAMP(3, 4);
        {
            uint32_t remote;
            asm volatile("mapa.shared::cluster.u32 %0, %1, %2;" : "=r"(remote) : "r"(sXch + threadIdx.x * 16), "r"(kh ^ 1));
            if (kh == 0) {
#pragma unroll
                for (int i = 0; i < 8; i++)
                    asm volatile("st.shared::cluster.v4.f32 [%0], {%1,%2,%3,%4};" ::"r"(remote + i * 4096), "f"(acc[32 + 4 * i]),
                                 "f"(acc[33 + 4 * i]), "f"(acc[34 + 4 * i]), "f"(acc[35 + 4 * i]) : "memory");
            } else {
#pragma unroll
                for (int i = 0; i < 8; i++)
                    asm volatile("st.shared::cluster.v4.f32 [%0], {%1,%2,%3,%4};" ::"r"(remote + i * 4096), "f"(acc[4 * i]),
                                 "f"(acc[1 + 4 * i]), "f"(acc[2 + 4 * i]), "f"(acc[3 + 4 * i]) : "memory");
#pragma unroll
                for (int i = 0; i < 32; i++) acc[i] = acc[32 + i];
            }
        }
        cluster_sync_all();
        mbar_wait(bar_epi, 0);
        const int lr = wg * 64 + (warp & 3) * 16 + g;
#pragma unroll
        for (int j = 0; j < 8; j++) {
            float4 o;
            asm volatile("ld.shared.v4.f32 {%0,%1,%2,%3}, [%4];" : "=f"(o.x), "=f"(o.y), "=f"(o.z), "=f"(o.w) : "r"(sXch + threadIdx.x * 16 + j * 4096));
            float v[4] = {acc[4 * j] + o.x, acc[4 * j + 1] + o.y, acc[4 * j + 2] + o.z, acc[4 * j + 3] + o.w};
#pragma unroll
            for (int hh = 0; hh < 2; hh++) {
                const int r = lr + 8 * hh;
                const uint32_t xaddr = sX + r * 128 + ((j ^ (r & 7)) << 4) + 4 * t;
                uint32_t xv; asm volatile("ld.shared.u32 %0, [%1];" : "=r"(xv) : "r"(xaddr));
                const int c0 = 8 * j + 2 * t;
                const uint32_t sa = sS + (r >> 6) * 8192 + (((r & 63) >> 3) << 4) + (r & 7) * 2;
                uint16_t s0r, s1r;
                asm volatile("ld.shared.u16 %0, [%1];" : "=h"(s0r) : "r"((sa + c0 * 128) ^ ((c0 & 7) << 4)));
                asm volatile("ld.shared.u16 %0, [%1];" : "=h"(s1r) : "r"((sa + (c0 + 1) * 128) ^ (((c0 + 1) & 7) << 4)));
                float s0 = __uint_as_float((uint32_t)s0r << 16), s1 = __uint_as_float((uint32_t)s1r << 16);
                float f0 = bf16_round(v[2 * hh]), f1 = bf16_round(v[2 * hh + 1]);
                float g0 = bf16_round(__fdividef(f0, 1.0f + __expf(-f0)));
                float g1 = bf16_round(__fdividef(f1, 1.0f + __expf(-f1)));
                float o0 = bf_lo(xv) + bf16_round(s0 * g0);
                float o1 = bf_hi(xv) + bf16_round(s1 * g1);
                asm volatile("st.shared.u32 [%0], %1;" ::"r"(xaddr), "r"(pack_bf16(o0, o1)) : "memory");
            }
        }
        fence_async_smem();
        __syncwarp();
        if (lane == 0) {
            tma_store_2d(&tm_out, sX + (wg * 64 + (warp & 3) * 16) * 128, col_fin, rb * 128 + wg * 64 + (warp & 3) * 16);
            bulk_commit();
            bulk_wait_read<0>();
        }
        if (threadIdx.x == 0) STAMP(3, 5);
    }
}

typedef CUresult (*EncodeFn)(CUtensorMap*, CUtensorMapDataType, cuuint32_t, void*, const cuuint64_t*, const cuuint64_t*,
                             const cuuint32_t*, const cuuint32_t*, CUtensorMapInterleave, CUtensorMapSwizzle,
                             CUtensorMapL2promotion, CUtensorMapFloatOOBfill);

void make_map(EncodeFn fn, CUtensorMap* m, const void* ptr, uint64_t inner, uint64_t outer, uint32_t box_in, uint32_t box_out,
              CUtensorMapSwizzle swz = CU_TENSOR_MAP_SWIZZLE_128B) {
    cuuint64_t dims[2] = {inner, outer};
    cuuint64_t strides[1] = {inner * 2};
    cuuint32_t box[2] = {box_in, box_out};
    cuuint32_t es[2] = {1, 1};
    fn(m, CU_TENSOR_MAP_DATA_TYPE_BFLOAT16, 2, const_cast<void*>(ptr), dims, strides, box, es, CU_TENSOR_MAP_INTERLEAVE_NONE,
       swz, CU_TENSOR_MAP_L2_PROMOTION_L2_256B, CU_TENSOR_MAP_FLOAT_OOB_FILL_NONE);
}
void make_map3(EncodeFn fn, CUtensorMap* m, const void* ptr, uint64_t cols, uint64_t rows, uint32_t atom, uint32_t box_rows,
               uint32_t box_atoms, CUtensorMapSwizzle swz) {
    cuuint64_t dims[3] = {atom, rows, cols / atom};
    cuuint64_t strides[2] = {cols * 2, (cuuint64_t)atom * 2};
    cuuint32_t box[3] = {atom, box_rows, box_atoms};
    cuuint32_t es[3] = {1, 1, 1};
    fn(m, CU_TENSOR_MAP_DATA_TYPE_BFLOAT16, 3, const_cast<void*>(ptr), dims, strides, box, es, CU_TENSOR_MAP_INTERLEAVE_NONE,
       swz, CU_TENSOR_MAP_L2_PROMOTION_L2_256B, CU_TENSOR_MAP_FLOAT_OOB_FILL_NONE);
}

template <typename... Args>
void launch_pdl(void (*kern)(Args...), int grid, int block, int smem, bool pdl, int cluster, Args... args) {
    cudaLaunchConfig_t cfg = {};
    cfg.gridDim = dim3(grid); cfg.blockDim = dim3(block); cfg.dynamicSmemBytes = smem; cfg.stream = cudaStreamPerThread;
    cudaLaunchAttribute at[2];
    int n = 0;
    if (pdl) {
        at[n].id = cudaLaunchAttributeProgrammaticStreamSerialization;
        at[n].val.programmaticStreamSerializationAllowed = 1;
        n++;
    }
    if (cluster > 1) {
        at[n].id = cudaLaunchAttributeClusterDimension;
        at[n].val.clusterDim.x = cluster; at[n].val.clusterDim.y = 1; at[n].val.clusterDim.z = 1;
        n++;
    }
    cfg.attrs = at; cfg.numAttrs = n;
    cudaLaunchKernelEx(&cfg, kern, args...);
}

}

extern "C" void kernel_launch(void* const* d_in, const int* in_sizes, int n_in, void* d_out, int out_size) {
    const __nv_bfloat16* x = (const __nv_bfloat16*)d_in[0];
    const __nv_bfloat16* A_re = (const __nv_bfloat16*)d_in[1];
    const __nv_bfloat16* A_im = (const __nv_bfloat16*)d_in[2];
    const __nv_bfloat16* B_re = (const __nv_bfloat16*)d_in[3];
    const __nv_bfloat16* B_im = (const __nv_bfloat16*)d_in[4];
    const __nv_bfloat16* C_re = (const __nv_bfloat16*)d_in[5];
    const __nv_bfloat16* C_im = (const __nv_bfloat16*)d_in[6];
    const __nv_bfloat16* log_dt = (const __nv_bfloat16*)d_in[7];
    const __nv_bfloat16* Dskip = (const __nv_bfloat16*)d_in[8];
    const __nv_bfloat16* wg = (const __nv_bfloat16*)d_in[10];
    const __nv_bfloat16* wu = (const __nv_bfloat16*)d_in[11];
    const __nv_bfloat16* wd = (const __nv_bfloat16*)d_in[12];
    __nv_bfloat16* out = (__nv_bfloat16*)d_out;

    static bool init = false;
    static CUtensorMap tm_xn, tm_wg4, tm_wu4, tm_wg3, tm_wu3, tm_hst, tm_h, tm_wd, tm_x, tm_sT, tm_out;
    static const void* last_ptrs[5] = {nullptr, nullptr, nullptr, nullptr, nullptr};
    if (!init || last_ptrs[0] != wg || last_ptrs[1] != wu || last_ptrs[2] != wd || last_ptrs[3] != x || last_ptrs[4] != out) {
        void* fnp = nullptr;
        cudaDriverEntryPointQueryResult qres;
        cudaGetDriverEntryPoint("cuTensorMapEncodeTiled", &fnp, cudaEnableDefault, &qres);
        EncodeFn fn = (EncodeFn)fnp;
        void *p_xn, *p_h, *p_sT;
        cudaGetSymbolAddress(&p_xn, g_xn);
        cudaGetSymbolAddress(&p_h, g_h);
        cudaGetSymbolAddress(&p_sT, g_sT);
        make_map(fn, &tm_xn, p_xn, D_, L_, 64, 128);
        make_map3(fn, &tm_wg4, wg, F_, D_, 32, 32, 4, CU_TENSOR_MAP_SWIZZLE_64B);
        make_map3(fn, &tm_wu4, wu, F_, D_, 32, 32, 4, CU_TENSOR_MAP_SWIZZLE_64B);
        make_map3(fn, &tm_wg3, wg, F_, D_, 32, 32, 3, CU_TENSOR_MAP_SWIZZLE_64B);
        make_map3(fn, &tm_wu3, wu, F_, D_, 32, 32, 3, CU_TENSOR_MAP_SWIZZLE_64B);
        make_map(fn, &tm_hst, p_h, F_, L_, 16, 16, CU_TENSOR_MAP_SWIZZLE_NONE);
        make_map(fn, &tm_h, p_h, F_, L_, 64, 128);
        make_map3(fn, &tm_wd, wd, D_, F_, 64, 64, 2, CU_TENSOR_MAP_SWIZZLE_128B);
        make_map(fn, &tm_x, x, D_, L_, 64, 128);
        make_map(fn, &tm_sT, p_sT, L_, D_, 64, 64);
        make_map(fn, &tm_out, out, D_, L_, 64, 16);
        cudaFuncSetAttribute(ln_kernel, cudaFuncAttributePreferredSharedMemoryCarveout, 100);
        cudaFuncSetAttribute(conv_kernel, cudaFuncAttributeMaxDynamicSharedMemorySize, CV_SMEM);
        cudaFuncSetAttribute(conv_kernel, cudaFuncAttributePreferredSharedMemoryCarveout, 100);
        cudaFuncSetAttribute(gemm1_kernel, cudaFuncAttributeMaxDynamicSharedMemorySize, G1_SMEM);
        cudaFuncSetAttribute(gemm2_kernel, cudaFuncAttributeMaxDynamicSharedMemorySize, G2_SMEM);
        last_ptrs[0] = wg; last_ptrs[1] = wu; last_ptrs[2] = wd; last_ptrs[3] = x; last_ptrs[4] = out;
        init = true;
    }
    launch_pdl(ln_kernel, L_ / LN_ROWS, 256, 0, false, 1, x, wg, wu, wd);
    launch_pdl(conv_kernel, D_ / CV_CH, 256, CV_SMEM, true, 1, A_re, A_im, B_re, B_im, C_re, C_im, log_dt, Dskip);
    launch_pdl(gemm1_kernel, 128, 384, G1_SMEM, true, 1, tm_xn, tm_wg4, tm_wu4, tm_wg3, tm_wu3, tm_hst);
    launch_pdl(gemm2_kernel, 128, 384, G2_SMEM, true, 2, tm_h, tm_wd, tm_x, tm_sT, tm_out);
}
```

```cpp
#include <cuda_runtime.h>
#include <cuda_bf16.h>
#include <cuda.h>
#include <stdint.h>

namespace {

constexpr int L_ = 2048, D_ = 512, NS_ = 128, F_ = 1792;

__device__ __align__(1024) __nv_bfloat16 g_xn[L_ * D_];
__device__ __align__(1024) __nv_bfloat16 g_xnT[D_ * L_];
__device__ __align__(1024) __nv_bfloat16 g_sT[D_ * L_];
__device__ __align__(1024) __nv_bfloat16 g_h[L_ * F_];

#define STAMP(k, i)

__device__ __forceinline__ uint32_t smem_u32(const void* p) { return (uint32_t)__cvta_generic_to_shared(p); }
__device__ __forceinline__ void pdl_wait() { asm volatile("griddepcontrol.wait;" ::: "memory"); }
__device__ __forceinline__ void pdl_launch() { asm volatile("griddepcontrol.launch_dependents;" ::: "memory"); }

__device__ __forceinline__ void mbar_init(uint32_t bar, uint32_t cnt) {
    asm volatile("mbarrier.init.shared::cta.b64 [%0], %1;" ::"r"(bar), "r"(cnt) : "memory");
}
__device__ __forceinline__ void mbar_expect_tx(uint32_t bar, uint32_t bytes) {
    asm volatile("mbarrier.arrive.expect_tx.shared::cta.b64 _, [%0], %1;" ::"r"(bar), "r"(bytes) : "memory");
}
__device__ __forceinline__ void mbar_arrive(uint32_t bar) {
    asm volatile("mbarrier.arrive.shared::cta.b64 _, [%0];" ::"r"(bar) : "memory");
}
__device__ __forceinline__ void mbar_wait(uint32_t bar, uint32_t parity) {
    asm volatile(
        "{\n.reg .pred p;\n"
        "WAIT_LOOP:\n"
        "mbarrier.try_wait.parity.shared::cta.b64 p, [%0], %1;\n"
        "@p bra WAIT_DONE;\n"
        "bra WAIT_LOOP;\n"
        "WAIT_DONE:\n}\n" ::"r"(bar), "r"(parity) : "memory");
}
__device__ __forceinline__ void tma_load_2d(uint32_t dst, const CUtensorMap* tm, int c0, int c1, uint32_t bar) {
    asm volatile(
        "cp.async.bulk.tensor.2d.shared::cluster.global.mbarrier::complete_tx::bytes [%0], [%1, {%3, %4}], [%2];"
        ::"r"(dst), "l"((uint64_t)tm), "r"(bar), "r"(c0), "r"(c1) : "memory");
}
__device__ __forceinline__ void prefetch_tmap(const CUtensorMap* tm) {
    asm volatile("prefetch.tensormap [%0];" ::"l"((uint64_t)tm) : "memory");
}
__device__ __forceinline__ uint64_t make_desc(uint32_t addr, uint32_t lbo, uint32_t sbo, uint64_t mode = 1) {
    uint64_t d = 0;
    d |= (uint64_t)((addr & 0x3FFFF) >> 4);
    d |= (uint64_t)((lbo >> 4) & 0x3FFF) << 16;
    d |= (uint64_t)((sbo >> 4) & 0x3FFF) << 32;
    d |= mode << 62;
    return d;
}
__device__ __forceinline__ void wgmma_fence() { asm volatile("wgmma.fence.sync.aligned;" ::: "memory"); }
__device__ __forceinline__ void wgmma_commit() { asm volatile("wgmma.commit_group.sync.aligned;" ::: "memory"); }
template <int N> __device__ __forceinline__ void wgmma_wait() {
    asm volatile("wgmma.wait_group.sync.aligned %0;" ::"n"(N) : "memory");
}

#define R8(a, i) "+f"(a[i + 0]), "+f"(a[i + 1]), "+f"(a[i + 2]), "+f"(a[i + 3]), "+f"(a[i + 4]), "+f"(a[i + 5]), "+f"(a[i + 6]), "+f"(a[i + 7])

__device__ __forceinline__ void wgmma_n256_k32(float* a, uint64_t da0, uint64_t da1, uint64_t db0, uint64_t db1, int scale_d) {
    asm volatile(
        "{\n.reg .pred p;\nsetp.ne.b32 p, %132, 0;\n"
        "wgmma.mma_async.sync.aligned.m64n256k16.f32.bf16.bf16 {%0,%1,%2,%3,%4,%5,%6,%7,%8,%9,%10,%11,%12,%13,%14,%15,%16,%17,%18,%19,%20,%21,%22,%23,%24,%25,%26,%27,%28,%29,%30,%31,%32,%33,%34,%35,%36,%37,%38,%39,%40,%41,%42,%43,%44,%45,%46,%47,%48,%49,%50,%51,%52,%53,%54,%55,%56,%57,%58,%59,%60,%61,%62,%63,%64,%65,%66,%67,%68,%69,%70,%71,%72,%73,%74,%75,%76,%77,%78,%79,%80,%81,%82,%83,%84,%85,%86,%87,%88,%89,%90,%91,%92,%93,%94,%95,%96,%97,%98,%99,%100,%101,%102,%103,%104,%105,%106,%107,%108,%109,%110,%111,%112,%113,%114,%115,%116,%117,%118,%119,%120,%121,%122,%123,%124,%125,%126,%127}, %128, %130, p, 1, 1, 0, 1;\n"
        "wgmma.mma_async.sync.aligned.m64n256k16.f32.bf16.bf16 {%0,%1,%2,%3,%4,%5,%6,%7,%8,%9,%10,%11,%12,%13,%14,%15,%16,%17,%18,%19,%20,%21,%22,%23,%24,%25,%26,%27,%28,%29,%30,%31,%32,%33,%34,%35,%36,%37,%38,%39,%40,%41,%42,%43,%44,%45,%46,%47,%48,%49,%50,%51,%52,%53,%54,%55,%56,%57,%58,%59,%60,%61,%62,%63,%64,%65,%66,%67,%68,%69,%70,%71,%72,%73,%74,%75,%76,%77,%78,%79,%80,%81,%82,%83,%84,%85,%86,%87,%88,%89,%90,%91,%92,%93,%94,%95,%96,%97,%98,%99,%100,%101,%102,%103,%104,%105,%106,%107,%108,%109,%110,%111,%112,%113,%114,%115,%116,%117,%118,%119,%120,%121,%122,%123,%124,%125,%126,%127}, %129, %131, 1, 1, 1, 0, 1;\n"
        "}\n"
        : R8(a, 0), R8(a, 8), R8(a, 16), R8(a, 24), R8(a, 32), R8(a, 40), R8(a, 48), R8(a, 56), R8(a, 64), R8(a, 72), R8(a, 80), R8(a, 88), R8(a, 96), R8(a, 104), R8(a, 112), R8(a, 120)
        : "l"(da0), "l"(da1), "l"(db0), "l"(db1), "r"(scale_d));
}
__device__ __forceinline__ void wgmma_n192_k32(float* a, uint64_t da0, uint64_t da1, uint64_t db0, uint64_t db1, int scale_d) {
    asm volatile(
        "{\n.reg .pred p;\nsetp.ne.b32 p, %100, 0;\n"
        "wgmma.mma_async.sync.aligned.m64n192k16.f32.bf16.bf16 {%0,%1,%2,%3,%4,%5,%6,%7,%8,%9,%10,%11,%12,%13,%14,%15,%16,%17,%18,%19,%20,%21,%22,%23,%24,%25,%26,%27,%28,%29,%30,%31,%32,%33,%34,%35,%36,%37,%38,%39,%40,%41,%42,%43,%44,%45,%46,%47,%48,%49,%50,%51,%52,%53,%54,%55,%56,%57,%58,%59,%60,%61,%62,%63,%64,%65,%66,%67,%68,%69,%70,%71,%72,%73,%74,%75,%76,%77,%78,%79,%80,%81,%82,%83,%84,%85,%86,%87,%88,%89,%90,%91,%92,%93,%94,%95}, %96, %98, p, 1, 1, 0, 1;\n"
        "wgmma.mma_async.sync.aligned.m64n192k16.f32.bf16.bf16 {%0,%1,%2,%3,%4,%5,%6,%7,%8,%9,%10,%11,%12,%13,%14,%15,%16,%17,%18,%19,%20,%21,%22,%23,%24,%25,%26,%27,%28,%29,%30,%31,%32,%33,%34,%35,%36,%37,%38,%39,%40,%41,%42,%43,%44,%45,%46,%47,%48,%49,%50,%51,%52,%53,%54,%55,%56,%57,%58,%59,%60,%61,%62,%63,%64,%65,%66,%67,%68,%69,%70,%71,%72,%73,%74,%75,%76,%77,%78,%79,%80,%81,%82,%83,%84,%85,%86,%87,%88,%89,%90,%91,%92,%93,%94,%95}, %97, %99, 1, 1, 1, 0, 1;\n"
        "}\n"
        : R8(a, 0), R8(a, 8), R8(a, 16), R8(a, 24), R8(a, 32), R8(a, 40), R8(a, 48), R8(a, 56), R8(a, 64), R8(a, 72), R8(a, 80), R8(a, 88)
        : "l"(da0), "l"(da1), "l"(db0), "l"(db1), "r"(scale_d));
}
__device__ __forceinline__ void wgmma_n128_k64(float* a, uint64_t da0, uint64_t da1, uint64_t da2, uint64_t da3,
                                               uint64_t db0, uint64_t db1, uint64_t db2, uint64_t db3, int scale_d) {
    asm volatile(
        "{\n.reg .pred p;\nsetp.ne.b32 p, %72, 0;\n"
        "wgmma.mma_async.sync.aligned.m64n128k16.f32.bf16.bf16 {%0,%1,%2,%3,%4,%5,%6,%7,%8,%9,%10,%11,%12,%13,%14,%15,%16,%17,%18,%19,%20,%21,%22,%23,%24,%25,%26,%27,%28,%29,%30,%31,%32,%33,%34,%35,%36,%37,%38,%39,%40,%41,%42,%43,%44,%45,%46,%47,%48,%49,%50,%51,%52,%53,%54,%55,%56,%57,%58,%59,%60,%61,%62,%63}, %64, %68, p, 1, 1, 0, 1;\n"
        "wgmma.mma_async.sync.aligned.m64n128k16.f32.bf16.bf16 {%0,%1,%2,%3,%4,%5,%6,%7,%8,%9,%10,%11,%12,%13,%14,%15,%16,%17,%18,%19,%20,%21,%22,%23,%24,%25,%26,%27,%28,%29,%30,%31,%32,%33,%34,%35,%36,%37,%38,%39,%40,%41,%42,%43,%44,%45,%46,%47,%48,%49,%50,%51,%52,%53,%54,%55,%56,%57,%58,%59,%60,%61,%62,%63}, %65, %69, 1, 1, 1, 0, 1;\n"
        "wgmma.mma_async.sync.aligned.m64n128k16.f32.bf16.bf16 {%0,%1,%2,%3,%4,%5,%6,%7,%8,%9,%10,%11,%12,%13,%14,%15,%16,%17,%18,%19,%20,%21,%22,%23,%24,%25,%26,%27,%28,%29,%30,%31,%32,%33,%34,%35,%36,%37,%38,%39,%40,%41,%42,%43,%44,%45,%46,%47,%48,%49,%50,%51,%52,%53,%54,%55,%56,%57,%58,%59,%60,%61,%62,%63}, %66, %70, 1, 1, 1, 0, 1;\n"
        "wgmma.mma_async.sync.aligned.m64n128k16.f32.bf16.bf16 {%0,%1,%2,%3,%4,%5,%6,%7,%8,%9,%10,%11,%12,%13,%14,%15,%16,%17,%18,%19,%20,%21,%22,%23,%24,%25,%26,%27,%28,%29,%30,%31,%32,%33,%34,%35,%36,%37,%38,%39,%40,%41,%42,%43,%44,%45,%46,%47,%48,%49,%50,%51,%52,%53,%54,%55,%56,%57,%58,%59,%60,%61,%62,%63}, %67, %71, 1, 1, 1, 0, 1;\n"
        "}\n"
        : R8(a, 0), R8(a, 8), R8(a, 16), R8(a, 24), R8(a, 32), R8(a, 40), R8(a, 48), R8(a, 56)
        : "l"(da0), "l"(da1), "l"(da2), "l"(da3), "l"(db0), "l"(db1), "l"(db2), "l"(db3), "r"(scale_d));
}

__device__ __forceinline__ float bf16_round(float x) { return __bfloat162float(__float2bfloat16_rn(x)); }
__device__ __forceinline__ uint32_t pack_bf16(float lo, float hi) {
    __nv_bfloat162 v = __floats2bfloat162_rn(lo, hi);
    return *reinterpret_cast<uint32_t*>(&v);
}
__device__ __forceinline__ float bf_lo(uint32_t v) { return __uint_as_float(v << 16); }
__device__ __forceinline__ float bf_hi(uint32_t v) { return __uint_as_float(v & 0xFFFF0000u); }

constexpr int LN_ROWS = 16;
__global__ void __launch_bounds__(256) ln_kernel(const __nv_bfloat16* __restrict__ x,
                                                  const __nv_bfloat16* __restrict__ wg,
                                                  const __nv_bfloat16* __restrict__ wu,
                                                  const __nv_bfloat16* __restrict__ wd) {
    pdl_launch();
    if (threadIdx.x == 0) STAMP(0, 0);
    __shared__ __align__(16) __nv_bfloat16 tile[LN_ROWS][D_ + 8];
    const int warp = threadIdx.x >> 5, lane = threadIdx.x & 31;
    const int row0 = blockIdx.x * LN_ROWS;
    {
        const int lines_per = (D_ * F_ * 2) / 128 / 128;
        if (threadIdx.x < lines_per) {
            size_t off = ((size_t)blockIdx.x * lines_per + threadIdx.x) * 128;
            asm volatile("prefetch.global.L2 [%0];" ::"l"((const char*)wg + off));
            asm volatile("prefetch.global.L2 [%0];" ::"l"((const char*)wu + off));
            asm volatile("prefetch.global.L2 [%0];" ::"l"((const char*)wd + off));
        }
    }
    uint4 v[2][2];
#pragma unroll
    for (int r = 0; r < 2; r++) {
        const __nv_bfloat16* xr = x + (size_t)(row0 + warp * 2 + r) * D_;
        v[r][0] = *reinterpret_cast<const uint4*>(xr + lane * 8);
        v[r][1] = *reinterpret_cast<const uint4*>(xr + 256 + lane * 8);
    }
#pragma unroll
    for (int r = 0; r < 2; r++) {
        float f[16];
        const uint32_t* w = reinterpret_cast<const uint32_t*>(&v[r][0]);
#pragma unroll
        for (int i = 0; i < 8; i++) { f[2 * i] = bf_lo(w[i]); f[2 * i + 1] = bf_hi(w[i]); }
        float s = 0.f;
#pragma unroll
        for (int i = 0; i < 16; i++) s += f[i];
#pragma unroll
        for (int o = 16; o > 0; o >>= 1) s += __shfl_xor_sync(0xffffffffu, s, o);
        const float mean = s * (1.0f / D_);
        float q = 0.f;
#pragma unroll
        for (int i = 0; i < 16; i++) { float d = f[i] - mean; q += d * d; }
#pragma unroll
        for (int o = 16; o > 0; o >>= 1) q += __shfl_xor_sync(0xffffffffu, q, o);
        const float mb = bf16_round(mean);
        const float vb = bf16_round(q * (1.0f / D_));
        const float den = bf16_round(sqrtf(bf16_round(vb + 1e-5f)));
        uint32_t o[8];
#pragma unroll
        for (int i = 0; i < 8; i++) {
            float a = __fdiv_rn(bf16_round(f[2 * i] - mb), den);
            float b = __fdiv_rn(bf16_round(f[2 * i + 1] - mb), den);
            o[i] = pack_bf16(a, b);
        }
        const int rr = warp * 2 + r;
        __nv_bfloat16* dst = g_xn + (size_t)(row0 + rr) * D_;
        *reinterpret_cast<uint4*>(dst + lane * 8) = make_uint4(o[0], o[1], o[2], o[3]);
        *reinterpret_cast<uint4*>(dst + 256 + lane * 8) = make_uint4(o[4], o[5], o[6], o[7]);
        *reinterpret_cast<uint4*>(&tile[rr][lane * 8]) = make_uint4(o[0], o[1], o[2], o[3]);
        *reinterpret_cast<uint4*>(&tile[rr][256 + lane * 8]) = make_uint4(o[4], o[5], o[6], o[7]);
    }
    __syncthreads();
    if (threadIdx.x == 0) STAMP(0, 1);
#pragma unroll
    for (int cc = 0; cc < 2; cc++) {
        const int c = threadIdx.x + cc * 256;
        uint32_t o[8];
#pragma unroll
        for (int i = 0; i < 8; i++) {
            uint32_t lo = *reinterpret_cast<const uint16_t*>(&tile[2 * i][c]);
            uint32_t hi = *reinterpret_cast<const uint16_t*>(&tile[2 * i + 1][c]);
            o[i] = lo | (hi << 16);
        }
        __nv_bfloat16* dst = g_xnT + (size_t)c * L_ + row0;
        *reinterpret_cast<uint4*>(dst) = make_uint4(o[0], o[1], o[2], o[3]);
        *reinterpret_cast<uint4*>(dst + 8) = make_uint4(o[4], o[5], o[6], o[7]);
    }
    if (threadIdx.x == 0) STAMP(0, 2);
}

struct cplx { float r, i; };
__device__ __forceinline__ cplx cmul(cplx a, cplx b) {
    cplx c; c.r = a.r * b.r - a.i * b.i; c.i = a.r * b.i + a.i * b.r; return c;
}
__device__ __forceinline__ cplx csq(cplx a) {
    cplx c; c.r = a.r * a.r - a.i * a.i; c.i = 2.0f * a.r * a.i; return c;
}
__device__ __forceinline__ cplx cexp_m(float ar, float ai, float m) {
    float mag;
    float e = (ar * m) * 1.4426950408889634f;
    asm("ex2.approx.ftz.f32 %0, %1;" : "=f"(mag) : "f"(e));
    float rr = (ai * m) * 0.15915494309189535f;
    rr -= rintf(rr);
    float th = rr * 6.283185307179586f;
    cplx c; c.r = mag * __cosf(th); c.i = mag * __sinf(th);
    return c;
}
__device__ __forceinline__ uint32_t to_tf32(float x) {
    uint32_t r; asm("cvt.rna.tf32.f32 %0, %1;" : "=r"(r) : "f"(x)); return r;
}
__device__ __forceinline__ void mma_tf32(float* c, uint32_t a0, uint32_t a1, uint32_t a2, uint32_t a3, uint32_t b0, uint32_t b1) {
    asm volatile("mma.sync.aligned.m16n8k8.row.col.f32.tf32.tf32.f32 {%0,%1,%2,%3}, {%4,%5,%6,%7}, {%8,%9}, {%0,%1,%2,%3};"
                 : "+f"(c[0]), "+f"(c[1]), "+f"(c[2]), "+f"(c[3])
                 : "r"(a0), "r"(a1), "r"(a2), "r"(a3), "r"(b0), "r"(b1));
}
__device__ __forceinline__ void mma_bf16(float* c, uint32_t a0, uint32_t a1, uint32_t a2, uint32_t a3, uint32_t b0, uint32_t b1) {
    asm volatile("mma.sync.aligned.m16n8k16.row.col.f32.bf16.bf16.f32 {%0,%1,%2,%3}, {%4,%5,%6,%7}, {%8,%9}, {%0,%1,%2,%3};"
                 : "+f"(c[0]), "+f"(c[1]), "+f"(c[2]), "+f"(c[3])
                 : "r"(a0), "r"(a1), "r"(a2), "r"(a3), "r"(b0), "r"(b1));
}
__device__ __forceinline__ void named_bar(int id, int n) { asm volatile("bar.sync %0, %1;" ::"r"(id), "r"(n) : "memory"); }

constexpr int CV_CH = 4;
constexpr int CV_CONST_B = NS_ * 12 * 4;
constexpr int CV_KV_B = 648 * 4;
constexpr int CV_Q_B = (L_ + 16) * 4;
constexpr int CV_U_B = (L_ + 128) * 2;
constexpr int CV_PER_CH = CV_CONST_B + 2 * CV_KV_B + CV_Q_B + CV_U_B;
constexpr int CV_SMEM = CV_CH * CV_PER_CH;

__global__ void __launch_bounds__(256) conv_kernel(const __nv_bfloat16* __restrict__ A_re, const __nv_bfloat16* __restrict__ A_im,
                                                    const __nv_bfloat16* __restrict__ B_re, const __nv_bfloat16* __restrict__ B_im,
                                                    const __nv_bfloat16* __restrict__ C_re, const __nv_bfloat16* __restrict__ C_im,
                                                    const __nv_bfloat16* __restrict__ log_dt, const __nv_bfloat16* __restrict__ Dskip) {
    pdl_launch();
    if (threadIdx.x == 0) STAMP(1, 0);
    extern __shared__ __align__(16) uint8_t smem[];
    const int warp = threadIdx.x >> 5, lane = threadIdx.x & 31;
    const int ch = warp >> 1, h = warp & 1;
    const int d = blockIdx.x * CV_CH + ch;
    const int g = lane >> 2, t = lane & 3;
    uint8_t* base = smem + ch * CV_PER_CH;
    float4* s_const = reinterpret_cast<float4*>(base);
    float* s_kv = reinterpret_cast<float*>(base + CV_CONST_B);
    uint32_t* s_q = reinterpret_cast<uint32_t*>(base + CV_CONST_B + 2 * CV_KV_B);
    __nv_bfloat16* s_u = reinterpret_cast<__nv_bfloat16*>(base + CV_CONST_B + 2 * CV_KV_B + CV_Q_B);
    const int bar_id = 1 + ch;

    const float dt = bf16_round(expf(__bfloat162float(log_dt[d])));
    float tail = 0.f;
    {
        const int n0 = h * 64 + lane * 2;
        const size_t off = (size_t)d * NS_ + n0;
        uint32_t war = *reinterpret_cast<const uint32_t*>(A_re + off);
        uint32_t wai = *reinterpret_cast<const uint32_t*>(A_im + off);
        uint32_t wbr = *reinterpret_cast<const uint32_t*>(B_re + off);
        uint32_t wbi = *reinterpret_cast<const uint32_t*>(B_im + off);
        uint32_t wcr = *reinterpret_cast<const uint32_t*>(C_re + off);
        uint32_t wci = *reinterpret_cast<const uint32_t*>(C_im + off);
#pragma unroll
        for (int j = 0; j < 2; j++) {
            float ar = dt * (j ? bf_hi(war) : bf_lo(war));
            float ai = dt * (j ? bf_hi(wai) : bf_lo(wai));
            cplx db = {dt * (j ? bf_hi(wbr) : bf_lo(wbr)), dt * (j ? bf_hi(wbi) : bf_lo(wbi))};
            cplx cc = {(j ? bf_hi(wcr) : bf_lo(wcr)), (j ? bf_hi(wci) : bf_lo(wci))};
            cplx cb = cmul(cc, db);
            cplx e128 = cexp_m(ar, ai, 128.f);
            cplx c256 = cmul(cb, cexp_m(ar, ai, 256.f));
            cplx c512 = cmul(cb, cexp_m(ar, ai, 512.f));
            cplx c1024 = cmul(cb, cexp_m(ar, ai, 1024.f));
            cplx c2048 = cmul(cb, cexp_m(ar, ai, 2048.f));
            tail += c2048.r;
            s_const[(n0 + j) * 3 + 0] = make_float4(ar, ai, cb.r, cb.i);
            s_const[(n0 + j) * 3 + 1] = make_float4(e128.r, e128.i, c256.r, c256.i);
            s_const[(n0 + j) * 3 + 2] = make_float4(c512.r, c512.i, c1024.r, c1024.i);
        }
#pragma unroll
        for (int o = 16; o > 0; o >>= 1) tail += __shfl_xor_sync(0xffffffffu, tail, o);
    }
    __syncwarp();
    if (threadIdx.x == 0) STAMP(1, 1);
    {
        float acc[5][4];
#pragma unroll
        for (int i = 0; i < 5; i++) { acc[i][0] = acc[i][1] = acc[i][2] = acc[i][3] = 0.f; }
        const float gf = (float)g;
#pragma unroll 2
        for (int s = 0; s < 16; s++) {
            const int n = h * 64 + s * 4 + t;
            const float4 k0 = s_const[n * 3 + 0], k1 = s_const[n * 3 + 1], k2 = s_const[n * 3 + 2];
            const cplx cb = {k0.z, k0.w}, e128 = {k1.x, k1.y}, c256 = {k1.z, k1.w}, c512 = {k2.x, k2.y}, c1024 = {k2.z, k2.w};
            cplx p1 = cexp_m(k0.x, k0.y, gf);
            cplx p1b = cexp_m(k0.x, k0.y, gf + 8.f);
            cplx r16a = cexp_m(k0.x, k0.y, gf * 16.f);
            cplx r16b = cmul(r16a, e128);
            cplx p2 = csq(p1), p4 = csq(p2), p8 = csq(p4);
            cplx r32a = csq(r16a), r32b = csq(r16b), r64a = csq(r32a), r64b = csq(r32b);
            cplx f0a = cmul(cb, p1), f0b = cmul(cb, p1b), f1 = cmul(c256, p2), f2 = cmul(c512, p4), f3 = cmul(c1024, p8);
            {
                uint32_t a0 = to_tf32(r16a.r), a1 = to_tf32(r16b.r), a2 = to_tf32(-r16a.i), a3 = to_tf32(-r16b.i);
                mma_tf32(acc[0], a0, a1, a2, a3, to_tf32(f0a.r), to_tf32(f0a.i));
                mma_tf32(acc[1], a0, a1, a2, a3, to_tf32(f0b.r), to_tf32(f0b.i));
                mma_tf32(acc[2], a0, a1, a2, a3, to_tf32(f1.r), to_tf32(f1.i));
            }
            mma_tf32(acc[3], to_tf32(r32a.r), to_tf32(r32b.r), to_tf32(-r32a.i), to_tf32(-r32b.i), to_tf32(f2.r), to_tf32(f2.i));
            mma_tf32(acc[4], to_tf32(r64a.r), to_tf32(r64b.r), to_tf32(-r64a.i), to_tf32(-r64b.i), to_tf32(f3.r), to_tf32(f3.i));
        }
        float* kv = s_kv + h * 648;
        *reinterpret_cast<float2*>(kv + 16 * g + 2 * t) = make_float2(acc[0][0], acc[0][1]);
        *reinterpret_cast<float2*>(kv + 16 * (g + 8) + 2 * t) = make_float2(acc[0][2], acc[0][3]);
        *reinterpret_cast<float2*>(kv + 16 * g + 8 + 2 * t) = make_float2(acc[1][0], acc[1][1]);
        *reinterpret_cast<float2*>(kv + 16 * (g + 8) + 8 + 2 * t) = make_float2(acc[1][2], acc[1][3]);
#pragma unroll
        for (int sg = 0; sg < 3; sg++) {
            *reinterpret_cast<float2*>(kv + 256 + 128 * sg + 8 * g + 2 * t) = make_float2(acc[2 + sg][0], acc[2 + sg][1]);
            *reinterpret_cast<float2*>(kv + 256 + 128 * sg + 8 * (g + 8) + 2 * t) = make_float2(acc[2 + sg][2], acc[2 + sg][3]);
        }
        if (lane == 0) kv[640] = tail;
    }
    named_bar(bar_id, 64);
    if (threadIdx.x == 0) STAMP(1, 2);
    {
        const int tid2 = h * 32 + lane;
        if (tid2 < 16) s_q[tid2] = 0u;
        for (int x = tid2; x < L_; x += 64) {
            float kc, kp;
            {
                int s = (x >= 1024) ? 3 : (x >= 512) ? 2 : (x >= 256) ? 1 : 0;
                int rq = (s == 0) ? x : ((x + (1 << (s - 1)) - 1 + ((x >> s) & 1)) >> s);
                int idx = 128 * s + rq;
                kc = s_kv[idx] + s_kv[648 + idx];
            }
            {
                int y = x - 1;
                if (y < 0) kp = 0.f;
                else {
                    int s = (y >= 1024) ? 3 : (y >= 512) ? 2 : (y >= 256) ? 1 : 0;
                    int rq = (s == 0) ? y : ((y + (1 << (s - 1)) - 1 + ((y >> s) & 1)) >> s);
                    int idx = 128 * s + rq;
                    kp = s_kv[idx] + s_kv[648 + idx];
                }
            }
            s_q[x + 16] = pack_bf16(kc, kp);
        }
    }
    if (threadIdx.x == 0) STAMP(1, 3);
    pdl_wait();
    if (threadIdx.x == 0) STAMP(1, 4);
    {
        const int tid2 = h * 32 + lane;
        if (tid2 < 16) *reinterpret_cast<uint4*>(s_u + tid2 * 8) = make_uint4(0, 0, 0, 0);
        const uint4* src = reinterpret_cast<const uint4*>(g_xnT + (size_t)d * L_);
#pragma unroll
        for (int i = 0; i < 4; i++) {
            *reinterpret_cast<uint4*>(s_u + 128 + (tid2 + i * 64) * 8) = src[tid2 + i * 64];
        }
    }
    named_bar(bar_id, 64);
    if (threadIdx.x == 0) STAMP(1, 5);
    float acc[16][4];
#pragma unroll
    for (int i = 0; i < 16; i++) { acc[i][0] = acc[i][1] = acc[i][2] = acc[i][3] = 0.f; }
    const uint32_t su_addr = smem_u32(s_u);
    for (int rr = 0; rr < 4; rr++) {
        const int r = h * 4 + rr;
        uint32_t ub[16][2];
        {
            const int mi = lane >> 3, rowi = lane & 7;
            uint32_t addr = su_addr + (uint32_t)((128 + 16 * (8 * (mi >> 1) + rowi - r) + 8 * (mi & 1)) * 2);
#pragma unroll
            for (int j = 0; j < 16; j += 2) {
                asm volatile("ldmatrix.sync.aligned.m8n8.x4.shared.b16 {%0,%1,%2,%3}, [%4];"
                             : "=r"(ub[j][0]), "=r"(ub[j][1]), "=r"(ub[j + 1][0]), "=r"(ub[j + 1][1])
                             : "r"(addr + (uint32_t)(j * 8 * 16 * 2)));
            }
        }
        const uint32_t* qp = s_q + 16 + 16 * r + g - 2 * t;
#pragma unroll
        for (int q = 0; q < 16; q++) {
            const uint32_t a0 = qp[128 * q], a1 = qp[128 * q + 8], a2 = qp[128 * q - 8];
#pragma unroll
            for (int nt = q; nt < 16; nt++) mma_bf16(acc[nt], a0, a1, a2, a0, ub[nt - q][0], ub[nt - q][1]);
        }
    }
    if (threadIdx.x == 0) STAMP(1, 6);
    named_bar(bar_id, 64);
    {
        float4* xch = reinterpret_cast<float4*>(base) + h * 256;
        if (h) {
#pragma unroll
            for (int i = 0; i < 8; i++) xch[i * 32 + lane] = make_float4(acc[i][0], acc[i][1], acc[i][2], acc[i][3]);
        } else {
#pragma unroll
            for (int i = 0; i < 8; i++) xch[i * 32 + lane] = make_float4(acc[8 + i][0], acc[8 + i][1], acc[8 + i][2], acc[8 + i][3]);
        }
    }
    named_bar(bar_id, 64);
    {
        const float4* xch = reinterpret_cast<const float4*>(base) + (h ^ 1) * 256;
        const float dsk = __bfloat162float(Dskip[d]);
        __nv_bfloat16* stg = reinterpret_cast<__nv_bfloat16*>(s_q);
#pragma unroll
        for (int i = 0; i < 8; i++) {
            float4 o = xch[i * 32 + lane];
            float y[4];
            if (h) { y[0] = acc[8 + i][0] + o.x; y[1] = acc[8 + i][1] + o.y; y[2] = acc[8 + i][2] + o.z; y[3] = acc[8 + i][3] + o.w; }
            else   { y[0] = acc[i][0] + o.x; y[1] = acc[i][1] + o.y; y[2] = acc[i][2] + o.z; y[3] = acc[i][3] + o.w; }
            const int nt = h * 8 + i;
#pragma unroll
            for (int e = 0; e < 4; e++) {
                const int tau = 16 * (8 * nt + 2 * t + (e & 1)) + g + 8 * (e >> 1);
                float u = __bfloat162float(s_u[128 + tau]);
                float sv = bf16_round(y[e]) + bf16_round(u * dsk);
                stg[tau] = __float2bfloat16_rn(sv);
            }
        }
        __syncwarp();
        uint4* dst = reinterpret_cast<uint4*>(g_sT + (size_t)d * L_ + h * 1024);
        const uint4* srcp = reinterpret_cast<const uint4*>(stg + h * 1024);
#pragma unroll
        for (int i = 0; i < 4; i++) dst[i * 32 + lane] = srcp[i * 32 + lane];
    }
    if (threadIdx.x == 0) STAMP(1, 7);
}

__device__ __forceinline__ uint32_t cluster_rank() { uint32_t r; asm volatile("mov.u32 %0, %%cluster_ctarank;" : "=r"(r)); return r; }
__device__ __forceinline__ void cluster_sync_all() {
    asm volatile("barrier.cluster.arrive.release.aligned;\nbarrier.cluster.wait.acquire.aligned;" ::: "memory");
}
__device__ __forceinline__ void mbar_arrive_remote(uint32_t bar, uint32_t cta) {
    asm volatile("{\n.reg .b32 ra;\nmapa.shared::cluster.u32 ra, %0, %1;\n"
                 "mbarrier.arrive.shared::cluster.b64 _, [ra];\n}\n" ::"r"(bar), "r"(cta) : "memory");
}
__device__ __forceinline__ void tma_load_2d_mc(uint32_t dst, const CUtensorMap* tm, int c0, int c1, uint32_t bar, uint16_t mask) {
    asm volatile(
        "cp.async.bulk.tensor.2d.shared::cluster.global.mbarrier::complete_tx::bytes.multicast::cluster [%0], [%1, {%3, %4}], [%2], %5;"
        ::"r"(dst), "l"((uint64_t)tm), "r"(bar), "r"(c0), "r"(c1), "h"(mask) : "memory");
}
__device__ __forceinline__ void tma_store_2d(const CUtensorMap* tm, uint32_t src, int c0, int c1) {
    asm volatile("cp.async.bulk.tensor.2d.global.shared::cta.bulk_group [%0, {%2, %3}], [%1];"
                 ::"l"((uint64_t)tm), "r"(src), "r"(c0), "r"(c1) : "memory");
}
__device__ __forceinline__ void bulk_commit() { asm volatile("cp.async.bulk.commit_group;" ::: "memory"); }
template <int N> __device__ __forceinline__ void bulk_wait_read() { asm volatile("cp.async.bulk.wait_group.read %0;" ::"n"(N) : "memory"); }
template <int N> __device__ __forceinline__ void bulk_wait() { asm volatile("cp.async.bulk.wait_group %0;" ::"n"(N) : "memory"); }
__device__ __forceinline__ void fence_async_smem() { asm volatile("fence.proxy.async.shared::cta;" ::: "memory"); }
__device__ __forceinline__ void stmatrix_x4(uint32_t addr, uint32_t r0, uint32_t r1, uint32_t r2, uint32_t r3) {
    asm volatile("stmatrix.sync.aligned.m8n8.x4.shared.b16 [%0], {%1,%2,%3,%4};" ::"r"(addr), "r"(r0), "r"(r1), "r"(r2), "r"(r3) : "memory");
}

constexpr int G1_STAGES = 5;
constexpr int G1_A_BYTES = 8 * 16384;
constexpr int G1_B_STAGE = 16384;
constexpr int G1_STG = 8 * 1024;
constexpr int G1_SMEM = G1_A_BYTES + G1_STAGES * G1_B_STAGE + G1_STG + 1024 + 256;
constexpr int G1_ITERS = 32;

__device__ __forceinline__ void tma_load_3d(uint32_t dst, const CUtensorMap* tm, int c0, int c1, int c2, uint32_t bar) {
    asm volatile(
        "cp.async.bulk.tensor.3d.shared::cluster.global.mbarrier::complete_tx::bytes [%0], [%1, {%3, %4, %5}], [%2];"
        ::"r"(dst), "l"((uint64_t)tm), "r"(bar), "r"(c0), "r"(c1), "r"(c2) : "memory");
}

__device__ __forceinline__ float gelu_tanh(float x) {
    float u = x * (0.7978845608028654f + 0.035677408136300125f * x * x);
    float t; asm("tanh.approx.f32 %0, %1;" : "=f"(t) : "f"(u));
    float hx = 0.5f * x;
    return fmaf(hx, t, hx);
}
__device__ __forceinline__ uint32_t geglu_pair(uint32_t p0, uint32_t p1) {
    float a = bf16_round(gelu_tanh(bf_lo(p0))) * bf_hi(p0);
    float b = bf16_round(gelu_tanh(bf_lo(p1))) * bf_hi(p1);
    return pack_bf16(a, b);
}

__global__ void __launch_bounds__(384, 1) gemm1_kernel(const __grid_constant__ CUtensorMap tm_xn,
                                                        const __grid_constant__ CUtensorMap tm_wg4,
                                                        const __grid_constant__ CUtensorMap tm_wu4,
                                                        const __grid_constant__ CUtensorMap tm_wg3,
                                                        const __grid_constant__ CUtensorMap tm_wu3,
                                                        const __grid_constant__ CUtensorMap tm_hst,
                                                        const __grid_constant__ CUtensorMap tm_hst96) {
    pdl_launch();
    if (threadIdx.x == 0) STAMP(2, 0);
    extern __shared__ uint8_t smem_raw[];
    const uint32_t sbase = (smem_u32(smem_raw) + 1023) & ~1023u;
    const uint32_t sA = sbase, sB = sbase + G1_A_BYTES, sStg = sB + G1_STAGES * G1_B_STAGE, sBar = sStg + G1_STG;
    const uint32_t bar_a = sBar, bar_full = sBar + 64, bar_empty = sBar + 64 + 8 * G1_STAGES;
    const int rb = blockIdx.x >> 3, cj = blockIdx.x & 7;
    const int warp = threadIdx.x >> 5, lane = threadIdx.x & 31;

    if (threadIdx.x == 0) {
        for (int i = 0; i < 8; i++) mbar_init(bar_a + 8 * i, 1);
        for (int i = 0; i < G1_STAGES; i++) { mbar_init(bar_full + 8 * i, 1); mbar_init(bar_empty + 8 * i, 8); }
        asm volatile("fence.mbarrier_init.release.cluster;" ::: "memory");
    }
    __syncthreads();

    if (warp >= 8) {
        asm volatile("setmaxnreg.dec.sync.aligned.u32 40;");
        if (lane == 0) {
            const int pw = warp - 8;
            if (pw == 0) { prefetch_tmap(&tm_wg4); prefetch_tmap(&tm_wu4); prefetch_tmap(&tm_xn); }
            if (pw == 1) { prefetch_tmap(&tm_wg3); prefetch_tmap(&tm_wu3); prefetch_tmap(&tm_hst); prefetch_tmap(&tm_hst96); }
            for (int it = pw; it < G1_ITERS; it += 4) {
                const int s = it % G1_STAGES, kb = it & 15;
                if (it >= G1_STAGES) mbar_wait(bar_empty + 8 * s, ((it / G1_STAGES) - 1) & 1);
                const uint32_t dst = sB + s * G1_B_STAGE;
                if (it < 16) {
                    mbar_expect_tx(bar_full + 8 * s, 16384);
                    tma_load_3d(dst, &tm_wg4, 0, kb * 32, cj * 7, bar_full + 8 * s);
                    tma_load_3d(dst + 8192, &tm_wu4, 0, kb * 32, cj * 7, bar_full + 8 * s);
                } else {
                    mbar_expect_tx(bar_full + 8 * s, 12288);
                    tma_load_3d(dst, &tm_wg3, 0, kb * 32, cj * 7 + 4, bar_full + 8 * s);
                    tma_load_3d(dst + 6144, &tm_wu3, 0, kb * 32, cj * 7 + 4, bar_full + 8 * s);
                }
                if (it < 4) {
                    pdl_wait();
                    if (pw == 0) STAMP(2, 1);
                    for (int k = pw; k < 8; k += 4) {
                        mbar_expect_tx(bar_a + 8 * k, 16384);
                        tma_load_2d(sA + k * 16384, &tm_xn, k * 64, rb * 128, bar_a + 8 * k);
                    }
                }
            }
        }
    } else {
        asm volatile("setmaxnreg.inc.sync.aligned.u32 232;");
        const int wg = __shfl_sync(0xffffffffu, (int)(threadIdx.x >> 7), 0);
        float r[160];
        const int row0 = rb * 128 + wg * 64 + (warp & 3) * 16;
        const uint64_t descA = make_desc(sA + wg * 8192, 16, 1024);
        const uint64_t descB = make_desc(sB, 2048, 512, 2);
        const uint32_t stg = sStg + warp * 1024;
        const uint32_t st_off = (uint32_t)(((lane & 7) + ((lane >> 3) & 1) * 8) * 32 + (lane >> 4) * 16);
        auto store_group = [&](const float* pk, int par, int col) {
            const uint32_t buf = stg + par * 512;
            uint32_t r0 = geglu_pair(__float_as_uint(pk[0]), __float_as_uint(pk[1]));
            uint32_t r1 = geglu_pair(__float_as_uint(pk[2]), __float_as_uint(pk[3]));
            uint32_t r2 = geglu_pair(__float_as_uint(pk[4]), __float_as_uint(pk[5]));
            uint32_t r3 = geglu_pair(__float_as_uint(pk[6]), __float_as_uint(pk[7]));
            if (lane == 0) bulk_wait_read<1>();
            __syncwarp();
            stmatrix_x4(buf + st_off, r0, r1, r2, r3);
            fence_async_smem();
            __syncwarp();
            if (lane == 0) { tma_store_2d(&tm_hst, buf, col, row0); bulk_commit(); }
        };
#pragma unroll
        for (int kb = 0; kb < 16; kb++) {
            const int it = kb, s = it % G1_STAGES;
            if ((kb & 1) == 0) mbar_wait(bar_a + 8 * (kb >> 1), 0);
            mbar_wait(bar_full + 8 * s, (it / G1_STAGES) & 1);
            if (threadIdx.x == 0 && (it & 7) == 0) STAMP(2, 2 + it / 8);
            wgmma_fence();
            const uint64_t da = descA + (uint64_t)(((kb >> 1) * 16384 + (kb & 1) * 64) >> 4);
            const uint64_t db = descB + (uint64_t)((s * G1_B_STAGE) >> 4);
            wgmma_n256_k32(r, da, da + 2, db, db + 64, kb != 0);
            wgmma_commit();
            if (kb > 0) {
                wgmma_wait<1>();
                if (lane == 0) mbar_arrive(bar_empty + 8 * ((it - 1) % G1_STAGES));
            }
        }
        wgmma_wait<0>();
        if (lane == 0) mbar_arrive(bar_empty + 8 * (15 % G1_STAGES));
#pragma unroll
        for (int i = 0; i < 32; i++) r[128 + i] = __uint_as_float(pack_bf16(r[i], r[64 + i]));
#pragma unroll
        for (int i = 32; i < 64; i++) r[64 + i] = __uint_as_float(pack_bf16(r[i], r[64 + i]));
#pragma unroll
        for (int kb = 0; kb < 16; kb++) {
            const int it = 16 + kb, s = it % G1_STAGES;
            mbar_wait(bar_full + 8 * s, (it / G1_STAGES) & 1);
            if (threadIdx.x == 0 && (it & 7) == 0) STAMP(2, 2 + it / 8);
            wgmma_fence();
            const uint64_t da = descA + (uint64_t)(((kb >> 1) * 16384 + (kb & 1) * 64) >> 4);
            const uint64_t db = descB + (uint64_t)((s * G1_B_STAGE) >> 4);
            wgmma_n192_k32(r, da, da + 2, db, db + 64, kb != 0);
            wgmma_commit();
            if (kb > 0 && it - 1 + G1_STAGES < G1_ITERS) {
                wgmma_wait<1>();
                if (lane == 0) mbar_arrive(bar_empty + 8 * ((it - 1) % G1_STAGES));
            }
            if ((kb & 1) == wg) {
                const int jj = kb >> 1;
                store_group(jj < 4 ? &r[128 + 8 * jj] : &r[64 + 8 * jj], jj & 1, cj * 224 + jj * 16);
            }
        }
        wgmma_wait<0>();
#pragma unroll
        for (int i = 0; i < 48; i++) r[i] = __uint_as_float(pack_bf16(r[i], r[48 + i]));
        if (threadIdx.x == 0) STAMP(2, 6);
        {
            uint32_t o[24];
#pragma unroll
            for (int i = 0; i < 24; i++) o[i] = geglu_pair(__float_as_uint(r[2 * i]), __float_as_uint(r[2 * i + 1]));
            named_bar(1 + wg, 128);
            const uint32_t fbuf = sA + ((warp & 3) >> 1) * 16384 + wg * 8192 + (warp & 1) * 4096;
            const uint32_t f_off = (uint32_t)(((lane & 7) + ((lane >> 3) & 1) * 8) * 192 + (lane >> 4) * 16);
#pragma unroll
            for (int jj = 0; jj < 6; jj++) stmatrix_x4(fbuf + f_off + jj * 32, o[4 * jj], o[4 * jj + 1], o[4 * jj + 2], o[4 * jj + 3]);
            fence_async_smem();
            __syncwarp();
            if (lane == 0) { tma_store_2d(&tm_hst96, fbuf, cj * 224 + 128, row0); bulk_commit(); }
        }
        if (lane == 0) bulk_wait_read<0>();
        if (threadIdx.x == 0) STAMP(2, 7);
    }
}

constexpr int G2_STAGES = 5;
constexpr int G2_STAGE = 16384 + 16384;
constexpr int G2_XCH = 32768;
constexpr int G2_EPI = 16384 + 16384;
constexpr int G2_SMEM = G2_STAGES * G2_STAGE + G2_XCH + G2_EPI + 1024 + 256;
constexpr int G2_KB = F_ / 64 / 2;

__global__ void __launch_bounds__(384, 1) gemm2_kernel(const __grid_constant__ CUtensorMap tm_h,
                                                        const __grid_constant__ CUtensorMap tm_wd,
                                                        const __grid_constant__ CUtensorMap tm_x,
                                                        const __grid_constant__ CUtensorMap tm_sT,
                                                        const __grid_constant__ CUtensorMap tm_out) {
    if (threadIdx.x == 0) STAMP(3, 0);
    extern __shared__ uint8_t smem_raw[];
    const uint32_t sbase = (smem_u32(smem_raw) + 1023) & ~1023u;
    const uint32_t sXch = sbase + G2_STAGES * G2_STAGE, sX = sXch + G2_XCH, sS = sX + 16384, sBar = sX + G2_EPI;
    const uint32_t bar_full = sBar, bar_empty = sBar + 8 * G2_STAGES, bar_epi = sBar + 16 * G2_STAGES, bar_xch = bar_epi + 8;
    const uint32_t kh = cluster_rank();
    const int cid = blockIdx.x >> 1;
    const int rb = cid >> 2, nb = cid & 3;
    const int col_fin = nb * 128 + kh * 64;
    const int warp = threadIdx.x >> 5, lane = threadIdx.x & 31;

    if (threadIdx.x == 0) {
        for (int i = 0; i < G2_STAGES; i++) { mbar_init(bar_full + 8 * i, 1); mbar_init(bar_empty + 8 * i, 8); }
        mbar_init(bar_epi, 1);
        mbar_init(bar_xch, 1);
        asm volatile("fence.mbarrier_init.release.cluster;" ::: "memory");
        mbar_expect_tx(bar_xch, G2_XCH);
    }
    cluster_sync_all();

    if (warp >= 8) {
        if (lane == 0) {
            const int pw = warp - 8;
            const int k0 = kh * G2_KB;
            if (pw == 0) { prefetch_tmap(&tm_wd); prefetch_tmap(&tm_h); }
            if (pw == 1) { prefetch_tmap(&tm_x); prefetch_tmap(&tm_sT); prefetch_tmap(&tm_out); }
            for (int it = pw; it < G2_STAGES; it += 4) {
                mbar_expect_tx(bar_full + 8 * it, G2_STAGE);
                tma_load_3d(sbase + it * G2_STAGE + 16384, &tm_wd, 0, (k0 + it) * 64, nb * 2, bar_full + 8 * it);
            }
            if (pw == 3) {
                mbar_expect_tx(bar_epi, G2_EPI);
                tma_load_2d(sX, &tm_x, col_fin, rb * 128, bar_epi);
            }
            pdl_wait();
            if (pw == 0) STAMP(3, 1);
            for (int it = pw; it < G2_STAGES; it += 4)
                tma_load_2d(sbase + it * G2_STAGE, &tm_h, (k0 + it) * 64, rb * 128, bar_full + 8 * it);
            if (pw == 3) {
                tma_load_2d(sS, &tm_sT, rb * 128, col_fin, bar_epi);
                tma_load_2d(sS + 8192, &tm_sT, rb * 128 + 64, col_fin, bar_epi);
            }
            for (int it = G2_STAGES + ((pw + 4 - (G2_STAGES & 3)) & 3); it < G2_KB; it += 4) {
                const int s = it % G2_STAGES;
                mbar_wait(bar_empty + 8 * s, ((it / G2_STAGES) - 1) & 1);
                mbar_expect_tx(bar_full + 8 * s, G2_STAGE);
                tma_load_2d(sbase + s * G2_STAGE, &tm_h, (k0 + it) * 64, rb * 128, bar_full + 8 * s);
                tma_load_3d(sbase + s * G2_STAGE + 16384, &tm_wd, 0, (k0 + it) * 64, nb * 2, bar_full + 8 * s);
            }
        }
    } else {
        const int wg = __shfl_sync(0xffffffffu, (int)(threadIdx.x >> 7), 0);
        const int g = lane >> 2, t = lane & 3;
        float acc[64];
        const uint64_t descA = make_desc(sbase + wg * 8192, 16, 1024);
        const uint64_t descB = make_desc(sbase + 16384, 8192, 1024);
#pragma unroll
        for (int it = 0; it < G2_KB; it++) {
            const int s = it % G2_STAGES;
            mbar_wait(bar_full + 8 * s, (it / G2_STAGES) & 1);
            if (threadIdx.x == 0 && (it == 0 || it == 7)) STAMP(3, 2 + it / 7);
            wgmma_fence();
            {
                const uint64_t da = descA + (uint64_t)((s * G2_STAGE) >> 4);
                const uint64_t db = descB + (uint64_t)((s * G2_STAGE) >> 4);
                wgmma_n128_k64(acc, da, da + 2, da + 4, da + 6, db, db + 128, db + 256, db + 384, it != 0);
            }
            wgmma_commit();
            if (it > 0 && it - 1 + G2_STAGES < G2_KB) {
                wgmma_wait<1>();
                if (lane == 0) mbar_arrive(bar_empty + 8 * ((it - 1) % G2_STAGES));
            }
        }
        const int lr = wg * 64 + (warp & 3) * 16 + g;
        uint32_t xv[16], sv[16];
        mbar_wait(bar_epi, 0);
#pragma unroll
        for (int j = 0; j < 8; j++) {
#pragma unroll
            for (int hh = 0; hh < 2; hh++) {
                const int r = lr + 8 * hh;
                asm volatile("ld.shared.u32 %0, [%1];" : "=r"(xv[2 * j + hh]) : "r"(sX + r * 128 + ((j ^ (r & 7)) << 4) + 4 * t));
                const int c0 = 8 * j + 2 * t;
                const uint32_t sa = sS + (r >> 6) * 8192 + (((r & 63) >> 3) << 4) + (r & 7) * 2;
                uint16_t s0r, s1r;
                asm volatile("ld.shared.u16 %0, [%1];" : "=h"(s0r) : "r"((sa + c0 * 128) ^ ((c0 & 7) << 4)));
                asm volatile("ld.shared.u16 %0, [%1];" : "=h"(s1r) : "r"((sa + (c0 + 1) * 128) ^ (((c0 + 1) & 7) << 4)));
                sv[2 * j + hh] = (uint32_t)s0r | ((uint32_t)s1r << 16);
            }
        }
        wgmma_wait<0>();
        if (threadIdx.x == 0) STAMP(3, 4);
        {
            uint32_t remote, rbar;
            asm volatile("mapa.shared::cluster.u32 %0, %1, %2;" : "=r"(remote) : "r"(sXch + threadIdx.x * 16), "r"(kh ^ 1));
            asm volatile("mapa.shared::cluster.u32 %0, %1, %2;" : "=r"(rbar) : "r"(bar_xch), "r"(kh ^ 1));
            if (kh == 0) {
#pragma unroll
                for (int i = 0; i < 8; i++)
                    asm volatile("st.async.shared::cluster.mbarrier::complete_tx::bytes.v4.f32 [%0], {%1,%2,%3,%4}, [%5];" ::"r"(remote + i * 4096),
                                 "f"(acc[32 + 4 * i]), "f"(acc[33 + 4 * i]), "f"(acc[34 + 4 * i]), "f"(acc[35 + 4 * i]), "r"(rbar) : "memory");
            } else {
#pragma unroll
                for (int i = 0; i < 8; i++)
                    asm volatile("st.async.shared::cluster.mbarrier::complete_tx::bytes.v4.f32 [%0], {%1,%2,%3,%4}, [%5];" ::"r"(remote + i * 4096),
                                 "f"(acc[4 * i]), "f"(acc[1 + 4 * i]), "f"(acc[2 + 4 * i]), "f"(acc[3 + 4 * i]), "r"(rbar) : "memory");
#pragma unroll
                for (int i = 0; i < 32; i++) acc[i] = acc[32 + i];
            }
        }
        if (threadIdx.x == 0) STAMP(3, 6);
        mbar_wait(bar_xch, 0);
        if (threadIdx.x == 0) STAMP(3, 7);
#pragma unroll
        for (int j = 0; j < 8; j++) {
            float4 o;
            asm volatile("ld.shared.v4.f32 {%0,%1,%2,%3}, [%4];" : "=f"(o.x), "=f"(o.y), "=f"(o.z), "=f"(o.w) : "r"(sXch + threadIdx.x * 16 + j * 4096));
            acc[4 * j] += o.x; acc[4 * j + 1] += o.y; acc[4 * j + 2] += o.z; acc[4 * j + 3] += o.w;
        }
#pragma unroll
        for (int i = 0; i < 16; i++) {
            float f0 = bf16_round(acc[2 * i]), f1 = bf16_round(acc[2 * i + 1]);
            float g0 = bf16_round(__fdividef(f0, 1.0f + __expf(-f0)));
            float g1 = bf16_round(__fdividef(f1, 1.0f + __expf(-f1)));
            float o0 = bf_lo(xv[i]) + bf16_round(bf_lo(sv[i]) * g0);
            float o1 = bf_hi(xv[i]) + bf16_round(bf_hi(sv[i]) * g1);
            xv[i] = pack_bf16(o0, o1);
        }
#pragma unroll
        for (int j = 0; j < 8; j++) {
#pragma unroll
            for (int hh = 0; hh < 2; hh++) {
                const int r = lr + 8 * hh;
                asm volatile("st.shared.u32 [%0], %1;" ::"r"(sX + r * 128 + ((j ^ (r & 7)) << 4) + 4 * t), "r"(xv[2 * j + hh]) : "memory");
            }
        }
        if (threadIdx.x == 0) STAMP(3, 9);
        fence_async_smem();
        __syncwarp();
        if (lane == 0) {
            tma_store_2d(&tm_out, sX + (wg * 64 + (warp & 3) * 16) * 128, col_fin, rb * 128 + wg * 64 + (warp & 3) * 16);
            bulk_commit();
            bulk_wait_read<0>();
        }
        if (threadIdx.x == 0) STAMP(3, 5);
    }
}

typedef CUresult (*EncodeFn)(CUtensorMap*, CUtensorMapDataType, cuuint32_t, void*, const cuuint64_t*, const cuuint64_t*,
                             const cuuint32_t*, const cuuint32_t*, CUtensorMapInterleave, CUtensorMapSwizzle,
                             CUtensorMapL2promotion, CUtensorMapFloatOOBfill);

void make_map(EncodeFn fn, CUtensorMap* m, const void* ptr, uint64_t inner, uint64_t outer, uint32_t box_in, uint32_t box_out,
              CUtensorMapSwizzle swz = CU_TENSOR_MAP_SWIZZLE_128B) {
    cuuint64_t dims[2] = {inner, outer};
    cuuint64_t strides[1] = {inner * 2};
    cuuint32_t box[2] = {box_in, box_out};
    cuuint32_t es[2] = {1, 1};
    fn(m, CU_TENSOR_MAP_DATA_TYPE_BFLOAT16, 2, const_cast<void*>(ptr), dims, strides, box, es, CU_TENSOR_MAP_INTERLEAVE_NONE,
       swz, CU_TENSOR_MAP_L2_PROMOTION_L2_256B, CU_TENSOR_MAP_FLOAT_OOB_FILL_NONE);
}
void make_map3(EncodeFn fn, CUtensorMap* m, const void* ptr, uint64_t cols, uint64_t rows, uint32_t atom, uint32_t box_rows,
               uint32_t box_atoms, CUtensorMapSwizzle swz) {
    cuuint64_t dims[3] = {atom, rows, cols / atom};
    cuuint64_t strides[2] = {cols * 2, (cuuint64_t)atom * 2};
    cuuint32_t box[3] = {atom, box_rows, box_atoms};
    cuuint32_t es[3] = {1, 1, 1};
    fn(m, CU_TENSOR_MAP_DATA_TYPE_BFLOAT16, 3, const_cast<void*>(ptr), dims, strides, box, es, CU_TENSOR_MAP_INTERLEAVE_NONE,
       swz, CU_TENSOR_MAP_L2_PROMOTION_L2_256B, CU_TENSOR_MAP_FLOAT_OOB_FILL_NONE);
}

template <typename... Args>
void launch_pdl(void (*kern)(Args...), int grid, int block, int smem, bool pdl, int cluster, Args... args) {
    cudaLaunchConfig_t cfg = {};
    cfg.gridDim = dim3(grid); cfg.blockDim = dim3(block); cfg.dynamicSmemBytes = smem; cfg.stream = cudaStreamPerThread;
    cudaLaunchAttribute at[2];
    int n = 0;
    if (pdl) {
        at[n].id = cudaLaunchAttributeProgrammaticStreamSerialization;
        at[n].val.programmaticStreamSerializationAllowed = 1;
        n++;
    }
    if (cluster > 1) {
        at[n].id = cudaLaunchAttributeClusterDimension;
        at[n].val.clusterDim.x = cluster; at[n].val.clusterDim.y = 1; at[n].val.clusterDim.z = 1;
        n++;
    }
    cfg.attrs = at; cfg.numAttrs = n;
    cudaLaunchKernelEx(&cfg, kern, args...);
}

}

extern "C" void kernel_launch(void* const* d_in, const int* in_sizes, int n_in, void* d_out, int out_size) {
    const __nv_bfloat16* x = (const __nv_bfloat16*)d_in[0];
    const __nv_bfloat16* A_re = (const __nv_bfloat16*)d_in[1];
    const __nv_bfloat16* A_im = (const __nv_bfloat16*)d_in[2];
    const __nv_bfloat16* B_re = (const __nv_bfloat16*)d_in[3];
    const __nv_bfloat16* B_im = (const __nv_bfloat16*)d_in[4];
    const __nv_bfloat16* C_re = (const __nv_bfloat16*)d_in[5];
    const __nv_bfloat16* C_im = (const __nv_bfloat16*)d_in[6];
    const __nv_bfloat16* log_dt = (const __nv_bfloat16*)d_in[7];
    const __nv_bfloat16* Dskip = (const __nv_bfloat16*)d_in[8];
    const __nv_bfloat16* wg = (const __nv_bfloat16*)d_in[10];
    const __nv_bfloat16* wu = (const __nv_bfloat16*)d_in[11];
    const __nv_bfloat16* wd = (const __nv_bfloat16*)d_in[12];
    __nv_bfloat16* out = (__nv_bfloat16*)d_out;

    static bool init = false;
    static CUtensorMap tm_xn, tm_wg4, tm_wu4, tm_wg3, tm_wu3, tm_hst, tm_hst96, tm_h, tm_wd, tm_x, tm_sT, tm_out;
    static const void* last_ptrs[5] = {nullptr, nullptr, nullptr, nullptr, nullptr};
    if (!init || last_ptrs[0] != wg || last_ptrs[1] != wu || last_ptrs[2] != wd || last_ptrs[3] != x || last_ptrs[4] != out) {
        void* fnp = nullptr;
        cudaDriverEntryPointQueryResult qres;
        cudaGetDriverEntryPoint("cuTensorMapEncodeTiled", &fnp, cudaEnableDefault, &qres);
        EncodeFn fn = (EncodeFn)fnp;
        void *p_xn, *p_h, *p_sT;
        cudaGetSymbolAddress(&p_xn, g_xn);
        cudaGetSymbolAddress(&p_h, g_h);
        cudaGetSymbolAddress(&p_sT, g_sT);
        make_map(fn, &tm_xn, p_xn, D_, L_, 64, 128);
        make_map3(fn, &tm_wg4, wg, F_, D_, 32, 32, 4, CU_TENSOR_MAP_SWIZZLE_64B);
        make_map3(fn, &tm_wu4, wu, F_, D_, 32, 32, 4, CU_TENSOR_MAP_SWIZZLE_64B);
        make_map3(fn, &tm_wg3, wg, F_, D_, 32, 32, 3, CU_TENSOR_MAP_SWIZZLE_64B);
        make_map3(fn, &tm_wu3, wu, F_, D_, 32, 32, 3, CU_TENSOR_MAP_SWIZZLE_64B);
        make_map(fn, &tm_hst, p_h, F_, L_, 16, 16, CU_TENSOR_MAP_SWIZZLE_NONE);
        make_map(fn, &tm_hst96, p_h, F_, L_, 96, 16, CU_TENSOR_MAP_SWIZZLE_NONE);
        make_map(fn, &tm_h, p_h, F_, L_, 64, 128);
        make_map3(fn, &tm_wd, wd, D_, F_, 64, 64, 2, CU_TENSOR_MAP_SWIZZLE_128B);
        make_map(fn, &tm_x, x, D_, L_, 64, 128);
        make_map(fn, &tm_sT, p_sT, L_, D_, 64, 64);
        make_map(fn, &tm_out, out, D_, L_, 64, 16);
        cudaFuncSetAttribute(ln_kernel, cudaFuncAttributePreferredSharedMemoryCarveout, 100);
        cudaFuncSetAttribute(conv_kernel, cudaFuncAttributeMaxDynamicSharedMemorySize, CV_SMEM);
        cudaFuncSetAttribute(conv_kernel, cudaFuncAttributePreferredSharedMemoryCarveout, 100);
        cudaFuncSetAttribute(gemm1_kernel, cudaFuncAttributeMaxDynamicSharedMemorySize, G1_SMEM);
        cudaFuncSetAttribute(gemm2_kernel, cudaFuncAttributeMaxDynamicSharedMemorySize, G2_SMEM);
        last_ptrs[0] = wg; last_ptrs[1] = wu; last_ptrs[2] = wd; last_ptrs[3] = x; last_ptrs[4] = out;
        init = true;
    }
    launch_pdl(ln_kernel, L_ / LN_ROWS, 256, 0, false, 1, x, wg, wu, wd);
    launch_pdl(conv_kernel, D_ / CV_CH, 256, CV_SMEM, true, 1, A_re, A_im, B_re, B_im, C_re, C_im, log_dt, Dskip);
    launch_pdl(gemm1_kernel, 128, 384, G1_SMEM, true, 1, tm_xn, tm_wg4, tm_wu4, tm_wg3, tm_wu3, tm_hst, tm_hst96);
    launch_pdl(gemm2_kernel, 128, 384, G2_SMEM, true, 2, tm_h, tm_wd, tm_x, tm_sT, tm_out);
}
```

```cpp
#include <cuda_runtime.h>
#include <cuda_bf16.h>
#include <cuda.h>
#include <stdint.h>

namespace {

constexpr int L_ = 2048, D_ = 512, NS_ = 128, F_ = 1792;

__device__ __align__(1024) __nv_bfloat16 g_xn[L_ * D_];
__device__ __align__(1024) __nv_bfloat16 g_xnT[D_ * L_];
__device__ __align__(1024) __nv_bfloat16 g_sT[D_ * L_];
__device__ __align__(1024) __nv_bfloat16 g_h[L_ * F_];

#define STAMP(k, i)

__device__ __forceinline__ uint32_t smem_u32(const void* p) { return (uint32_t)__cvta_generic_to_shared(p); }
__device__ __forceinline__ void pdl_wait() { asm volatile("griddepcontrol.wait;" ::: "memory"); }
__device__ __forceinline__ void pdl_launch() { asm volatile("griddepcontrol.launch_dependents;" ::: "memory"); }

__device__ __forceinline__ void mbar_init(uint32_t bar, uint32_t cnt) {
    asm volatile("mbarrier.init.shared::cta.b64 [%0], %1;" ::"r"(bar), "r"(cnt) : "memory");
}
__device__ __forceinline__ void mbar_expect_tx(uint32_t bar, uint32_t bytes) {
    asm volatile("mbarrier.arrive.expect_tx.shared::cta.b64 _, [%0], %1;" ::"r"(bar), "r"(bytes) : "memory");
}
__device__ __forceinline__ void mbar_arrive(uint32_t bar) {
    asm volatile("mbarrier.arrive.shared::cta.b64 _, [%0];" ::"r"(bar) : "memory");
}
__device__ __forceinline__ void mbar_wait(uint32_t bar, uint32_t parity) {
    asm volatile(
        "{\n.reg .pred p;\n"
        "WAIT_LOOP:\n"
        "mbarrier.try_wait.parity.shared::cta.b64 p, [%0], %1;\n"
        "@p bra WAIT_DONE;\n"
        "bra WAIT_LOOP;\n"
        "WAIT_DONE:\n}\n" ::"r"(bar), "r"(parity) : "memory");
}
__device__ __forceinline__ void tma_load_2d(uint32_t dst, const CUtensorMap* tm, int c0, int c1, uint32_t bar) {
    asm volatile(
        "cp.async.bulk.tensor.2d.shared::cluster.global.mbarrier::complete_tx::bytes [%0], [%1, {%3, %4}], [%2];"
        ::"r"(dst), "l"((uint64_t)tm), "r"(bar), "r"(c0), "r"(c1) : "memory");
}
__device__ __forceinline__ void prefetch_tmap(const CUtensorMap* tm) {
    asm volatile("prefetch.tensormap [%0];" ::"l"((uint64_t)tm) : "memory");
}
__device__ __forceinline__ uint64_t make_desc(uint32_t addr, uint32_t lbo, uint32_t sbo, uint64_t mode = 1) {
    uint64_t d = 0;
    d |= (uint64_t)((addr & 0x3FFFF) >> 4);
    d |= (uint64_t)((lbo >> 4) & 0x3FFF) << 16;
    d |= (uint64_t)((sbo >> 4) & 0x3FFF) << 32;
    d |= mode << 62;
    return d;
}
__device__ __forceinline__ void wgmma_fence() { asm volatile("wgmma.fence.sync.aligned;" ::: "memory"); }
__device__ __forceinline__ void wgmma_commit() { asm volatile("wgmma.commit_group.sync.aligned;" ::: "memory"); }
template <int N> __device__ __forceinline__ void wgmma_wait() {
    asm volatile("wgmma.wait_group.sync.aligned %0;" ::"n"(N) : "memory");
}

#define R8(a, i) "+f"(a[i + 0]), "+f"(a[i + 1]), "+f"(a[i + 2]), "+f"(a[i + 3]), "+f"(a[i + 4]), "+f"(a[i + 5]), "+f"(a[i + 6]), "+f"(a[i + 7])

__device__ __forceinline__ void wgmma_n256_k32(float* a, uint64_t da0, uint64_t da1, uint64_t db0, uint64_t db1, int scale_d) {
    asm volatile(
        "{\n.reg .pred p;\nsetp.ne.b32 p, %132, 0;\n"
        "wgmma.mma_async.sync.aligned.m64n256k16.f32.bf16.bf16 {%0,%1,%2,%3,%4,%5,%6,%7,%8,%9,%10,%11,%12,%13,%14,%15,%16,%17,%18,%19,%20,%21,%22,%23,%24,%25,%26,%27,%28,%29,%30,%31,%32,%33,%34,%35,%36,%37,%38,%39,%40,%41,%42,%43,%44,%45,%46,%47,%48,%49,%50,%51,%52,%53,%54,%55,%56,%57,%58,%59,%60,%61,%62,%63,%64,%65,%66,%67,%68,%69,%70,%71,%72,%73,%74,%75,%76,%77,%78,%79,%80,%81,%82,%83,%84,%85,%86,%87,%88,%89,%90,%91,%92,%93,%94,%95,%96,%97,%98,%99,%100,%101,%102,%103,%104,%105,%106,%107,%108,%109,%110,%111,%112,%113,%114,%115,%116,%117,%118,%119,%120,%121,%122,%123,%124,%125,%126,%127}, %128, %130, p, 1, 1, 0, 1;\n"
        "wgmma.mma_async.sync.aligned.m64n256k16.f32.bf16.bf16 {%0,%1,%2,%3,%4,%5,%6,%7,%8,%9,%10,%11,%12,%13,%14,%15,%16,%17,%18,%19,%20,%21,%22,%23,%24,%25,%26,%27,%28,%29,%30,%31,%32,%33,%34,%35,%36,%37,%38,%39,%40,%41,%42,%43,%44,%45,%46,%47,%48,%49,%50,%51,%52,%53,%54,%55,%56,%57,%58,%59,%60,%61,%62,%63,%64,%65,%66,%67,%68,%69,%70,%71,%72,%73,%74,%75,%76,%77,%78,%79,%80,%81,%82,%83,%84,%85,%86,%87,%88,%89,%90,%91,%92,%93,%94,%95,%96,%97,%98,%99,%100,%101,%102,%103,%104,%105,%106,%107,%108,%109,%110,%111,%112,%113,%114,%115,%116,%117,%118,%119,%120,%121,%122,%123,%124,%125,%126,%127}, %129, %131, 1, 1, 1, 0, 1;\n"
        "}\n"
        : R8(a, 0), R8(a, 8), R8(a, 16), R8(a, 24), R8(a, 32), R8(a, 40), R8(a, 48), R8(a, 56), R8(a, 64), R8(a, 72), R8(a, 80), R8(a, 88), R8(a, 96), R8(a, 104), R8(a, 112), R8(a, 120)
        : "l"(da0), "l"(da1), "l"(db0), "l"(db1), "r"(scale_d));
}
__device__ __forceinline__ void wgmma_n192_k32(float* a, uint64_t da0, uint64_t da1, uint64_t db0, uint64_t db1, int scale_d) {
    asm volatile(
        "{\n.reg .pred p;\nsetp.ne.b32 p, %100, 0;\n"
        "wgmma.mma_async.sync.aligned.m64n192k16.f32.bf16.bf16 {%0,%1,%2,%3,%4,%5,%6,%7,%8,%9,%10,%11,%12,%13,%14,%15,%16,%17,%18,%19,%20,%21,%22,%23,%24,%25,%26,%27,%28,%29,%30,%31,%32,%33,%34,%35,%36,%37,%38,%39,%40,%41,%42,%43,%44,%45,%46,%47,%48,%49,%50,%51,%52,%53,%54,%55,%56,%57,%58,%59,%60,%61,%62,%63,%64,%65,%66,%67,%68,%69,%70,%71,%72,%73,%74,%75,%76,%77,%78,%79,%80,%81,%82,%83,%84,%85,%86,%87,%88,%89,%90,%91,%92,%93,%94,%95}, %96, %98, p, 1, 1, 0, 1;\n"
        "wgmma.mma_async.sync.aligned.m64n192k16.f32.bf16.bf16 {%0,%1,%2,%3,%4,%5,%6,%7,%8,%9,%10,%11,%12,%13,%14,%15,%16,%17,%18,%19,%20,%21,%22,%23,%24,%25,%26,%27,%28,%29,%30,%31,%32,%33,%34,%35,%36,%37,%38,%39,%40,%41,%42,%43,%44,%45,%46,%47,%48,%49,%50,%51,%52,%53,%54,%55,%56,%57,%58,%59,%60,%61,%62,%63,%64,%65,%66,%67,%68,%69,%70,%71,%72,%73,%74,%75,%76,%77,%78,%79,%80,%81,%82,%83,%84,%85,%86,%87,%88,%89,%90,%91,%92,%93,%94,%95}, %97, %99, 1, 1, 1, 0, 1;\n"
        "}\n"
        : R8(a, 0), R8(a, 8), R8(a, 16), R8(a, 24), R8(a, 32), R8(a, 40), R8(a, 48), R8(a, 56), R8(a, 64), R8(a, 72), R8(a, 80), R8(a, 88)
        : "l"(da0), "l"(da1), "l"(db0), "l"(db1), "r"(scale_d));
}
__device__ __forceinline__ void wgmma_n128_k64(float* a, uint64_t da0, uint64_t da1, uint64_t da2, uint64_t da3,
                                               uint64_t db0, uint64_t db1, uint64_t db2, uint64_t db3, int scale_d) {
    asm volatile(
        "{\n.reg .pred p;\nsetp.ne.b32 p, %72, 0;\n"
        "wgmma.mma_async.sync.aligned.m64n128k16.f32.bf16.bf16 {%0,%1,%2,%3,%4,%5,%6,%7,%8,%9,%10,%11,%12,%13,%14,%15,%16,%17,%18,%19,%20,%21,%22,%23,%24,%25,%26,%27,%28,%29,%30,%31,%32,%33,%34,%35,%36,%37,%38,%39,%40,%41,%42,%43,%44,%45,%46,%47,%48,%49,%50,%51,%52,%53,%54,%55,%56,%57,%58,%59,%60,%61,%62,%63}, %64, %68, p, 1, 1, 0, 1;\n"
        "wgmma.mma_async.sync.aligned.m64n128k16.f32.bf16.bf16 {%0,%1,%2,%3,%4,%5,%6,%7,%8,%9,%10,%11,%12,%13,%14,%15,%16,%17,%18,%19,%20,%21,%22,%23,%24,%25,%26,%27,%28,%29,%30,%31,%32,%33,%34,%35,%36,%37,%38,%39,%40,%41,%42,%43,%44,%45,%46,%47,%48,%49,%50,%51,%52,%53,%54,%55,%56,%57,%58,%59,%60,%61,%62,%63}, %65, %69, 1, 1, 1, 0, 1;\n"
        "wgmma.mma_async.sync.aligned.m64n128k16.f32.bf16.bf16 {%0,%1,%2,%3,%4,%5,%6,%7,%8,%9,%10,%11,%12,%13,%14,%15,%16,%17,%18,%19,%20,%21,%22,%23,%24,%25,%26,%27,%28,%29,%30,%31,%32,%33,%34,%35,%36,%37,%38,%39,%40,%41,%42,%43,%44,%45,%46,%47,%48,%49,%50,%51,%52,%53,%54,%55,%56,%57,%58,%59,%60,%61,%62,%63}, %66, %70, 1, 1, 1, 0, 1;\n"
        "wgmma.mma_async.sync.aligned.m64n128k16.f32.bf16.bf16 {%0,%1,%2,%3,%4,%5,%6,%7,%8,%9,%10,%11,%12,%13,%14,%15,%16,%17,%18,%19,%20,%21,%22,%23,%24,%25,%26,%27,%28,%29,%30,%31,%32,%33,%34,%35,%36,%37,%38,%39,%40,%41,%42,%43,%44,%45,%46,%47,%48,%49,%50,%51,%52,%53,%54,%55,%56,%57,%58,%59,%60,%61,%62,%63}, %67, %71, 1, 1, 1, 0, 1;\n"
        "}\n"
        : R8(a, 0), R8(a, 8), R8(a, 16), R8(a, 24), R8(a, 32), R8(a, 40), R8(a, 48), R8(a, 56)
        : "l"(da0), "l"(da1), "l"(da2), "l"(da3), "l"(db0), "l"(db1), "l"(db2), "l"(db3), "r"(scale_d));
}

__device__ __forceinline__ float bf16_round(float x) {
    uint32_t p; asm("cvt.rn.bf16x2.f32 %0, %1, %2;" : "=r"(p) : "f"(x), "f"(0.0f));
    return __uint_as_float(p);
}
__device__ __forceinline__ uint32_t pack_bf16(float lo, float hi) {
    __nv_bfloat162 v = __floats2bfloat162_rn(lo, hi);
    return *reinterpret_cast<uint32_t*>(&v);
}
__device__ __forceinline__ float bf_lo(uint32_t v) { return __uint_as_float(v << 16); }
__device__ __forceinline__ float bf_hi(uint32_t v) { return __uint_as_float(v & 0xFFFF0000u); }

constexpr int LN_ROWS = 16;
__global__ void __launch_bounds__(256) ln_kernel(const __nv_bfloat16* __restrict__ x,
                                                  const __nv_bfloat16* __restrict__ wg,
                                                  const __nv_bfloat16* __restrict__ wu,
                                                  const __nv_bfloat16* __restrict__ wd) {
    pdl_launch();
    if (threadIdx.x == 0) STAMP(0, 0);
    __shared__ __align__(16) __nv_bfloat16 tile[LN_ROWS][D_ + 8];
    const int warp = threadIdx.x >> 5, lane = threadIdx.x & 31;
    const int row0 = blockIdx.x * LN_ROWS;
    {
        const int lines_per = (D_ * F_ * 2) / 128 / 128;
        if (threadIdx.x < lines_per) {
            size_t off = ((size_t)blockIdx.x * lines_per + threadIdx.x) * 128;
            asm volatile("prefetch.global.L2 [%0];" ::"l"((const char*)wg + off));
            asm volatile("prefetch.global.L2 [%0];" ::"l"((const char*)wu + off));
            asm volatile("prefetch.global.L2 [%0];" ::"l"((const char*)wd + off));
        }
    }
    uint4 v[2][2];
#pragma unroll
    for (int r = 0; r < 2; r++) {
        const __nv_bfloat16* xr = x + (size_t)(row0 + warp * 2 + r) * D_;
        v[r][0] = *reinterpret_cast<const uint4*>(xr + lane * 8);
        v[r][1] = *reinterpret_cast<const uint4*>(xr + 256 + lane * 8);
    }
#pragma unroll
    for (int r = 0; r < 2; r++) {
        float f[16];
        const uint32_t* w = reinterpret_cast<const uint32_t*>(&v[r][0]);
#pragma unroll
        for (int i = 0; i < 8; i++) { f[2 * i] = bf_lo(w[i]); f[2 * i + 1] = bf_hi(w[i]); }
        float s = 0.f;
#pragma unroll
        for (int i = 0; i < 16; i++) s += f[i];
#pragma unroll
        for (int o = 16; o > 0; o >>= 1) s += __shfl_xor_sync(0xffffffffu, s, o);
        const float mean = s * (1.0f / D_);
        float q = 0.f;
#pragma unroll
        for (int i = 0; i < 16; i++) { float d = f[i] - mean; q += d * d; }
#pragma unroll
        for (int o = 16; o > 0; o >>= 1) q += __shfl_xor_sync(0xffffffffu, q, o);
        const float mb = bf16_round(mean);
        const float vb = bf16_round(q * (1.0f / D_));
        const float den = bf16_round(sqrtf(bf16_round(vb + 1e-5f)));
        uint32_t o[8];
#pragma unroll
        for (int i = 0; i < 8; i++) {
            float a = __fdiv_rn(bf16_round(f[2 * i] - mb), den);
            float b = __fdiv_rn(bf16_round(f[2 * i + 1] - mb), den);
            o[i] = pack_bf16(a, b);
        }
        const int rr = warp * 2 + r;
        __nv_bfloat16* dst = g_xn + (size_t)(row0 + rr) * D_;
        *reinterpret_cast<uint4*>(dst + lane * 8) = make_uint4(o[0], o[1], o[2], o[3]);
        *reinterpret_cast<uint4*>(dst + 256 + lane * 8) = make_uint4(o[4], o[5], o[6], o[7]);
        *reinterpret_cast<uint4*>(&tile[rr][lane * 8]) = make_uint4(o[0], o[1], o[2], o[3]);
        *reinterpret_cast<uint4*>(&tile[rr][256 + lane * 8]) = make_uint4(o[4], o[5], o[6], o[7]);
    }
    __syncthreads();
    if (threadIdx.x == 0) STAMP(0, 1);
#pragma unroll
    for (int cc = 0; cc < 2; cc++) {
        const int c = threadIdx.x + cc * 256;
        uint32_t o[8];
#pragma unroll
        for (int i = 0; i < 8; i++) {
            uint32_t lo = *reinterpret_cast<const uint16_t*>(&tile[2 * i][c]);
            uint32_t hi = *reinterpret_cast<const uint16_t*>(&tile[2 * i + 1][c]);
            o[i] = lo | (hi << 16);
        }
        __nv_bfloat16* dst = g_xnT + (size_t)c * L_ + row0;
        *reinterpret_cast<uint4*>(dst) = make_uint4(o[0], o[1], o[2], o[3]);
        *reinterpret_cast<uint4*>(dst + 8) = make_uint4(o[4], o[5], o[6], o[7]);
    }
    if (threadIdx.x == 0) STAMP(0, 2);
}

struct cplx { float r, i; };
__device__ __forceinline__ cplx cmul(cplx a, cplx b) {
    cplx c; c.r = a.r * b.r - a.i * b.i; c.i = a.r * b.i + a.i * b.r; return c;
}
__device__ __forceinline__ cplx csq(cplx a) {
    cplx c; c.r = a.r * a.r - a.i * a.i; c.i = 2.0f * a.r * a.i; return c;
}
__device__ __forceinline__ cplx cexp_m(float ar, float ai, float m) {
    float mag;
    float e = (ar * m) * 1.4426950408889634f;
    asm("ex2.approx.ftz.f32 %0, %1;" : "=f"(mag) : "f"(e));
    float rr = (ai * m) * 0.15915494309189535f;
    rr -= rintf(rr);
    float th = rr * 6.283185307179586f;
    cplx c; c.r = mag * __cosf(th); c.i = mag * __sinf(th);
    return c;
}
__device__ __forceinline__ uint32_t to_tf32(float x) {
    uint32_t r; asm("cvt.rna.tf32.f32 %0, %1;" : "=r"(r) : "f"(x)); return r;
}
__device__ __forceinline__ void mma_tf32(float* c, uint32_t a0, uint32_t a1, uint32_t a2, uint32_t a3, uint32_t b0, uint32_t b1) {
    asm volatile("mma.sync.aligned.m16n8k8.row.col.f32.tf32.tf32.f32 {%0,%1,%2,%3}, {%4,%5,%6,%7}, {%8,%9}, {%0,%1,%2,%3};"
                 : "+f"(c[0]), "+f"(c[1]), "+f"(c[2]), "+f"(c[3])
                 : "r"(a0), "r"(a1), "r"(a2), "r"(a3), "r"(b0), "r"(b1));
}
__device__ __forceinline__ void mma_bf16(float* c, uint32_t a0, uint32_t a1, uint32_t a2, uint32_t a3, uint32_t b0, uint32_t b1) {
    asm volatile("mma.sync.aligned.m16n8k16.row.col.f32.bf16.bf16.f32 {%0,%1,%2,%3}, {%4,%5,%6,%7}, {%8,%9}, {%0,%1,%2,%3};"
                 : "+f"(c[0]), "+f"(c[1]), "+f"(c[2]), "+f"(c[3])
                 : "r"(a0), "r"(a1), "r"(a2), "r"(a3), "r"(b0), "r"(b1));
}
__device__ __forceinline__ void named_bar(int id, int n) { asm volatile("bar.sync %0, %1;" ::"r"(id), "r"(n) : "memory"); }

constexpr int CV_CH = 4;
constexpr int CV_CONST_B = NS_ * 12 * 4;
constexpr int CV_KV_B = 648 * 4;
constexpr int CV_Q_B = (L_ + 16) * 4;
constexpr int CV_U_B = (L_ + 128) * 2;
constexpr int CV_PER_CH = CV_CONST_B + 2 * CV_KV_B + CV_Q_B + CV_U_B;
constexpr int CV_SMEM = CV_CH * CV_PER_CH;

__global__ void __launch_bounds__(256) conv_kernel(const __nv_bfloat16* __restrict__ A_re, const __nv_bfloat16* __restrict__ A_im,
                                                    const __nv_bfloat16* __restrict__ B_re, const __nv_bfloat16* __restrict__ B_im,
                                                    const __nv_bfloat16* __restrict__ C_re, const __nv_bfloat16* __restrict__ C_im,
                                                    const __nv_bfloat16* __restrict__ log_dt, const __nv_bfloat16* __restrict__ Dskip) {
    pdl_launch();
    if (threadIdx.x == 0) STAMP(1, 0);
    extern __shared__ __align__(16) uint8_t smem[];
    const int warp = threadIdx.x >> 5, lane = threadIdx.x & 31;
    const int ch = warp >> 1, h = warp & 1;
    const int d = blockIdx.x * CV_CH + ch;
    const int g = lane >> 2, t = lane & 3;
    uint8_t* base = smem + ch * CV_PER_CH;
    float4* s_const = reinterpret_cast<float4*>(base);
    float* s_kv = reinterpret_cast<float*>(base + CV_CONST_B);
    uint32_t* s_q = reinterpret_cast<uint32_t*>(base + CV_CONST_B + 2 * CV_KV_B);
    __nv_bfloat16* s_u = reinterpret_cast<__nv_bfloat16*>(base + CV_CONST_B + 2 * CV_KV_B + CV_Q_B);
    const int bar_id = 1 + ch;

    const float dt = bf16_round(expf(__bfloat162float(log_dt[d])));
    float tail = 0.f;
    {
        const int n0 = h * 64 + lane * 2;
        const size_t off = (size_t)d * NS_ + n0;
        uint32_t war = *reinterpret_cast<const uint32_t*>(A_re + off);
        uint32_t wai = *reinterpret_cast<const uint32_t*>(A_im + off);
        uint32_t wbr = *reinterpret_cast<const uint32_t*>(B_re + off);
        uint32_t wbi = *reinterpret_cast<const uint32_t*>(B_im + off);
        uint32_t wcr = *reinterpret_cast<const uint32_t*>(C_re + off);
        uint32_t wci = *reinterpret_cast<const uint32_t*>(C_im + off);
#pragma unroll
        for (int j = 0; j < 2; j++) {
            float ar = dt * (j ? bf_hi(war) : bf_lo(war));
            float ai = dt * (j ? bf_hi(wai) : bf_lo(wai));
            cplx db = {dt * (j ? bf_hi(wbr) : bf_lo(wbr)), dt * (j ? bf_hi(wbi) : bf_lo(wbi))};
            cplx cc = {(j ? bf_hi(wcr) : bf_lo(wcr)), (j ? bf_hi(wci) : bf_lo(wci))};
            cplx cb = cmul(cc, db);
            cplx e128 = cexp_m(ar, ai, 128.f);
            cplx c256 = cmul(cb, cexp_m(ar, ai, 256.f));
            cplx c512 = cmul(cb, cexp_m(ar, ai, 512.f));
            cplx c1024 = cmul(cb, cexp_m(ar, ai, 1024.f));
            cplx c2048 = cmul(cb, cexp_m(ar, ai, 2048.f));
            tail += c2048.r;
            s_const[(n0 + j) * 3 + 0] = make_float4(ar, ai, cb.r, cb.i);
            s_const[(n0 + j) * 3 + 1] = make_float4(e128.r, e128.i, c256.r, c256.i);
            s_const[(n0 + j) * 3 + 2] = make_float4(c512.r, c512.i, c1024.r, c1024.i);
        }
#pragma unroll
        for (int o = 16; o > 0; o >>= 1) tail += __shfl_xor_sync(0xffffffffu, tail, o);
    }
    __syncwarp();
    if (threadIdx.x == 0) STAMP(1, 1);
    {
        float acc[5][4];
#pragma unroll
        for (int i = 0; i < 5; i++) { acc[i][0] = acc[i][1] = acc[i][2] = acc[i][3] = 0.f; }
        const float gf = (float)g;
#pragma unroll 2
        for (int s = 0; s < 16; s++) {
            const int n = h * 64 + s * 4 + t;
            const float4 k0 = s_const[n * 3 + 0], k1 = s_const[n * 3 + 1], k2 = s_const[n * 3 + 2];
            const cplx cb = {k0.z, k0.w}, e128 = {k1.x, k1.y}, c256 = {k1.z, k1.w}, c512 = {k2.x, k2.y}, c1024 = {k2.z, k2.w};
            cplx p1 = cexp_m(k0.x, k0.y, gf);
            cplx p1b = cexp_m(k0.x, k0.y, gf + 8.f);
            cplx r16a = cexp_m(k0.x, k0.y, gf * 16.f);
            cplx r16b = cmul(r16a, e128);
            cplx p2 = csq(p1), p4 = csq(p2), p8 = csq(p4);
            cplx r32a = csq(r16a), r32b = csq(r16b), r64a = csq(r32a), r64b = csq(r32b);
            cplx f0a = cmul(cb, p1), f0b = cmul(cb, p1b), f1 = cmul(c256, p2), f2 = cmul(c512, p4), f3 = cmul(c1024, p8);
            {
                uint32_t a0 = to_tf32(r16a.r), a1 = to_tf32(r16b.r), a2 = to_tf32(-r16a.i), a3 = to_tf32(-r16b.i);
                mma_tf32(acc[0], a0, a1, a2, a3, to_tf32(f0a.r), to_tf32(f0a.i));
                mma_tf32(acc[1], a0, a1, a2, a3, to_tf32(f0b.r), to_tf32(f0b.i));
                mma_tf32(acc[2], a0, a1, a2, a3, to_tf32(f1.r), to_tf32(f1.i));
            }
            mma_tf32(acc[3], to_tf32(r32a.r), to_tf32(r32b.r), to_tf32(-r32a.i), to_tf32(-r32b.i), to_tf32(f2.r), to_tf32(f2.i));
            mma_tf32(acc[4], to_tf32(r64a.r), to_tf32(r64b.r), to_tf32(-r64a.i), to_tf32(-r64b.i), to_tf32(f3.r), to_tf32(f3.i));
        }
        float* kv = s_kv + h * 648;
        *reinterpret_cast<float2*>(kv + 16 * g + 2 * t) = make_float2(acc[0][0], acc[0][1]);
        *reinterpret_cast<float2*>(kv + 16 * (g + 8) + 2 * t) = make_float2(acc[0][2], acc[0][3]);
        *reinterpret_cast<float2*>(kv + 16 * g + 8 + 2 * t) = make_float2(acc[1][0], acc[1][1]);
        *reinterpret_cast<float2*>(kv + 16 * (g + 8) + 8 + 2 * t) = make_float2(acc[1][2], acc[1][3]);
#pragma unroll
        for (int sg = 0; sg < 3; sg++) {
            *reinterpret_cast<float2*>(kv + 256 + 128 * sg + 8 * g + 2 * t) = make_float2(acc[2 + sg][0], acc[2 + sg][1]);
            *reinterpret_cast<float2*>(kv + 256 + 128 * sg + 8 * (g + 8) + 2 * t) = make_float2(acc[2 + sg][2], acc[2 + sg][3]);
        }
        if (lane == 0) kv[640] = tail;
    }
    named_bar(bar_id, 64);
    if (threadIdx.x == 0) STAMP(1, 2);
    {
        const int tid2 = h * 32 + lane;
        if (tid2 < 16) s_q[tid2] = 0u;
        for (int x = tid2; x < L_; x += 64) {
            float kc, kp;
            {
                int s = (x >= 1024) ? 3 : (x >= 512) ? 2 : (x >= 256) ? 1 : 0;
                int rq = (s == 0) ? x : ((x + (1 << (s - 1)) - 1 + ((x >> s) & 1)) >> s);
                int idx = 128 * s + rq;
                kc = s_kv[idx] + s_kv[648 + idx];
            }
            {
                int y = x - 1;
                if (y < 0) kp = 0.f;
                else {
                    int s = (y >= 1024) ? 3 : (y >= 512) ? 2 : (y >= 256) ? 1 : 0;
                    int rq = (s == 0) ? y : ((y + (1 << (s - 1)) - 1 + ((y >> s) & 1)) >> s);
                    int idx = 128 * s + rq;
                    kp = s_kv[idx] + s_kv[648 + idx];
                }
            }
            s_q[x + 16] = pack_bf16(kc, kp);
        }
    }
    if (threadIdx.x == 0) STAMP(1, 3);
    pdl_wait();
    if (threadIdx.x == 0) STAMP(1, 4);
    {
        const int tid2 = h * 32 + lane;
        if (tid2 < 16) *reinterpret_cast<uint4*>(s_u + tid2 * 8) = make_uint4(0, 0, 0, 0);
        const uint4* src = reinterpret_cast<const uint4*>(g_xnT + (size_t)d * L_);
#pragma unroll
        for (int i = 0; i < 4; i++) {
            *reinterpret_cast<uint4*>(s_u + 128 + (tid2 + i * 64) * 8) = src[tid2 + i * 64];
        }
    }
    named_bar(bar_id, 64);
    if (threadIdx.x == 0) STAMP(1, 5);
    float acc[16][4];
#pragma unroll
    for (int i = 0; i < 16; i++) { acc[i][0] = acc[i][1] = acc[i][2] = acc[i][3] = 0.f; }
    const uint32_t su_addr = smem_u32(s_u);
    for (int rr = 0; rr < 4; rr++) {
        const int r = h * 4 + rr;
        uint32_t ub[16][2];
        {
            const int mi = lane >> 3, rowi = lane & 7;
            uint32_t addr = su_addr + (uint32_t)((128 + 16 * (8 * (mi >> 1) + rowi - r) + 8 * (mi & 1)) * 2);
#pragma unroll
            for (int j = 0; j < 16; j += 2) {
                asm volatile("ldmatrix.sync.aligned.m8n8.x4.shared.b16 {%0,%1,%2,%3}, [%4];"
                             : "=r"(ub[j][0]), "=r"(ub[j][1]), "=r"(ub[j + 1][0]), "=r"(ub[j + 1][1])
                             : "r"(addr + (uint32_t)(j * 8 * 16 * 2)));
            }
        }
        const uint32_t* qp = s_q + 16 + 16 * r + g - 2 * t;
#pragma unroll
        for (int q = 0; q < 16; q++) {
            const uint32_t a0 = qp[128 * q], a1 = qp[128 * q + 8], a2 = qp[128 * q - 8];
#pragma unroll
            for (int nt = q; nt < 16; nt++) mma_bf16(acc[nt], a0, a1, a2, a0, ub[nt - q][0], ub[nt - q][1]);
        }
    }
    if (threadIdx.x == 0) STAMP(1, 6);
    named_bar(bar_id, 64);
    {
        float4* xch = reinterpret_cast<float4*>(base) + h * 256;
        if (h) {
#pragma unroll
            for (int i = 0; i < 8; i++) xch[i * 32 + lane] = make_float4(acc[i][0], acc[i][1], acc[i][2], acc[i][3]);
        } else {
#pragma unroll
            for (int i = 0; i < 8; i++) xch[i * 32 + lane] = make_float4(acc[8 + i][0], acc[8 + i][1], acc[8 + i][2], acc[8 + i][3]);
        }
    }
    named_bar(bar_id, 64);
    {
        const float4* xch = reinterpret_cast<const float4*>(base) + (h ^ 1) * 256;
        const float dsk = __bfloat162float(Dskip[d]);
        __nv_bfloat16* stg = reinterpret_cast<__nv_bfloat16*>(s_q);
#pragma unroll
        for (int i = 0; i < 8; i++) {
            float4 o = xch[i * 32 + lane];
            float y[4];
            if (h) { y[0] = acc[8 + i][0] + o.x; y[1] = acc[8 + i][1] + o.y; y[2] = acc[8 + i][2] + o.z; y[3] = acc[8 + i][3] + o.w; }
            else   { y[0] = acc[i][0] + o.x; y[1] = acc[i][1] + o.y; y[2] = acc[i][2] + o.z; y[3] = acc[i][3] + o.w; }
            const int nt = h * 8 + i;
#pragma unroll
            for (int e = 0; e < 4; e++) {
                const int tau = 16 * (8 * nt + 2 * t + (e & 1)) + g + 8 * (e >> 1);
                float u = __bfloat162float(s_u[128 + tau]);
                float sv = bf16_round(y[e]) + bf16_round(u * dsk);
                reinterpret_cast<uint16_t*>(stg)[tau] = (uint16_t)(__float_as_uint(bf16_round(sv)) >> 16);
            }
        }
        __syncwarp();
        uint4* dst = reinterpret_cast<uint4*>(g_sT + (size_t)d * L_ + h * 1024);
        const uint4* srcp = reinterpret_cast<const uint4*>(stg + h * 1024);
#pragma unroll
        for (int i = 0; i < 4; i++) dst[i * 32 + lane] = srcp[i * 32 + lane];
    }
    if (threadIdx.x == 0) STAMP(1, 7);
}

__device__ __forceinline__ uint32_t cluster_rank() { uint32_t r; asm volatile("mov.u32 %0, %%cluster_ctarank;" : "=r"(r)); return r; }
__device__ __forceinline__ void cluster_sync_all() {
    asm volatile("barrier.cluster.arrive.release.aligned;\nbarrier.cluster.wait.acquire.aligned;" ::: "memory");
}
__device__ __forceinline__ void mbar_arrive_remote(uint32_t bar, uint32_t cta) {
    asm volatile("{\n.reg .b32 ra;\nmapa.shared::cluster.u32 ra, %0, %1;\n"
                 "mbarrier.arrive.shared::cluster.b64 _, [ra];\n}\n" ::"r"(bar), "r"(cta) : "memory");
}
__device__ __forceinline__ void tma_load_2d_mc(uint32_t dst, const CUtensorMap* tm, int c0, int c1, uint32_t bar, uint16_t mask) {
    asm volatile(
        "cp.async.bulk.tensor.2d.shared::cluster.global.mbarrier::complete_tx::bytes.multicast::cluster [%0], [%1, {%3, %4}], [%2], %5;"
        ::"r"(dst), "l"((uint64_t)tm), "r"(bar), "r"(c0), "r"(c1), "h"(mask) : "memory");
}
__device__ __forceinline__ void tma_store_2d(const CUtensorMap* tm, uint32_t src, int c0, int c1) {
    asm volatile("cp.async.bulk.tensor.2d.global.shared::cta.bulk_group [%0, {%2, %3}], [%1];"
                 ::"l"((uint64_t)tm), "r"(src), "r"(c0), "r"(c1) : "memory");
}
__device__ __forceinline__ void bulk_commit() { asm volatile("cp.async.bulk.commit_group;" ::: "memory"); }
template <int N> __device__ __forceinline__ void bulk_wait_read() { asm volatile("cp.async.bulk.wait_group.read %0;" ::"n"(N) : "memory"); }
template <int N> __device__ __forceinline__ void bulk_wait() { asm volatile("cp.async.bulk.wait_group %0;" ::"n"(N) : "memory"); }
__device__ __forceinline__ void fence_async_smem() { asm volatile("fence.proxy.async.shared::cta;" ::: "memory"); }
__device__ __forceinline__ void stmatrix_x4(uint32_t addr, uint32_t r0, uint32_t r1, uint32_t r2, uint32_t r3) {
    asm volatile("stmatrix.sync.aligned.m8n8.x4.shared.b16 [%0], {%1,%2,%3,%4};" ::"r"(addr), "r"(r0), "r"(r1), "r"(r2), "r"(r3) : "memory");
}

constexpr int G1_STAGES = 5;
constexpr int G1_A_BYTES = 8 * 16384;
constexpr int G1_B_STAGE = 16384;
constexpr int G1_STG = 8 * 1024;
constexpr int G1_SMEM = G1_A_BYTES + G1_STAGES * G1_B_STAGE + G1_STG + 1024 + 256;
constexpr int G1_ITERS = 32;

__device__ __forceinline__ void tma_load_3d(uint32_t dst, const CUtensorMap* tm, int c0, int c1, int c2, uint32_t bar) {
    asm volatile(
        "cp.async.bulk.tensor.3d.shared::cluster.global.mbarrier::complete_tx::bytes [%0], [%1, {%3, %4, %5}], [%2];"
        ::"r"(dst), "l"((uint64_t)tm), "r"(bar), "r"(c0), "r"(c1), "r"(c2) : "memory");
}

__device__ __forceinline__ float gelu_tanh(float x) {
    float u = x * (0.7978845608028654f + 0.035677408136300125f * x * x);
    float t; asm("tanh.approx.f32 %0, %1;" : "=f"(t) : "f"(u));
    float hx = 0.5f * x;
    return fmaf(hx, t, hx);
}
__device__ __forceinline__ uint32_t geglu_pair(uint32_t p0, uint32_t p1) {
    float a = bf16_round(gelu_tanh(bf_lo(p0))) * bf_hi(p0);
    float b = bf16_round(gelu_tanh(bf_lo(p1))) * bf_hi(p1);
    return pack_bf16(a, b);
}

__global__ void __launch_bounds__(384, 1) gemm1_kernel(const __grid_constant__ CUtensorMap tm_xn,
                                                        const __grid_constant__ CUtensorMap tm_wg4,
                                                        const __grid_constant__ CUtensorMap tm_wu4,
                                                        const __grid_constant__ CUtensorMap tm_wg3,
                                                        const __grid_constant__ CUtensorMap tm_wu3,
                                                        const __grid_constant__ CUtensorMap tm_hst,
                                                        const __grid_constant__ CUtensorMap tm_hst96) {
    pdl_launch();
    if (threadIdx.x == 0) STAMP(2, 0);
    extern __shared__ uint8_t smem_raw[];
    const uint32_t sbase = (smem_u32(smem_raw) + 1023) & ~1023u;
    const uint32_t sA = sbase, sB = sbase + G1_A_BYTES, sStg = sB + G1_STAGES * G1_B_STAGE, sBar = sStg + G1_STG;
    const uint32_t bar_a = sBar, bar_full = sBar + 64, bar_empty = sBar + 64 + 8 * G1_STAGES;
    const int rb = blockIdx.x >> 3, cj = blockIdx.x & 7;
    const int warp = threadIdx.x >> 5, lane = threadIdx.x & 31;

    if (threadIdx.x == 0) {
        for (int i = 0; i < 8; i++) mbar_init(bar_a + 8 * i, 1);
        for (int i = 0; i < G1_STAGES; i++) { mbar_init(bar_full + 8 * i, 1); mbar_init(bar_empty + 8 * i, 8); }
        asm volatile("fence.mbarrier_init.release.cluster;" ::: "memory");
    }
    __syncthreads();

    if (warp >= 8) {
        asm volatile("setmaxnreg.dec.sync.aligned.u32 40;");
        if (lane == 0) {
            const int pw = warp - 8;
            if (pw == 0) { prefetch_tmap(&tm_wg4); prefetch_tmap(&tm_wu4); prefetch_tmap(&tm_xn); }
            if (pw == 1) { prefetch_tmap(&tm_wg3); prefetch_tmap(&tm_wu3); prefetch_tmap(&tm_hst); prefetch_tmap(&tm_hst96); }
            for (int it = pw; it < G1_ITERS; it += 4) {
                const int s = it % G1_STAGES, kb = it & 15;
                if (it >= G1_STAGES) mbar_wait(bar_empty + 8 * s, ((it / G1_STAGES) - 1) & 1);
                const uint32_t dst = sB + s * G1_B_STAGE;
                if (it < 16) {
                    mbar_expect_tx(bar_full + 8 * s, 16384);
                    tma_load_3d(dst, &tm_wg4, 0, kb * 32, cj * 7, bar_full + 8 * s);
                    tma_load_3d(dst + 8192, &tm_wu4, 0, kb * 32, cj * 7, bar_full + 8 * s);
                } else {
                    mbar_expect_tx(bar_full + 8 * s, 12288);
                    tma_load_3d(dst, &tm_wg3, 0, kb * 32, cj * 7 + 4, bar_full + 8 * s);
                    tma_load_3d(dst + 6144, &tm_wu3, 0, kb * 32, cj * 7 + 4, bar_full + 8 * s);
                }
                if (it < 4) {
                    pdl_wait();
                    if (pw == 0) STAMP(2, 1);
                    for (int k = pw; k < 8; k += 4) {
                        mbar_expect_tx(bar_a + 8 * k, 16384);
                        tma_load_2d(sA + k * 16384, &tm_xn, k * 64, rb * 128, bar_a + 8 * k);
                    }
                }
            }
        }
    } else {
        asm volatile("setmaxnreg.inc.sync.aligned.u32 232;");
        const int wg = __shfl_sync(0xffffffffu, (int)(threadIdx.x >> 7), 0);
        float r[160];
        const int row0 = rb * 128 + wg * 64 + (warp & 3) * 16;
        const uint64_t descA = make_desc(sA + wg * 8192, 16, 1024);
        const uint64_t descB = make_desc(sB, 2048, 512, 2);
        const uint32_t stg = sStg + warp * 1024;
        const uint32_t st_off = (uint32_t)(((lane & 7) + ((lane >> 3) & 1) * 8) * 32 + (lane >> 4) * 16);
        auto store_group = [&](const float* pk, int par, int col) {
            const uint32_t buf = stg + par * 512;
            uint32_t r0 = geglu_pair(__float_as_uint(pk[0]), __float_as_uint(pk[1]));
            uint32_t r1 = geglu_pair(__float_as_uint(pk[2]), __float_as_uint(pk[3]));
            uint32_t r2 = geglu_pair(__float_as_uint(pk[4]), __float_as_uint(pk[5]));
            uint32_t r3 = geglu_pair(__float_as_uint(pk[6]), __float_as_uint(pk[7]));
            if (lane == 0) bulk_wait_read<1>();
            __syncwarp();
            stmatrix_x4(buf + st_off, r0, r1, r2, r3);
            fence_async_smem();
            __syncwarp();
            if (lane == 0) { tma_store_2d(&tm_hst, buf, col, row0); bulk_commit(); }
        };
#pragma unroll
        for (int kb = 0; kb < 16; kb++) {
            const int it = kb, s = it % G1_STAGES;
            if ((kb & 1) == 0) mbar_wait(bar_a + 8 * (kb >> 1), 0);
            mbar_wait(bar_full + 8 * s, (it / G1_STAGES) & 1);
            if (threadIdx.x == 0 && (it & 7) == 0) STAMP(2, 2 + it / 8);
            wgmma_fence();
            const uint64_t da = descA + (uint64_t)(((kb >> 1) * 16384 + (kb & 1) * 64) >> 4);
            const uint64_t db = descB + (uint64_t)((s * G1_B_STAGE) >> 4);
            wgmma_n256_k32(r, da, da + 2, db, db + 64, kb != 0);
            wgmma_commit();
            if (kb > 0) {
                wgmma_wait<1>();
                if (lane == 0) mbar_arrive(bar_empty + 8 * ((it - 1) % G1_STAGES));
            }
        }
        wgmma_wait<0>();
        if (lane == 0) mbar_arrive(bar_empty + 8 * (15 % G1_STAGES));
#pragma unroll
        for (int i = 0; i < 32; i++) r[128 + i] = __uint_as_float(pack_bf16(r[i], r[64 + i]));
#pragma unroll
        for (int i = 32; i < 64; i++) r[64 + i] = __uint_as_float(pack_bf16(r[i], r[64 + i]));
#pragma unroll
        for (int kb = 0; kb < 16; kb++) {
            const int it = 16 + kb, s = it % G1_STAGES;
            mbar_wait(bar_full + 8 * s, (it / G1_STAGES) & 1);
            if (threadIdx.x == 0 && (it & 7) == 0) STAMP(2, 2 + it / 8);
            wgmma_fence();
            const uint64_t da = descA + (uint64_t)(((kb >> 1) * 16384 + (kb & 1) * 64) >> 4);
            const uint64_t db = descB + (uint64_t)((s * G1_B_STAGE) >> 4);
            wgmma_n192_k32(r, da, da + 2, db, db + 64, kb != 0);
            wgmma_commit();
            if (kb > 0 && it - 1 + G1_STAGES < G1_ITERS) {
                wgmma_wait<1>();
                if (lane == 0) mbar_arrive(bar_empty + 8 * ((it - 1) % G1_STAGES));
            }
            if ((kb & 1) == wg) {
                const int jj = kb >> 1;
                store_group(jj < 4 ? &r[128 + 8 * jj] : &r[64 + 8 * jj], jj & 1, cj * 224 + jj * 16);
            }
        }
        wgmma_wait<0>();
#pragma unroll
        for (int i = 0; i < 48; i++) r[i] = __uint_as_float(pack_bf16(r[i], r[48 + i]));
        if (threadIdx.x == 0) STAMP(2, 6);
        {
            uint32_t o[24];
#pragma unroll
            for (int i = 0; i < 24; i++) o[i] = geglu_pair(__float_as_uint(r[2 * i]), __float_as_uint(r[2 * i + 1]));
            named_bar(1 + wg, 128);
            const uint32_t fbuf = sA + ((warp & 3) >> 1) * 16384 + wg * 8192 + (warp & 1) * 4096;
            const uint32_t f_off = (uint32_t)(((lane & 7) + ((lane >> 3) & 1) * 8) * 192 + (lane >> 4) * 16);
#pragma unroll
            for (int jj = 0; jj < 6; jj++) stmatrix_x4(fbuf + f_off + jj * 32, o[4 * jj], o[4 * jj + 1], o[4 * jj + 2], o[4 * jj + 3]);
            fence_async_smem();
            __syncwarp();
            if (lane == 0) { tma_store_2d(&tm_hst96, fbuf, cj * 224 + 128, row0); bulk_commit(); }
        }
        if (lane == 0) bulk_wait_read<0>();
        if (threadIdx.x == 0) STAMP(2, 7);
    }
}

constexpr int G2_STAGES = 5;
constexpr int G2_STAGE = 16384 + 16384;
constexpr int G2_XCH = 32768;
constexpr int G2_EPI = 16384 + 16384;
constexpr int G2_SMEM = G2_STAGES * G2_STAGE + G2_XCH + G2_EPI + 1024 + 256;
constexpr int G2_KB = F_ / 64 / 2;

__global__ void __launch_bounds__(384, 1) gemm2_kernel(const __grid_constant__ CUtensorMap tm_h,
                                                        const __grid_constant__ CUtensorMap tm_wd,
                                                        const __grid_constant__ CUtensorMap tm_x,
                                                        const __grid_constant__ CUtensorMap tm_sT,
                                                        const __grid_constant__ CUtensorMap tm_out) {
    if (threadIdx.x == 0) STAMP(3, 0);
    extern __shared__ uint8_t smem_raw[];
    const uint32_t sbase = (smem_u32(smem_raw) + 1023) & ~1023u;
    const uint32_t sXch = sbase + G2_STAGES * G2_STAGE, sX = sXch + G2_XCH, sS = sX + 16384, sBar = sX + G2_EPI;
    const uint32_t bar_full = sBar, bar_empty = sBar + 8 * G2_STAGES, bar_epi = sBar + 16 * G2_STAGES, bar_xch = bar_epi + 8;
    const uint32_t kh = cluster_rank();
    const int cid = blockIdx.x >> 1;
    const int rb = cid >> 2, nb = cid & 3;
    const int col_fin = nb * 128 + kh * 64;
    const int warp = threadIdx.x >> 5, lane = threadIdx.x & 31;

    if (threadIdx.x == 0) {
        for (int i = 0; i < G2_STAGES; i++) { mbar_init(bar_full + 8 * i, 1); mbar_init(bar_empty + 8 * i, 8); }
        mbar_init(bar_epi, 1);
        mbar_init(bar_xch, 1);
        asm volatile("fence.mbarrier_init.release.cluster;" ::: "memory");
        mbar_expect_tx(bar_xch, G2_XCH);
    }
    cluster_sync_all();

    if (warp >= 8) {
        if (lane == 0) {
            const int pw = warp - 8;
            const int k0 = kh * G2_KB;
            if (pw == 0) { prefetch_tmap(&tm_wd); prefetch_tmap(&tm_h); }
            if (pw == 1) { prefetch_tmap(&tm_x); prefetch_tmap(&tm_sT); prefetch_tmap(&tm_out); }
            for (int it = pw; it < G2_STAGES; it += 4) {
                mbar_expect_tx(bar_full + 8 * it, G2_STAGE);
                tma_load_3d(sbase + it * G2_STAGE + 16384, &tm_wd, 0, (k0 + it) * 64, nb * 2, bar_full + 8 * it);
            }
            if (pw == 3) {
                mbar_expect_tx(bar_epi, G2_EPI);
                tma_load_2d(sX, &tm_x, col_fin, rb * 128, bar_epi);
            }
            pdl_wait();
            if (pw == 0) STAMP(3, 1);
            for (int it = pw; it < G2_STAGES; it += 4)
                tma_load_2d(sbase + it * G2_STAGE, &tm_h, (k0 + it) * 64, rb * 128, bar_full + 8 * it);
            if (pw == 3) {
                tma_load_2d(sS, &tm_sT, rb * 128, col_fin, bar_epi);
                tma_load_2d(sS + 8192, &tm_sT, rb * 128 + 64, col_fin, bar_epi);
            }
            for (int it = G2_STAGES + ((pw + 4 - (G2_STAGES & 3)) & 3); it < G2_KB; it += 4) {
                const int s = it % G2_STAGES;
                mbar_wait(bar_empty + 8 * s, ((it / G2_STAGES) - 1) & 1);
                mbar_expect_tx(bar_full + 8 * s, G2_STAGE);
                tma_load_2d(sbase + s * G2_STAGE, &tm_h, (k0 + it) * 64, rb * 128, bar_full + 8 * s);
                tma_load_3d(sbase + s * G2_STAGE + 16384, &tm_wd, 0, (k0 + it) * 64, nb * 2, bar_full + 8 * s);
            }
        }
    } else {
        const int wg = __shfl_sync(0xffffffffu, (int)(threadIdx.x >> 7), 0);
        const int g = lane >> 2, t = lane & 3;
        float acc[64];
        const uint64_t descA = make_desc(sbase + wg * 8192, 16, 1024);
        const uint64_t descB = make_desc(sbase + 16384, 8192, 1024);
#pragma unroll
        for (int it = 0; it < G2_KB; it++) {
            const int s = it % G2_STAGES;
            mbar_wait(bar_full + 8 * s, (it / G2_STAGES) & 1);
            if (threadIdx.x == 0 && (it == 0 || it == 7)) STAMP(3, 2 + it / 7);
            wgmma_fence();
            {
                const uint64_t da = descA + (uint64_t)((s * G2_STAGE) >> 4);
                const uint64_t db = descB + (uint64_t)((s * G2_STAGE) >> 4);
                wgmma_n128_k64(acc, da, da + 2, da + 4, da + 6, db, db + 128, db + 256, db + 384, it != 0);
            }
            wgmma_commit();
            if (it > 0 && it - 1 + G2_STAGES < G2_KB) {
                wgmma_wait<1>();
                if (lane == 0) mbar_arrive(bar_empty + 8 * ((it - 1) % G2_STAGES));
            }
        }
        const int lr = wg * 64 + (warp & 3) * 16 + g;
        uint32_t xv[16], sv[16];
        mbar_wait(bar_epi, 0);
#pragma unroll
        for (int j = 0; j < 8; j++) {
#pragma unroll
            for (int hh = 0; hh < 2; hh++) {
                const int r = lr + 8 * hh;
                asm volatile("ld.shared.u32 %0, [%1];" : "=r"(xv[2 * j + hh]) : "r"(sX + r * 128 + ((j ^ (r & 7)) << 4) + 4 * t));
                const int c0 = 8 * j + 2 * t;
                const uint32_t sa = sS + (r >> 6) * 8192 + (((r & 63) >> 3) << 4) + (r & 7) * 2;
                uint16_t s0r, s1r;
                asm volatile("ld.shared.u16 %0, [%1];" : "=h"(s0r) : "r"((sa + c0 * 128) ^ ((c0 & 7) << 4)));
                asm volatile("ld.shared.u16 %0, [%1];" : "=h"(s1r) : "r"((sa + (c0 + 1) * 128) ^ (((c0 + 1) & 7) << 4)));
                sv[2 * j + hh] = (uint32_t)s0r | ((uint32_t)s1r << 16);
            }
        }
        wgmma_wait<0>();
        if (threadIdx.x == 0) STAMP(3, 4);
        {
            uint32_t remote, rbar;
            asm volatile("mapa.shared::cluster.u32 %0, %1, %2;" : "=r"(remote) : "r"(sXch + threadIdx.x * 16), "r"(kh ^ 1));
            asm volatile("mapa.shared::cluster.u32 %0, %1, %2;" : "=r"(rbar) : "r"(bar_xch), "r"(kh ^ 1));
            if (kh == 0) {
#pragma unroll
                for (int i = 0; i < 8; i++)
                    asm volatile("st.async.shared::cluster.mbarrier::complete_tx::bytes.v4.f32 [%0], {%1,%2,%3,%4}, [%5];" ::"r"(remote + i * 4096),
                                 "f"(acc[32 + 4 * i]), "f"(acc[33 + 4 * i]), "f"(acc[34 + 4 * i]), "f"(acc[35 + 4 * i]), "r"(rbar) : "memory");
            } else {
#pragma unroll
                for (int i = 0; i < 8; i++)
                    asm volatile("st.async.shared::cluster.mbarrier::complete_tx::bytes.v4.f32 [%0], {%1,%2,%3,%4}, [%5];" ::"r"(remote + i * 4096),
                                 "f"(acc[4 * i]), "f"(acc[1 + 4 * i]), "f"(acc[2 + 4 * i]), "f"(acc[3 + 4 * i]), "r"(rbar) : "memory");
#pragma unroll
                for (int i = 0; i < 32; i++) acc[i] = acc[32 + i];
            }
        }
        if (threadIdx.x == 0) STAMP(3, 6);
        mbar_wait(bar_xch, 0);
        if (threadIdx.x == 0) STAMP(3, 7);
#pragma unroll
        for (int j = 0; j < 8; j++) {
            float4 o;
            asm volatile("ld.shared.v4.f32 {%0,%1,%2,%3}, [%4];" : "=f"(o.x), "=f"(o.y), "=f"(o.z), "=f"(o.w) : "r"(sXch + threadIdx.x * 16 + j * 4096));
            acc[4 * j] += o.x; acc[4 * j + 1] += o.y; acc[4 * j + 2] += o.z; acc[4 * j + 3] += o.w;
        }
#pragma unroll
        for (int i = 0; i < 16; i++) {
            float f0 = bf16_round(acc[2 * i]), f1 = bf16_round(acc[2 * i + 1]);
            float g0 = bf16_round(__fdividef(f0, 1.0f + __expf(-f0)));
            float g1 = bf16_round(__fdividef(f1, 1.0f + __expf(-f1)));
            float o0 = bf_lo(xv[i]) + bf16_round(bf_lo(sv[i]) * g0);
            float o1 = bf_hi(xv[i]) + bf16_round(bf_hi(sv[i]) * g1);
            xv[i] = pack_bf16(o0, o1);
        }
#pragma unroll
        for (int j = 0; j < 8; j++) {
#pragma unroll
            for (int hh = 0; hh < 2; hh++) {
                const int r = lr + 8 * hh;
                asm volatile("st.shared.u32 [%0], %1;" ::"r"(sX + r * 128 + ((j ^ (r & 7)) << 4) + 4 * t), "r"(xv[2 * j + hh]) : "memory");
            }
        }
        if (threadIdx.x == 0) STAMP(3, 9);
        fence_async_smem();
        __syncwarp();
        if (lane == 0) {
            tma_store_2d(&tm_out, sX + (wg * 64 + (warp & 3) * 16) * 128, col_fin, rb * 128 + wg * 64 + (warp & 3) * 16);
            bulk_commit();
            bulk_wait_read<0>();
        }
        if (threadIdx.x == 0) STAMP(3, 5);
    }
}

typedef CUresult (*EncodeFn)(CUtensorMap*, CUtensorMapDataType, cuuint32_t, void*, const cuuint64_t*, const cuuint64_t*,
                             const cuuint32_t*, const cuuint32_t*, CUtensorMapInterleave, CUtensorMapSwizzle,
                             CUtensorMapL2promotion, CUtensorMapFloatOOBfill);

void make_map(EncodeFn fn, CUtensorMap* m, const void* ptr, uint64_t inner, uint64_t outer, uint32_t box_in, uint32_t box_out,
              CUtensorMapSwizzle swz = CU_TENSOR_MAP_SWIZZLE_128B) {
    cuuint64_t dims[2] = {inner, outer};
    cuuint64_t strides[1] = {inner * 2};
    cuuint32_t box[2] = {box_in, box_out};
    cuuint32_t es[2] = {1, 1};
    fn(m, CU_TENSOR_MAP_DATA_TYPE_BFLOAT16, 2, const_cast<void*>(ptr), dims, strides, box, es, CU_TENSOR_MAP_INTERLEAVE_NONE,
       swz, CU_TENSOR_MAP_L2_PROMOTION_L2_256B, CU_TENSOR_MAP_FLOAT_OOB_FILL_NONE);
}
void make_map3(EncodeFn fn, CUtensorMap* m, const void* ptr, uint64_t cols, uint64_t rows, uint32_t atom, uint32_t box_rows,
               uint32_t box_atoms, CUtensorMapSwizzle swz) {
    cuuint64_t dims[3] = {atom, rows, cols / atom};
    cuuint64_t strides[2] = {cols * 2, (cuuint64_t)atom * 2};
    cuuint32_t box[3] = {atom, box_rows, box_atoms};
    cuuint32_t es[3] = {1, 1, 1};
    fn(m, CU_TENSOR_MAP_DATA_TYPE_BFLOAT16, 3, const_cast<void*>(ptr), dims, strides, box, es, CU_TENSOR_MAP_INTERLEAVE_NONE,
       swz, CU_TENSOR_MAP_L2_PROMOTION_L2_256B, CU_TENSOR_MAP_FLOAT_OOB_FILL_NONE);
}

template <typename... Args>
void launch_pdl(void (*kern)(Args...), int grid, int block, int smem, bool pdl, int cluster, Args... args) {
    cudaLaunchConfig_t cfg = {};
    cfg.gridDim = dim3(grid); cfg.blockDim = dim3(block); cfg.dynamicSmemBytes = smem; cfg.stream = cudaStreamPerThread;
    cudaLaunchAttribute at[2];
    int n = 0;
    if (pdl) {
        at[n].id = cudaLaunchAttributeProgrammaticStreamSerialization;
        at[n].val.programmaticStreamSerializationAllowed = 1;
        n++;
    }
    if (cluster > 1) {
        at[n].id = cudaLaunchAttributeClusterDimension;
        at[n].val.clusterDim.x = cluster; at[n].val.clusterDim.y = 1; at[n].val.clusterDim.z = 1;
        n++;
    }
    cfg.attrs = at; cfg.numAttrs = n;
    cudaLaunchKernelEx(&cfg, kern, args...);
}

}

extern "C" void kernel_launch(void* const* d_in, const int* in_sizes, int n_in, void* d_out, int out_size) {
    const __nv_bfloat16* x = (const __nv_bfloat16*)d_in[0];
    const __nv_bfloat16* A_re = (const __nv_bfloat16*)d_in[1];
    const __nv_bfloat16* A_im = (const __nv_bfloat16*)d_in[2];
    const __nv_bfloat16* B_re = (const __nv_bfloat16*)d_in[3];
    const __nv_bfloat16* B_im = (const __nv_bfloat16*)d_in[4];
    const __nv_bfloat16* C_re = (const __nv_bfloat16*)d_in[5];
    const __nv_bfloat16* C_im = (const __nv_bfloat16*)d_in[6];
    const __nv_bfloat16* log_dt = (const __nv_bfloat16*)d_in[7];
    const __nv_bfloat16* Dskip = (const __nv_bfloat16*)d_in[8];
    const __nv_bfloat16* wg = (const __nv_bfloat16*)d_in[10];
    const __nv_bfloat16* wu = (const __nv_bfloat16*)d_in[11];
    const __nv_bfloat16* wd = (const __nv_bfloat16*)d_in[12];
    __nv_bfloat16* out = (__nv_bfloat16*)d_out;

    static bool init = false;
    static CUtensorMap tm_xn, tm_wg4, tm_wu4, tm_wg3, tm_wu3, tm_hst, tm_hst96, tm_h, tm_wd, tm_x, tm_sT, tm_out;
    static const void* last_ptrs[5] = {nullptr, nullptr, nullptr, nullptr, nullptr};
    if (!init || last_ptrs[0] != wg || last_ptrs[1] != wu || last_ptrs[2] != wd || last_ptrs[3] != x || last_ptrs[4] != out) {
        void* fnp = nullptr;
        cudaDriverEntryPointQueryResult qres;
        cudaGetDriverEntryPoint("cuTensorMapEncodeTiled", &fnp, cudaEnableDefault, &qres);
        EncodeFn fn = (EncodeFn)fnp;
        void *p_xn, *p_h, *p_sT;
        cudaGetSymbolAddress(&p_xn, g_xn);
        cudaGetSymbolAddress(&p_h, g_h);
        cudaGetSymbolAddress(&p_sT, g_sT);
        make_map(fn, &tm_xn, p_xn, D_, L_, 64, 128);
        make_map3(fn, &tm_wg4, wg, F_, D_, 32, 32, 4, CU_TENSOR_MAP_SWIZZLE_64B);
        make_map3(fn, &tm_wu4, wu, F_, D_, 32, 32, 4, CU_TENSOR_MAP_SWIZZLE_64B);
        make_map3(fn, &tm_wg3, wg, F_, D_, 32, 32, 3, CU_TENSOR_MAP_SWIZZLE_64B);
        make_map3(fn, &tm_wu3, wu, F_, D_, 32, 32, 3, CU_TENSOR_MAP_SWIZZLE_64B);
        make_map(fn, &tm_hst, p_h, F_, L_, 16, 16, CU_TENSOR_MAP_SWIZZLE_NONE);
        make_map(fn, &tm_hst96, p_h, F_, L_, 96, 16, CU_TENSOR_MAP_SWIZZLE_NONE);
        make_map(fn, &tm_h, p_h, F_, L_, 64, 128);
        make_map3(fn, &tm_wd, wd, D_, F_, 64, 64, 2, CU_TENSOR_MAP_SWIZZLE_128B);
        make_map(fn, &tm_x, x, D_, L_, 64, 128);
        make_map(fn, &tm_sT, p_sT, L_, D_, 64, 64);
        make_map(fn, &tm_out, out, D_, L_, 64, 16);
        cudaFuncSetAttribute(ln_kernel, cudaFuncAttributePreferredSharedMemoryCarveout, 100);
        cudaFuncSetAttribute(conv_kernel, cudaFuncAttributeMaxDynamicSharedMemorySize, CV_SMEM);
        cudaFuncSetAttribute(conv_kernel, cudaFuncAttributePreferredSharedMemoryCarveout, 100);
        cudaFuncSetAttribute(gemm1_kernel, cudaFuncAttributeMaxDynamicSharedMemorySize, G1_SMEM);
        cudaFuncSetAttribute(gemm2_kernel, cudaFuncAttributeMaxDynamicSharedMemorySize, G2_SMEM);
        last_ptrs[0] = wg; last_ptrs[1] = wu; last_ptrs[2] = wd; last_ptrs[3] = x; last_ptrs[4] = out;
        init = true;
    }
    launch_pdl(ln_kernel, L_ / LN_ROWS, 256, 0, false, 1, x, wg, wu, wd);
    launch_pdl(conv_kernel, D_ / CV_CH, 256, CV_SMEM, true, 1, A_re, A_im, B_re, B_im, C_re, C_im, log_dt, Dskip);
    launch_pdl(gemm1_kernel, 128, 384, G1_SMEM, true, 1, tm_xn, tm_wg4, tm_wu4, tm_wg3, tm_wu3, tm_hst, tm_hst96);
    launch_pdl(gemm2_kernel, 128, 384, G2_SMEM, true, 2, tm_h, tm_wd, tm_x, tm_sT, tm_out);
}
```

```cpp
#include <cuda_runtime.h>
#include <cuda_bf16.h>
#include <cuda.h>
#include <stdint.h>

namespace {

constexpr int L_ = 2048, D_ = 512, NS_ = 128, F_ = 1792;

__device__ __align__(1024) __nv_bfloat16 g_xn[L_ * D_];
__device__ __align__(1024) __nv_bfloat16 g_xnT[D_ * L_];
__device__ __align__(1024) __nv_bfloat16 g_sT[D_ * L_];
__device__ __align__(1024) __nv_bfloat16 g_h[L_ * F_];

#define STAMP(k, i)

__device__ __forceinline__ uint32_t smem_u32(const void* p) { return (uint32_t)__cvta_generic_to_shared(p); }
__device__ __forceinline__ void pdl_wait() { asm volatile("griddepcontrol.wait;" ::: "memory"); }
__device__ __forceinline__ void pdl_launch() { asm volatile("griddepcontrol.launch_dependents;" ::: "memory"); }

__device__ __forceinline__ void mbar_init(uint32_t bar, uint32_t cnt) {
    asm volatile("mbarrier.init.shared::cta.b64 [%0], %1;" ::"r"(bar), "r"(cnt) : "memory");
}
__device__ __forceinline__ void mbar_expect_tx(uint32_t bar, uint32_t bytes) {
    asm volatile("mbarrier.arrive.expect_tx.shared::cta.b64 _, [%0], %1;" ::"r"(bar), "r"(bytes) : "memory");
}
__device__ __forceinline__ void mbar_arrive(uint32_t bar) {
    asm volatile("mbarrier.arrive.shared::cta.b64 _, [%0];" ::"r"(bar) : "memory");
}
__device__ __forceinline__ void mbar_wait(uint32_t bar, uint32_t parity) {
    asm volatile(
        "{\n.reg .pred p;\n"
        "WAIT_LOOP:\n"
        "mbarrier.try_wait.parity.shared::cta.b64 p, [%0], %1;\n"
        "@p bra WAIT_DONE;\n"
        "bra WAIT_LOOP;\n"
        "WAIT_DONE:\n}\n" ::"r"(bar), "r"(parity) : "memory");
}
__device__ __forceinline__ void tma_load_2d(uint32_t dst, const CUtensorMap* tm, int c0, int c1, uint32_t bar) {
    asm volatile(
        "cp.async.bulk.tensor.2d.shared::cluster.global.mbarrier::complete_tx::bytes [%0], [%1, {%3, %4}], [%2];"
        ::"r"(dst), "l"((uint64_t)tm), "r"(bar), "r"(c0), "r"(c1) : "memory");
}
__device__ __forceinline__ void prefetch_tmap(const CUtensorMap* tm) {
    asm volatile("prefetch.tensormap [%0];" ::"l"((uint64_t)tm) : "memory");
}
__device__ __forceinline__ uint64_t make_desc(uint32_t addr, uint32_t lbo, uint32_t sbo, uint64_t mode = 1) {
    uint64_t d = 0;
    d |= (uint64_t)((addr & 0x3FFFF) >> 4);
    d |= (uint64_t)((lbo >> 4) & 0x3FFF) << 16;
    d |= (uint64_t)((sbo >> 4) & 0x3FFF) << 32;
    d |= mode << 62;
    return d;
}
__device__ __forceinline__ void wgmma_fence() { asm volatile("wgmma.fence.sync.aligned;" ::: "memory"); }
__device__ __forceinline__ void wgmma_commit() { asm volatile("wgmma.commit_group.sync.aligned;" ::: "memory"); }
template <int N> __device__ __forceinline__ void wgmma_wait() {
    asm volatile("wgmma.wait_group.sync.aligned %0;" ::"n"(N) : "memory");
}

#define R8(a, i) "+f"(a[i + 0]), "+f"(a[i + 1]), "+f"(a[i + 2]), "+f"(a[i + 3]), "+f"(a[i + 4]), "+f"(a[i + 5]), "+f"(a[i + 6]), "+f"(a[i + 7])

__device__ __forceinline__ void wgmma_n256_k32(float* a, uint64_t da0, uint64_t da1, uint64_t db0, uint64_t db1, int scale_d) {
    asm volatile(
        "{\n.reg .pred p;\nsetp.ne.b32 p, %132, 0;\n"
        "wgmma.mma_async.sync.aligned.m64n256k16.f32.bf16.bf16 {%0,%1,%2,%3,%4,%5,%6,%7,%8,%9,%10,%11,%12,%13,%14,%15,%16,%17,%18,%19,%20,%21,%22,%23,%24,%25,%26,%27,%28,%29,%30,%31,%32,%33,%34,%35,%36,%37,%38,%39,%40,%41,%42,%43,%44,%45,%46,%47,%48,%49,%50,%51,%52,%53,%54,%55,%56,%57,%58,%59,%60,%61,%62,%63,%64,%65,%66,%67,%68,%69,%70,%71,%72,%73,%74,%75,%76,%77,%78,%79,%80,%81,%82,%83,%84,%85,%86,%87,%88,%89,%90,%91,%92,%93,%94,%95,%96,%97,%98,%99,%100,%101,%102,%103,%104,%105,%106,%107,%108,%109,%110,%111,%112,%113,%114,%115,%116,%117,%118,%119,%120,%121,%122,%123,%124,%125,%126,%127}, %128, %130, p, 1, 1, 0, 1;\n"
        "wgmma.mma_async.sync.aligned.m64n256k16.f32.bf16.bf16 {%0,%1,%2,%3,%4,%5,%6,%7,%8,%9,%10,%11,%12,%13,%14,%15,%16,%17,%18,%19,%20,%21,%22,%23,%24,%25,%26,%27,%28,%29,%30,%31,%32,%33,%34,%35,%36,%37,%38,%39,%40,%41,%42,%43,%44,%45,%46,%47,%48,%49,%50,%51,%52,%53,%54,%55,%56,%57,%58,%59,%60,%61,%62,%63,%64,%65,%66,%67,%68,%69,%70,%71,%72,%73,%74,%75,%76,%77,%78,%79,%80,%81,%82,%83,%84,%85,%86,%87,%88,%89,%90,%91,%92,%93,%94,%95,%96,%97,%98,%99,%100,%101,%102,%103,%104,%105,%106,%107,%108,%109,%110,%111,%112,%113,%114,%115,%116,%117,%118,%119,%120,%121,%122,%123,%124,%125,%126,%127}, %129, %131, 1, 1, 1, 0, 1;\n"
        "}\n"
        : R8(a, 0), R8(a, 8), R8(a, 16), R8(a, 24), R8(a, 32), R8(a, 40), R8(a, 48), R8(a, 56), R8(a, 64), R8(a, 72), R8(a, 80), R8(a, 88), R8(a, 96), R8(a, 104), R8(a, 112), R8(a, 120)
        : "l"(da0), "l"(da1), "l"(db0), "l"(db1), "r"(scale_d));
}
__device__ __forceinline__ void wgmma_n192_k32(float* a, uint64_t da0, uint64_t da1, uint64_t db0, uint64_t db1, int scale_d) {
    asm volatile(
        "{\n.reg .pred p;\nsetp.ne.b32 p, %100, 0;\n"
        "wgmma.mma_async.sync.aligned.m64n192k16.f32.bf16.bf16 {%0,%1,%2,%3,%4,%5,%6,%7,%8,%9,%10,%11,%12,%13,%14,%15,%16,%17,%18,%19,%20,%21,%22,%23,%24,%25,%26,%27,%28,%29,%30,%31,%32,%33,%34,%35,%36,%37,%38,%39,%40,%41,%42,%43,%44,%45,%46,%47,%48,%49,%50,%51,%52,%53,%54,%55,%56,%57,%58,%59,%60,%61,%62,%63,%64,%65,%66,%67,%68,%69,%70,%71,%72,%73,%74,%75,%76,%77,%78,%79,%80,%81,%82,%83,%84,%85,%86,%87,%88,%89,%90,%91,%92,%93,%94,%95}, %96, %98, p, 1, 1, 0, 1;\n"
        "wgmma.mma_async.sync.aligned.m64n192k16.f32.bf16.bf16 {%0,%1,%2,%3,%4,%5,%6,%7,%8,%9,%10,%11,%12,%13,%14,%15,%16,%17,%18,%19,%20,%21,%22,%23,%24,%25,%26,%27,%28,%29,%30,%31,%32,%33,%34,%35,%36,%37,%38,%39,%40,%41,%42,%43,%44,%45,%46,%47,%48,%49,%50,%51,%52,%53,%54,%55,%56,%57,%58,%59,%60,%61,%62,%63,%64,%65,%66,%67,%68,%69,%70,%71,%72,%73,%74,%75,%76,%77,%78,%79,%80,%81,%82,%83,%84,%85,%86,%87,%88,%89,%90,%91,%92,%93,%94,%95}, %97, %99, 1, 1, 1, 0, 1;\n"
        "}\n"
        : R8(a, 0), R8(a, 8), R8(a, 16), R8(a, 24), R8(a, 32), R8(a, 40), R8(a, 48), R8(a, 56), R8(a, 64), R8(a, 72), R8(a, 80), R8(a, 88)
        : "l"(da0), "l"(da1), "l"(db0), "l"(db1), "r"(scale_d));
}
__device__ __forceinline__ void wgmma_n128_k64(float* a, uint64_t da0, uint64_t da1, uint64_t da2, uint64_t da3,
                                               uint64_t db0, uint64_t db1, uint64_t db2, uint64_t db3, int scale_d) {
    asm volatile(
        "{\n.reg .pred p;\nsetp.ne.b32 p, %72, 0;\n"
        "wgmma.mma_async.sync.aligned.m64n128k16.f32.bf16.bf16 {%0,%1,%2,%3,%4,%5,%6,%7,%8,%9,%10,%11,%12,%13,%14,%15,%16,%17,%18,%19,%20,%21,%22,%23,%24,%25,%26,%27,%28,%29,%30,%31,%32,%33,%34,%35,%36,%37,%38,%39,%40,%41,%42,%43,%44,%45,%46,%47,%48,%49,%50,%51,%52,%53,%54,%55,%56,%57,%58,%59,%60,%61,%62,%63}, %64, %68, p, 1, 1, 0, 1;\n"
        "wgmma.mma_async.sync.aligned.m64n128k16.f32.bf16.bf16 {%0,%1,%2,%3,%4,%5,%6,%7,%8,%9,%10,%11,%12,%13,%14,%15,%16,%17,%18,%19,%20,%21,%22,%23,%24,%25,%26,%27,%28,%29,%30,%31,%32,%33,%34,%35,%36,%37,%38,%39,%40,%41,%42,%43,%44,%45,%46,%47,%48,%49,%50,%51,%52,%53,%54,%55,%56,%57,%58,%59,%60,%61,%62,%63}, %65, %69, 1, 1, 1, 0, 1;\n"
        "wgmma.mma_async.sync.aligned.m64n128k16.f32.bf16.bf16 {%0,%1,%2,%3,%4,%5,%6,%7,%8,%9,%10,%11,%12,%13,%14,%15,%16,%17,%18,%19,%20,%21,%22,%23,%24,%25,%26,%27,%28,%29,%30,%31,%32,%33,%34,%35,%36,%37,%38,%39,%40,%41,%42,%43,%44,%45,%46,%47,%48,%49,%50,%51,%52,%53,%54,%55,%56,%57,%58,%59,%60,%61,%62,%63}, %66, %70, 1, 1, 1, 0, 1;\n"
        "wgmma.mma_async.sync.aligned.m64n128k16.f32.bf16.bf16 {%0,%1,%2,%3,%4,%5,%6,%7,%8,%9,%10,%11,%12,%13,%14,%15,%16,%17,%18,%19,%20,%21,%22,%23,%24,%25,%26,%27,%28,%29,%30,%31,%32,%33,%34,%35,%36,%37,%38,%39,%40,%41,%42,%43,%44,%45,%46,%47,%48,%49,%50,%51,%52,%53,%54,%55,%56,%57,%58,%59,%60,%61,%62,%63}, %67, %71, 1, 1, 1, 0, 1;\n"
        "}\n"
        : R8(a, 0), R8(a, 8), R8(a, 16), R8(a, 24), R8(a, 32), R8(a, 40), R8(a, 48), R8(a, 56)
        : "l"(da0), "l"(da1), "l"(da2), "l"(da3), "l"(db0), "l"(db1), "l"(db2), "l"(db3), "r"(scale_d));
}

__device__ __forceinline__ float bf16_round(float x) {
    uint32_t p; asm("cvt.rn.bf16x2.f32 %0, %1, %2;" : "=r"(p) : "f"(x), "f"(0.0f));
    return __uint_as_float(p);
}
__device__ __forceinline__ uint32_t pack_bf16(float lo, float hi) {
    __nv_bfloat162 v = __floats2bfloat162_rn(lo, hi);
    return *reinterpret_cast<uint32_t*>(&v);
}
__device__ __forceinline__ float bf_lo(uint32_t v) { return __uint_as_float(v << 16); }
__device__ __forceinline__ float bf_hi(uint32_t v) { return __uint_as_float(v & 0xFFFF0000u); }

constexpr int LN_ROWS = 16;
__global__ void __launch_bounds__(256) ln_kernel(const __nv_bfloat16* __restrict__ x,
                                                  const __nv_bfloat16* __restrict__ wg,
                                                  const __nv_bfloat16* __restrict__ wu,
                                                  const __nv_bfloat16* __restrict__ wd) {
    pdl_launch();
    if (threadIdx.x == 0) STAMP(0, 0);
    __shared__ __align__(16) __nv_bfloat16 tile[LN_ROWS][D_ + 8];
    const int warp = threadIdx.x >> 5, lane = threadIdx.x & 31;
    const int row0 = blockIdx.x * LN_ROWS;
    {
        const int lines_per = (D_ * F_ * 2) / 128 / 128;
        if (threadIdx.x < lines_per) {
            size_t off = ((size_t)blockIdx.x * lines_per + threadIdx.x) * 128;
            asm volatile("prefetch.global.L2 [%0];" ::"l"((const char*)wg + off));
            asm volatile("prefetch.global.L2 [%0];" ::"l"((const char*)wu + off));
            asm volatile("prefetch.global.L2 [%0];" ::"l"((const char*)wd + off));
        }
    }
    uint4 v[2][2];
#pragma unroll
    for (int r = 0; r < 2; r++) {
        const __nv_bfloat16* xr = x + (size_t)(row0 + warp * 2 + r) * D_;
        v[r][0] = *reinterpret_cast<const uint4*>(xr + lane * 8);
        v[r][1] = *reinterpret_cast<const uint4*>(xr + 256 + lane * 8);
    }
#pragma unroll
    for (int r = 0; r < 2; r++) {
        float f[16];
        const uint32_t* w = reinterpret_cast<const uint32_t*>(&v[r][0]);
#pragma unroll
        for (int i = 0; i < 8; i++) { f[2 * i] = bf_lo(w[i]); f[2 * i + 1] = bf_hi(w[i]); }
        float s = 0.f;
#pragma unroll
        for (int i = 0; i < 16; i++) s += f[i];
#pragma unroll
        for (int o = 16; o > 0; o >>= 1) s += __shfl_xor_sync(0xffffffffu, s, o);
        const float mean = s * (1.0f / D_);
        float q = 0.f;
#pragma unroll
        for (int i = 0; i < 16; i++) { float d = f[i] - mean; q += d * d; }
#pragma unroll
        for (int o = 16; o > 0; o >>= 1) q += __shfl_xor_sync(0xffffffffu, q, o);
        const float mb = bf16_round(mean);
        const float vb = bf16_round(q * (1.0f / D_));
        const float den = bf16_round(sqrtf(bf16_round(vb + 1e-5f)));
        uint32_t o[8];
#pragma unroll
        for (int i = 0; i < 8; i++) {
            float a = __fdiv_rn(bf16_round(f[2 * i] - mb), den);
            float b = __fdiv_rn(bf16_round(f[2 * i + 1] - mb), den);
            o[i] = pack_bf16(a, b);
        }
        const int rr = warp * 2 + r;
        __nv_bfloat16* dst = g_xn + (size_t)(row0 + rr) * D_;
        *reinterpret_cast<uint4*>(dst + lane * 8) = make_uint4(o[0], o[1], o[2], o[3]);
        *reinterpret_cast<uint4*>(dst + 256 + lane * 8) = make_uint4(o[4], o[5], o[6], o[7]);
        *reinterpret_cast<uint4*>(&tile[rr][lane * 8]) = make_uint4(o[0], o[1], o[2], o[3]);
        *reinterpret_cast<uint4*>(&tile[rr][256 + lane * 8]) = make_uint4(o[4], o[5], o[6], o[7]);
    }
    __syncthreads();
    if (threadIdx.x == 0) STAMP(0, 1);
#pragma unroll
    for (int cc = 0; cc < 2; cc++) {
        const int c = threadIdx.x + cc * 256;
        uint32_t o[8];
#pragma unroll
        for (int i = 0; i < 8; i++) {
            uint32_t lo = *reinterpret_cast<const uint16_t*>(&tile[2 * i][c]);
            uint32_t hi = *reinterpret_cast<const uint16_t*>(&tile[2 * i + 1][c]);
            o[i] = lo | (hi << 16);
        }
        __nv_bfloat16* dst = g_xnT + (size_t)c * L_ + row0;
        *reinterpret_cast<uint4*>(dst) = make_uint4(o[0], o[1], o[2], o[3]);
        *reinterpret_cast<uint4*>(dst + 8) = make_uint4(o[4], o[5], o[6], o[7]);
    }
    if (threadIdx.x == 0) STAMP(0, 2);
}

struct cplx { float r, i; };
__device__ __forceinline__ cplx cmul(cplx a, cplx b) {
    cplx c; c.r = a.r * b.r - a.i * b.i; c.i = a.r * b.i + a.i * b.r; return c;
}
__device__ __forceinline__ cplx csq(cplx a) {
    cplx c; c.r = a.r * a.r - a.i * a.i; c.i = 2.0f * a.r * a.i; return c;
}
__device__ __forceinline__ cplx cexp_m(float ar, float ai, float m) {
    float mag;
    float e = (ar * m) * 1.4426950408889634f;
    asm("ex2.approx.ftz.f32 %0, %1;" : "=f"(mag) : "f"(e));
    float rr = (ai * m) * 0.15915494309189535f;
    rr -= rintf(rr);
    float th = rr * 6.283185307179586f;
    cplx c; c.r = mag * __cosf(th); c.i = mag * __sinf(th);
    return c;
}
__device__ __forceinline__ uint32_t to_tf32(float x) {
    uint32_t r; asm("cvt.rna.tf32.f32 %0, %1;" : "=r"(r) : "f"(x)); return r;
}
__device__ __forceinline__ void mma_tf32(float* c, uint32_t a0, uint32_t a1, uint32_t a2, uint32_t a3, uint32_t b0, uint32_t b1) {
    asm volatile("mma.sync.aligned.m16n8k8.row.col.f32.tf32.tf32.f32 {%0,%1,%2,%3}, {%4,%5,%6,%7}, {%8,%9}, {%0,%1,%2,%3};"
                 : "+f"(c[0]), "+f"(c[1]), "+f"(c[2]), "+f"(c[3])
                 : "r"(a0), "r"(a1), "r"(a2), "r"(a3), "r"(b0), "r"(b1));
}
__device__ __forceinline__ void mma_bf16(float* c, uint32_t a0, uint32_t a1, uint32_t a2, uint32_t a3, uint32_t b0, uint32_t b1) {
    asm volatile("mma.sync.aligned.m16n8k16.row.col.f32.bf16.bf16.f32 {%0,%1,%2,%3}, {%4,%5,%6,%7}, {%8,%9}, {%0,%1,%2,%3};"
                 : "+f"(c[0]), "+f"(c[1]), "+f"(c[2]), "+f"(c[3])
                 : "r"(a0), "r"(a1), "r"(a2), "r"(a3), "r"(b0), "r"(b1));
}
__device__ __forceinline__ void named_bar(int id, int n) { asm volatile("bar.sync %0, %1;" ::"r"(id), "r"(n) : "memory"); }

constexpr int CV_CH = 4;
constexpr int CV_CONST_B = NS_ * 12 * 4;
constexpr int CV_KV_B = 648 * 4;
constexpr int CV_Q_B = (L_ + 16) * 4;
constexpr int CV_U_B = (L_ + 128) * 2;
constexpr int CV_PER_CH = CV_CONST_B + 2 * CV_KV_B + CV_Q_B + CV_U_B;
constexpr int CV_SMEM = CV_CH * CV_PER_CH;

__global__ void __launch_bounds__(256) conv_kernel(const __nv_bfloat16* __restrict__ A_re, const __nv_bfloat16* __restrict__ A_im,
                                                    const __nv_bfloat16* __restrict__ B_re, const __nv_bfloat16* __restrict__ B_im,
                                                    const __nv_bfloat16* __restrict__ C_re, const __nv_bfloat16* __restrict__ C_im,
                                                    const __nv_bfloat16* __restrict__ log_dt, const __nv_bfloat16* __restrict__ Dskip) {
    pdl_launch();
    if (threadIdx.x == 0) STAMP(1, 0);
    extern __shared__ __align__(16) uint8_t smem[];
    const int warp = threadIdx.x >> 5, lane = threadIdx.x & 31;
    const int ch = warp >> 1, h = warp & 1;
    const int d = blockIdx.x * CV_CH + ch;
    const int g = lane >> 2, t = lane & 3;
    uint8_t* base = smem + ch * CV_PER_CH;
    float4* s_const = reinterpret_cast<float4*>(base);
    float* s_kv = reinterpret_cast<float*>(base + CV_CONST_B);
    uint32_t* s_q = reinterpret_cast<uint32_t*>(base + CV_CONST_B + 2 * CV_KV_B);
    __nv_bfloat16* s_u = reinterpret_cast<__nv_bfloat16*>(base + CV_CONST_B + 2 * CV_KV_B + CV_Q_B);
    const int bar_id = 1 + ch;

    const float dt = bf16_round(expf(__bfloat162float(log_dt[d])));
    float tail = 0.f;
    {
        const int n0 = h * 64 + lane * 2;
        const size_t off = (size_t)d * NS_ + n0;
        uint32_t war = *reinterpret_cast<const uint32_t*>(A_re + off);
        uint32_t wai = *reinterpret_cast<const uint32_t*>(A_im + off);
        uint32_t wbr = *reinterpret_cast<const uint32_t*>(B_re + off);
        uint32_t wbi = *reinterpret_cast<const uint32_t*>(B_im + off);
        uint32_t wcr = *reinterpret_cast<const uint32_t*>(C_re + off);
        uint32_t wci = *reinterpret_cast<const uint32_t*>(C_im + off);
#pragma unroll
        for (int j = 0; j < 2; j++) {
            float ar = dt * (j ? bf_hi(war) : bf_lo(war));
            float ai = dt * (j ? bf_hi(wai) : bf_lo(wai));
            cplx db = {dt * (j ? bf_hi(wbr) : bf_lo(wbr)), dt * (j ? bf_hi(wbi) : bf_lo(wbi))};
            cplx cc = {(j ? bf_hi(wcr) : bf_lo(wcr)), (j ? bf_hi(wci) : bf_lo(wci))};
            cplx cb = cmul(cc, db);
            cplx e128 = cexp_m(ar, ai, 128.f);
            cplx c256 = cmul(cb, cexp_m(ar, ai, 256.f));
            cplx c512 = cmul(cb, cexp_m(ar, ai, 512.f));
            cplx c1024 = cmul(cb, cexp_m(ar, ai, 1024.f));
            cplx c2048 = cmul(cb, cexp_m(ar, ai, 2048.f));
            tail += c2048.r;
            s_const[(n0 + j) * 3 + 0] = make_float4(ar, ai, cb.r, cb.i);
            s_const[(n0 + j) * 3 + 1] = make_float4(e128.r, e128.i, c256.r, c256.i);
            s_const[(n0 + j) * 3 + 2] = make_float4(c512.r, c512.i, c1024.r, c1024.i);
        }
#pragma unroll
        for (int o = 16; o > 0; o >>= 1) tail += __shfl_xor_sync(0xffffffffu, tail, o);
    }
    __syncwarp();
    if (threadIdx.x == 0) STAMP(1, 1);
    {
        float acc[5][4];
#pragma unroll
        for (int i = 0; i < 5; i++) { acc[i][0] = acc[i][1] = acc[i][2] = acc[i][3] = 0.f; }
        const float gf = (float)g;
#pragma unroll 2
        for (int s = 0; s < 16; s++) {
            const int n = h * 64 + s * 4 + t;
            const float4 k0 = s_const[n * 3 + 0], k1 = s_const[n * 3 + 1], k2 = s_const[n * 3 + 2];
            const cplx cb = {k0.z, k0.w}, e128 = {k1.x, k1.y}, c256 = {k1.z, k1.w}, c512 = {k2.x, k2.y}, c1024 = {k2.z, k2.w};
            cplx p1 = cexp_m(k0.x, k0.y, gf);
            cplx p1b = cexp_m(k0.x, k0.y, gf + 8.f);
            cplx r16a = cexp_m(k0.x, k0.y, gf * 16.f);
            cplx r16b = cmul(r16a, e128);
            cplx p2 = csq(p1), p4 = csq(p2), p8 = csq(p4);
            cplx r32a = csq(r16a), r32b = csq(r16b), r64a = csq(r32a), r64b = csq(r32b);
            cplx f0a = cmul(cb, p1), f0b = cmul(cb, p1b), f1 = cmul(c256, p2), f2 = cmul(c512, p4), f3 = cmul(c1024, p8);
            {
                uint32_t a0 = to_tf32(r16a.r), a1 = to_tf32(r16b.r), a2 = to_tf32(-r16a.i), a3 = to_tf32(-r16b.i);
                mma_tf32(acc[0], a0, a1, a2, a3, to_tf32(f0a.r), to_tf32(f0a.i));
                mma_tf32(acc[1], a0, a1, a2, a3, to_tf32(f0b.r), to_tf32(f0b.i));
                mma_tf32(acc[2], a0, a1, a2, a3, to_tf32(f1.r), to_tf32(f1.i));
            }
            mma_tf32(acc[3], to_tf32(r32a.r), to_tf32(r32b.r), to_tf32(-r32a.i), to_tf32(-r32b.i), to_tf32(f2.r), to_tf32(f2.i));
            mma_tf32(acc[4], to_tf32(r64a.r), to_tf32(r64b.r), to_tf32(-r64a.i), to_tf32(-r64b.i), to_tf32(f3.r), to_tf32(f3.i));
        }
        float* kv = s_kv + h * 648;
        *reinterpret_cast<float2*>(kv + 16 * g + 2 * t) = make_float2(acc[0][0], acc[0][1]);
        *reinterpret_cast<float2*>(kv + 16 * (g + 8) + 2 * t) = make_float2(acc[0][2], acc[0][3]);
        *reinterpret_cast<float2*>(kv + 16 * g + 8 + 2 * t) = make_float2(acc[1][0], acc[1][1]);
        *reinterpret_cast<float2*>(kv + 16 * (g + 8) + 8 + 2 * t) = make_float2(acc[1][2], acc[1][3]);
#pragma unroll
        for (int sg = 0; sg < 3; sg++) {
            *reinterpret_cast<float2*>(kv + 256 + 128 * sg + 8 * g + 2 * t) = make_float2(acc[2 + sg][0], acc[2 + sg][1]);
            *reinterpret_cast<float2*>(kv + 256 + 128 * sg + 8 * (g + 8) + 2 * t) = make_float2(acc[2 + sg][2], acc[2 + sg][3]);
        }
        if (lane == 0) kv[640] = tail;
    }
    named_bar(bar_id, 64);
    if (threadIdx.x == 0) STAMP(1, 2);
    {
        const int tid2 = h * 32 + lane;
        if (tid2 < 16) s_q[tid2] = 0u;
        for (int x = tid2; x < L_; x += 64) {
            float kc, kp;
            {
                int s = (x >= 1024) ? 3 : (x >= 512) ? 2 : (x >= 256) ? 1 : 0;
                int rq = (s == 0) ? x : ((x + (1 << (s - 1)) - 1 + ((x >> s) & 1)) >> s);
                int idx = 128 * s + rq;
                kc = s_kv[idx] + s_kv[648 + idx];
            }
            {
                int y = x - 1;
                if (y < 0) kp = 0.f;
                else {
                    int s = (y >= 1024) ? 3 : (y >= 512) ? 2 : (y >= 256) ? 1 : 0;
                    int rq = (s == 0) ? y : ((y + (1 << (s - 1)) - 1 + ((y >> s) & 1)) >> s);
                    int idx = 128 * s + rq;
                    kp = s_kv[idx] + s_kv[648 + idx];
                }
            }
            s_q[x + 16] = pack_bf16(kc, kp);
        }
    }
    if (threadIdx.x == 0) STAMP(1, 3);
    pdl_wait();
    if (threadIdx.x == 0) STAMP(1, 4);
    {
        const int tid2 = h * 32 + lane;
        if (tid2 < 16) *reinterpret_cast<uint4*>(s_u + tid2 * 8) = make_uint4(0, 0, 0, 0);
        const uint4* src = reinterpret_cast<const uint4*>(g_xnT + (size_t)d * L_);
#pragma unroll
        for (int i = 0; i < 4; i++) {
            *reinterpret_cast<uint4*>(s_u + 128 + (tid2 + i * 64) * 8) = src[tid2 + i * 64];
        }
    }
    named_bar(bar_id, 64);
    if (threadIdx.x == 0) STAMP(1, 5);
    float acc[16][4];
#pragma unroll
    for (int i = 0; i < 16; i++) { acc[i][0] = acc[i][1] = acc[i][2] = acc[i][3] = 0.f; }
    const uint32_t su_addr = smem_u32(s_u);
    for (int rr = 0; rr < 4; rr++) {
        const int r = h * 4 + rr;
        uint32_t ub[16][2];
        {
            const int mi = lane >> 3, rowi = lane & 7;
            uint32_t addr = su_addr + (uint32_t)((128 + 16 * (8 * (mi >> 1) + rowi - r) + 8 * (mi & 1)) * 2);
#pragma unroll
            for (int j = 0; j < 16; j += 2) {
                asm volatile("ldmatrix.sync.aligned.m8n8.x4.shared.b16 {%0,%1,%2,%3}, [%4];"
                             : "=r"(ub[j][0]), "=r"(ub[j][1]), "=r"(ub[j + 1][0]), "=r"(ub[j + 1][1])
                             : "r"(addr + (uint32_t)(j * 8 * 16 * 2)));
            }
        }
        const uint32_t* qp = s_q + 16 + 16 * r + g - 2 * t;
#pragma unroll
        for (int q = 0; q < 16; q++) {
            const uint32_t a0 = qp[128 * q], a1 = qp[128 * q + 8], a2 = qp[128 * q - 8];
#pragma unroll
            for (int nt = q; nt < 16; nt++) mma_bf16(acc[nt], a0, a1, a2, a0, ub[nt - q][0], ub[nt - q][1]);
        }
    }
    if (threadIdx.x == 0) STAMP(1, 6);
    named_bar(bar_id, 64);
    {
        float4* xch = reinterpret_cast<float4*>(base) + h * 256;
        if (h) {
#pragma unroll
            for (int i = 0; i < 8; i++) xch[i * 32 + lane] = make_float4(acc[i][0], acc[i][1], acc[i][2], acc[i][3]);
        } else {
#pragma unroll
            for (int i = 0; i < 8; i++) xch[i * 32 + lane] = make_float4(acc[8 + i][0], acc[8 + i][1], acc[8 + i][2], acc[8 + i][3]);
        }
    }
    named_bar(bar_id, 64);
    {
        const float4* xch = reinterpret_cast<const float4*>(base) + (h ^ 1) * 256;
        const float dsk = __bfloat162float(Dskip[d]);
        __nv_bfloat16* stg = reinterpret_cast<__nv_bfloat16*>(s_q);
#pragma unroll
        for (int i = 0; i < 8; i++) {
            float4 o = xch[i * 32 + lane];
            float y[4];
            if (h) { y[0] = acc[8 + i][0] + o.x; y[1] = acc[8 + i][1] + o.y; y[2] = acc[8 + i][2] + o.z; y[3] = acc[8 + i][3] + o.w; }
            else   { y[0] = acc[i][0] + o.x; y[1] = acc[i][1] + o.y; y[2] = acc[i][2] + o.z; y[3] = acc[i][3] + o.w; }
            const int nt = h * 8 + i;
#pragma unroll
            for (int e = 0; e < 4; e++) {
                const int tau = 16 * (8 * nt + 2 * t + (e & 1)) + g + 8 * (e >> 1);
                float u = __bfloat162float(s_u[128 + tau]);
                float sv = bf16_round(y[e]) + bf16_round(u * dsk);
                reinterpret_cast<uint16_t*>(stg)[tau] = (uint16_t)(__float_as_uint(bf16_round(sv)) >> 16);
            }
        }
        __syncwarp();
        uint4* dst = reinterpret_cast<uint4*>(g_sT + (size_t)d * L_ + h * 1024);
        const uint4* srcp = reinterpret_cast<const uint4*>(stg + h * 1024);
#pragma unroll
        for (int i = 0; i < 4; i++) dst[i * 32 + lane] = srcp[i * 32 + lane];
    }
    if (threadIdx.x == 0) STAMP(1, 7);
}

__device__ __forceinline__ uint32_t cluster_rank() { uint32_t r; asm volatile("mov.u32 %0, %%cluster_ctarank;" : "=r"(r)); return r; }
__device__ __forceinline__ void cluster_sync_all() {
    asm volatile("barrier.cluster.arrive.release.aligned;\nbarrier.cluster.wait.acquire.aligned;" ::: "memory");
}
__device__ __forceinline__ void mbar_arrive_remote(uint32_t bar, uint32_t cta) {
    asm volatile("{\n.reg .b32 ra;\nmapa.shared::cluster.u32 ra, %0, %1;\n"
                 "mbarrier.arrive.shared::cluster.b64 _, [ra];\n}\n" ::"r"(bar), "r"(cta) : "memory");
}
__device__ __forceinline__ void tma_load_2d_mc(uint32_t dst, const CUtensorMap* tm, int c0, int c1, uint32_t bar, uint16_t mask) {
    asm volatile(
        "cp.async.bulk.tensor.2d.shared::cluster.global.mbarrier::complete_tx::bytes.multicast::cluster [%0], [%1, {%3, %4}], [%2], %5;"
        ::"r"(dst), "l"((uint64_t)tm), "r"(bar), "r"(c0), "r"(c1), "h"(mask) : "memory");
}
__device__ __forceinline__ void tma_store_2d(const CUtensorMap* tm, uint32_t src, int c0, int c1) {
    asm volatile("cp.async.bulk.tensor.2d.global.shared::cta.bulk_group [%0, {%2, %3}], [%1];"
                 ::"l"((uint64_t)tm), "r"(src), "r"(c0), "r"(c1) : "memory");
}
__device__ __forceinline__ void bulk_commit() { asm volatile("cp.async.bulk.commit_group;" ::: "memory"); }
template <int N> __device__ __forceinline__ void bulk_wait_read() { asm volatile("cp.async.bulk.wait_group.read %0;" ::"n"(N) : "memory"); }
template <int N> __device__ __forceinline__ void bulk_wait() { asm volatile("cp.async.bulk.wait_group %0;" ::"n"(N) : "memory"); }
__device__ __forceinline__ void fence_async_smem() { asm volatile("fence.proxy.async.shared::cta;" ::: "memory"); }
__device__ __forceinline__ void stmatrix_x4(uint32_t addr, uint32_t r0, uint32_t r1, uint32_t r2, uint32_t r3) {
    asm volatile("stmatrix.sync.aligned.m8n8.x4.shared.b16 [%0], {%1,%2,%3,%4};" ::"r"(addr), "r"(r0), "r"(r1), "r"(r2), "r"(r3) : "memory");
}

constexpr int G1_STAGES = 5;
constexpr int G1_A_BYTES = 8 * 16384;
constexpr int G1_B_STAGE = 16384;
constexpr int G1_STG = 8 * 1024;
constexpr int G1_SMEM = G1_A_BYTES + G1_STAGES * G1_B_STAGE + G1_STG + 1024 + 256;
constexpr int G1_ITERS = 32;

__device__ __forceinline__ void tma_load_3d(uint32_t dst, const CUtensorMap* tm, int c0, int c1, int c2, uint32_t bar) {
    asm volatile(
        "cp.async.bulk.tensor.3d.shared::cluster.global.mbarrier::complete_tx::bytes [%0], [%1, {%3, %4, %5}], [%2];"
        ::"r"(dst), "l"((uint64_t)tm), "r"(bar), "r"(c0), "r"(c1), "r"(c2) : "memory");
}

__device__ __forceinline__ float gelu_tanh(float x) {
    float u = x * (0.7978845608028654f + 0.035677408136300125f * x * x);
    float t; asm("tanh.approx.f32 %0, %1;" : "=f"(t) : "f"(u));
    float hx = 0.5f * x;
    return fmaf(hx, t, hx);
}
__device__ __forceinline__ uint32_t geglu_pair(uint32_t p0, uint32_t p1) {
    float a = bf16_round(gelu_tanh(bf_lo(p0))) * bf_hi(p0);
    float b = bf16_round(gelu_tanh(bf_lo(p1))) * bf_hi(p1);
    return pack_bf16(a, b);
}

__global__ void __launch_bounds__(384, 1) gemm1_kernel(const __grid_constant__ CUtensorMap tm_xn,
                                                        const __grid_constant__ CUtensorMap tm_wg4,
                                                        const __grid_constant__ CUtensorMap tm_wu4,
                                                        const __grid_constant__ CUtensorMap tm_wg3,
                                                        const __grid_constant__ CUtensorMap tm_wu3,
                                                        const __grid_constant__ CUtensorMap tm_hst,
                                                        const __grid_constant__ CUtensorMap tm_hst96) {
    pdl_launch();
    if (threadIdx.x == 0) STAMP(2, 0);
    extern __shared__ uint8_t smem_raw[];
    const uint32_t sbase = (smem_u32(smem_raw) + 1023) & ~1023u;
    const uint32_t sA = sbase, sB = sbase + G1_A_BYTES, sStg = sB + G1_STAGES * G1_B_STAGE, sBar = sStg + G1_STG;
    const uint32_t bar_a = sBar, bar_full = sBar + 64, bar_empty = sBar + 64 + 8 * G1_STAGES;
    const int rb = blockIdx.x >> 3, cj = blockIdx.x & 7;
    const int warp = threadIdx.x >> 5, lane = threadIdx.x & 31;

    if (threadIdx.x == 0) {
        for (int i = 0; i < 8; i++) mbar_init(bar_a + 8 * i, 1);
        for (int i = 0; i < G1_STAGES; i++) { mbar_init(bar_full + 8 * i, 1); mbar_init(bar_empty + 8 * i, 8); }
        asm volatile("fence.mbarrier_init.release.cluster;" ::: "memory");
    }
    __syncthreads();

    if (warp >= 8) {
        asm volatile("setmaxnreg.dec.sync.aligned.u32 40;");
        if (lane == 0) {
            const int pw = warp - 8;
            if (pw == 0) { prefetch_tmap(&tm_wg4); prefetch_tmap(&tm_wu4); prefetch_tmap(&tm_xn); }
            if (pw == 1) { prefetch_tmap(&tm_wg3); prefetch_tmap(&tm_wu3); prefetch_tmap(&tm_hst); prefetch_tmap(&tm_hst96); }
            for (int it = pw; it < G1_ITERS; it += 4) {
                const int s = it % G1_STAGES, kb = it & 15;
                if (it >= G1_STAGES) mbar_wait(bar_empty + 8 * s, ((it / G1_STAGES) - 1) & 1);
                const uint32_t dst = sB + s * G1_B_STAGE;
                if (it < 16) {
                    mbar_expect_tx(bar_full + 8 * s, 16384);
                    tma_load_3d(dst, &tm_wg4, 0, kb * 32, cj * 7, bar_full + 8 * s);
                    tma_load_3d(dst + 8192, &tm_wu4, 0, kb * 32, cj * 7, bar_full + 8 * s);
                } else {
                    mbar_expect_tx(bar_full + 8 * s, 12288);
                    tma_load_3d(dst, &tm_wg3, 0, kb * 32, cj * 7 + 4, bar_full + 8 * s);
                    tma_load_3d(dst + 6144, &tm_wu3, 0, kb * 32, cj * 7 + 4, bar_full + 8 * s);
                }
                if (it < 4) {
                    pdl_wait();
                    if (pw == 0) STAMP(2, 1);
                    for (int k = pw; k < 8; k += 4) {
                        mbar_expect_tx(bar_a + 8 * k, 16384);
                        tma_load_2d(sA + k * 16384, &tm_xn, k * 64, rb * 128, bar_a + 8 * k);
                    }
                }
            }
        }
    } else {
        asm volatile("setmaxnreg.inc.sync.aligned.u32 232;");
        const int wg = __shfl_sync(0xffffffffu, (int)(threadIdx.x >> 7), 0);
        float r[160];
        const int row0 = rb * 128 + wg * 64 + (warp & 3) * 16;
        const uint64_t descA = make_desc(sA + wg * 8192, 16, 1024);
        const uint64_t descB = make_desc(sB, 2048, 512, 2);
        const uint32_t stg = sStg + warp * 1024;
        const uint32_t st_off = (uint32_t)(((lane & 7) + ((lane >> 3) & 1) * 8) * 32 + (lane >> 4) * 16);
        __nv_bfloat16* hrow = g_h + (size_t)(row0 + (lane >> 1)) * F_ + (lane & 1) * 8;
        auto store_group = [&](const float* pk, int par, int col) {
            const uint32_t buf = stg + par * 512;
            uint32_t r0 = geglu_pair(__float_as_uint(pk[0]), __float_as_uint(pk[1]));
            uint32_t r1 = geglu_pair(__float_as_uint(pk[2]), __float_as_uint(pk[3]));
            uint32_t r2 = geglu_pair(__float_as_uint(pk[4]), __float_as_uint(pk[5]));
            uint32_t r3 = geglu_pair(__float_as_uint(pk[6]), __float_as_uint(pk[7]));
            stmatrix_x4(buf + st_off, r0, r1, r2, r3);
            __syncwarp();
            uint4 v;
            asm volatile("ld.shared.v4.u32 {%0,%1,%2,%3}, [%4];" : "=r"(v.x), "=r"(v.y), "=r"(v.z), "=r"(v.w) : "r"(buf + lane * 16));
            *reinterpret_cast<uint4*>(hrow + col) = v;
        };
#pragma unroll
        for (int kb = 0; kb < 16; kb++) {
            const int it = kb, s = it % G1_STAGES;
            if ((kb & 1) == 0) mbar_wait(bar_a + 8 * (kb >> 1), 0);
            mbar_wait(bar_full + 8 * s, (it / G1_STAGES) & 1);
            if (threadIdx.x == 0 && (it & 7) == 0) STAMP(2, 2 + it / 8);
            wgmma_fence();
            const uint64_t da = descA + (uint64_t)(((kb >> 1) * 16384 + (kb & 1) * 64) >> 4);
            const uint64_t db = descB + (uint64_t)((s * G1_B_STAGE) >> 4);
            wgmma_n256_k32(r, da, da + 2, db, db + 64, kb != 0);
            wgmma_commit();
            if (kb > 0) {
                wgmma_wait<1>();
                if (lane == 0) mbar_arrive(bar_empty + 8 * ((it - 1) % G1_STAGES));
            }
        }
        wgmma_wait<0>();
        if (lane == 0) mbar_arrive(bar_empty + 8 * (15 % G1_STAGES));
#pragma unroll
        for (int i = 0; i < 32; i++) r[128 + i] = __uint_as_float(pack_bf16(r[i], r[64 + i]));
#pragma unroll
        for (int i = 32; i < 64; i++) r[64 + i] = __uint_as_float(pack_bf16(r[i], r[64 + i]));
#pragma unroll
        for (int kb = 0; kb < 16; kb++) {
            const int it = 16 + kb, s = it % G1_STAGES;
            mbar_wait(bar_full + 8 * s, (it / G1_STAGES) & 1);
            if (threadIdx.x == 0 && (it & 7) == 0) STAMP(2, 2 + it / 8);
            wgmma_fence();
            const uint64_t da = descA + (uint64_t)(((kb >> 1) * 16384 + (kb & 1) * 64) >> 4);
            const uint64_t db = descB + (uint64_t)((s * G1_B_STAGE) >> 4);
            wgmma_n192_k32(r, da, da + 2, db, db + 64, kb != 0);
            wgmma_commit();
            if (kb > 0 && it - 1 + G1_STAGES < G1_ITERS) {
                wgmma_wait<1>();
                if (lane == 0) mbar_arrive(bar_empty + 8 * ((it - 1) % G1_STAGES));
            }
            if ((kb & 1) == wg) {
                const int jj = kb >> 1;
                store_group(jj < 4 ? &r[128 + 8 * jj] : &r[64 + 8 * jj], jj & 1, cj * 224 + jj * 16);
            }
        }
        wgmma_wait<0>();
#pragma unroll
        for (int i = 0; i < 48; i++) r[i] = __uint_as_float(pack_bf16(r[i], r[48 + i]));
        if (threadIdx.x == 0) STAMP(2, 6);
#pragma unroll
        for (int jj = 0; jj < 6; jj++) store_group(&r[8 * jj], jj & 1, cj * 224 + 128 + jj * 16);
        if (threadIdx.x == 0) STAMP(2, 7);
    }
}

constexpr int G2_STAGES = 5;
constexpr int G2_STAGE = 16384 + 16384;
constexpr int G2_XCH = 32768;
constexpr int G2_EPI = 16384 + 16384;
constexpr int G2_SMEM = G2_STAGES * G2_STAGE + G2_XCH + G2_EPI + 1024 + 256;
constexpr int G2_KB = F_ / 64 / 2;

__global__ void __launch_bounds__(384, 1) gemm2_kernel(const __grid_constant__ CUtensorMap tm_h,
                                                        const __grid_constant__ CUtensorMap tm_wd,
                                                        const __grid_constant__ CUtensorMap tm_x,
                                                        const __grid_constant__ CUtensorMap tm_sT,
                                                        const __grid_constant__ CUtensorMap tm_out) {
    if (threadIdx.x == 0) STAMP(3, 0);
    extern __shared__ uint8_t smem_raw[];
    const uint32_t sbase = (smem_u32(smem_raw) + 1023) & ~1023u;
    const uint32_t sXch = sbase + G2_STAGES * G2_STAGE, sX = sXch + G2_XCH, sS = sX + 16384, sBar = sX + G2_EPI;
    const uint32_t bar_full = sBar, bar_empty = sBar + 8 * G2_STAGES, bar_epi = sBar + 16 * G2_STAGES, bar_xch = bar_epi + 8;
    const uint32_t kh = cluster_rank();
    const int cid = blockIdx.x >> 1;
    const int rb = cid >> 2, nb = cid & 3;
    const int col_fin = nb * 128 + kh * 64;
    const int warp = threadIdx.x >> 5, lane = threadIdx.x & 31;

    if (threadIdx.x == 0) {
        for (int i = 0; i < G2_STAGES; i++) { mbar_init(bar_full + 8 * i, 1); mbar_init(bar_empty + 8 * i, 8); }
        mbar_init(bar_epi, 1);
        mbar_init(bar_xch, 1);
        asm volatile("fence.mbarrier_init.release.cluster;" ::: "memory");
        mbar_expect_tx(bar_xch, G2_XCH);
    }
    cluster_sync_all();

    if (warp >= 8) {
        if (lane == 0) {
            const int pw = warp - 8;
            const int k0 = kh * G2_KB;
            if (pw == 0) { prefetch_tmap(&tm_wd); prefetch_tmap(&tm_h); }
            if (pw == 1) { prefetch_tmap(&tm_x); prefetch_tmap(&tm_sT); prefetch_tmap(&tm_out); }
            for (int it = pw; it < G2_STAGES; it += 4) {
                mbar_expect_tx(bar_full + 8 * it, G2_STAGE);
                tma_load_3d(sbase + it * G2_STAGE + 16384, &tm_wd, 0, (k0 + it) * 64, nb * 2, bar_full + 8 * it);
            }
            if (pw == 3) {
                mbar_expect_tx(bar_epi, G2_EPI);
                tma_load_2d(sX, &tm_x, col_fin, rb * 128, bar_epi);
            }
            pdl_wait();
            if (pw == 0) STAMP(3, 1);
            for (int it = pw; it < G2_STAGES; it += 4)
                tma_load_2d(sbase + it * G2_STAGE, &tm_h, (k0 + it) * 64, rb * 128, bar_full + 8 * it);
            if (pw == 3) {
                tma_load_2d(sS, &tm_sT, rb * 128, col_fin, bar_epi);
                tma_load_2d(sS + 8192, &tm_sT, rb * 128 + 64, col_fin, bar_epi);
            }
            for (int it = G2_STAGES + ((pw + 4 - (G2_STAGES & 3)) & 3); it < G2_KB; it += 4) {
                const int s = it % G2_STAGES;
                mbar_wait(bar_empty + 8 * s, ((it / G2_STAGES) - 1) & 1);
                mbar_expect_tx(bar_full + 8 * s, G2_STAGE);
                tma_load_2d(sbase + s * G2_STAGE, &tm_h, (k0 + it) * 64, rb * 128, bar_full + 8 * s);
                tma_load_3d(sbase + s * G2_STAGE + 16384, &tm_wd, 0, (k0 + it) * 64, nb * 2, bar_full + 8 * s);
            }
        }
    } else {
        const int wg = __shfl_sync(0xffffffffu, (int)(threadIdx.x >> 7), 0);
        const int g = lane >> 2, t = lane & 3;
        float acc[64];
        const uint64_t descA = make_desc(sbase + wg * 8192, 16, 1024);
        const uint64_t descB = make_desc(sbase + 16384, 8192, 1024);
#pragma unroll
        for (int it = 0; it < G2_KB; it++) {
            const int s = it % G2_STAGES;
            mbar_wait(bar_full + 8 * s, (it / G2_STAGES) & 1);
            if (threadIdx.x == 0 && (it == 0 || it == 7)) STAMP(3, 2 + it / 7);
            wgmma_fence();
            {
                const uint64_t da = descA + (uint64_t)((s * G2_STAGE) >> 4);
                const uint64_t db = descB + (uint64_t)((s * G2_STAGE) >> 4);
                wgmma_n128_k64(acc, da, da + 2, da + 4, da + 6, db, db + 128, db + 256, db + 384, it != 0);
            }
            wgmma_commit();
            if (it > 0 && it - 1 + G2_STAGES < G2_KB) {
                wgmma_wait<1>();
                if (lane == 0) mbar_arrive(bar_empty + 8 * ((it - 1) % G2_STAGES));
            }
        }
        const int lr = wg * 64 + (warp & 3) * 16 + g;
        uint32_t xv[16], sv[16];
        mbar_wait(bar_epi, 0);
#pragma unroll
        for (int j = 0; j < 8; j++) {
#pragma unroll
            for (int hh = 0; hh < 2; hh++) {
                const int r = lr + 8 * hh;
                asm volatile("ld.shared.u32 %0, [%1];" : "=r"(xv[2 * j + hh]) : "r"(sX + r * 128 + ((j ^ (r & 7)) << 4) + 4 * t));
                const int c0 = 8 * j + 2 * t;
                const uint32_t sa = sS + (r >> 6) * 8192 + (((r & 63) >> 3) << 4) + (r & 7) * 2;
                uint16_t s0r, s1r;
                asm volatile("ld.shared.u16 %0, [%1];" : "=h"(s0r) : "r"((sa + c0 * 128) ^ ((c0 & 7) << 4)));
                asm volatile("ld.shared.u16 %0, [%1];" : "=h"(s1r) : "r"((sa + (c0 + 1) * 128) ^ (((c0 + 1) & 7) << 4)));
                sv[2 * j + hh] = (uint32_t)s0r | ((uint32_t)s1r << 16);
            }
        }
        wgmma_wait<0>();
        if (threadIdx.x == 0) STAMP(3, 4);
        {
            uint32_t remote, rbar;
            asm volatile("mapa.shared::cluster.u32 %0, %1, %2;" : "=r"(remote) : "r"(sXch + threadIdx.x * 16), "r"(kh ^ 1));
            asm volatile("mapa.shared::cluster.u32 %0, %1, %2;" : "=r"(rbar) : "r"(bar_xch), "r"(kh ^ 1));
            if (kh == 0) {
#pragma unroll
                for (int i = 0; i < 8; i++)
                    asm volatile("st.async.shared::cluster.mbarrier::complete_tx::bytes.v4.f32 [%0], {%1,%2,%3,%4}, [%5];" ::"r"(remote + i * 4096),
                                 "f"(acc[32 + 4 * i]), "f"(acc[33 + 4 * i]), "f"(acc[34 + 4 * i]), "f"(acc[35 + 4 * i]), "r"(rbar) : "memory");
            } else {
#pragma unroll
                for (int i = 0; i < 8; i++)
                    asm volatile("st.async.shared::cluster.mbarrier::complete_tx::bytes.v4.f32 [%0], {%1,%2,%3,%4}, [%5];" ::"r"(remote + i * 4096),
                                 "f"(acc[4 * i]), "f"(acc[1 + 4 * i]), "f"(acc[2 + 4 * i]), "f"(acc[3 + 4 * i]), "r"(rbar) : "memory");
#pragma unroll
                for (int i = 0; i < 32; i++) acc[i] = acc[32 + i];
            }
        }
        if (threadIdx.x == 0) STAMP(3, 6);
        mbar_wait(bar_xch, 0);
        if (threadIdx.x == 0) STAMP(3, 7);
#pragma unroll
        for (int j = 0; j < 8; j++) {
            float4 o;
            asm volatile("ld.shared.v4.f32 {%0,%1,%2,%3}, [%4];" : "=f"(o.x), "=f"(o.y), "=f"(o.z), "=f"(o.w) : "r"(sXch + threadIdx.x * 16 + j * 4096));
            acc[4 * j] += o.x; acc[4 * j + 1] += o.y; acc[4 * j + 2] += o.z; acc[4 * j + 3] += o.w;
        }
#pragma unroll
        for (int i = 0; i < 16; i++) {
            float f0 = bf16_round(acc[2 * i]), f1 = bf16_round(acc[2 * i + 1]);
            float g0 = bf16_round(__fdividef(f0, 1.0f + __expf(-f0)));
            float g1 = bf16_round(__fdividef(f1, 1.0f + __expf(-f1)));
            float o0 = bf_lo(xv[i]) + bf16_round(bf_lo(sv[i]) * g0);
            float o1 = bf_hi(xv[i]) + bf16_round(bf_hi(sv[i]) * g1);
            xv[i] = pack_bf16(o0, o1);
        }
#pragma unroll
        for (int j = 0; j < 8; j++) {
#pragma unroll
            for (int hh = 0; hh < 2; hh++) {
                const int r = lr + 8 * hh;
                asm volatile("st.shared.u32 [%0], %1;" ::"r"(sX + r * 128 + ((j ^ (r & 7)) << 4) + 4 * t), "r"(xv[2 * j + hh]) : "memory");
            }
        }
        if (threadIdx.x == 0) STAMP(3, 9);
        fence_async_smem();
        __syncwarp();
        if (lane == 0) {
            tma_store_2d(&tm_out, sX + (wg * 64 + (warp & 3) * 16) * 128, col_fin, rb * 128 + wg * 64 + (warp & 3) * 16);
            bulk_commit();
            bulk_wait_read<0>();
        }
        if (threadIdx.x == 0) STAMP(3, 5);
    }
}

typedef CUresult (*EncodeFn)(CUtensorMap*, CUtensorMapDataType, cuuint32_t, void*, const cuuint64_t*, const cuuint64_t*,
                             const cuuint32_t*, const cuuint32_t*, CUtensorMapInterleave, CUtensorMapSwizzle,
                             CUtensorMapL2promotion, CUtensorMapFloatOOBfill);

void make_map(EncodeFn fn, CUtensorMap* m, const void* ptr, uint64_t inner, uint64_t outer, uint32_t box_in, uint32_t box_out,
              CUtensorMapSwizzle swz = CU_TENSOR_MAP_SWIZZLE_128B) {
    cuuint64_t dims[2] = {inner, outer};
    cuuint64_t strides[1] = {inner * 2};
    cuuint32_t box[2] = {box_in, box_out};
    cuuint32_t es[2] = {1, 1};
    fn(m, CU_TENSOR_MAP_DATA_TYPE_BFLOAT16, 2, const_cast<void*>(ptr), dims, strides, box, es, CU_TENSOR_MAP_INTERLEAVE_NONE,
       swz, CU_TENSOR_MAP_L2_PROMOTION_L2_256B, CU_TENSOR_MAP_FLOAT_OOB_FILL_NONE);
}
void make_map3(EncodeFn fn, CUtensorMap* m, const void* ptr, uint64_t cols, uint64_t rows, uint32_t atom, uint32_t box_rows,
               uint32_t box_atoms, CUtensorMapSwizzle swz) {
    cuuint64_t dims[3] = {atom, rows, cols / atom};
    cuuint64_t strides[2] = {cols * 2, (cuuint64_t)atom * 2};
    cuuint32_t box[3] = {atom, box_rows, box_atoms};
    cuuint32_t es[3] = {1, 1, 1};
    fn(m, CU_TENSOR_MAP_DATA_TYPE_BFLOAT16, 3, const_cast<void*>(ptr), dims, strides, box, es, CU_TENSOR_MAP_INTERLEAVE_NONE,
       swz, CU_TENSOR_MAP_L2_PROMOTION_L2_256B, CU_TENSOR_MAP_FLOAT_OOB_FILL_NONE);
}

template <typename... Args>
void launch_pdl(void (*kern)(Args...), int grid, int block, int smem, bool pdl, int cluster, Args... args) {
    cudaLaunchConfig_t cfg = {};
    cfg.gridDim = dim3(grid); cfg.blockDim = dim3(block); cfg.dynamicSmemBytes = smem; cfg.stream = cudaStreamPerThread;
    cudaLaunchAttribute at[2];
    int n = 0;
    if (pdl) {
        at[n].id = cudaLaunchAttributeProgrammaticStreamSerialization;
        at[n].val.programmaticStreamSerializationAllowed = 1;
        n++;
    }
    if (cluster > 1) {
        at[n].id = cudaLaunchAttributeClusterDimension;
        at[n].val.clusterDim.x = cluster; at[n].val.clusterDim.y = 1; at[n].val.clusterDim.z = 1;
        n++;
    }
    cfg.attrs = at; cfg.numAttrs = n;
    cudaLaunchKernelEx(&cfg, kern, args...);
}

}

extern "C" void kernel_launch(void* const* d_in, const int* in_sizes, int n_in, void* d_out, int out_size) {
    const __nv_bfloat16* x = (const __nv_bfloat16*)d_in[0];
    const __nv_bfloat16* A_re = (const __nv_bfloat16*)d_in[1];
    const __nv_bfloat16* A_im = (const __nv_bfloat16*)d_in[2];
    const __nv_bfloat16* B_re = (const __nv_bfloat16*)d_in[3];
    const __nv_bfloat16* B_im = (const __nv_bfloat16*)d_in[4];
    const __nv_bfloat16* C_re = (const __nv_bfloat16*)d_in[5];
    const __nv_bfloat16* C_im = (const __nv_bfloat16*)d_in[6];
    const __nv_bfloat16* log_dt = (const __nv_bfloat16*)d_in[7];
    const __nv_bfloat16* Dskip = (const __nv_bfloat16*)d_in[8];
    const __nv_bfloat16* wg = (const __nv_bfloat16*)d_in[10];
    const __nv_bfloat16* wu = (const __nv_bfloat16*)d_in[11];
    const __nv_bfloat16* wd = (const __nv_bfloat16*)d_in[12];
    __nv_bfloat16* out = (__nv_bfloat16*)d_out;

    static bool init = false;
    static CUtensorMap tm_xn, tm_wg4, tm_wu4, tm_wg3, tm_wu3, tm_hst, tm_hst96, tm_h, tm_wd, tm_x, tm_sT, tm_out;
    static const void* last_ptrs[5] = {nullptr, nullptr, nullptr, nullptr, nullptr};
    if (!init || last_ptrs[0] != wg || last_ptrs[1] != wu || last_ptrs[2] != wd || last_ptrs[3] != x || last_ptrs[4] != out) {
        void* fnp = nullptr;
        cudaDriverEntryPointQueryResult qres;
        cudaGetDriverEntryPoint("cuTensorMapEncodeTiled", &fnp, cudaEnableDefault, &qres);
        EncodeFn fn = (EncodeFn)fnp;
        void *p_xn, *p_h, *p_sT;
        cudaGetSymbolAddress(&p_xn, g_xn);
        cudaGetSymbolAddress(&p_h, g_h);
        cudaGetSymbolAddress(&p_sT, g_sT);
        make_map(fn, &tm_xn, p_xn, D_, L_, 64, 128);
        make_map3(fn, &tm_wg4, wg, F_, D_, 32, 32, 4, CU_TENSOR_MAP_SWIZZLE_64B);
        make_map3(fn, &tm_wu4, wu, F_, D_, 32, 32, 4, CU_TENSOR_MAP_SWIZZLE_64B);
        make_map3(fn, &tm_wg3, wg, F_, D_, 32, 32, 3, CU_TENSOR_MAP_SWIZZLE_64B);
        make_map3(fn, &tm_wu3, wu, F_, D_, 32, 32, 3, CU_TENSOR_MAP_SWIZZLE_64B);
        make_map(fn, &tm_hst, p_h, F_, L_, 16, 16, CU_TENSOR_MAP_SWIZZLE_NONE);
        make_map(fn, &tm_hst96, p_h, F_, L_, 96, 16, CU_TENSOR_MAP_SWIZZLE_NONE);
        make_map(fn, &tm_h, p_h, F_, L_, 64, 128);
        make_map3(fn, &tm_wd, wd, D_, F_, 64, 64, 2, CU_TENSOR_MAP_SWIZZLE_128B);
        make_map(fn, &tm_x, x, D_, L_, 64, 128);
        make_map(fn, &tm_sT, p_sT, L_, D_, 64, 64);
        make_map(fn, &tm_out, out, D_, L_, 64, 16);
        cudaFuncSetAttribute(ln_kernel, cudaFuncAttributePreferredSharedMemoryCarveout, 100);
        cudaFuncSetAttribute(conv_kernel, cudaFuncAttributeMaxDynamicSharedMemorySize, CV_SMEM);
        cudaFuncSetAttribute(conv_kernel, cudaFuncAttributePreferredSharedMemoryCarveout, 100);
        cudaFuncSetAttribute(gemm1_kernel, cudaFuncAttributeMaxDynamicSharedMemorySize, G1_SMEM);
        cudaFuncSetAttribute(gemm2_kernel, cudaFuncAttributeMaxDynamicSharedMemorySize, G2_SMEM);
        last_ptrs[0] = wg; last_ptrs[1] = wu; last_ptrs[2] = wd; last_ptrs[3] = x; last_ptrs[4] = out;
        init = true;
    }
    launch_pdl(ln_kernel, L_ / LN_ROWS, 256, 0, false, 1, x, wg, wu, wd);
    launch_pdl(conv_kernel, D_ / CV_CH, 256, CV_SMEM, true, 1, A_re, A_im, B_re, B_im, C_re, C_im, log_dt, Dskip);
    launch_pdl(gemm1_kernel, 128, 384, G1_SMEM, true, 1, tm_xn, tm_wg4, tm_wu4, tm_wg3, tm_wu3, tm_hst, tm_hst96);
    launch_pdl(gemm2_kernel, 128, 384, G2_SMEM, true, 2, tm_h, tm_wd, tm_x, tm_sT, tm_out);
}
```

```cpp
#include <cuda_runtime.h>
#include <cuda_bf16.h>
#include <cuda.h>
#include <stdint.h>

namespace {

constexpr int L_ = 2048, D_ = 512, NS_ = 128, F_ = 1792;

__device__ __align__(1024) __nv_bfloat16 g_xn[L_ * D_];
__device__ __align__(1024) __nv_bfloat16 g_xnT[D_ * L_];
__device__ __align__(1024) __nv_bfloat16 g_sT[D_ * L_];
__device__ __align__(1024) __nv_bfloat16 g_h[L_ * F_];

#define STAMP(k, i)

__device__ __forceinline__ uint32_t smem_u32(const void* p) { return (uint32_t)__cvta_generic_to_shared(p); }
__device__ __forceinline__ void pdl_wait() { asm volatile("griddepcontrol.wait;" ::: "memory"); }
__device__ __forceinline__ void pdl_launch() { asm volatile("griddepcontrol.launch_dependents;" ::: "memory"); }

__device__ __forceinline__ void mbar_init(uint32_t bar, uint32_t cnt) {
    asm volatile("mbarrier.init.shared::cta.b64 [%0], %1;" ::"r"(bar), "r"(cnt) : "memory");
}
__device__ __forceinline__ void mbar_expect_tx(uint32_t bar, uint32_t bytes) {
    asm volatile("mbarrier.arrive.expect_tx.shared::cta.b64 _, [%0], %1;" ::"r"(bar), "r"(bytes) : "memory");
}
__device__ __forceinline__ void mbar_arrive(uint32_t bar) {
    asm volatile("mbarrier.arrive.shared::cta.b64 _, [%0];" ::"r"(bar) : "memory");
}
__device__ __forceinline__ void mbar_wait(uint32_t bar, uint32_t parity) {
    asm volatile(
        "{\n.reg .pred p;\n"
        "WAIT_LOOP:\n"
        "mbarrier.try_wait.parity.shared::cta.b64 p, [%0], %1;\n"
        "@p bra WAIT_DONE;\n"
        "bra WAIT_LOOP;\n"
        "WAIT_DONE:\n}\n" ::"r"(bar), "r"(parity) : "memory");
}
__device__ __forceinline__ void tma_load_2d(uint32_t dst, const CUtensorMap* tm, int c0, int c1, uint32_t bar) {
    asm volatile(
        "cp.async.bulk.tensor.2d.shared::cluster.global.mbarrier::complete_tx::bytes [%0], [%1, {%3, %4}], [%2];"
        ::"r"(dst), "l"((uint64_t)tm), "r"(bar), "r"(c0), "r"(c1) : "memory");
}
__device__ __forceinline__ void prefetch_tmap(const CUtensorMap* tm) {
    asm volatile("prefetch.tensormap [%0];" ::"l"((uint64_t)tm) : "memory");
}
__device__ __forceinline__ uint64_t make_desc(uint32_t addr, uint32_t lbo, uint32_t sbo, uint64_t mode = 1) {
    uint64_t d = 0;
    d |= (uint64_t)((addr & 0x3FFFF) >> 4);
    d |= (uint64_t)((lbo >> 4) & 0x3FFF) << 16;
    d |= (uint64_t)((sbo >> 4) & 0x3FFF) << 32;
    d |= mode << 62;
    return d;
}
__device__ __forceinline__ void wgmma_fence() { asm volatile("wgmma.fence.sync.aligned;" ::: "memory"); }
__device__ __forceinline__ void wgmma_commit() { asm volatile("wgmma.commit_group.sync.aligned;" ::: "memory"); }
template <int N> __device__ __forceinline__ void wgmma_wait() {
    asm volatile("wgmma.wait_group.sync.aligned %0;" ::"n"(N) : "memory");
}

#define R8(a, i) "+f"(a[i + 0]), "+f"(a[i + 1]), "+f"(a[i + 2]), "+f"(a[i + 3]), "+f"(a[i + 4]), "+f"(a[i + 5]), "+f"(a[i + 6]), "+f"(a[i + 7])

__device__ __forceinline__ void wgmma_n256_k32(float* a, uint64_t da0, uint64_t da1, uint64_t db0, uint64_t db1, int scale_d) {
    asm volatile(
        "{\n.reg .pred p;\nsetp.ne.b32 p, %132, 0;\n"
        "wgmma.mma_async.sync.aligned.m64n256k16.f32.bf16.bf16 {%0,%1,%2,%3,%4,%5,%6,%7,%8,%9,%10,%11,%12,%13,%14,%15,%16,%17,%18,%19,%20,%21,%22,%23,%24,%25,%26,%27,%28,%29,%30,%31,%32,%33,%34,%35,%36,%37,%38,%39,%40,%41,%42,%43,%44,%45,%46,%47,%48,%49,%50,%51,%52,%53,%54,%55,%56,%57,%58,%59,%60,%61,%62,%63,%64,%65,%66,%67,%68,%69,%70,%71,%72,%73,%74,%75,%76,%77,%78,%79,%80,%81,%82,%83,%84,%85,%86,%87,%88,%89,%90,%91,%92,%93,%94,%95,%96,%97,%98,%99,%100,%101,%102,%103,%104,%105,%106,%107,%108,%109,%110,%111,%112,%113,%114,%115,%116,%117,%118,%119,%120,%121,%122,%123,%124,%125,%126,%127}, %128, %130, p, 1, 1, 0, 1;\n"
        "wgmma.mma_async.sync.aligned.m64n256k16.f32.bf16.bf16 {%0,%1,%2,%3,%4,%5,%6,%7,%8,%9,%10,%11,%12,%13,%14,%15,%16,%17,%18,%19,%20,%21,%22,%23,%24,%25,%26,%27,%28,%29,%30,%31,%32,%33,%34,%35,%36,%37,%38,%39,%40,%41,%42,%43,%44,%45,%46,%47,%48,%49,%50,%51,%52,%53,%54,%55,%56,%57,%58,%59,%60,%61,%62,%63,%64,%65,%66,%67,%68,%69,%70,%71,%72,%73,%74,%75,%76,%77,%78,%79,%80,%81,%82,%83,%84,%85,%86,%87,%88,%89,%90,%91,%92,%93,%94,%95,%96,%97,%98,%99,%100,%101,%102,%103,%104,%105,%106,%107,%108,%109,%110,%111,%112,%113,%114,%115,%116,%117,%118,%119,%120,%121,%122,%123,%124,%125,%126,%127}, %129, %131, 1, 1, 1, 0, 1;\n"
        "}\n"
        : R8(a, 0), R8(a, 8), R8(a, 16), R8(a, 24), R8(a, 32), R8(a, 40), R8(a, 48), R8(a, 56), R8(a, 64), R8(a, 72), R8(a, 80), R8(a, 88), R8(a, 96), R8(a, 104), R8(a, 112), R8(a, 120)
        : "l"(da0), "l"(da1), "l"(db0), "l"(db1), "r"(scale_d));
}
__device__ __forceinline__ void wgmma_n192_k32(float* a, uint64_t da0, uint64_t da1, uint64_t db0, uint64_t db1, int scale_d) {
    asm volatile(
        "{\n.reg .pred p;\nsetp.ne.b32 p, %100, 0;\n"
        "wgmma.mma_async.sync.aligned.m64n192k16.f32.bf16.bf16 {%0,%1,%2,%3,%4,%5,%6,%7,%8,%9,%10,%11,%12,%13,%14,%15,%16,%17,%18,%19,%20,%21,%22,%23,%24,%25,%26,%27,%28,%29,%30,%31,%32,%33,%34,%35,%36,%37,%38,%39,%40,%41,%42,%43,%44,%45,%46,%47,%48,%49,%50,%51,%52,%53,%54,%55,%56,%57,%58,%59,%60,%61,%62,%63,%64,%65,%66,%67,%68,%69,%70,%71,%72,%73,%74,%75,%76,%77,%78,%79,%80,%81,%82,%83,%84,%85,%86,%87,%88,%89,%90,%91,%92,%93,%94,%95}, %96, %98, p, 1, 1, 0, 1;\n"
        "wgmma.mma_async.sync.aligned.m64n192k16.f32.bf16.bf16 {%0,%1,%2,%3,%4,%5,%6,%7,%8,%9,%10,%11,%12,%13,%14,%15,%16,%17,%18,%19,%20,%21,%22,%23,%24,%25,%26,%27,%28,%29,%30,%31,%32,%33,%34,%35,%36,%37,%38,%39,%40,%41,%42,%43,%44,%45,%46,%47,%48,%49,%50,%51,%52,%53,%54,%55,%56,%57,%58,%59,%60,%61,%62,%63,%64,%65,%66,%67,%68,%69,%70,%71,%72,%73,%74,%75,%76,%77,%78,%79,%80,%81,%82,%83,%84,%85,%86,%87,%88,%89,%90,%91,%92,%93,%94,%95}, %97, %99, 1, 1, 1, 0, 1;\n"
        "}\n"
        : R8(a, 0), R8(a, 8), R8(a, 16), R8(a, 24), R8(a, 32), R8(a, 40), R8(a, 48), R8(a, 56), R8(a, 64), R8(a, 72), R8(a, 80), R8(a, 88)
        : "l"(da0), "l"(da1), "l"(db0), "l"(db1), "r"(scale_d));
}
__device__ __forceinline__ void wgmma_n192(float* a, uint64_t da0, uint64_t db0, int scale_d) {
    asm volatile(
        "{\n.reg .pred p;\nsetp.ne.b32 p, %98, 0;\n"
        "wgmma.mma_async.sync.aligned.m64n192k16.f32.bf16.bf16 {%0,%1,%2,%3,%4,%5,%6,%7,%8,%9,%10,%11,%12,%13,%14,%15,%16,%17,%18,%19,%20,%21,%22,%23,%24,%25,%26,%27,%28,%29,%30,%31,%32,%33,%34,%35,%36,%37,%38,%39,%40,%41,%42,%43,%44,%45,%46,%47,%48,%49,%50,%51,%52,%53,%54,%55,%56,%57,%58,%59,%60,%61,%62,%63,%64,%65,%66,%67,%68,%69,%70,%71,%72,%73,%74,%75,%76,%77,%78,%79,%80,%81,%82,%83,%84,%85,%86,%87,%88,%89,%90,%91,%92,%93,%94,%95}, %96, %97, p, 1, 1, 0, 1;\n"
        "}\n"
        : R8(a, 0), R8(a, 8), R8(a, 16), R8(a, 24), R8(a, 32), R8(a, 40), R8(a, 48), R8(a, 56), R8(a, 64), R8(a, 72), R8(a, 80), R8(a, 88)
        : "l"(da0), "l"(db0), "r"(scale_d));
}
__device__ __forceinline__ void wgmma_n128_k64(float* a, uint64_t da0, uint64_t da1, uint64_t da2, uint64_t da3,
                                               uint64_t db0, uint64_t db1, uint64_t db2, uint64_t db3, int scale_d) {
    asm volatile(
        "{\n.reg .pred p;\nsetp.ne.b32 p, %72, 0;\n"
        "wgmma.mma_async.sync.aligned.m64n128k16.f32.bf16.bf16 {%0,%1,%2,%3,%4,%5,%6,%7,%8,%9,%10,%11,%12,%13,%14,%15,%16,%17,%18,%19,%20,%21,%22,%23,%24,%25,%26,%27,%28,%29,%30,%31,%32,%33,%34,%35,%36,%37,%38,%39,%40,%41,%42,%43,%44,%45,%46,%47,%48,%49,%50,%51,%52,%53,%54,%55,%56,%57,%58,%59,%60,%61,%62,%63}, %64, %68, p, 1, 1, 0, 1;\n"
        "wgmma.mma_async.sync.aligned.m64n128k16.f32.bf16.bf16 {%0,%1,%2,%3,%4,%5,%6,%7,%8,%9,%10,%11,%12,%13,%14,%15,%16,%17,%18,%19,%20,%21,%22,%23,%24,%25,%26,%27,%28,%29,%30,%31,%32,%33,%34,%35,%36,%37,%38,%39,%40,%41,%42,%43,%44,%45,%46,%47,%48,%49,%50,%51,%52,%53,%54,%55,%56,%57,%58,%59,%60,%61,%62,%63}, %65, %69, 1, 1, 1, 0, 1;\n"
        "wgmma.mma_async.sync.aligned.m64n128k16.f32.bf16.bf16 {%0,%1,%2,%3,%4,%5,%6,%7,%8,%9,%10,%11,%12,%13,%14,%15,%16,%17,%18,%19,%20,%21,%22,%23,%24,%25,%26,%27,%28,%29,%30,%31,%32,%33,%34,%35,%36,%37,%38,%39,%40,%41,%42,%43,%44,%45,%46,%47,%48,%49,%50,%51,%52,%53,%54,%55,%56,%57,%58,%59,%60,%61,%62,%63}, %66, %70, 1, 1, 1, 0, 1;\n"
        "wgmma.mma_async.sync.aligned.m64n128k16.f32.bf16.bf16 {%0,%1,%2,%3,%4,%5,%6,%7,%8,%9,%10,%11,%12,%13,%14,%15,%16,%17,%18,%19,%20,%21,%22,%23,%24,%25,%26,%27,%28,%29,%30,%31,%32,%33,%34,%35,%36,%37,%38,%39,%40,%41,%42,%43,%44,%45,%46,%47,%48,%49,%50,%51,%52,%53,%54,%55,%56,%57,%58,%59,%60,%61,%62,%63}, %67, %71, 1, 1, 1, 0, 1;\n"
        "}\n"
        : R8(a, 0), R8(a, 8), R8(a, 16), R8(a, 24), R8(a, 32), R8(a, 40), R8(a, 48), R8(a, 56)
        : "l"(da0), "l"(da1), "l"(da2), "l"(da3), "l"(db0), "l"(db1), "l"(db2), "l"(db3), "r"(scale_d));
}

__device__ __forceinline__ float bf16_round(float x) {
    uint32_t p; asm("cvt.rn.bf16x2.f32 %0, %1, %2;" : "=r"(p) : "f"(x), "f"(0.0f));
    return __uint_as_float(p);
}
__device__ __forceinline__ uint32_t pack_bf16(float lo, float hi) {
    __nv_bfloat162 v = __floats2bfloat162_rn(lo, hi);
    return *reinterpret_cast<uint32_t*>(&v);
}
__device__ __forceinline__ float bf_lo(uint32_t v) { return __uint_as_float(v << 16); }
__device__ __forceinline__ float bf_hi(uint32_t v) { return __uint_as_float(v & 0xFFFF0000u); }

constexpr int LN_ROWS = 16;
__global__ void __launch_bounds__(256) ln_kernel(const __nv_bfloat16* __restrict__ x,
                                                  const __nv_bfloat16* __restrict__ wg,
                                                  const __nv_bfloat16* __restrict__ wu,
                                                  const __nv_bfloat16* __restrict__ wd) {
    pdl_launch();
    if (threadIdx.x == 0) STAMP(0, 0);
    __shared__ __align__(16) __nv_bfloat16 tile[LN_ROWS][D_ + 8];
    const int warp = threadIdx.x >> 5, lane = threadIdx.x & 31;
    const int row0 = blockIdx.x * LN_ROWS;
    {
        const int lines_per = (D_ * F_ * 2) / 128 / 128;
        if (threadIdx.x < lines_per) {
            size_t off = ((size_t)blockIdx.x * lines_per + threadIdx.x) * 128;
            asm volatile("prefetch.global.L2 [%0];" ::"l"((const char*)wg + off));
            asm volatile("prefetch.global.L2 [%0];" ::"l"((const char*)wu + off));
            asm volatile("prefetch.global.L2 [%0];" ::"l"((const char*)wd + off));
        }
    }
    uint4 v[2][2];
#pragma unroll
    for (int r = 0; r < 2; r++) {
        const __nv_bfloat16* xr = x + (size_t)(row0 + warp * 2 + r) * D_;
        v[r][0] = *reinterpret_cast<const uint4*>(xr + lane * 8);
        v[r][1] = *reinterpret_cast<const uint4*>(xr + 256 + lane * 8);
    }
#pragma unroll
    for (int r = 0; r < 2; r++) {
        float f[16];
        const uint32_t* w = reinterpret_cast<const uint32_t*>(&v[r][0]);
#pragma unroll
        for (int i = 0; i < 8; i++) { f[2 * i] = bf_lo(w[i]); f[2 * i + 1] = bf_hi(w[i]); }
        float s = 0.f;
#pragma unroll
        for (int i = 0; i < 16; i++) s += f[i];
#pragma unroll
        for (int o = 16; o > 0; o >>= 1) s += __shfl_xor_sync(0xffffffffu, s, o);
        const float mean = s * (1.0f / D_);
        float q = 0.f;
#pragma unroll
        for (int i = 0; i < 16; i++) { float d = f[i] - mean; q += d * d; }
#pragma unroll
        for (int o = 16; o > 0; o >>= 1) q += __shfl_xor_sync(0xffffffffu, q, o);
        const float mb = bf16_round(mean);
        const float vb = bf16_round(q * (1.0f / D_));
        const float den = bf16_round(sqrtf(bf16_round(vb + 1e-5f)));
        uint32_t o[8];
#pragma unroll
        for (int i = 0; i < 8; i++) {
            float a = __fdiv_rn(bf16_round(f[2 * i] - mb), den);
            float b = __fdiv_rn(bf16_round(f[2 * i + 1] - mb), den);
            o[i] = pack_bf16(a, b);
        }
        const int rr = warp * 2 + r;
        __nv_bfloat16* dst = g_xn + (size_t)(row0 + rr) * D_;
        *reinterpret_cast<uint4*>(dst + lane * 8) = make_uint4(o[0], o[1], o[2], o[3]);
        *reinterpret_cast<uint4*>(dst + 256 + lane * 8) = make_uint4(o[4], o[5], o[6], o[7]);
        *reinterpret_cast<uint4*>(&tile[rr][lane * 8]) = make_uint4(o[0], o[1], o[2], o[3]);
        *reinterpret_cast<uint4*>(&tile[rr][256 + lane * 8]) = make_uint4(o[4], o[5], o[6], o[7]);
    }
    __syncthreads();
    if (threadIdx.x == 0) STAMP(0, 1);
#pragma unroll
    for (int cc = 0; cc < 2; cc++) {
        const int c = threadIdx.x + cc * 256;
        uint32_t o[8];
#pragma unroll
        for (int i = 0; i < 8; i++) {
            uint32_t lo = *reinterpret_cast<const uint16_t*>(&tile[2 * i][c]);
            uint32_t hi = *reinterpret_cast<const uint16_t*>(&tile[2 * i + 1][c]);
            o[i] = lo | (hi << 16);
        }
        __nv_bfloat16* dst = g_xnT + (size_t)c * L_ + row0;
        *reinterpret_cast<uint4*>(dst) = make_uint4(o[0], o[1], o[2], o[3]);
        *reinterpret_cast<uint4*>(dst + 8) = make_uint4(o[4], o[5], o[6], o[7]);
    }
    if (threadIdx.x == 0) STAMP(0, 2);
}

struct cplx { float r, i; };
__device__ __forceinline__ cplx cmul(cplx a, cplx b) {
    cplx c; c.r = a.r * b.r - a.i * b.i; c.i = a.r * b.i + a.i * b.r; return c;
}
__device__ __forceinline__ cplx csq(cplx a) {
    cplx c; c.r = a.r * a.r - a.i * a.i; c.i = 2.0f * a.r * a.i; return c;
}
__device__ __forceinline__ cplx cexp_m(float ar, float ai, float m) {
    float mag;
    float e = (ar * m) * 1.4426950408889634f;
    asm("ex2.approx.ftz.f32 %0, %1;" : "=f"(mag) : "f"(e));
    float rr = (ai * m) * 0.15915494309189535f;
    rr -= rintf(rr);
    float th = rr * 6.283185307179586f;
    cplx c; c.r = mag * __cosf(th); c.i = mag * __sinf(th);
    return c;
}
__device__ __forceinline__ uint32_t to_tf32(float x) {
    uint32_t r; asm("cvt.rna.tf32.f32 %0, %1;" : "=r"(r) : "f"(x)); return r;
}
__device__ __forceinline__ void mma_tf32(float* c, uint32_t a0, uint32_t a1, uint32_t a2, uint32_t a3, uint32_t b0, uint32_t b1) {
    asm volatile("mma.sync.aligned.m16n8k8.row.col.f32.tf32.tf32.f32 {%0,%1,%2,%3}, {%4,%5,%6,%7}, {%8,%9}, {%0,%1,%2,%3};"
                 : "+f"(c[0]), "+f"(c[1]), "+f"(c[2]), "+f"(c[3])
                 : "r"(a0), "r"(a1), "r"(a2), "r"(a3), "r"(b0), "r"(b1));
}
__device__ __forceinline__ void mma_bf16(float* c, uint32_t a0, uint32_t a1, uint32_t a2, uint32_t a3, uint32_t b0, uint32_t b1) {
    asm volatile("mma.sync.aligned.m16n8k16.row.col.f32.bf16.bf16.f32 {%0,%1,%2,%3}, {%4,%5,%6,%7}, {%8,%9}, {%0,%1,%2,%3};"
                 : "+f"(c[0]), "+f"(c[1]), "+f"(c[2]), "+f"(c[3])
                 : "r"(a0), "r"(a1), "r"(a2), "r"(a3), "r"(b0), "r"(b1));
}
__device__ __forceinline__ void named_bar(int id, int n) { asm volatile("bar.sync %0, %1;" ::"r"(id), "r"(n) : "memory"); }

constexpr int CV_CH = 4;
constexpr int CV_CONST_B = NS_ * 12 * 4;
constexpr int CV_KV_B = 648 * 4;
constexpr int CV_Q_B = (L_ + 16) * 4;
constexpr int CV_U_B = (L_ + 128) * 2;
constexpr int CV_PER_CH = CV_CONST_B + 2 * CV_KV_B + CV_Q_B + CV_U_B;
constexpr int CV_SMEM = CV_CH * CV_PER_CH;

__global__ void __launch_bounds__(256) conv_kernel(const __nv_bfloat16* __restrict__ A_re, const __nv_bfloat16* __restrict__ A_im,
                                                    const __nv_bfloat16* __restrict__ B_re, const __nv_bfloat16* __restrict__ B_im,
                                                    const __nv_bfloat16* __restrict__ C_re, const __nv_bfloat16* __restrict__ C_im,
                                                    const __nv_bfloat16* __restrict__ log_dt, const __nv_bfloat16* __restrict__ Dskip) {
    pdl_launch();
    if (threadIdx.x == 0) STAMP(1, 0);
    extern __shared__ __align__(16) uint8_t smem[];
    const int warp = threadIdx.x >> 5, lane = threadIdx.x & 31;
    const int ch = warp >> 1, h = warp & 1;
    const int d = blockIdx.x * CV_CH + ch;
    const int g = lane >> 2, t = lane & 3;
    uint8_t* base = smem + ch * CV_PER_CH;
    float4* s_const = reinterpret_cast<float4*>(base);
    float* s_kv = reinterpret_cast<float*>(base + CV_CONST_B);
    uint32_t* s_q = reinterpret_cast<uint32_t*>(base + CV_CONST_B + 2 * CV_KV_B);
    __nv_bfloat16* s_u = reinterpret_cast<__nv_bfloat16*>(base + CV_CONST_B + 2 * CV_KV_B + CV_Q_B);
    const int bar_id = 1 + ch;

    const float dt = bf16_round(expf(__bfloat162float(log_dt[d])));
    float tail = 0.f;
    {
        const int n0 = h * 64 + lane * 2;
        const size_t off = (size_t)d * NS_ + n0;
        uint32_t war = *reinterpret_cast<const uint32_t*>(A_re + off);
        uint32_t wai = *reinterpret_cast<const uint32_t*>(A_im + off);
        uint32_t wbr = *reinterpret_cast<const uint32_t*>(B_re + off);
        uint32_t wbi = *reinterpret_cast<const uint32_t*>(B_im + off);
        uint32_t wcr = *reinterpret_cast<const uint32_t*>(C_re + off);
        uint32_t wci = *reinterpret_cast<const uint32_t*>(C_im + off);
#pragma unroll
        for (int j = 0; j < 2; j++) {
            float ar = dt * (j ? bf_hi(war) : bf_lo(war));
            float ai = dt * (j ? bf_hi(wai) : bf_lo(wai));
            cplx db = {dt * (j ? bf_hi(wbr) : bf_lo(wbr)), dt * (j ? bf_hi(wbi) : bf_lo(wbi))};
            cplx cc = {(j ? bf_hi(wcr) : bf_lo(wcr)), (j ? bf_hi(wci) : bf_lo(wci))};
            cplx cb = cmul(cc, db);
            cplx e128 = cexp_m(ar, ai, 128.f);
            cplx c256 = cmul(cb, cexp_m(ar, ai, 256.f));
            cplx c512 = cmul(cb, cexp_m(ar, ai, 512.f));
            cplx c1024 = cmul(cb, cexp_m(ar, ai, 1024.f));
            cplx c2048 = cmul(cb, cexp_m(ar, ai, 2048.f));
            tail += c2048.r;
            s_const[(n0 + j) * 3 + 0] = make_float4(ar, ai, cb.r, cb.i);
            s_const[(n0 + j) * 3 + 1] = make_float4(e128.r, e128.i, c256.r, c256.i);
            s_const[(n0 + j) * 3 + 2] = make_float4(c512.r, c512.i, c1024.r, c1024.i);
        }
#pragma unroll
        for (int o = 16; o > 0; o >>= 1) tail += __shfl_xor_sync(0xffffffffu, tail, o);
    }
    __syncwarp();
    if (threadIdx.x == 0) STAMP(1, 1);
    {
        float acc[5][4];
#pragma unroll
        for (int i = 0; i < 5; i++) { acc[i][0] = acc[i][1] = acc[i][2] = acc[i][3] = 0.f; }
        const float gf = (float)g;
#pragma unroll 2
        for (int s = 0; s < 16; s++) {
            const int n = h * 64 + s * 4 + t;
            const float4 k0 = s_const[n * 3 + 0], k1 = s_const[n * 3 + 1], k2 = s_const[n * 3 + 2];
            const cplx cb = {k0.z, k0.w}, e128 = {k1.x, k1.y}, c256 = {k1.z, k1.w}, c512 = {k2.x, k2.y}, c1024 = {k2.z, k2.w};
            cplx p1 = cexp_m(k0.x, k0.y, gf);
            cplx p1b = cexp_m(k0.x, k0.y, gf + 8.f);
            cplx r16a = cexp_m(k0.x, k0.y, gf * 16.f);
            cplx r16b = cmul(r16a, e128);
            cplx p2 = csq(p1), p4 = csq(p2), p8 = csq(p4);
            cplx r32a = csq(r16a), r32b = csq(r16b), r64a = csq(r32a), r64b = csq(r32b);
            cplx f0a = cmul(cb, p1), f0b = cmul(cb, p1b), f1 = cmul(c256, p2), f2 = cmul(c512, p4), f3 = cmul(c1024, p8);
            {
                uint32_t a0 = to_tf32(r16a.r), a1 = to_tf32(r16b.r), a2 = to_tf32(-r16a.i), a3 = to_tf32(-r16b.i);
                mma_tf32(acc[0], a0, a1, a2, a3, to_tf32(f0a.r), to_tf32(f0a.i));
                mma_tf32(acc[1], a0, a1, a2, a3, to_tf32(f0b.r), to_tf32(f0b.i));
                mma_tf32(acc[2], a0, a1, a2, a3, to_tf32(f1.r), to_tf32(f1.i));
            }
            mma_tf32(acc[3], to_tf32(r32a.r), to_tf32(r32b.r), to_tf32(-r32a.i), to_tf32(-r32b.i), to_tf32(f2.r), to_tf32(f2.i));
            mma_tf32(acc[4], to_tf32(r64a.r), to_tf32(r64b.r), to_tf32(-r64a.i), to_tf32(-r64b.i), to_tf32(f3.r), to_tf32(f3.i));
        }
        float* kv = s_kv + h * 648;
        *reinterpret_cast<float2*>(kv + 16 * g + 2 * t) = make_float2(acc[0][0], acc[0][1]);
        *reinterpret_cast<float2*>(kv + 16 * (g + 8) + 2 * t) = make_float2(acc[0][2], acc[0][3]);
        *reinterpret_cast<float2*>(kv + 16 * g + 8 + 2 * t) = make_float2(acc[1][0], acc[1][1]);
        *reinterpret_cast<float2*>(kv + 16 * (g + 8) + 8 + 2 * t) = make_float2(acc[1][2], acc[1][3]);
#pragma unroll
        for (int sg = 0; sg < 3; sg++) {
            *reinterpret_cast<float2*>(kv + 256 + 128 * sg + 8 * g + 2 * t) = make_float2(acc[2 + sg][0], acc[2 + sg][1]);
            *reinterpret_cast<float2*>(kv + 256 + 128 * sg + 8 * (g + 8) + 2 * t) = make_float2(acc[2 + sg][2], acc[2 + sg][3]);
        }
        if (lane == 0) kv[640] = tail;
    }
    named_bar(bar_id, 64);
    if (threadIdx.x == 0) STAMP(1, 2);
    {
        const int tid2 = h * 32 + lane;
        if (tid2 < 16) s_q[tid2] = 0u;
        for (int x = tid2; x < L_; x += 64) {
            float kc, kp;
            {
                int s = (x >= 1024) ? 3 : (x >= 512) ? 2 : (x >= 256) ? 1 : 0;
                int rq = (s == 0) ? x : ((x + (1 << (s - 1)) - 1 + ((x >> s) & 1)) >> s);
                int idx = 128 * s + rq;
                kc = s_kv[idx] + s_kv[648 + idx];
            }
            {
                int y = x - 1;
                if (y < 0) kp = 0.f;
                else {
                    int s = (y >= 1024) ? 3 : (y >= 512) ? 2 : (y >= 256) ? 1 : 0;
                    int rq = (s == 0) ? y : ((y + (1 << (s - 1)) - 1 + ((y >> s) & 1)) >> s);
                    int idx = 128 * s + rq;
                    kp = s_kv[idx] + s_kv[648 + idx];
                }
            }
            s_q[x + 16] = pack_bf16(kc, kp);
        }
    }
    if (threadIdx.x == 0) STAMP(1, 3);
    pdl_wait();
    if (threadIdx.x == 0) STAMP(1, 4);
    {
        const int tid2 = h * 32 + lane;
        if (tid2 < 16) *reinterpret_cast<uint4*>(s_u + tid2 * 8) = make_uint4(0, 0, 0, 0);
        const uint4* src = reinterpret_cast<const uint4*>(g_xnT + (size_t)d * L_);
#pragma unroll
        for (int i = 0; i < 4; i++) {
            *reinterpret_cast<uint4*>(s_u + 128 + (tid2 + i * 64) * 8) = src[tid2 + i * 64];
        }
    }
    named_bar(bar_id, 64);
    if (threadIdx.x == 0) STAMP(1, 5);
    float acc[16][4];
#pragma unroll
    for (int i = 0; i < 16; i++) { acc[i][0] = acc[i][1] = acc[i][2] = acc[i][3] = 0.f; }
    const uint32_t su_addr = smem_u32(s_u);
    for (int rr = 0; rr < 4; rr++) {
        const int r = h * 4 + rr;
        uint32_t ub[16][2];
        {
            const int mi = lane >> 3, rowi = lane & 7;
            uint32_t addr = su_addr + (uint32_t)((128 + 16 * (8 * (mi >> 1) + rowi - r) + 8 * (mi & 1)) * 2);
#pragma unroll
            for (int j = 0; j < 16; j += 2) {
                asm volatile("ldmatrix.sync.aligned.m8n8.x4.shared.b16 {%0,%1,%2,%3}, [%4];"
                             : "=r"(ub[j][0]), "=r"(ub[j][1]), "=r"(ub[j + 1][0]), "=r"(ub[j + 1][1])
                             : "r"(addr + (uint32_t)(j * 8 * 16 * 2)));
            }
        }
        const uint32_t* qp = s_q + 16 + 16 * r + g - 2 * t;
#pragma unroll
        for (int q = 0; q < 16; q++) {
            const uint32_t a0 = qp[128 * q], a1 = qp[128 * q + 8], a2 = qp[128 * q - 8];
#pragma unroll
            for (int nt = q; nt < 16; nt++) mma_bf16(acc[nt], a0, a1, a2, a0, ub[nt - q][0], ub[nt - q][1]);
        }
    }
    if (threadIdx.x == 0) STAMP(1, 6);
    named_bar(bar_id, 64);
    {
        float4* xch = reinterpret_cast<float4*>(base) + h * 256;
        if (h) {
#pragma unroll
            for (int i = 0; i < 8; i++) xch[i * 32 + lane] = make_float4(acc[i][0], acc[i][1], acc[i][2], acc[i][3]);
        } else {
#pragma unroll
            for (int i = 0; i < 8; i++) xch[i * 32 + lane] = make_float4(acc[8 + i][0], acc[8 + i][1], acc[8 + i][2], acc[8 + i][3]);
        }
    }
    named_bar(bar_id, 64);
    {
        const float4* xch = reinterpret_cast<const float4*>(base) + (h ^ 1) * 256;
        const float dsk = __bfloat162float(Dskip[d]);
        __nv_bfloat16* stg = reinterpret_cast<__nv_bfloat16*>(s_q);
#pragma unroll
        for (int i = 0; i < 8; i++) {
            float4 o = xch[i * 32 + lane];
            float y[4];
            if (h) { y[0] = acc[8 + i][0] + o.x; y[1] = acc[8 + i][1] + o.y; y[2] = acc[8 + i][2] + o.z; y[3] = acc[8 + i][3] + o.w; }
            else   { y[0] = acc[i][0] + o.x; y[1] = acc[i][1] + o.y; y[2] = acc[i][2] + o.z; y[3] = acc[i][3] + o.w; }
            const int nt = h * 8 + i;
#pragma unroll
            for (int e = 0; e < 4; e++) {
                const int tau = 16 * (8 * nt + 2 * t + (e & 1)) + g + 8 * (e >> 1);
                float u = __bfloat162float(s_u[128 + tau]);
                float sv = bf16_round(y[e]) + bf16_round(u * dsk);
                reinterpret_cast<uint16_t*>(stg)[tau] = (uint16_t)(__float_as_uint(bf16_round(sv)) >> 16);
            }
        }
        __syncwarp();
        uint4* dst = reinterpret_cast<uint4*>(g_sT + (size_t)d * L_ + h * 1024);
        const uint4* srcp = reinterpret_cast<const uint4*>(stg + h * 1024);
#pragma unroll
        for (int i = 0; i < 4; i++) dst[i * 32 + lane] = srcp[i * 32 + lane];
    }
    if (threadIdx.x == 0) STAMP(1, 7);
}

__device__ __forceinline__ uint32_t cluster_rank() { uint32_t r; asm volatile("mov.u32 %0, %%cluster_ctarank;" : "=r"(r)); return r; }
__device__ __forceinline__ void cluster_sync_all() {
    asm volatile("barrier.cluster.arrive.release.aligned;\nbarrier.cluster.wait.acquire.aligned;" ::: "memory");
}
__device__ __forceinline__ void mbar_arrive_remote(uint32_t bar, uint32_t cta) {
    asm volatile("{\n.reg .b32 ra;\nmapa.shared::cluster.u32 ra, %0, %1;\n"
                 "mbarrier.arrive.shared::cluster.b64 _, [ra];\n}\n" ::"r"(bar), "r"(cta) : "memory");
}
__device__ __forceinline__ void tma_load_2d_mc(uint32_t dst, const CUtensorMap* tm, int c0, int c1, uint32_t bar, uint16_t mask) {
    asm volatile(
        "cp.async.bulk.tensor.2d.shared::cluster.global.mbarrier::complete_tx::bytes.multicast::cluster [%0], [%1, {%3, %4}], [%2], %5;"
        ::"r"(dst), "l"((uint64_t)tm), "r"(bar), "r"(c0), "r"(c1), "h"(mask) : "memory");
}
__device__ __forceinline__ void tma_store_2d(const CUtensorMap* tm, uint32_t src, int c0, int c1) {
    asm volatile("cp.async.bulk.tensor.2d.global.shared::cta.bulk_group [%0, {%2, %3}], [%1];"
                 ::"l"((uint64_t)tm), "r"(src), "r"(c0), "r"(c1) : "memory");
}
__device__ __forceinline__ void bulk_commit() { asm volatile("cp.async.bulk.commit_group;" ::: "memory"); }
template <int N> __device__ __forceinline__ void bulk_wait_read() { asm volatile("cp.async.bulk.wait_group.read %0;" ::"n"(N) : "memory"); }
template <int N> __device__ __forceinline__ void bulk_wait() { asm volatile("cp.async.bulk.wait_group %0;" ::"n"(N) : "memory"); }
__device__ __forceinline__ void fence_async_smem() { asm volatile("fence.proxy.async.shared::cta;" ::: "memory"); }
__device__ __forceinline__ void stmatrix_x4(uint32_t addr, uint32_t r0, uint32_t r1, uint32_t r2, uint32_t r3) {
    asm volatile("stmatrix.sync.aligned.m8n8.x4.shared.b16 [%0], {%1,%2,%3,%4};" ::"r"(addr), "r"(r0), "r"(r1), "r"(r2), "r"(r3) : "memory");
}

constexpr int G1_STAGES = 5;
constexpr int G1_A_BYTES = 8 * 16384;
constexpr int G1_B_STAGE = 16384;
constexpr int G1_STG = 8 * 1024;
constexpr int G1_SMEM = G1_A_BYTES + G1_STAGES * G1_B_STAGE + G1_STG + 1024 + 256;
constexpr int G1_ITERS = 32;

__device__ __forceinline__ void tma_load_3d(uint32_t dst, const CUtensorMap* tm, int c0, int c1, int c2, uint32_t bar) {
    asm volatile(
        "cp.async.bulk.tensor.3d.shared::cluster.global.mbarrier::complete_tx::bytes [%0], [%1, {%3, %4, %5}], [%2];"
        ::"r"(dst), "l"((uint64_t)tm), "r"(bar), "r"(c0), "r"(c1), "r"(c2) : "memory");
}

__device__ __forceinline__ float gelu_tanh(float x) {
    float u = x * (0.7978845608028654f + 0.035677408136300125f * x * x);
    float t; asm("tanh.approx.f32 %0, %1;" : "=f"(t) : "f"(u));
    float hx = 0.5f * x;
    return fmaf(hx, t, hx);
}
__device__ __forceinline__ uint32_t geglu_pair(uint32_t g2, uint32_t u2) {
    uint32_t a = pack_bf16(gelu_tanh(bf_lo(g2)), gelu_tanh(bf_hi(g2)));
    uint32_t r; asm("mul.rn.bf16x2 %0, %1, %2;" : "=r"(r) : "r"(a), "r"(u2));
    return r;
}

__global__ void __launch_bounds__(384, 1) gemm1_kernel(const __grid_constant__ CUtensorMap tm_xn,
                                                        const __grid_constant__ CUtensorMap tm_wg4,
                                                        const __grid_constant__ CUtensorMap tm_wu4,
                                                        const __grid_constant__ CUtensorMap tm_wg3,
                                                        const __grid_constant__ CUtensorMap tm_wu3,
                                                        const __grid_constant__ CUtensorMap tm_hst,
                                                        const __grid_constant__ CUtensorMap tm_hst96) {
    pdl_launch();
    if (threadIdx.x == 0) STAMP(2, 0);
    extern __shared__ uint8_t smem_raw[];
    const uint32_t sbase = (smem_u32(smem_raw) + 1023) & ~1023u;
    const uint32_t sA = sbase, sB = sbase + G1_A_BYTES, sStg = sB + G1_STAGES * G1_B_STAGE, sBar = sStg + G1_STG;
    const uint32_t bar_a = sBar, bar_full = sBar + 64, bar_empty = sBar + 64 + 8 * G1_STAGES;
    const int rb = blockIdx.x >> 3, cj = blockIdx.x & 7;
    const int warp = threadIdx.x >> 5, lane = threadIdx.x & 31;

    if (threadIdx.x == 0) {
        for (int i = 0; i < 8; i++) mbar_init(bar_a + 8 * i, 1);
        for (int i = 0; i < G1_STAGES; i++) { mbar_init(bar_full + 8 * i, 1); mbar_init(bar_empty + 8 * i, 8); }
        asm volatile("fence.mbarrier_init.release.cluster;" ::: "memory");
    }
    __syncthreads();

    if (warp >= 8) {
        asm volatile("setmaxnreg.dec.sync.aligned.u32 40;");
        if (lane == 0) {
            const int pw = warp - 8;
            if (pw == 0) { prefetch_tmap(&tm_wg4); prefetch_tmap(&tm_wu4); prefetch_tmap(&tm_xn); }
            if (pw == 1) { prefetch_tmap(&tm_wg3); prefetch_tmap(&tm_wu3); prefetch_tmap(&tm_hst); prefetch_tmap(&tm_hst96); }
            for (int it = pw; it < G1_ITERS; it += 4) {
                const int s = it % G1_STAGES, kb = it & 15;
                if (it >= G1_STAGES) mbar_wait(bar_empty + 8 * s, ((it / G1_STAGES) - 1) & 1);
                const uint32_t dst = sB + s * G1_B_STAGE;
                if (it < 16) {
                    mbar_expect_tx(bar_full + 8 * s, 16384);
                    tma_load_3d(dst, &tm_wg4, 0, kb * 32, cj * 7, bar_full + 8 * s);
                    tma_load_3d(dst + 8192, &tm_wu4, 0, kb * 32, cj * 7, bar_full + 8 * s);
                } else {
                    mbar_expect_tx(bar_full + 8 * s, 12288);
                    tma_load_3d(dst, &tm_wg3, 0, kb * 32, cj * 7 + 4, bar_full + 8 * s);
                    tma_load_3d(dst + 6144, &tm_wu3, 0, kb * 32, cj * 7 + 4, bar_full + 8 * s);
                }
                if (it < 4) {
                    pdl_wait();
                    if (pw == 0) STAMP(2, 1);
                    for (int k = pw; k < 8; k += 4) {
                        mbar_expect_tx(bar_a + 8 * k, 16384);
                        tma_load_2d(sA + k * 16384, &tm_xn, k * 64, rb * 128, bar_a + 8 * k);
                    }
                }
            }
        }
    } else {
        asm volatile("setmaxnreg.inc.sync.aligned.u32 232;");
        const int wg = __shfl_sync(0xffffffffu, (int)(threadIdx.x >> 7), 0);
        float r[160];
        const int row0 = rb * 128 + wg * 64 + (warp & 3) * 16;
        const uint64_t descA = make_desc(sA + wg * 8192, 16, 1024);
        const uint64_t descB = make_desc(sB, 2048, 512, 2);
        const uint32_t stg = sStg + warp * 1024;
        const uint32_t st_off = (uint32_t)(((lane & 7) + ((lane >> 3) & 1) * 8) * 32 + (lane >> 4) * 16);
        __nv_bfloat16* hrow = g_h + (size_t)(row0 + (lane >> 1)) * F_ + (lane & 1) * 8 + cj * 224;
#pragma unroll
        for (int kb = 0; kb < 16; kb++) {
            const int it = kb, s = it % G1_STAGES;
            if ((kb & 1) == 0) mbar_wait(bar_a + 8 * (kb >> 1), 0);
            mbar_wait(bar_full + 8 * s, (it / G1_STAGES) & 1);
            if (threadIdx.x == 0 && (it & 7) == 0) STAMP(2, 2 + it / 8);
            wgmma_fence();
            const uint64_t da = descA + (uint64_t)(((kb >> 1) * 16384 + (kb & 1) * 64) >> 4);
            const uint64_t db = descB + (uint64_t)((s * G1_B_STAGE) >> 4);
            wgmma_n256_k32(r, da, da + 2, db, db + 64, kb != 0);
            wgmma_commit();
            if (kb > 0) {
                wgmma_wait<1>();
                if (lane == 0) mbar_arrive(bar_empty + 8 * ((it - 1) % G1_STAGES));
            }
        }
        wgmma_wait<0>();
        if (lane == 0) mbar_arrive(bar_empty + 8 * (15 % G1_STAGES));
#pragma unroll
        for (int i = 0; i < 32; i++) r[128 + i] = __uint_as_float(pack_bf16(r[2 * i], r[2 * i + 1]));
#pragma unroll
        for (int i = 31; i >= 0; i--) r[96 + i] = __uint_as_float(pack_bf16(r[64 + 2 * i], r[65 + 2 * i]));
        uint32_t eo[4];
        uint4 pv = make_uint4(0, 0, 0, 0);
#pragma unroll
        for (int kb = 0; kb < 16; kb++) {
            const int it = 16 + kb, s = it % G1_STAGES;
            mbar_wait(bar_full + 8 * s, (it / G1_STAGES) & 1);
            if (threadIdx.x == 0 && (it & 7) == 0) STAMP(2, 2 + it / 8);
            wgmma_fence();
            const uint64_t da = descA + (uint64_t)(((kb >> 1) * 16384 + (kb & 1) * 64) >> 4);
            const uint64_t db = descB + (uint64_t)((s * G1_B_STAGE) >> 4);
            const int jj = kb >> 1;
            wgmma_n192(r, da, db, kb != 0);
            eo[(kb & 1) * 2] = geglu_pair(__float_as_uint(r[128 + 2 * kb]), __float_as_uint(r[96 + 2 * kb]));
            wgmma_n192(r, da + 2, db + 64, 1);
            wgmma_commit();
            eo[(kb & 1) * 2 + 1] = geglu_pair(__float_as_uint(r[129 + 2 * kb]), __float_as_uint(r[97 + 2 * kb]));
            if (kb & 1) {
                if (jj > 0) *reinterpret_cast<uint4*>(hrow + (jj - 1) * 16) = pv;
                stmatrix_x4(stg + (jj & 1) * 512 + st_off, eo[0], eo[1], eo[2], eo[3]);
            } else if (jj > 0) {
                __syncwarp();
                asm volatile("ld.shared.v4.u32 {%0,%1,%2,%3}, [%4];" : "=r"(pv.x), "=r"(pv.y), "=r"(pv.z), "=r"(pv.w)
                             : "r"(stg + ((jj - 1) & 1) * 512 + lane * 16));
            }
            if (kb > 0 && it - 1 + G1_STAGES < G1_ITERS) {
                wgmma_wait<1>();
                if (lane == 0) mbar_arrive(bar_empty + 8 * ((it - 1) % G1_STAGES));
            }
        }
        __syncwarp();
        asm volatile("ld.shared.v4.u32 {%0,%1,%2,%3}, [%4];" : "=r"(pv.x), "=r"(pv.y), "=r"(pv.z), "=r"(pv.w) : "r"(stg + 512 + lane * 16));
        wgmma_wait<0>();
        *reinterpret_cast<uint4*>(hrow + 7 * 16) = pv;
        if (threadIdx.x == 0) STAMP(2, 6);
        {
            uint32_t o[24];
#pragma unroll
            for (int i = 0; i < 24; i++) o[i] = geglu_pair(pack_bf16(r[2 * i], r[2 * i + 1]), pack_bf16(r[48 + 2 * i], r[49 + 2 * i]));
            named_bar(1 + wg, 128);
            const uint32_t fbuf = sA + ((warp & 3) >> 1) * 16384 + wg * 8192 + (warp & 1) * 4096;
#pragma unroll
            for (int jj = 0; jj < 6; jj++) stmatrix_x4(fbuf + jj * 512 + st_off, o[4 * jj], o[4 * jj + 1], o[4 * jj + 2], o[4 * jj + 3]);
            __syncwarp();
            uint4 v[6];
#pragma unroll
            for (int jj = 0; jj < 6; jj++)
                asm volatile("ld.shared.v4.u32 {%0,%1,%2,%3}, [%4];" : "=r"(v[jj].x), "=r"(v[jj].y), "=r"(v[jj].z), "=r"(v[jj].w)
                             : "r"(fbuf + jj * 512 + lane * 16));
#pragma unroll
            for (int jj = 0; jj < 6; jj++) *reinterpret_cast<uint4*>(hrow + 128 + jj * 16) = v[jj];
        }
        if (threadIdx.x == 0) STAMP(2, 7);
    }
}

constexpr int G2_STAGES = 5;
constexpr int G2_STAGE = 16384 + 16384;
constexpr int G2_XCH = 32768;
constexpr int G2_EPI = 16384 + 16384;
constexpr int G2_SMEM = G2_STAGES * G2_STAGE + G2_XCH + G2_EPI + 1024 + 256;
constexpr int G2_KB = F_ / 64 / 2;

__global__ void __launch_bounds__(384, 1) gemm2_kernel(const __grid_constant__ CUtensorMap tm_h,
                                                        const __grid_constant__ CUtensorMap tm_wd,
                                                        const __grid_constant__ CUtensorMap tm_x,
                                                        const __grid_constant__ CUtensorMap tm_sT,
                                                        const __grid_constant__ CUtensorMap tm_out) {
    if (threadIdx.x == 0) STAMP(3, 0);
    extern __shared__ uint8_t smem_raw[];
    const uint32_t sbase = (smem_u32(smem_raw) + 1023) & ~1023u;
    const uint32_t sXch = sbase + G2_STAGES * G2_STAGE, sX = sXch + G2_XCH, sS = sX + 16384, sBar = sX + G2_EPI;
    const uint32_t bar_full = sBar, bar_empty = sBar + 8 * G2_STAGES, bar_epi = sBar + 16 * G2_STAGES, bar_xch = bar_epi + 8;
    const uint32_t kh = cluster_rank();
    const int cid = blockIdx.x >> 1;
    const int rb = cid >> 2, nb = cid & 3;
    const int col_fin = nb * 128 + kh * 64;
    const int warp = threadIdx.x >> 5, lane = threadIdx.x & 31;

    if (threadIdx.x == 0) {
        for (int i = 0; i < G2_STAGES; i++) { mbar_init(bar_full + 8 * i, 1); mbar_init(bar_empty + 8 * i, 8); }
        mbar_init(bar_epi, 1);
        mbar_init(bar_xch, 1);
        asm volatile("fence.mbarrier_init.release.cluster;" ::: "memory");
        mbar_expect_tx(bar_xch, G2_XCH);
    }
    cluster_sync_all();

    if (warp >= 8) {
        if (lane == 0) {
            const int pw = warp - 8;
            const int k0 = kh * G2_KB;
            if (pw == 0) { prefetch_tmap(&tm_wd); prefetch_tmap(&tm_h); }
            if (pw == 1) { prefetch_tmap(&tm_x); prefetch_tmap(&tm_sT); prefetch_tmap(&tm_out); }
            for (int it = pw; it < G2_STAGES; it += 4) {
                mbar_expect_tx(bar_full + 8 * it, G2_STAGE);
                tma_load_3d(sbase + it * G2_STAGE + 16384, &tm_wd, 0, (k0 + it) * 64, nb * 2, bar_full + 8 * it);
            }
            if (pw == 3) {
                mbar_expect_tx(bar_epi, G2_EPI);
                tma_load_2d(sX, &tm_x, col_fin, rb * 128, bar_epi);
            }
            pdl_wait();
            if (pw == 0) STAMP(3, 1);
            for (int it = pw; it < G2_STAGES; it += 4)
                tma_load_2d(sbase + it * G2_STAGE, &tm_h, (k0 + it) * 64, rb * 128, bar_full + 8 * it);
            if (pw == 3) {
                tma_load_2d(sS, &tm_sT, rb * 128, col_fin, bar_epi);
                tma_load_2d(sS + 8192, &tm_sT, rb * 128 + 64, col_fin, bar_epi);
            }
            for (int it = G2_STAGES + ((pw + 4 - (G2_STAGES & 3)) & 3); it < G2_KB; it += 4) {
                const int s = it % G2_STAGES;
                mbar_wait(bar_empty + 8 * s, ((it / G2_STAGES) - 1) & 1);
                mbar_expect_tx(bar_full + 8 * s, G2_STAGE);
                tma_load_2d(sbase + s * G2_STAGE, &tm_h, (k0 + it) * 64, rb * 128, bar_full + 8 * s);
                tma_load_3d(sbase + s * G2_STAGE + 16384, &tm_wd, 0, (k0 + it) * 64, nb * 2, bar_full + 8 * s);
            }
        }
    } else {
        const int wg = __shfl_sync(0xffffffffu, (int)(threadIdx.x >> 7), 0);
        const int g = lane >> 2, t = lane & 3;
        float acc[64];
        const uint64_t descA = make_desc(sbase + wg * 8192, 16, 1024);
        const uint64_t descB = make_desc(sbase + 16384, 8192, 1024);
#pragma unroll
        for (int it = 0; it < G2_KB; it++) {
            const int s = it % G2_STAGES;
            mbar_wait(bar_full + 8 * s, (it / G2_STAGES) & 1);
            if (threadIdx.x == 0 && (it == 0 || it == 7)) STAMP(3, 2 + it / 7);
            wgmma_fence();
            {
                const uint64_t da = descA + (uint64_t)((s * G2_STAGE) >> 4);
                const uint64_t db = descB + (uint64_t)((s * G2_STAGE) >> 4);
                wgmma_n128_k64(acc, da, da + 2, da + 4, da + 6, db, db + 128, db + 256, db + 384, it != 0);
            }
            wgmma_commit();
            if (it > 0 && it - 1 + G2_STAGES < G2_KB) {
                wgmma_wait<1>();
                if (lane == 0) mbar_arrive(bar_empty + 8 * ((it - 1) % G2_STAGES));
            }
        }
        const int lr = wg * 64 + (warp & 3) * 16 + g;
        uint32_t xv[16], sv[16];
        mbar_wait(bar_epi, 0);
#pragma unroll
        for (int j = 0; j < 8; j++) {
#pragma unroll
            for (int hh = 0; hh < 2; hh++) {
                const int r = lr + 8 * hh;
                asm volatile("ld.shared.u32 %0, [%1];" : "=r"(xv[2 * j + hh]) : "r"(sX + r * 128 + ((j ^ (r & 7)) << 4) + 4 * t));
                const int c0 = 8 * j + 2 * t;
                const uint32_t sa = sS + (r >> 6) * 8192 + (((r & 63) >> 3) << 4) + (r & 7) * 2;
                uint16_t s0r, s1r;
                asm volatile("ld.shared.u16 %0, [%1];" : "=h"(s0r) : "r"((sa + c0 * 128) ^ ((c0 & 7) << 4)));
                asm volatile("ld.shared.u16 %0, [%1];" : "=h"(s1r) : "r"((sa + (c0 + 1) * 128) ^ (((c0 + 1) & 7) << 4)));
                sv[2 * j + hh] = (uint32_t)s0r | ((uint32_t)s1r << 16);
            }
        }
        wgmma_wait<0>();
        if (threadIdx.x == 0) STAMP(3, 4);
        {
            uint32_t remote, rbar;
            asm volatile("mapa.shared::cluster.u32 %0, %1, %2;" : "=r"(remote) : "r"(sXch + threadIdx.x * 16), "r"(kh ^ 1));
            asm volatile("mapa.shared::cluster.u32 %0, %1, %2;" : "=r"(rbar) : "r"(bar_xch), "r"(kh ^ 1));
            if (kh == 0) {
#pragma unroll
                for (int i = 0; i < 8; i++)
                    asm volatile("st.async.shared::cluster.mbarrier::complete_tx::bytes.v4.f32 [%0], {%1,%2,%3,%4}, [%5];" ::"r"(remote + i * 4096),
                                 "f"(acc[32 + 4 * i]), "f"(acc[33 + 4 * i]), "f"(acc[34 + 4 * i]), "f"(acc[35 + 4 * i]), "r"(rbar) : "memory");
            } else {
#pragma unroll
                for (int i = 0; i < 8; i++)
                    asm volatile("st.async.shared::cluster.mbarrier::complete_tx::bytes.v4.f32 [%0], {%1,%2,%3,%4}, [%5];" ::"r"(remote + i * 4096),
                                 "f"(acc[4 * i]), "f"(acc[1 + 4 * i]), "f"(acc[2 + 4 * i]), "f"(acc[3 + 4 * i]), "r"(rbar) : "memory");
#pragma unroll
                for (int i = 0; i < 32; i++) acc[i] = acc[32 + i];
            }
        }
        if (threadIdx.x == 0) STAMP(3, 6);
        mbar_wait(bar_xch, 0);
        if (threadIdx.x == 0) STAMP(3, 7);
#pragma unroll
        for (int j = 0; j < 8; j++) {
            float4 o;
            asm volatile("ld.shared.v4.f32 {%0,%1,%2,%3}, [%4];" : "=f"(o.x), "=f"(o.y), "=f"(o.z), "=f"(o.w) : "r"(sXch + threadIdx.x * 16 + j * 4096));
            acc[4 * j] += o.x; acc[4 * j + 1] += o.y; acc[4 * j + 2] += o.z; acc[4 * j + 3] += o.w;
        }
#pragma unroll
        for (int i = 0; i < 16; i++) {
            float f0 = bf16_round(acc[2 * i]), f1 = bf16_round(acc[2 * i + 1]);
            float g0 = bf16_round(__fdividef(f0, 1.0f + __expf(-f0)));
            float g1 = bf16_round(__fdividef(f1, 1.0f + __expf(-f1)));
            float o0 = bf_lo(xv[i]) + bf16_round(bf_lo(sv[i]) * g0);
            float o1 = bf_hi(xv[i]) + bf16_round(bf_hi(sv[i]) * g1);
            xv[i] = pack_bf16(o0, o1);
        }
#pragma unroll
        for (int j = 0; j < 8; j++) {
#pragma unroll
            for (int hh = 0; hh < 2; hh++) {
                const int r = lr + 8 * hh;
                asm volatile("st.shared.u32 [%0], %1;" ::"r"(sX + r * 128 + ((j ^ (r & 7)) << 4) + 4 * t), "r"(xv[2 * j + hh]) : "memory");
            }
        }
        if (threadIdx.x == 0) STAMP(3, 9);
        fence_async_smem();
        __syncwarp();
        if (lane == 0) {
            tma_store_2d(&tm_out, sX + (wg * 64 + (warp & 3) * 16) * 128, col_fin, rb * 128 + wg * 64 + (warp & 3) * 16);
            bulk_commit();
            bulk_wait_read<0>();
        }
        if (threadIdx.x == 0) STAMP(3, 5);
    }
}

typedef CUresult (*EncodeFn)(CUtensorMap*, CUtensorMapDataType, cuuint32_t, void*, const cuuint64_t*, const cuuint64_t*,
                             const cuuint32_t*, const cuuint32_t*, CUtensorMapInterleave, CUtensorMapSwizzle,
                             CUtensorMapL2promotion, CUtensorMapFloatOOBfill);

void make_map(EncodeFn fn, CUtensorMap* m, const void* ptr, uint64_t inner, uint64_t outer, uint32_t box_in, uint32_t box_out,
              CUtensorMapSwizzle swz = CU_TENSOR_MAP_SWIZZLE_128B) {
    cuuint64_t dims[2] = {inner, outer};
    cuuint64_t strides[1] = {inner * 2};
    cuuint32_t box[2] = {box_in, box_out};
    cuuint32_t es[2] = {1, 1};
    fn(m, CU_TENSOR_MAP_DATA_TYPE_BFLOAT16, 2, const_cast<void*>(ptr), dims, strides, box, es, CU_TENSOR_MAP_INTERLEAVE_NONE,
       swz, CU_TENSOR_MAP_L2_PROMOTION_L2_256B, CU_TENSOR_MAP_FLOAT_OOB_FILL_NONE);
}
void make_map3(EncodeFn fn, CUtensorMap* m, const void* ptr, uint64_t cols, uint64_t rows, uint32_t atom, uint32_t box_rows,
               uint32_t box_atoms, CUtensorMapSwizzle swz) {
    cuuint64_t dims[3] = {atom, rows, cols / atom};
    cuuint64_t strides[2] = {cols * 2, (cuuint64_t)atom * 2};
    cuuint32_t box[3] = {atom, box_rows, box_atoms};
    cuuint32_t es[3] = {1, 1, 1};
    fn(m, CU_TENSOR_MAP_DATA_TYPE_BFLOAT16, 3, const_cast<void*>(ptr), dims, strides, box, es, CU_TENSOR_MAP_INTERLEAVE_NONE,
       swz, CU_TENSOR_MAP_L2_PROMOTION_L2_256B, CU_TENSOR_MAP_FLOAT_OOB_FILL_NONE);
}

template <typename... Args>
void launch_pdl(void (*kern)(Args...), int grid, int block, int smem, bool pdl, int cluster, Args... args) {
    cudaLaunchConfig_t cfg = {};
    cfg.gridDim = dim3(grid); cfg.blockDim = dim3(block); cfg.dynamicSmemBytes = smem; cfg.stream = cudaStreamPerThread;
    cudaLaunchAttribute at[2];
    int n = 0;
    if (pdl) {
        at[n].id = cudaLaunchAttributeProgrammaticStreamSerialization;
        at[n].val.programmaticStreamSerializationAllowed = 1;
        n++;
    }
    if (cluster > 1) {
        at[n].id = cudaLaunchAttributeClusterDimension;
        at[n].val.clusterDim.x = cluster; at[n].val.clusterDim.y = 1; at[n].val.clusterDim.z = 1;
        n++;
    }
    cfg.attrs = at; cfg.numAttrs = n;
    cudaLaunchKernelEx(&cfg, kern, args...);
}

}

extern "C" void kernel_launch(void* const* d_in, const int* in_sizes, int n_in, void* d_out, int out_size) {
    const __nv_bfloat16* x = (const __nv_bfloat16*)d_in[0];
    const __nv_bfloat16* A_re = (const __nv_bfloat16*)d_in[1];
    const __nv_bfloat16* A_im = (const __nv_bfloat16*)d_in[2];
    const __nv_bfloat16* B_re = (const __nv_bfloat16*)d_in[3];
    const __nv_bfloat16* B_im = (const __nv_bfloat16*)d_in[4];
    const __nv_bfloat16* C_re = (const __nv_bfloat16*)d_in[5];
    const __nv_bfloat16* C_im = (const __nv_bfloat16*)d_in[6];
    const __nv_bfloat16* log_dt = (const __nv_bfloat16*)d_in[7];
    const __nv_bfloat16* Dskip = (const __nv_bfloat16*)d_in[8];
    const __nv_bfloat16* wg = (const __nv_bfloat16*)d_in[10];
    const __nv_bfloat16* wu = (const __nv_bfloat16*)d_in[11];
    const __nv_bfloat16* wd = (const __nv_bfloat16*)d_in[12];
    __nv_bfloat16* out = (__nv_bfloat16*)d_out;

    static bool init = false;
    static CUtensorMap tm_xn, tm_wg4, tm_wu4, tm_wg3, tm_wu3, tm_hst, tm_hst96, tm_h, tm_wd, tm_x, tm_sT, tm_out;
    static const void* last_ptrs[5] = {nullptr, nullptr, nullptr, nullptr, nullptr};
    if (!init || last_ptrs[0] != wg || last_ptrs[1] != wu || last_ptrs[2] != wd || last_ptrs[3] != x || last_ptrs[4] != out) {
        void* fnp = nullptr;
        cudaDriverEntryPointQueryResult qres;
        cudaGetDriverEntryPoint("cuTensorMapEncodeTiled", &fnp, cudaEnableDefault, &qres);
        EncodeFn fn = (EncodeFn)fnp;
        void *p_xn, *p_h, *p_sT;
        cudaGetSymbolAddress(&p_xn, g_xn);
        cudaGetSymbolAddress(&p_h, g_h);
        cudaGetSymbolAddress(&p_sT, g_sT);
        make_map(fn, &tm_xn, p_xn, D_, L_, 64, 128);
        make_map3(fn, &tm_wg4, wg, F_, D_, 32, 32, 4, CU_TENSOR_MAP_SWIZZLE_64B);
        make_map3(fn, &tm_wu4, wu, F_, D_, 32, 32, 4, CU_TENSOR_MAP_SWIZZLE_64B);
        make_map3(fn, &tm_wg3, wg, F_, D_, 32, 32, 3, CU_TENSOR_MAP_SWIZZLE_64B);
        make_map3(fn, &tm_wu3, wu, F_, D_, 32, 32, 3, CU_TENSOR_MAP_SWIZZLE_64B);
        make_map(fn, &tm_hst, p_h, F_, L_, 16, 16, CU_TENSOR_MAP_SWIZZLE_NONE);
        make_map(fn, &tm_hst96, p_h, F_, L_, 96, 16, CU_TENSOR_MAP_SWIZZLE_NONE);
        make_map(fn, &tm_h, p_h, F_, L_, 64, 128);
        make_map3(fn, &tm_wd, wd, D_, F_, 64, 64, 2, CU_TENSOR_MAP_SWIZZLE_128B);
        make_map(fn, &tm_x, x, D_, L_, 64, 128);
        make_map(fn, &tm_sT, p_sT, L_, D_, 64, 64);
        make_map(fn, &tm_out, out, D_, L_, 64, 16);
        cudaFuncSetAttribute(ln_kernel, cudaFuncAttributePreferredSharedMemoryCarveout, 100);
        cudaFuncSetAttribute(conv_kernel, cudaFuncAttributeMaxDynamicSharedMemorySize, CV_SMEM);
        cudaFuncSetAttribute(conv_kernel, cudaFuncAttributePreferredSharedMemoryCarveout, 100);
        cudaFuncSetAttribute(gemm1_kernel, cudaFuncAttributeMaxDynamicSharedMemorySize, G1_SMEM);
        cudaFuncSetAttribute(gemm2_kernel, cudaFuncAttributeMaxDynamicSharedMemorySize, G2_SMEM);
        last_ptrs[0] = wg; last_ptrs[1] = wu; last_ptrs[2] = wd; last_ptrs[3] = x; last_ptrs[4] = out;
        init = true;
    }
    launch_pdl(ln_kernel, L_ / LN_ROWS, 256, 0, false, 1, x, wg, wu, wd);
    launch_pdl(conv_kernel, D_ / CV_CH, 256, CV_SMEM, true, 1, A_re, A_im, B_re, B_im, C_re, C_im, log_dt, Dskip);
    launch_pdl(gemm1_kernel, 128, 384, G1_SMEM, true, 1, tm_xn, tm_wg4, tm_wu4, tm_wg3, tm_wu3, tm_hst, tm_hst96);
    launch_pdl(gemm2_kernel, 128, 384, G2_SMEM, true, 2, tm_h, tm_wd, tm_x, tm_sT, tm_out);
}
```

```cpp
#include <cuda_runtime.h>
#include <cuda_bf16.h>
#include <cuda.h>
#include <stdint.h>

namespace {

constexpr int L_ = 2048, D_ = 512, NS_ = 128, F_ = 1792;

__device__ __align__(1024) __nv_bfloat16 g_xn[L_ * D_];
__device__ __align__(1024) __nv_bfloat16 g_xnT[D_ * L_];
__device__ __align__(1024) __nv_bfloat16 g_sT[D_ * L_];
__device__ __align__(1024) __nv_bfloat16 g_h[L_ * F_];

#define STAMP(k, i)

__device__ __forceinline__ uint32_t smem_u32(const void* p) { return (uint32_t)__cvta_generic_to_shared(p); }
__device__ __forceinline__ void pdl_wait() { asm volatile("griddepcontrol.wait;" ::: "memory"); }
__device__ __forceinline__ void pdl_launch() { asm volatile("griddepcontrol.launch_dependents;" ::: "memory"); }

__device__ __forceinline__ void mbar_init(uint32_t bar, uint32_t cnt) {
    asm volatile("mbarrier.init.shared::cta.b64 [%0], %1;" ::"r"(bar), "r"(cnt) : "memory");
}
__device__ __forceinline__ void mbar_expect_tx(uint32_t bar, uint32_t bytes) {
    asm volatile("mbarrier.arrive.expect_tx.shared::cta.b64 _, [%0], %1;" ::"r"(bar), "r"(bytes) : "memory");
}
__device__ __forceinline__ void mbar_arrive(uint32_t bar) {
    asm volatile("mbarrier.arrive.shared::cta.b64 _, [%0];" ::"r"(bar) : "memory");
}
__device__ __forceinline__ void mbar_wait(uint32_t bar, uint32_t parity) {
    asm volatile(
        "{\n.reg .pred p;\n"
        "WAIT_LOOP:\n"
        "mbarrier.try_wait.parity.shared::cta.b64 p, [%0], %1;\n"
        "@p bra WAIT_DONE;\n"
        "bra WAIT_LOOP;\n"
        "WAIT_DONE:\n}\n" ::"r"(bar), "r"(parity) : "memory");
}
__device__ __forceinline__ void tma_load_2d(uint32_t dst, const CUtensorMap* tm, int c0, int c1, uint32_t bar) {
    asm volatile(
        "cp.async.bulk.tensor.2d.shared::cluster.global.mbarrier::complete_tx::bytes [%0], [%1, {%3, %4}], [%2];"
        ::"r"(dst), "l"((uint64_t)tm), "r"(bar), "r"(c0), "r"(c1) : "memory");
}
__device__ __forceinline__ void prefetch_tmap(const CUtensorMap* tm) {
    asm volatile("prefetch.tensormap [%0];" ::"l"((uint64_t)tm) : "memory");
}
__device__ __forceinline__ uint64_t make_desc(uint32_t addr, uint32_t lbo, uint32_t sbo, uint64_t mode = 1) {
    uint64_t d = 0;
    d |= (uint64_t)((addr & 0x3FFFF) >> 4);
    d |= (uint64_t)((lbo >> 4) & 0x3FFF) << 16;
    d |= (uint64_t)((sbo >> 4) & 0x3FFF) << 32;
    d |= mode << 62;
    return d;
}
__device__ __forceinline__ void wgmma_fence() { asm volatile("wgmma.fence.sync.aligned;" ::: "memory"); }
__device__ __forceinline__ void wgmma_commit() { asm volatile("wgmma.commit_group.sync.aligned;" ::: "memory"); }
template <int N> __device__ __forceinline__ void wgmma_wait() {
    asm volatile("wgmma.wait_group.sync.aligned %0;" ::"n"(N) : "memory");
}

#define R8(a, i) "+f"(a[i + 0]), "+f"(a[i + 1]), "+f"(a[i + 2]), "+f"(a[i + 3]), "+f"(a[i + 4]), "+f"(a[i + 5]), "+f"(a[i + 6]), "+f"(a[i + 7])

__device__ __forceinline__ void wgmma_n256_k32(float* a, uint64_t da0, uint64_t da1, uint64_t db0, uint64_t db1, int scale_d) {
    asm volatile(
        "{\n.reg .pred p;\nsetp.ne.b32 p, %132, 0;\n"
        "wgmma.mma_async.sync.aligned.m64n256k16.f32.bf16.bf16 {%0,%1,%2,%3,%4,%5,%6,%7,%8,%9,%10,%11,%12,%13,%14,%15,%16,%17,%18,%19,%20,%21,%22,%23,%24,%25,%26,%27,%28,%29,%30,%31,%32,%33,%34,%35,%36,%37,%38,%39,%40,%41,%42,%43,%44,%45,%46,%47,%48,%49,%50,%51,%52,%53,%54,%55,%56,%57,%58,%59,%60,%61,%62,%63,%64,%65,%66,%67,%68,%69,%70,%71,%72,%73,%74,%75,%76,%77,%78,%79,%80,%81,%82,%83,%84,%85,%86,%87,%88,%89,%90,%91,%92,%93,%94,%95,%96,%97,%98,%99,%100,%101,%102,%103,%104,%105,%106,%107,%108,%109,%110,%111,%112,%113,%114,%115,%116,%117,%118,%119,%120,%121,%122,%123,%124,%125,%126,%127}, %128, %130, p, 1, 1, 0, 1;\n"
        "wgmma.mma_async.sync.aligned.m64n256k16.f32.bf16.bf16 {%0,%1,%2,%3,%4,%5,%6,%7,%8,%9,%10,%11,%12,%13,%14,%15,%16,%17,%18,%19,%20,%21,%22,%23,%24,%25,%26,%27,%28,%29,%30,%31,%32,%33,%34,%35,%36,%37,%38,%39,%40,%41,%42,%43,%44,%45,%46,%47,%48,%49,%50,%51,%52,%53,%54,%55,%56,%57,%58,%59,%60,%61,%62,%63,%64,%65,%66,%67,%68,%69,%70,%71,%72,%73,%74,%75,%76,%77,%78,%79,%80,%81,%82,%83,%84,%85,%86,%87,%88,%89,%90,%91,%92,%93,%94,%95,%96,%97,%98,%99,%100,%101,%102,%103,%104,%105,%106,%107,%108,%109,%110,%111,%112,%113,%114,%115,%116,%117,%118,%119,%120,%121,%122,%123,%124,%125,%126,%127}, %129, %131, 1, 1, 1, 0, 1;\n"
        "}\n"
        : R8(a, 0), R8(a, 8), R8(a, 16), R8(a, 24), R8(a, 32), R8(a, 40), R8(a, 48), R8(a, 56), R8(a, 64), R8(a, 72), R8(a, 80), R8(a, 88), R8(a, 96), R8(a, 104), R8(a, 112), R8(a, 120)
        : "l"(da0), "l"(da1), "l"(db0), "l"(db1), "r"(scale_d));
}
__device__ __forceinline__ void wgmma_n192_k32(float* a, uint64_t da0, uint64_t da1, uint64_t db0, uint64_t db1, int scale_d) {
    asm volatile(
        "{\n.reg .pred p;\nsetp.ne.b32 p, %100, 0;\n"
        "wgmma.mma_async.sync.aligned.m64n192k16.f32.bf16.bf16 {%0,%1,%2,%3,%4,%5,%6,%7,%8,%9,%10,%11,%12,%13,%14,%15,%16,%17,%18,%19,%20,%21,%22,%23,%24,%25,%26,%27,%28,%29,%30,%31,%32,%33,%34,%35,%36,%37,%38,%39,%40,%41,%42,%43,%44,%45,%46,%47,%48,%49,%50,%51,%52,%53,%54,%55,%56,%57,%58,%59,%60,%61,%62,%63,%64,%65,%66,%67,%68,%69,%70,%71,%72,%73,%74,%75,%76,%77,%78,%79,%80,%81,%82,%83,%84,%85,%86,%87,%88,%89,%90,%91,%92,%93,%94,%95}, %96, %98, p, 1, 1, 0, 1;\n"
        "wgmma.mma_async.sync.aligned.m64n192k16.f32.bf16.bf16 {%0,%1,%2,%3,%4,%5,%6,%7,%8,%9,%10,%11,%12,%13,%14,%15,%16,%17,%18,%19,%20,%21,%22,%23,%24,%25,%26,%27,%28,%29,%30,%31,%32,%33,%34,%35,%36,%37,%38,%39,%40,%41,%42,%43,%44,%45,%46,%47,%48,%49,%50,%51,%52,%53,%54,%55,%56,%57,%58,%59,%60,%61,%62,%63,%64,%65,%66,%67,%68,%69,%70,%71,%72,%73,%74,%75,%76,%77,%78,%79,%80,%81,%82,%83,%84,%85,%86,%87,%88,%89,%90,%91,%92,%93,%94,%95}, %97, %99, 1, 1, 1, 0, 1;\n"
        "}\n"
        : R8(a, 0), R8(a, 8), R8(a, 16), R8(a, 24), R8(a, 32), R8(a, 40), R8(a, 48), R8(a, 56), R8(a, 64), R8(a, 72), R8(a, 80), R8(a, 88)
        : "l"(da0), "l"(da1), "l"(db0), "l"(db1), "r"(scale_d));
}
__device__ __forceinline__ void wgmma_n192(float* a, uint64_t da0, uint64_t db0, int scale_d) {
    asm volatile(
        "{\n.reg .pred p;\nsetp.ne.b32 p, %98, 0;\n"
        "wgmma.mma_async.sync.aligned.m64n192k16.f32.bf16.bf16 {%0,%1,%2,%3,%4,%5,%6,%7,%8,%9,%10,%11,%12,%13,%14,%15,%16,%17,%18,%19,%20,%21,%22,%23,%24,%25,%26,%27,%28,%29,%30,%31,%32,%33,%34,%35,%36,%37,%38,%39,%40,%41,%42,%43,%44,%45,%46,%47,%48,%49,%50,%51,%52,%53,%54,%55,%56,%57,%58,%59,%60,%61,%62,%63,%64,%65,%66,%67,%68,%69,%70,%71,%72,%73,%74,%75,%76,%77,%78,%79,%80,%81,%82,%83,%84,%85,%86,%87,%88,%89,%90,%91,%92,%93,%94,%95}, %96, %97, p, 1, 1, 0, 1;\n"
        "}\n"
        : R8(a, 0), R8(a, 8), R8(a, 16), R8(a, 24), R8(a, 32), R8(a, 40), R8(a, 48), R8(a, 56), R8(a, 64), R8(a, 72), R8(a, 80), R8(a, 88)
        : "l"(da0), "l"(db0), "r"(scale_d));
}
__device__ __forceinline__ void wgmma_n128_k64(float* a, uint64_t da0, uint64_t da1, uint64_t da2, uint64_t da3,
                                               uint64_t db0, uint64_t db1, uint64_t db2, uint64_t db3, int scale_d) {
    asm volatile(
        "{\n.reg .pred p;\nsetp.ne.b32 p, %72, 0;\n"
        "wgmma.mma_async.sync.aligned.m64n128k16.f32.bf16.bf16 {%0,%1,%2,%3,%4,%5,%6,%7,%8,%9,%10,%11,%12,%13,%14,%15,%16,%17,%18,%19,%20,%21,%22,%23,%24,%25,%26,%27,%28,%29,%30,%31,%32,%33,%34,%35,%36,%37,%38,%39,%40,%41,%42,%43,%44,%45,%46,%47,%48,%49,%50,%51,%52,%53,%54,%55,%56,%57,%58,%59,%60,%61,%62,%63}, %64, %68, p, 1, 1, 0, 1;\n"
        "wgmma.mma_async.sync.aligned.m64n128k16.f32.bf16.bf16 {%0,%1,%2,%3,%4,%5,%6,%7,%8,%9,%10,%11,%12,%13,%14,%15,%16,%17,%18,%19,%20,%21,%22,%23,%24,%25,%26,%27,%28,%29,%30,%31,%32,%33,%34,%35,%36,%37,%38,%39,%40,%41,%42,%43,%44,%45,%46,%47,%48,%49,%50,%51,%52,%53,%54,%55,%56,%57,%58,%59,%60,%61,%62,%63}, %65, %69, 1, 1, 1, 0, 1;\n"
        "wgmma.mma_async.sync.aligned.m64n128k16.f32.bf16.bf16 {%0,%1,%2,%3,%4,%5,%6,%7,%8,%9,%10,%11,%12,%13,%14,%15,%16,%17,%18,%19,%20,%21,%22,%23,%24,%25,%26,%27,%28,%29,%30,%31,%32,%33,%34,%35,%36,%37,%38,%39,%40,%41,%42,%43,%44,%45,%46,%47,%48,%49,%50,%51,%52,%53,%54,%55,%56,%57,%58,%59,%60,%61,%62,%63}, %66, %70, 1, 1, 1, 0, 1;\n"
        "wgmma.mma_async.sync.aligned.m64n128k16.f32.bf16.bf16 {%0,%1,%2,%3,%4,%5,%6,%7,%8,%9,%10,%11,%12,%13,%14,%15,%16,%17,%18,%19,%20,%21,%22,%23,%24,%25,%26,%27,%28,%29,%30,%31,%32,%33,%34,%35,%36,%37,%38,%39,%40,%41,%42,%43,%44,%45,%46,%47,%48,%49,%50,%51,%52,%53,%54,%55,%56,%57,%58,%59,%60,%61,%62,%63}, %67, %71, 1, 1, 1, 0, 1;\n"
        "}\n"
        : R8(a, 0), R8(a, 8), R8(a, 16), R8(a, 24), R8(a, 32), R8(a, 40), R8(a, 48), R8(a, 56)
        : "l"(da0), "l"(da1), "l"(da2), "l"(da3), "l"(db0), "l"(db1), "l"(db2), "l"(db3), "r"(scale_d));
}

__device__ __forceinline__ float bf16_round(float x) {
    uint32_t p; asm("cvt.rn.bf16x2.f32 %0, %1, %2;" : "=r"(p) : "f"(x), "f"(0.0f));
    return __uint_as_float(p);
}
__device__ __forceinline__ uint32_t pack_bf16(float lo, float hi) {
    __nv_bfloat162 v = __floats2bfloat162_rn(lo, hi);
    return *reinterpret_cast<uint32_t*>(&v);
}
__device__ __forceinline__ float bf_lo(uint32_t v) { return __uint_as_float(v << 16); }
__device__ __forceinline__ float bf_hi(uint32_t v) { return __uint_as_float(v & 0xFFFF0000u); }

constexpr int LN_ROWS = 16;
__global__ void __launch_bounds__(256) ln_kernel(const __nv_bfloat16* __restrict__ x,
                                                  const __nv_bfloat16* __restrict__ wg,
                                                  const __nv_bfloat16* __restrict__ wu,
                                                  const __nv_bfloat16* __restrict__ wd) {
    pdl_launch();
    if (threadIdx.x == 0) STAMP(0, 0);
    __shared__ __align__(16) __nv_bfloat16 tile[LN_ROWS][D_ + 8];
    const int warp = threadIdx.x >> 5, lane = threadIdx.x & 31;
    const int row0 = blockIdx.x * LN_ROWS;
    {
        const int lines_per = (D_ * F_ * 2) / 128 / 128;
        if (threadIdx.x < lines_per) {
            size_t off = ((size_t)blockIdx.x * lines_per + threadIdx.x) * 128;
            asm volatile("prefetch.global.L2 [%0];" ::"l"((const char*)wg + off));
            asm volatile("prefetch.global.L2 [%0];" ::"l"((const char*)wu + off));
            asm volatile("prefetch.global.L2 [%0];" ::"l"((const char*)wd + off));
        }
    }
    uint4 v[2][2];
#pragma unroll
    for (int r = 0; r < 2; r++) {
        const __nv_bfloat16* xr = x + (size_t)(row0 + warp * 2 + r) * D_;
        v[r][0] = *reinterpret_cast<const uint4*>(xr + lane * 8);
        v[r][1] = *reinterpret_cast<const uint4*>(xr + 256 + lane * 8);
    }
#pragma unroll
    for (int r = 0; r < 2; r++) {
        float f[16];
        const uint32_t* w = reinterpret_cast<const uint32_t*>(&v[r][0]);
#pragma unroll
        for (int i = 0; i < 8; i++) { f[2 * i] = bf_lo(w[i]); f[2 * i + 1] = bf_hi(w[i]); }
        float s = 0.f;
#pragma unroll
        for (int i = 0; i < 16; i++) s += f[i];
#pragma unroll
        for (int o = 16; o > 0; o >>= 1) s += __shfl_xor_sync(0xffffffffu, s, o);
        const float mean = s * (1.0f / D_);
        float q = 0.f;
#pragma unroll
        for (int i = 0; i < 16; i++) { float d = f[i] - mean; q += d * d; }
#pragma unroll
        for (int o = 16; o > 0; o >>= 1) q += __shfl_xor_sync(0xffffffffu, q, o);
        const float mb = bf16_round(mean);
        const float vb = bf16_round(q * (1.0f / D_));
        const float den = bf16_round(sqrtf(bf16_round(vb + 1e-5f)));
        uint32_t o[8];
#pragma unroll
        for (int i = 0; i < 8; i++) {
            float a = __fdiv_rn(bf16_round(f[2 * i] - mb), den);
            float b = __fdiv_rn(bf16_round(f[2 * i + 1] - mb), den);
            o[i] = pack_bf16(a, b);
        }
        const int rr = warp * 2 + r;
        __nv_bfloat16* dst = g_xn + (size_t)(row0 + rr) * D_;
        *reinterpret_cast<uint4*>(dst + lane * 8) = make_uint4(o[0], o[1], o[2], o[3]);
        *reinterpret_cast<uint4*>(dst + 256 + lane * 8) = make_uint4(o[4], o[5], o[6], o[7]);
        *reinterpret_cast<uint4*>(&tile[rr][lane * 8]) = make_uint4(o[0], o[1], o[2], o[3]);
        *reinterpret_cast<uint4*>(&tile[rr][256 + lane * 8]) = make_uint4(o[4], o[5], o[6], o[7]);
    }
    __syncthreads();
    if (threadIdx.x == 0) STAMP(0, 1);
#pragma unroll
    for (int cc = 0; cc < 2; cc++) {
        const int c = threadIdx.x + cc * 256;
        uint32_t o[8];
#pragma unroll
        for (int i = 0; i < 8; i++) {
            uint32_t lo = *reinterpret_cast<const uint16_t*>(&tile[2 * i][c]);
            uint32_t hi = *reinterpret_cast<const uint16_t*>(&tile[2 * i + 1][c]);
            o[i] = lo | (hi << 16);
        }
        __nv_bfloat16* dst = g_xnT + (size_t)c * L_ + row0;
        *reinterpret_cast<uint4*>(dst) = make_uint4(o[0], o[1], o[2], o[3]);
        *reinterpret_cast<uint4*>(dst + 8) = make_uint4(o[4], o[5], o[6], o[7]);
    }
    if (threadIdx.x == 0) STAMP(0, 2);
}

struct cplx { float r, i; };
__device__ __forceinline__ cplx cmul(cplx a, cplx b) {
    cplx c; c.r = a.r * b.r - a.i * b.i; c.i = a.r * b.i + a.i * b.r; return c;
}
__device__ __forceinline__ cplx csq(cplx a) {
    cplx c; c.r = a.r * a.r - a.i * a.i; c.i = 2.0f * a.r * a.i; return c;
}
__device__ __forceinline__ cplx cexp_m(float ar2, float ai2, float m) {
    float mag;
    asm("ex2.approx.ftz.f32 %0, %1;" : "=f"(mag) : "f"(ar2 * m));
    float rr = ai2 * m;
    rr -= rintf(rr);
    float th = rr * 6.283185307179586f;
    cplx c; c.r = mag * __cosf(th); c.i = mag * __sinf(th);
    return c;
}
__device__ __forceinline__ uint32_t to_tf32(float x) { return __float_as_uint(x) + 0x1000u; }
__device__ __forceinline__ void mma_tf32(float* c, uint32_t a0, uint32_t a1, uint32_t a2, uint32_t a3, uint32_t b0, uint32_t b1) {
    asm volatile("mma.sync.aligned.m16n8k8.row.col.f32.tf32.tf32.f32 {%0,%1,%2,%3}, {%4,%5,%6,%7}, {%8,%9}, {%0,%1,%2,%3};"
                 : "+f"(c[0]), "+f"(c[1]), "+f"(c[2]), "+f"(c[3])
                 : "r"(a0), "r"(a1), "r"(a2), "r"(a3), "r"(b0), "r"(b1));
}
__device__ __forceinline__ void mma_bf16(float* c, uint32_t a0, uint32_t a1, uint32_t a2, uint32_t a3, uint32_t b0, uint32_t b1) {
    asm volatile("mma.sync.aligned.m16n8k16.row.col.f32.bf16.bf16.f32 {%0,%1,%2,%3}, {%4,%5,%6,%7}, {%8,%9}, {%0,%1,%2,%3};"
                 : "+f"(c[0]), "+f"(c[1]), "+f"(c[2]), "+f"(c[3])
                 : "r"(a0), "r"(a1), "r"(a2), "r"(a3), "r"(b0), "r"(b1));
}
__device__ __forceinline__ void named_bar(int id, int n) { asm volatile("bar.sync %0, %1;" ::"r"(id), "r"(n) : "memory"); }
__device__ __forceinline__ void ldsm_x4(uint32_t addr, uint32_t& r0, uint32_t& r1, uint32_t& r2, uint32_t& r3) {
    asm volatile("ldmatrix.sync.aligned.m8n8.x4.shared.b16 {%0,%1,%2,%3}, [%4];" : "=r"(r0), "=r"(r1), "=r"(r2), "=r"(r3) : "r"(addr));
}
__device__ __forceinline__ void ldsm_x4_t(uint32_t addr, uint32_t& r0, uint32_t& r1, uint32_t& r2, uint32_t& r3) {
    asm volatile("ldmatrix.sync.aligned.m8n8.x4.trans.shared.b16 {%0,%1,%2,%3}, [%4];" : "=r"(r0), "=r"(r1), "=r"(r2), "=r"(r3) : "r"(addr));
}

constexpr int CV_CH = 4;
constexpr int CV_O_CONST = 0;
constexpr int CV_O_KP = 12288;
constexpr int CV_O_Q = CV_O_KP + 10368;
constexpr int CV_O_Q2 = CV_O_Q + 2304;
constexpr int CV_O_Q3 = CV_O_Q2 + 1024;
constexpr int CV_O_W3 = CV_O_Q3 + 768;
constexpr int CV_O_W5 = CV_O_W3 + 3104;
constexpr int CV_O_W7 = CV_O_W5 + 3104;
constexpr int CV_O_W9 = CV_O_W7 + 2048;
constexpr int CV_O_STG = 32768;
constexpr int CV_O_U = CV_O_W9 + 2048;
constexpr int CV_PER_CH = CV_O_U + 4352;
static_assert(CV_O_U >= CV_O_STG + 4096, "staging overlaps u");
constexpr int CV_SMEM = CV_CH * CV_PER_CH;

__global__ void __launch_bounds__(512, 1) conv_kernel(const __nv_bfloat16* __restrict__ A_re, const __nv_bfloat16* __restrict__ A_im,
                                                       const __nv_bfloat16* __restrict__ B_re, const __nv_bfloat16* __restrict__ B_im,
                                                       const __nv_bfloat16* __restrict__ C_re, const __nv_bfloat16* __restrict__ C_im,
                                                       const __nv_bfloat16* __restrict__ log_dt, const __nv_bfloat16* __restrict__ Dskip) {
    pdl_launch();
    if (threadIdx.x == 0) STAMP(1, 0);
    extern __shared__ __align__(16) uint8_t smem[];
    const int warp = threadIdx.x >> 5, lane = threadIdx.x & 31;
    const int ch = warp >> 2, w = warp & 3, tc = threadIdx.x & 127;
    const int d = blockIdx.x * CV_CH + ch;
    const int g = lane >> 2, t = lane & 3;
    uint8_t* base = smem + ch * CV_PER_CH;
    float4* s_const = reinterpret_cast<float4*>(base + CV_O_CONST);
    float* s_kp = reinterpret_cast<float*>(base + CV_O_KP);
    uint32_t* s_q = reinterpret_cast<uint32_t*>(base + CV_O_Q);
    uint32_t* s_q2 = reinterpret_cast<uint32_t*>(base + CV_O_Q2);
    uint32_t* s_q3 = reinterpret_cast<uint32_t*>(base + CV_O_Q3);
    __nv_bfloat16* s_u = reinterpret_cast<__nv_bfloat16*>(base + CV_O_U);
    const int bar_id = 1 + ch;

    float tail;
    {
        const float dt = bf16_round(expf(__bfloat162float(log_dt[d])));
        const size_t off = (size_t)d * NS_ + tc;
        const float ar = dt * __bfloat162float(A_re[off]), ai = dt * __bfloat162float(A_im[off]);
        const cplx db = {dt * __bfloat162float(B_re[off]), dt * __bfloat162float(B_im[off])};
        const cplx cc = {__bfloat162float(C_re[off]), __bfloat162float(C_im[off])};
        const cplx cb = cmul(cc, db);
        const float ar2 = ar * 1.4426950408889634f, ai2 = ai * 0.15915494309189535f;
        const cplx e8 = cexp_m(ar2, ai2, 8.f), e128 = cexp_m(ar2, ai2, 128.f);
        const cplx cb8 = cmul(cb, e8);
        const cplx c256 = cmul(cb, cexp_m(ar2, ai2, 256.f));
        const cplx c512 = cmul(cb, cexp_m(ar2, ai2, 512.f)), c768 = cmul(cb, cexp_m(ar2, ai2, 768.f));
        const cplx c1024 = cmul(cb, cexp_m(ar2, ai2, 1024.f)), c1280 = cmul(cb, cexp_m(ar2, ai2, 1280.f));
        const cplx c1536 = cmul(cb, cexp_m(ar2, ai2, 1536.f)), c1792 = cmul(cb, cexp_m(ar2, ai2, 1792.f));
        tail = cmul(cb, cexp_m(ar2, ai2, 2048.f)).r;
        float4* c = s_const + tc * 6;
        c[0] = make_float4(ar2, ai2, cb.r, cb.i);
        c[1] = make_float4(e128.r, e128.i, cb8.r, cb8.i);
        c[2] = make_float4(c256.r, c256.i, e8.r, e8.i);
        c[3] = make_float4(c512.r, c512.i, c768.r, c768.i);
        c[4] = make_float4(c1024.r, c1024.i, c1280.r, c1280.i);
        c[5] = make_float4(c1536.r, c1536.i, c1792.r, c1792.i);
#pragma unroll
        for (int o = 16; o > 0; o >>= 1) tail += __shfl_xor_sync(0xffffffffu, tail, o);
    }
    __syncwarp();
    if (threadIdx.x == 0) STAMP(1, 1);
    {
        float acc[5][4];
#pragma unroll
        for (int i = 0; i < 5; i++) { acc[i][0] = acc[i][1] = acc[i][2] = acc[i][3] = 0.f; }
        const float gf = (float)g, g16 = 16.f * gf, g4 = 4.f * (float)(g & 3);
#pragma unroll 2
        for (int s = 0; s < 8; s++) {
            const float4* c = s_const + (w * 32 + s * 4 + t) * 6;
            const float4 k0 = c[0], k1 = c[1], k2 = c[2];
            const float2 k3 = reinterpret_cast<const float2*>(c + 3)[g >> 2];
            const float2 k4 = reinterpret_cast<const float2*>(c + 4)[g >> 1];
            const cplx cb = {k0.z, k0.w}, e128 = {k1.x, k1.y}, cb8 = {k1.z, k1.w}, c256 = {k2.x, k2.y}, e8 = {k2.z, k2.w};
            const cplx c2 = {k3.x, k3.y}, c3 = {k4.x, k4.y};
            const cplx p1 = cexp_m(k0.x, k0.y, gf);
            const cplx r16a = cexp_m(k0.x, k0.y, g16);
            const cplx q4 = cexp_m(k0.x, k0.y, g4);
            const cplx r16b = cmul(r16a, e128);
            const cplx f0a = cmul(cb, p1), f0b = cmul(cb8, p1), f1 = cmul(c256, csq(p1)), f2 = cmul(c2, q4);
            cplx f3 = cmul(c3, e8);
            if (!(g & 1)) f3 = c3;
            const uint32_t a0 = to_tf32(r16a.r), a1 = to_tf32(r16b.r), a2 = to_tf32(-r16a.i), a3 = to_tf32(-r16b.i);
            mma_tf32(acc[0], a0, a1, a2, a3, to_tf32(f0a.r), to_tf32(f0a.i));
            mma_tf32(acc[1], a0, a1, a2, a3, to_tf32(f0b.r), to_tf32(f0b.i));
            mma_tf32(acc[2], a0, a1, a2, a3, to_tf32(f1.r), to_tf32(f1.i));
            mma_tf32(acc[3], a0, a1, a2, a3, to_tf32(f2.r), to_tf32(f2.i));
            mma_tf32(acc[4], a0, a1, a2, a3, to_tf32(f3.r), to_tf32(f3.i));
        }
        float* kv = s_kp + w * 648;
#pragma unroll
        for (int hh = 0; hh < 2; hh++) {
            const int i = g + 8 * hh;
            *reinterpret_cast<float2*>(kv + 16 * i + 2 * t) = make_float2(acc[0][2 * hh], acc[0][2 * hh + 1]);
            *reinterpret_cast<float2*>(kv + 16 * i + 8 + 2 * t) = make_float2(acc[1][2 * hh], acc[1][2 * hh + 1]);
            *reinterpret_cast<float2*>(kv + 256 + 8 * i + 2 * t) = make_float2(acc[2][2 * hh], acc[2][2 * hh + 1]);
            *reinterpret_cast<float2*>(kv + 384 + 64 * (t >> 1) + 2 * (t & 1) + 4 * i) = make_float2(acc[3][2 * hh], acc[3][2 * hh + 1]);
            *reinterpret_cast<float2*>(kv + 512 + 32 * t + 2 * i) = make_float2(acc[4][2 * hh], acc[4][2 * hh + 1]);
        }
        if (lane == 0) kv[640] = tail;
    }
    named_bar(bar_id, 128);
    if (threadIdx.x == 0) STAMP(1, 2);
#pragma unroll
    for (int i = 0; i < 6; i++) {
        const int idx = tc + 128 * i;
        if (idx < 641) s_kp[idx] = (s_kp[idx] + s_kp[648 + idx]) + (s_kp[1296 + idx] + s_kp[1944 + idx]);
    }
    named_bar(bar_id, 128);
    {
        auto kdir = [&](int l) -> float {
            if (l < 0 || l > 512) return 0.f;
            const int idx = (l < 256) ? l : 128 + ((l + ((l >> 1) & 1)) >> 1);
            return s_kp[idx];
        };
#pragma unroll
        for (int i = 0; i < 5; i++) {
            const int e = tc + 128 * i;
            if (e < 576) s_q[e] = pack_bf16(kdir(e - 16), kdir(e - 17));
        }
#pragma unroll
        for (int i = 0; i < 2; i++) {
            const int e = tc + 128 * i, a = e >> 6, ii = (e & 63) - 16;
            const int b = 385 + (a >> 1) + 2 * (a & 1);
            const float v0 = (ii >= 0 && ii < 32) ? s_kp[b + 4 * ii] : 0.f;
            const float v1 = (ii >= 1 && ii < 33) ? s_kp[b + 4 * (ii - 1)] : 0.f;
            s_q2[e] = pack_bf16(v0, v1);
        }
#pragma unroll
        for (int i = 0; i < 2; i++) {
            const int e = tc + 128 * i;
            if (e < 192) {
                const int a = e >= 96, jj = e - 96 * a - 16;
                const float v0 = (jj >= 0 && jj < 64) ? s_kp[513 + a + 2 * jj] : 0.f;
                const float v1 = (jj >= 1 && jj < 65) ? s_kp[513 + a + 2 * (jj - 1)] : 0.f;
                s_q3[e] = pack_bf16(v0, v1);
            }
        }
    }
    const float kc512 = s_kp[384], kc1024 = s_kp[512];
    if (threadIdx.x == 0) STAMP(1, 3);
    pdl_wait();
    if (threadIdx.x == 0) STAMP(1, 4);
    {
        if (tc < 16) *reinterpret_cast<uint4*>(s_u + tc * 8) = make_uint4(0, 0, 0, 0);
        const uint4* src = reinterpret_cast<const uint4*>(g_xnT + (size_t)d * L_);
        const uint4 v0 = src[tc], v1 = src[tc + 128];
        *reinterpret_cast<uint4*>(s_u + 128 + tc * 8) = v0;
        *reinterpret_cast<uint4*>(s_u + 128 + (tc + 128) * 8) = v1;
        if (tc < 2) *reinterpret_cast<uint4*>(base + (tc ? CV_O_W5 : CV_O_W3)) = make_uint4(0, 0, 0, 0);
    }
    named_bar(bar_id, 128);
#pragma unroll
    for (int rep = 0; rep < 2; rep++) {
        const int m = tc + 128 * rep;
        if (m < 192) {
            float P[30];
            const uint4* up = reinterpret_cast<const uint4*>(s_u + 128 + 8 * m - 24);
            P[0] = 0.f;
#pragma unroll
            for (int c4 = 0; c4 < 4; c4++) {
                const uint4 v = up[c4];
                const uint32_t ww[4] = {v.x, v.y, v.z, v.w};
#pragma unroll
                for (int j = 0; j < 4; j++) {
                    const int k = c4 * 8 + 2 * j;
                    if (k + 1 <= 29) P[k + 1] = P[k] + bf_lo(ww[j]);
                    if (k + 2 <= 29) P[k + 2] = P[k + 1] + bf_hi(ww[j]);
                }
            }
            uint32_t o3[4], o5[4], o7[4], o9[4];
#pragma unroll
            for (int j = 0; j < 4; j++) {
                const int i = 2 * j;
                o3[j] = pack_bf16(P[i + 22] - P[i + 19], P[i + 23] - P[i + 20]);
                o5[j] = pack_bf16(P[i + 19] - P[i + 14], P[i + 20] - P[i + 15]);
                o7[j] = pack_bf16(P[i + 20] - P[i + 13], P[i + 21] - P[i + 14]);
                o9[j] = pack_bf16(P[i + 13] - P[i + 4], P[i + 14] - P[i + 5]);
            }
            *reinterpret_cast<uint4*>(base + CV_O_W3 + 16 + m * 16) = make_uint4(o3[0], o3[1], o3[2], o3[3]);
            *reinterpret_cast<uint4*>(base + CV_O_W5 + 16 + m * 16) = make_uint4(o5[0], o5[1], o5[2], o5[3]);
            if (m < 128) {
                *reinterpret_cast<uint4*>(base + CV_O_W7 + m * 16) = make_uint4(o7[0], o7[1], o7[2], o7[3]);
                *reinterpret_cast<uint4*>(base + CV_O_W9 + m * 16) = make_uint4(o9[0], o9[1], o9[2], o9[3]);
            }
        }
    }
    if (threadIdx.x == 0) STAMP(1, 5);
    float acc[16][4];
#pragma unroll
    for (int i = 0; i < 16; i++) { acc[i][0] = acc[i][1] = acc[i][2] = acc[i][3] = 0.f; }
    const uint32_t sb_addr = smem_u32(base);
    const int mi = lane >> 3, rowi = lane & 7;
#pragma unroll 1
    for (int rr = 0; rr < 2; rr++) {
        const int r = 2 * w + rr;
        uint32_t ub[16][2];
        {
            const uint32_t addr = sb_addr + CV_O_U + (uint32_t)((128 + 16 * (8 * (mi >> 1) + rowi - r) + 8 * (mi & 1)) * 2);
#pragma unroll
            for (int j = 0; j < 16; j += 2) ldsm_x4(addr + (uint32_t)(j * 256), ub[j][0], ub[j][1], ub[j + 1][0], ub[j + 1][1]);
        }
        const uint32_t* qp = s_q + 16 + 16 * r + g - 2 * t;
#pragma unroll
        for (int q = 0; q < 4; q++) {
            const uint32_t a0 = qp[128 * q], a1 = qp[128 * q + 8], a2 = qp[128 * q - 8];
#pragma unroll
            for (int nt = q; nt < 16; nt++) mma_bf16(acc[nt], a0, a1, a2, a0, ub[nt - q][0], ub[nt - q][1]);
        }
        if (r == 0) {
            const uint32_t a0 = qp[512], a1 = qp[520], a2 = qp[504];
#pragma unroll
            for (int nt = 4; nt < 16; nt++) mma_bf16(acc[nt], a0, a1, a2, a0, ub[nt - 4][0], ub[nt - 4][1]);
        }
    }
    named_bar(bar_id, 128);
    {
        uint32_t bq[7];
        const uint32_t* q2 = s_q2 + w * 64 + 16 + g - 2 * t - 32;
#pragma unroll
        for (int dlt = 3; dlt <= 9; dlt++) bq[dlt - 3] = q2[8 * dlt];
        const uint32_t addr = sb_addr + ((w >> 1) ? CV_O_W5 : CV_O_W3) + (uint32_t)((8 + 16 * (8 * (mi >> 1) + rowi) + 8 * (mi & 1) - 8 * (w & 1)) * 2);
#pragma unroll
        for (int kp = 0; kp < 6; kp++) {
            uint32_t a0, a1, a2, a3;
            ldsm_x4_t(addr + kp * 512, a0, a1, a2, a3);
#pragma unroll
            for (int dlt = 4; dlt <= 9; dlt++) {
                if (2 * kp + dlt < 16) mma_bf16(acc[2 * kp + dlt], a0, a1, a2, a3, bq[dlt - 3], bq[dlt - 4]);
            }
        }
    }
    if (w >= 2) {
        uint32_t bq[9];
        const uint32_t* q3 = s_q3 + (w - 2) * 96 + 16 + g - 2 * t - 64;
#pragma unroll
        for (int dlt = 7; dlt <= 15; dlt++) bq[dlt - 7] = q3[8 * dlt];
        const uint32_t addr = sb_addr + ((w - 2) ? CV_O_W9 : CV_O_W7) + (uint32_t)((16 * (8 * (mi >> 1) + rowi) + 8 * (mi & 1)) * 2);
#pragma unroll
        for (int kp = 0; kp < 4; kp++) {
            uint32_t a0, a1, a2, a3;
            ldsm_x4_t(addr + kp * 512, a0, a1, a2, a3);
#pragma unroll
            for (int dlt = 8; dlt <= 15; dlt++) {
                if (2 * kp + dlt < 16) mma_bf16(acc[2 * kp + dlt], a0, a1, a2, a3, bq[dlt - 7], bq[dlt - 8]);
            }
        }
    }
    if (threadIdx.x == 0) STAMP(1, 6);
    named_bar(bar_id, 128);
    {
        float4* xch = reinterpret_cast<float4*>(base) + w * 512;
#pragma unroll
        for (int i = 0; i < 16; i++) xch[i * 32 + lane] = make_float4(acc[i][0], acc[i][1], acc[i][2], acc[i][3]);
    }
    named_bar(bar_id, 128);
    {
        const float4* xch = reinterpret_cast<const float4*>(base) + (4 * w) * 32 + lane;
        const float dsk = __bfloat162float(Dskip[d]);
        uint16_t* stg = reinterpret_cast<uint16_t*>(base + CV_O_STG);
        const uint16_t* uu = reinterpret_cast<const uint16_t*>(s_u) + 128;
        auto uval = [&](int i) -> float { return i >= 0 ? __uint_as_float((uint32_t)uu[i] << 16) : 0.f; };
#pragma unroll
        for (int i = 0; i < 4; i++) {
            const float4 p0 = xch[i * 32], p1 = xch[512 + i * 32], p2 = xch[1024 + i * 32], p3 = xch[1536 + i * 32];
            const float y[4] = {(p0.x + p1.x) + (p2.x + p3.x), (p0.y + p1.y) + (p2.y + p3.y), (p0.z + p1.z) + (p2.z + p3.z), (p0.w + p1.w) + (p2.w + p3.w)};
            const int nt = 4 * w + i;
#pragma unroll
            for (int e = 0; e < 4; e++) {
                const int tau = 16 * (8 * nt + 2 * t + (e & 1)) + g + 8 * (e >> 1);
                float yy = y[e];
                if (w >= 1) yy = fmaf(kc512, uval(tau - 513) + uval(tau - 514), yy);
                if (w >= 2) yy = fmaf(kc1024, uval(tau - 1027) + uval(tau - 1028), yy);
                const float sv = bf16_round(yy) + bf16_round(uval(tau) * dsk);
                stg[tau] = (uint16_t)(__float_as_uint(bf16_round(sv)) >> 16);
            }
        }
        __syncwarp();
        uint4* dst = reinterpret_cast<uint4*>(g_sT + (size_t)d * L_ + w * 512);
        const uint4* srcp = reinterpret_cast<const uint4*>(stg + w * 512);
        dst[lane] = srcp[lane];
        dst[32 + lane] = srcp[32 + lane];
    }
    if (threadIdx.x == 0) STAMP(1, 7);
}

__device__ __forceinline__ uint32_t cluster_rank() { uint32_t r; asm volatile("mov.u32 %0, %%cluster_ctarank;" : "=r"(r)); return r; }
__device__ __forceinline__ void cluster_sync_all() {
    asm volatile("barrier.cluster.arrive.release.aligned;\nbarrier.cluster.wait.acquire.aligned;" ::: "memory");
}
__device__ __forceinline__ void mbar_arrive_remote(uint32_t bar, uint32_t cta) {
    asm volatile("{\n.reg .b32 ra;\nmapa.shared::cluster.u32 ra, %0, %1;\n"
                 "mbarrier.arrive.shared::cluster.b64 _, [ra];\n}\n" ::"r"(bar), "r"(cta) : "memory");
}
__device__ __forceinline__ void tma_load_2d_mc(uint32_t dst, const CUtensorMap* tm, int c0, int c1, uint32_t bar, uint16_t mask) {
    asm volatile(
        "cp.async.bulk.tensor.2d.shared::cluster.global.mbarrier::complete_tx::bytes.multicast::cluster [%0], [%1, {%3, %4}], [%2], %5;"
        ::"r"(dst), "l"((uint64_t)tm), "r"(bar), "r"(c0), "r"(c1), "h"(mask) : "memory");
}
__device__ __forceinline__ void tma_store_2d(const CUtensorMap* tm, uint32_t src, int c0, int c1) {
    asm volatile("cp.async.bulk.tensor.2d.global.shared::cta.bulk_group [%0, {%2, %3}], [%1];"
                 ::"l"((uint64_t)tm), "r"(src), "r"(c0), "r"(c1) : "memory");
}
__device__ __forceinline__ void bulk_commit() { asm volatile("cp.async.bulk.commit_group;" ::: "memory"); }
template <int N> __device__ __forceinline__ void bulk_wait_read() { asm volatile("cp.async.bulk.wait_group.read %0;" ::"n"(N) : "memory"); }
template <int N> __device__ __forceinline__ void bulk_wait() { asm volatile("cp.async.bulk.wait_group %0;" ::"n"(N) : "memory"); }
__device__ __forceinline__ void fence_async_smem() { asm volatile("fence.proxy.async.shared::cta;" ::: "memory"); }
__device__ __forceinline__ void stmatrix_x4(uint32_t addr, uint32_t r0, uint32_t r1, uint32_t r2, uint32_t r3) {
    asm volatile("stmatrix.sync.aligned.m8n8.x4.shared.b16 [%0], {%1,%2,%3,%4};" ::"r"(addr), "r"(r0), "r"(r1), "r"(r2), "r"(r3) : "memory");
}

constexpr int G1_STAGES = 5;
constexpr int G1_A_BYTES = 8 * 16384;
constexpr int G1_B_STAGE = 16384;
constexpr int G1_STG = 8 * 1024;
constexpr int G1_SMEM = G1_A_BYTES + G1_STAGES * G1_B_STAGE + G1_STG + 1024 + 256;
constexpr int G1_ITERS = 32;

__device__ __forceinline__ void tma_load_3d(uint32_t dst, const CUtensorMap* tm, int c0, int c1, int c2, uint32_t bar) {
    asm volatile(
        "cp.async.bulk.tensor.3d.shared::cluster.global.mbarrier::complete_tx::bytes [%0], [%1, {%3, %4, %5}], [%2];"
        ::"r"(dst), "l"((uint64_t)tm), "r"(bar), "r"(c0), "r"(c1), "r"(c2) : "memory");
}

__device__ __forceinline__ float gelu_tanh(float x) {
    float u = x * (0.7978845608028654f + 0.035677408136300125f * x * x);
    float t; asm("tanh.approx.f32 %0, %1;" : "=f"(t) : "f"(u));
    float hx = 0.5f * x;
    return fmaf(hx, t, hx);
}
__device__ __forceinline__ uint32_t geglu_pair(uint32_t g2, uint32_t u2) {
    uint32_t a = pack_bf16(gelu_tanh(bf_lo(g2)), gelu_tanh(bf_hi(g2)));
    uint32_t r; asm("mul.rn.bf16x2 %0, %1, %2;" : "=r"(r) : "r"(a), "r"(u2));
    return r;
}

__global__ void __launch_bounds__(384, 1) gemm1_kernel(const __grid_constant__ CUtensorMap tm_xn,
                                                        const __grid_constant__ CUtensorMap tm_wg4,
                                                        const __grid_constant__ CUtensorMap tm_wu4,
                                                        const __grid_constant__ CUtensorMap tm_wg3,
                                                        const __grid_constant__ CUtensorMap tm_wu3,
                                                        const __grid_constant__ CUtensorMap tm_hst,
                                                        const __grid_constant__ CUtensorMap tm_hst96) {
    pdl_launch();
    if (threadIdx.x == 0) STAMP(2, 0);
    extern __shared__ uint8_t smem_raw[];
    const uint32_t sbase = (smem_u32(smem_raw) + 1023) & ~1023u;
    const uint32_t sA = sbase, sB = sbase + G1_A_BYTES, sStg = sB + G1_STAGES * G1_B_STAGE, sBar = sStg + G1_STG;
    const uint32_t bar_a = sBar, bar_full = sBar + 64, bar_empty = sBar + 64 + 8 * G1_STAGES;
    const int rb = blockIdx.x >> 3, cj = blockIdx.x & 7;
    const int warp = threadIdx.x >> 5, lane = threadIdx.x & 31;

    if (threadIdx.x == 0) {
        for (int i = 0; i < 8; i++) mbar_init(bar_a + 8 * i, 1);
        for (int i = 0; i < G1_STAGES; i++) { mbar_init(bar_full + 8 * i, 1); mbar_init(bar_empty + 8 * i, 8); }
        asm volatile("fence.mbarrier_init.release.cluster;" ::: "memory");
    }
    __syncthreads();

    if (warp >= 8) {
        asm volatile("setmaxnreg.dec.sync.aligned.u32 40;");
        if (lane == 0) {
            const int pw = warp - 8;
            if (pw == 0) { prefetch_tmap(&tm_wg4); prefetch_tmap(&tm_wu4); prefetch_tmap(&tm_xn); }
            if (pw == 1) { prefetch_tmap(&tm_wg3); prefetch_tmap(&tm_wu3); prefetch_tmap(&tm_hst); prefetch_tmap(&tm_hst96); }
            for (int it = pw; it < G1_ITERS; it += 4) {
                const int s = it % G1_STAGES, kb = it & 15;
                if (it >= G1_STAGES) mbar_wait(bar_empty + 8 * s, ((it / G1_STAGES) - 1) & 1);
                const uint32_t dst = sB + s * G1_B_STAGE;
                if (it < 16) {
                    mbar_expect_tx(bar_full + 8 * s, 16384);
                    tma_load_3d(dst, &tm_wg4, 0, kb * 32, cj * 7, bar_full + 8 * s);
                    tma_load_3d(dst + 8192, &tm_wu4, 0, kb * 32, cj * 7, bar_full + 8 * s);
                } else {
                    mbar_expect_tx(bar_full + 8 * s, 12288);
                    tma_load_3d(dst, &tm_wg3, 0, kb * 32, cj * 7 + 4, bar_full + 8 * s);
                    tma_load_3d(dst + 6144, &tm_wu3, 0, kb * 32, cj * 7 + 4, bar_full + 8 * s);
                }
                if (it < 4) {
                    pdl_wait();
                    if (pw == 0) STAMP(2, 1);
                    for (int k = pw; k < 8; k += 4) {
                        mbar_expect_tx(bar_a + 8 * k, 16384);
                        tma_load_2d(sA + k * 16384, &tm_xn, k * 64, rb * 128, bar_a + 8 * k);
                    }
                }
            }
        }
    } else {
        asm volatile("setmaxnreg.inc.sync.aligned.u32 232;");
        const int wg = __shfl_sync(0xffffffffu, (int)(threadIdx.x >> 7), 0);
        float r[160];
        const int row0 = rb * 128 + wg * 64 + (warp & 3) * 16;
        const uint64_t descA = make_desc(sA + wg * 8192, 16, 1024);
        const uint64_t descB = make_desc(sB, 2048, 512, 2);
        const uint32_t stg = sStg + warp * 1024;
        const uint32_t st_off = (uint32_t)(((lane & 7) + ((lane >> 3) & 1) * 8) * 32 + (lane >> 4) * 16);
        __nv_bfloat16* hrow = g_h + (size_t)(row0 + (lane >> 1)) * F_ + (lane & 1) * 8 + cj * 224;
#pragma unroll
        for (int kb = 0; kb < 16; kb++) {
            const int it = kb, s = it % G1_STAGES;
            if ((kb & 1) == 0) mbar_wait(bar_a + 8 * (kb >> 1), 0);
            mbar_wait(bar_full + 8 * s, (it / G1_STAGES) & 1);
            if (threadIdx.x == 0 && (it & 7) == 0) STAMP(2, 2 + it / 8);
            wgmma_fence();
            const uint64_t da = descA + (uint64_t)(((kb >> 1) * 16384 + (kb & 1) * 64) >> 4);
            const uint64_t db = descB + (uint64_t)((s * G1_B_STAGE) >> 4);
            wgmma_n256_k32(r, da, da + 2, db, db + 64, kb != 0);
            wgmma_commit();
            if (kb > 0) {
                wgmma_wait<1>();
                if (lane == 0) mbar_arrive(bar_empty + 8 * ((it - 1) % G1_STAGES));
            }
        }
        wgmma_wait<0>();
        if (lane == 0) mbar_arrive(bar_empty + 8 * (15 % G1_STAGES));
#pragma unroll
        for (int i = 0; i < 32; i++) r[128 + i] = __uint_as_float(pack_bf16(r[2 * i], r[2 * i + 1]));
#pragma unroll
        for (int i = 31; i >= 0; i--) r[96 + i] = __uint_as_float(pack_bf16(r[64 + 2 * i], r[65 + 2 * i]));
        uint32_t eo[4];
        uint4 pv = make_uint4(0, 0, 0, 0);
#pragma unroll
        for (int kb = 0; kb < 16; kb++) {
            const int it = 16 + kb, s = it % G1_STAGES;
            mbar_wait(bar_full + 8 * s, (it / G1_STAGES) & 1);
            if (threadIdx.x == 0 && (it & 7) == 0) STAMP(2, 2 + it / 8);
            wgmma_fence();
            const uint64_t da = descA + (uint64_t)(((kb >> 1) * 16384 + (kb & 1) * 64) >> 4);
            const uint64_t db = descB + (uint64_t)((s * G1_B_STAGE) >> 4);
            const int jj = kb >> 1;
            wgmma_n192(r, da, db, kb != 0);
            eo[(kb & 1) * 2] = geglu_pair(__float_as_uint(r[128 + 2 * kb]), __float_as_uint(r[96 + 2 * kb]));
            wgmma_n192(r, da + 2, db + 64, 1);
            wgmma_commit();
            eo[(kb & 1) * 2 + 1] = geglu_pair(__float_as_uint(r[129 + 2 * kb]), __float_as_uint(r[97 + 2 * kb]));
            if (kb & 1) {
                if (jj > 0) *reinterpret_cast<uint4*>(hrow + (jj - 1) * 16) = pv;
                stmatrix_x4(stg + (jj & 1) * 512 + st_off, eo[0], eo[1], eo[2], eo[3]);
            } else if (jj > 0) {
                __syncwarp();
                asm volatile("ld.shared.v4.u32 {%0,%1,%2,%3}, [%4];" : "=r"(pv.x), "=r"(pv.y), "=r"(pv.z), "=r"(pv.w)
                             : "r"(stg + ((jj - 1) & 1) * 512 + lane * 16));
            }
            if (kb > 0 && it - 1 + G1_STAGES < G1_ITERS) {
                wgmma_wait<1>();
                if (lane == 0) mbar_arrive(bar_empty + 8 * ((it - 1) % G1_STAGES));
            }
        }
        __syncwarp();
        asm volatile("ld.shared.v4.u32 {%0,%1,%2,%3}, [%4];" : "=r"(pv.x), "=r"(pv.y), "=r"(pv.z), "=r"(pv.w) : "r"(stg + 512 + lane * 16));
        wgmma_wait<0>();
        *reinterpret_cast<uint4*>(hrow + 7 * 16) = pv;
        if (threadIdx.x == 0) STAMP(2, 6);
        {
            uint32_t o[24];
#pragma unroll
            for (int i = 0; i < 24; i++) o[i] = geglu_pair(pack_bf16(r[2 * i], r[2 * i + 1]), pack_bf16(r[48 + 2 * i], r[49 + 2 * i]));
            named_bar(1 + wg, 128);
            const uint32_t fbuf = sA + ((warp & 3) >> 1) * 16384 + wg * 8192 + (warp & 1) * 4096;
#pragma unroll
            for (int jj = 0; jj < 6; jj++) stmatrix_x4(fbuf + jj * 512 + st_off, o[4 * jj], o[4 * jj + 1], o[4 * jj + 2], o[4 * jj + 3]);
            __syncwarp();
            uint4 v[6];
#pragma unroll
            for (int jj = 0; jj < 6; jj++)
                asm volatile("ld.shared.v4.u32 {%0,%1,%2,%3}, [%4];" : "=r"(v[jj].x), "=r"(v[jj].y), "=r"(v[jj].z), "=r"(v[jj].w)
                             : "r"(fbuf + jj * 512 + lane * 16));
#pragma unroll
            for (int jj = 0; jj < 6; jj++) *reinterpret_cast<uint4*>(hrow + 128 + jj * 16) = v[jj];
        }
        if (threadIdx.x == 0) STAMP(2, 7);
    }
}

constexpr int G2_STAGES = 5;
constexpr int G2_STAGE = 16384 + 16384;
constexpr int G2_XCH = 32768;
constexpr int G2_EPI = 16384 + 16384;
constexpr int G2_SMEM = G2_STAGES * G2_STAGE + G2_XCH + G2_EPI + 1024 + 256;
constexpr int G2_KB = F_ / 64 / 2;

__global__ void __launch_bounds__(384, 1) gemm2_kernel(const __grid_constant__ CUtensorMap tm_h,
                                                        const __grid_constant__ CUtensorMap tm_wd,
                                                        const __grid_constant__ CUtensorMap tm_x,
                                                        const __grid_constant__ CUtensorMap tm_sT,
                                                        const __grid_constant__ CUtensorMap tm_out) {
    if (threadIdx.x == 0) STAMP(3, 0);
    extern __shared__ uint8_t smem_raw[];
    const uint32_t sbase = (smem_u32(smem_raw) + 1023) & ~1023u;
    const uint32_t sXch = sbase + G2_STAGES * G2_STAGE, sX = sXch + G2_XCH, sS = sX + 16384, sBar = sX + G2_EPI;
    const uint32_t bar_full = sBar, bar_empty = sBar + 8 * G2_STAGES, bar_epi = sBar + 16 * G2_STAGES, bar_xch = bar_epi + 8;
    const uint32_t kh = cluster_rank();
    const int cid = blockIdx.x >> 1;
    const int rb = cid >> 2, nb = cid & 3;
    const int col_fin = nb * 128 + kh * 64;
    const int warp = threadIdx.x >> 5, lane = threadIdx.x & 31;

    if (threadIdx.x == 0) {
        for (int i = 0; i < G2_STAGES; i++) { mbar_init(bar_full + 8 * i, 1); mbar_init(bar_empty + 8 * i, 8); }
        mbar_init(bar_epi, 1);
        mbar_init(bar_xch, 1);
        asm volatile("fence.mbarrier_init.release.cluster;" ::: "memory");
        mbar_expect_tx(bar_xch, G2_XCH);
    }
    cluster_sync_all();

    if (warp >= 8) {
        if (lane == 0) {
            const int pw = warp - 8;
            const int k0 = kh * G2_KB;
            if (pw == 0) { prefetch_tmap(&tm_wd); prefetch_tmap(&tm_h); }
            if (pw == 1) { prefetch_tmap(&tm_x); prefetch_tmap(&tm_sT); prefetch_tmap(&tm_out); }
            for (int it = pw; it < G2_STAGES; it += 4) {
                mbar_expect_tx(bar_full + 8 * it, G2_STAGE);
                tma_load_3d(sbase + it * G2_STAGE + 16384, &tm_wd, 0, (k0 + it) * 64, nb * 2, bar_full + 8 * it);
            }
            if (pw == 3) {
                mbar_expect_tx(bar_epi, G2_EPI);
                tma_load_2d(sX, &tm_x, col_fin, rb * 128, bar_epi);
            }
            pdl_wait();
            if (pw == 0) STAMP(3, 1);
            for (int it = pw; it < G2_STAGES; it += 4)
                tma_load_2d(sbase + it * G2_STAGE, &tm_h, (k0 + it) * 64, rb * 128, bar_full + 8 * it);
            if (pw == 3) {
                tma_load_2d(sS, &tm_sT, rb * 128, col_fin, bar_epi);
                tma_load_2d(sS + 8192, &tm_sT, rb * 128 + 64, col_fin, bar_epi);
            }
            for (int it = G2_STAGES + ((pw + 4 - (G2_STAGES & 3)) & 3); it < G2_KB; it += 4) {
                const int s = it % G2_STAGES;
                mbar_wait(bar_empty + 8 * s, ((it / G2_STAGES) - 1) & 1);
                mbar_expect_tx(bar_full + 8 * s, G2_STAGE);
                tma_load_2d(sbase + s * G2_STAGE, &tm_h, (k0 + it) * 64, rb * 128, bar_full + 8 * s);
                tma_load_3d(sbase + s * G2_STAGE + 16384, &tm_wd, 0, (k0 + it) * 64, nb * 2, bar_full + 8 * s);
            }
        }
    } else {
        const int wg = __shfl_sync(0xffffffffu, (int)(threadIdx.x >> 7), 0);
        const int g = lane >> 2, t = lane & 3;
        float acc[64];
        const uint64_t descA = make_desc(sbase + wg * 8192, 16, 1024);
        const uint64_t descB = make_desc(sbase + 16384, 8192, 1024);
#pragma unroll
        for (int it = 0; it < G2_KB; it++) {
            const int s = it % G2_STAGES;
            mbar_wait(bar_full + 8 * s, (it / G2_STAGES) & 1);
            if (threadIdx.x == 0 && (it == 0 || it == 7)) STAMP(3, 2 + it / 7);
            wgmma_fence();
            {
                const uint64_t da = descA + (uint64_t)((s * G2_STAGE) >> 4);
                const uint64_t db = descB + (uint64_t)((s * G2_STAGE) >> 4);
                wgmma_n128_k64(acc, da, da + 2, da + 4, da + 6, db, db + 128, db + 256, db + 384, it != 0);
            }
            wgmma_commit();
            if (it > 0 && it - 1 + G2_STAGES < G2_KB) {
                wgmma_wait<1>();
                if (lane == 0) mbar_arrive(bar_empty + 8 * ((it - 1) % G2_STAGES));
            }
        }
        const int lr = wg * 64 + (warp & 3) * 16 + g;
        uint32_t xv[16], sv[16];
        mbar_wait(bar_epi, 0);
#pragma unroll
        for (int j = 0; j < 8; j++) {
#pragma unroll
            for (int hh = 0; hh < 2; hh++) {
                const int r = lr + 8 * hh;
                asm volatile("ld.shared.u32 %0, [%1];" : "=r"(xv[2 * j + hh]) : "r"(sX + r * 128 + ((j ^ (r & 7)) << 4) + 4 * t));
                const int c0 = 8 * j + 2 * t;
                const uint32_t sa = sS + (r >> 6) * 8192 + (((r & 63) >> 3) << 4) + (r & 7) * 2;
                uint16_t s0r, s1r;
                asm volatile("ld.shared.u16 %0, [%1];" : "=h"(s0r) : "r"((sa + c0 * 128) ^ ((c0 & 7) << 4)));
                asm volatile("ld.shared.u16 %0, [%1];" : "=h"(s1r) : "r"((sa + (c0 + 1) * 128) ^ (((c0 + 1) & 7) << 4)));
                sv[2 * j + hh] = (uint32_t)s0r | ((uint32_t)s1r << 16);
            }
        }
        wgmma_wait<0>();
        if (threadIdx.x == 0) STAMP(3, 4);
        {
            uint32_t remote, rbar;
            asm volatile("mapa.shared::cluster.u32 %0, %1, %2;" : "=r"(remote) : "r"(sXch + threadIdx.x * 16), "r"(kh ^ 1));
            asm volatile("mapa.shared::cluster.u32 %0, %1, %2;" : "=r"(rbar) : "r"(bar_xch), "r"(kh ^ 1));
            if (kh == 0) {
#pragma unroll
                for (int i = 0; i < 8; i++)
                    asm volatile("st.async.shared::cluster.mbarrier::complete_tx::bytes.v4.f32 [%0], {%1,%2,%3,%4}, [%5];" ::"r"(remote + i * 4096),
                                 "f"(acc[32 + 4 * i]), "f"(acc[33 + 4 * i]), "f"(acc[34 + 4 * i]), "f"(acc[35 + 4 * i]), "r"(rbar) : "memory");
            } else {
#pragma unroll
                for (int i = 0; i < 8; i++)
                    asm volatile("st.async.shared::cluster.mbarrier::complete_tx::bytes.v4.f32 [%0], {%1,%2,%3,%4}, [%5];" ::"r"(remote + i * 4096),
                                 "f"(acc[4 * i]), "f"(acc[1 + 4 * i]), "f"(acc[2 + 4 * i]), "f"(acc[3 + 4 * i]), "r"(rbar) : "memory");
#pragma unroll
                for (int i = 0; i < 32; i++) acc[i] = acc[32 + i];
            }
        }
        if (threadIdx.x == 0) STAMP(3, 6);
        mbar_wait(bar_xch, 0);
        if (threadIdx.x == 0) STAMP(3, 7);
#pragma unroll
        for (int j = 0; j < 8; j++) {
            float4 o;
            asm volatile("ld.shared.v4.f32 {%0,%1,%2,%3}, [%4];" : "=f"(o.x), "=f"(o.y), "=f"(o.z), "=f"(o.w) : "r"(sXch + threadIdx.x * 16 + j * 4096));
            acc[4 * j] += o.x; acc[4 * j + 1] += o.y; acc[4 * j + 2] += o.z; acc[4 * j + 3] += o.w;
        }
#pragma unroll
        for (int i = 0; i < 16; i++) {
            float f0 = bf16_round(acc[2 * i]), f1 = bf16_round(acc[2 * i + 1]);
            float g0 = bf16_round(__fdividef(f0, 1.0f + __expf(-f0)));
            float g1 = bf16_round(__fdividef(f1, 1.0f + __expf(-f1)));
            float o0 = bf_lo(xv[i]) + bf16_round(bf_lo(sv[i]) * g0);
            float o1 = bf_hi(xv[i]) + bf16_round(bf_hi(sv[i]) * g1);
            xv[i] = pack_bf16(o0, o1);
        }
#pragma unroll
        for (int j = 0; j < 8; j++) {
#pragma unroll
            for (int hh = 0; hh < 2; hh++) {
                const int r = lr + 8 * hh;
                asm volatile("st.shared.u32 [%0], %1;" ::"r"(sX + r * 128 + ((j ^ (r & 7)) << 4) + 4 * t), "r"(xv[2 * j + hh]) : "memory");
            }
        }
        if (threadIdx.x == 0) STAMP(3, 9);
        fence_async_smem();
        __syncwarp();
        if (lane == 0) {
            tma_store_2d(&tm_out, sX + (wg * 64 + (warp & 3) * 16) * 128, col_fin, rb * 128 + wg * 64 + (warp & 3) * 16);
            bulk_commit();
            bulk_wait_read<0>();
        }
        if (threadIdx.x == 0) STAMP(3, 5);
    }
}

typedef CUresult (*EncodeFn)(CUtensorMap*, CUtensorMapDataType, cuuint32_t, void*, const cuuint64_t*, const cuuint64_t*,
                             const cuuint32_t*, const cuuint32_t*, CUtensorMapInterleave, CUtensorMapSwizzle,
                             CUtensorMapL2promotion, CUtensorMapFloatOOBfill);

void make_map(EncodeFn fn, CUtensorMap* m, const void* ptr, uint64_t inner, uint64_t outer, uint32_t box_in, uint32_t box_out,
              CUtensorMapSwizzle swz = CU_TENSOR_MAP_SWIZZLE_128B) {
    cuuint64_t dims[2] = {inner, outer};
    cuuint64_t strides[1] = {inner * 2};
    cuuint32_t box[2] = {box_in, box_out};
    cuuint32_t es[2] = {1, 1};
    fn(m, CU_TENSOR_MAP_DATA_TYPE_BFLOAT16, 2, const_cast<void*>(ptr), dims, strides, box, es, CU_TENSOR_MAP_INTERLEAVE_NONE,
       swz, CU_TENSOR_MAP_L2_PROMOTION_L2_256B, CU_TENSOR_MAP_FLOAT_OOB_FILL_NONE);
}
void make_map3(EncodeFn fn, CUtensorMap* m, const void* ptr, uint64_t cols, uint64_t rows, uint32_t atom, uint32_t box_rows,
               uint32_t box_atoms, CUtensorMapSwizzle swz) {
    cuuint64_t dims[3] = {atom, rows, cols / atom};
    cuuint64_t strides[2] = {cols * 2, (cuuint64_t)atom * 2};
    cuuint32_t box[3] = {atom, box_rows, box_atoms};
    cuuint32_t es[3] = {1, 1, 1};
    fn(m, CU_TENSOR_MAP_DATA_TYPE_BFLOAT16, 3, const_cast<void*>(ptr), dims, strides, box, es, CU_TENSOR_MAP_INTERLEAVE_NONE,
       swz, CU_TENSOR_MAP_L2_PROMOTION_L2_256B, CU_TENSOR_MAP_FLOAT_OOB_FILL_NONE);
}

template <typename... Args>
void launch_pdl(void (*kern)(Args...), int grid, int block, int smem, bool pdl, int cluster, Args... args) {
    cudaLaunchConfig_t cfg = {};
    cfg.gridDim = dim3(grid); cfg.blockDim = dim3(block); cfg.dynamicSmemBytes = smem; cfg.stream = cudaStreamPerThread;
    cudaLaunchAttribute at[2];
    int n = 0;
    if (pdl) {
        at[n].id = cudaLaunchAttributeProgrammaticStreamSerialization;
        at[n].val.programmaticStreamSerializationAllowed = 1;
        n++;
    }
    if (cluster > 1) {
        at[n].id = cudaLaunchAttributeClusterDimension;
        at[n].val.clusterDim.x = cluster; at[n].val.clusterDim.y = 1; at[n].val.clusterDim.z = 1;
        n++;
    }
    cfg.attrs = at; cfg.numAttrs = n;
    cudaLaunchKernelEx(&cfg, kern, args...);
}

}

extern "C" void kernel_launch(void* const* d_in, const int* in_sizes, int n_in, void* d_out, int out_size) {
    const __nv_bfloat16* x = (const __nv_bfloat16*)d_in[0];
    const __nv_bfloat16* A_re = (const __nv_bfloat16*)d_in[1];
    const __nv_bfloat16* A_im = (const __nv_bfloat16*)d_in[2];
    const __nv_bfloat16* B_re = (const __nv_bfloat16*)d_in[3];
    const __nv_bfloat16* B_im = (const __nv_bfloat16*)d_in[4];
    const __nv_bfloat16* C_re = (const __nv_bfloat16*)d_in[5];
    const __nv_bfloat16* C_im = (const __nv_bfloat16*)d_in[6];
    const __nv_bfloat16* log_dt = (const __nv_bfloat16*)d_in[7];
    const __nv_bfloat16* Dskip = (const __nv_bfloat16*)d_in[8];
    const __nv_bfloat16* wg = (const __nv_bfloat16*)d_in[10];
    const __nv_bfloat16* wu = (const __nv_bfloat16*)d_in[11];
    const __nv_bfloat16* wd = (const __nv_bfloat16*)d_in[12];
    __nv_bfloat16* out = (__nv_bfloat16*)d_out;

    static bool init = false;
    static CUtensorMap tm_xn, tm_wg4, tm_wu4, tm_wg3, tm_wu3, tm_hst, tm_hst96, tm_h, tm_wd, tm_x, tm_sT, tm_out;
    static const void* last_ptrs[5] = {nullptr, nullptr, nullptr, nullptr, nullptr};
    if (!init || last_ptrs[0] != wg || last_ptrs[1] != wu || last_ptrs[2] != wd || last_ptrs[3] != x || last_ptrs[4] != out) {
        void* fnp = nullptr;
        cudaDriverEntryPointQueryResult qres;
        cudaGetDriverEntryPoint("cuTensorMapEncodeTiled", &fnp, cudaEnableDefault, &qres);
        EncodeFn fn = (EncodeFn)fnp;
        void *p_xn, *p_h, *p_sT;
        cudaGetSymbolAddress(&p_xn, g_xn);
        cudaGetSymbolAddress(&p_h, g_h);
        cudaGetSymbolAddress(&p_sT, g_sT);
        make_map(fn, &tm_xn, p_xn, D_, L_, 64, 128);
        make_map3(fn, &tm_wg4, wg, F_, D_, 32, 32, 4, CU_TENSOR_MAP_SWIZZLE_64B);
        make_map3(fn, &tm_wu4, wu, F_, D_, 32, 32, 4, CU_TENSOR_MAP_SWIZZLE_64B);
        make_map3(fn, &tm_wg3, wg, F_, D_, 32, 32, 3, CU_TENSOR_MAP_SWIZZLE_64B);
        make_map3(fn, &tm_wu3, wu, F_, D_, 32, 32, 3, CU_TENSOR_MAP_SWIZZLE_64B);
        make_map(fn, &tm_hst, p_h, F_, L_, 16, 16, CU_TENSOR_MAP_SWIZZLE_NONE);
        make_map(fn, &tm_hst96, p_h, F_, L_, 96, 16, CU_TENSOR_MAP_SWIZZLE_NONE);
        make_map(fn, &tm_h, p_h, F_, L_, 64, 128);
        make_map3(fn, &tm_wd, wd, D_, F_, 64, 64, 2, CU_TENSOR_MAP_SWIZZLE_128B);
        make_map(fn, &tm_x, x, D_, L_, 64, 128);
        make_map(fn, &tm_sT, p_sT, L_, D_, 64, 64);
        make_map(fn, &tm_out, out, D_, L_, 64, 16);
        cudaFuncSetAttribute(ln_kernel, cudaFuncAttributePreferredSharedMemoryCarveout, 100);
        cudaFuncSetAttribute(conv_kernel, cudaFuncAttributeMaxDynamicSharedMemorySize, CV_SMEM);
        cudaFuncSetAttribute(conv_kernel, cudaFuncAttributePreferredSharedMemoryCarveout, 100);
        cudaFuncSetAttribute(gemm1_kernel, cudaFuncAttributeMaxDynamicSharedMemorySize, G1_SMEM);
        cudaFuncSetAttribute(gemm2_kernel, cudaFuncAttributeMaxDynamicSharedMemorySize, G2_SMEM);
        last_ptrs[0] = wg; last_ptrs[1] = wu; last_ptrs[2] = wd; last_ptrs[3] = x; last_ptrs[4] = out;
        init = true;
    }
    launch_pdl(ln_kernel, L_ / LN_ROWS, 256, 0, false, 1, x, wg, wu, wd);
    launch_pdl(conv_kernel, D_ / CV_CH, 512, CV_SMEM, true, 1, A_re, A_im, B_re, B_im, C_re, C_im, log_dt, Dskip);
    launch_pdl(gemm1_kernel, 128, 384, G1_SMEM, true, 1, tm_xn, tm_wg4, tm_wu4, tm_wg3, tm_wu3, tm_hst, tm_hst96);
    launch_pdl(gemm2_kernel, 128, 384, G2_SMEM, true, 2, tm_h, tm_wd, tm_x, tm_sT, tm_out);
}
```

```cpp
#include <cuda_runtime.h>
#include <cuda_bf16.h>
#include <cuda.h>
#include <stdint.h>

namespace {

constexpr int L_ = 2048, D_ = 512, NS_ = 128, F_ = 1792;

__device__ __align__(1024) __nv_bfloat16 g_xn[L_ * D_];
__device__ __align__(1024) __nv_bfloat16 g_xnT[D_ * L_];
__device__ __align__(1024) __nv_bfloat16 g_sT[D_ * L_];
__device__ __align__(1024) __nv_bfloat16 g_h[L_ * F_];
__device__ unsigned int g_ln_count;

#define STAMP(k, i)

__device__ __forceinline__ uint32_t smem_u32(const void* p) { return (uint32_t)__cvta_generic_to_shared(p); }
__device__ __forceinline__ void pdl_wait() { asm volatile("griddepcontrol.wait;" ::: "memory"); }
__device__ __forceinline__ void pdl_launch() { asm volatile("griddepcontrol.launch_dependents;" ::: "memory"); }

__device__ __forceinline__ void mbar_init(uint32_t bar, uint32_t cnt) {
    asm volatile("mbarrier.init.shared::cta.b64 [%0], %1;" ::"r"(bar), "r"(cnt) : "memory");
}
__device__ __forceinline__ void mbar_expect_tx(uint32_t bar, uint32_t bytes) {
    asm volatile("mbarrier.arrive.expect_tx.shared::cta.b64 _, [%0], %1;" ::"r"(bar), "r"(bytes) : "memory");
}
__device__ __forceinline__ void mbar_arrive(uint32_t bar) {
    asm volatile("mbarrier.arrive.shared::cta.b64 _, [%0];" ::"r"(bar) : "memory");
}
__device__ __forceinline__ void mbar_wait(uint32_t bar, uint32_t parity) {
    asm volatile(
        "{\n.reg .pred p;\n"
        "WAIT_LOOP:\n"
        "mbarrier.try_wait.parity.shared::cta.b64 p, [%0], %1;\n"
        "@p bra WAIT_DONE;\n"
        "bra WAIT_LOOP;\n"
        "WAIT_DONE:\n}\n" ::"r"(bar), "r"(parity) : "memory");
}
__device__ __forceinline__ void tma_load_2d(uint32_t dst, const CUtensorMap* tm, int c0, int c1, uint32_t bar) {
    asm volatile(
        "cp.async.bulk.tensor.2d.shared::cluster.global.mbarrier::complete_tx::bytes [%0], [%1, {%3, %4}], [%2];"
        ::"r"(dst), "l"((uint64_t)tm), "r"(bar), "r"(c0), "r"(c1) : "memory");
}
__device__ __forceinline__ void prefetch_tmap(const CUtensorMap* tm) {
    asm volatile("prefetch.tensormap [%0];" ::"l"((uint64_t)tm) : "memory");
}
__device__ __forceinline__ uint64_t make_desc(uint32_t addr, uint32_t lbo, uint32_t sbo, uint64_t mode = 1) {
    uint64_t d = 0;
    d |= (uint64_t)((addr & 0x3FFFF) >> 4);
    d |= (uint64_t)((lbo >> 4) & 0x3FFF) << 16;
    d |= (uint64_t)((sbo >> 4) & 0x3FFF) << 32;
    d |= mode << 62;
    return d;
}
__device__ __forceinline__ void wgmma_fence() { asm volatile("wgmma.fence.sync.aligned;" ::: "memory"); }
__device__ __forceinline__ void wgmma_commit() { asm volatile("wgmma.commit_group.sync.aligned;" ::: "memory"); }
template <int N> __device__ __forceinline__ void wgmma_wait() {
    asm volatile("wgmma.wait_group.sync.aligned %0;" ::"n"(N) : "memory");
}

#define R8(a, i) "+f"(a[i + 0]), "+f"(a[i + 1]), "+f"(a[i + 2]), "+f"(a[i + 3]), "+f"(a[i + 4]), "+f"(a[i + 5]), "+f"(a[i + 6]), "+f"(a[i + 7])

__device__ __forceinline__ void wgmma_n256_k32(float* a, uint64_t da0, uint64_t da1, uint64_t db0, uint64_t db1, int scale_d) {
    asm volatile(
        "{\n.reg .pred p;\nsetp.ne.b32 p, %132, 0;\n"
        "wgmma.mma_async.sync.aligned.m64n256k16.f32.bf16.bf16 {%0,%1,%2,%3,%4,%5,%6,%7,%8,%9,%10,%11,%12,%13,%14,%15,%16,%17,%18,%19,%20,%21,%22,%23,%24,%25,%26,%27,%28,%29,%30,%31,%32,%33,%34,%35,%36,%37,%38,%39,%40,%41,%42,%43,%44,%45,%46,%47,%48,%49,%50,%51,%52,%53,%54,%55,%56,%57,%58,%59,%60,%61,%62,%63,%64,%65,%66,%67,%68,%69,%70,%71,%72,%73,%74,%75,%76,%77,%78,%79,%80,%81,%82,%83,%84,%85,%86,%87,%88,%89,%90,%91,%92,%93,%94,%95,%96,%97,%98,%99,%100,%101,%102,%103,%104,%105,%106,%107,%108,%109,%110,%111,%112,%113,%114,%115,%116,%117,%118,%119,%120,%121,%122,%123,%124,%125,%126,%127}, %128, %130, p, 1, 1, 0, 1;\n"
        "wgmma.mma_async.sync.aligned.m64n256k16.f32.bf16.bf16 {%0,%1,%2,%3,%4,%5,%6,%7,%8,%9,%10,%11,%12,%13,%14,%15,%16,%17,%18,%19,%20,%21,%22,%23,%24,%25,%26,%27,%28,%29,%30,%31,%32,%33,%34,%35,%36,%37,%38,%39,%40,%41,%42,%43,%44,%45,%46,%47,%48,%49,%50,%51,%52,%53,%54,%55,%56,%57,%58,%59,%60,%61,%62,%63,%64,%65,%66,%67,%68,%69,%70,%71,%72,%73,%74,%75,%76,%77,%78,%79,%80,%81,%82,%83,%84,%85,%86,%87,%88,%89,%90,%91,%92,%93,%94,%95,%96,%97,%98,%99,%100,%101,%102,%103,%104,%105,%106,%107,%108,%109,%110,%111,%112,%113,%114,%115,%116,%117,%118,%119,%120,%121,%122,%123,%124,%125,%126,%127}, %129, %131, 1, 1, 1, 0, 1;\n"
        "}\n"
        : R8(a, 0), R8(a, 8), R8(a, 16), R8(a, 24), R8(a, 32), R8(a, 40), R8(a, 48), R8(a, 56), R8(a, 64), R8(a, 72), R8(a, 80), R8(a, 88), R8(a, 96), R8(a, 104), R8(a, 112), R8(a, 120)
        : "l"(da0), "l"(da1), "l"(db0), "l"(db1), "r"(scale_d));
}
__device__ __forceinline__ void wgmma_n192_k32(float* a, uint64_t da0, uint64_t da1, uint64_t db0, uint64_t db1, int scale_d) {
    asm volatile(
        "{\n.reg .pred p;\nsetp.ne.b32 p, %100, 0;\n"
        "wgmma.mma_async.sync.aligned.m64n192k16.f32.bf16.bf16 {%0,%1,%2,%3,%4,%5,%6,%7,%8,%9,%10,%11,%12,%13,%14,%15,%16,%17,%18,%19,%20,%21,%22,%23,%24,%25,%26,%27,%28,%29,%30,%31,%32,%33,%34,%35,%36,%37,%38,%39,%40,%41,%42,%43,%44,%45,%46,%47,%48,%49,%50,%51,%52,%53,%54,%55,%56,%57,%58,%59,%60,%61,%62,%63,%64,%65,%66,%67,%68,%69,%70,%71,%72,%73,%74,%75,%76,%77,%78,%79,%80,%81,%82,%83,%84,%85,%86,%87,%88,%89,%90,%91,%92,%93,%94,%95}, %96, %98, p, 1, 1, 0, 1;\n"
        "wgmma.mma_async.sync.aligned.m64n192k16.f32.bf16.bf16 {%0,%1,%2,%3,%4,%5,%6,%7,%8,%9,%10,%11,%12,%13,%14,%15,%16,%17,%18,%19,%20,%21,%22,%23,%24,%25,%26,%27,%28,%29,%30,%31,%32,%33,%34,%35,%36,%37,%38,%39,%40,%41,%42,%43,%44,%45,%46,%47,%48,%49,%50,%51,%52,%53,%54,%55,%56,%57,%58,%59,%60,%61,%62,%63,%64,%65,%66,%67,%68,%69,%70,%71,%72,%73,%74,%75,%76,%77,%78,%79,%80,%81,%82,%83,%84,%85,%86,%87,%88,%89,%90,%91,%92,%93,%94,%95}, %97, %99, 1, 1, 1, 0, 1;\n"
        "}\n"
        : R8(a, 0), R8(a, 8), R8(a, 16), R8(a, 24), R8(a, 32), R8(a, 40), R8(a, 48), R8(a, 56), R8(a, 64), R8(a, 72), R8(a, 80), R8(a, 88)
        : "l"(da0), "l"(da1), "l"(db0), "l"(db1), "r"(scale_d));
}
__device__ __forceinline__ void wgmma_n192(float* a, uint64_t da0, uint64_t db0, int scale_d) {
    asm volatile(
        "{\n.reg .pred p;\nsetp.ne.b32 p, %98, 0;\n"
        "wgmma.mma_async.sync.aligned.m64n192k16.f32.bf16.bf16 {%0,%1,%2,%3,%4,%5,%6,%7,%8,%9,%10,%11,%12,%13,%14,%15,%16,%17,%18,%19,%20,%21,%22,%23,%24,%25,%26,%27,%28,%29,%30,%31,%32,%33,%34,%35,%36,%37,%38,%39,%40,%41,%42,%43,%44,%45,%46,%47,%48,%49,%50,%51,%52,%53,%54,%55,%56,%57,%58,%59,%60,%61,%62,%63,%64,%65,%66,%67,%68,%69,%70,%71,%72,%73,%74,%75,%76,%77,%78,%79,%80,%81,%82,%83,%84,%85,%86,%87,%88,%89,%90,%91,%92,%93,%94,%95}, %96, %97, p, 1, 1, 0, 1;\n"
        "}\n"
        : R8(a, 0), R8(a, 8), R8(a, 16), R8(a, 24), R8(a, 32), R8(a, 40), R8(a, 48), R8(a, 56), R8(a, 64), R8(a, 72), R8(a, 80), R8(a, 88)
        : "l"(da0), "l"(db0), "r"(scale_d));
}
__device__ __forceinline__ void wgmma_n128_k64(float* a, uint64_t da0, uint64_t da1, uint64_t da2, uint64_t da3,
                                               uint64_t db0, uint64_t db1, uint64_t db2, uint64_t db3, int scale_d) {
    asm volatile(
        "{\n.reg .pred p;\nsetp.ne.b32 p, %72, 0;\n"
        "wgmma.mma_async.sync.aligned.m64n128k16.f32.bf16.bf16 {%0,%1,%2,%3,%4,%5,%6,%7,%8,%9,%10,%11,%12,%13,%14,%15,%16,%17,%18,%19,%20,%21,%22,%23,%24,%25,%26,%27,%28,%29,%30,%31,%32,%33,%34,%35,%36,%37,%38,%39,%40,%41,%42,%43,%44,%45,%46,%47,%48,%49,%50,%51,%52,%53,%54,%55,%56,%57,%58,%59,%60,%61,%62,%63}, %64, %68, p, 1, 1, 0, 1;\n"
        "wgmma.mma_async.sync.aligned.m64n128k16.f32.bf16.bf16 {%0,%1,%2,%3,%4,%5,%6,%7,%8,%9,%10,%11,%12,%13,%14,%15,%16,%17,%18,%19,%20,%21,%22,%23,%24,%25,%26,%27,%28,%29,%30,%31,%32,%33,%34,%35,%36,%37,%38,%39,%40,%41,%42,%43,%44,%45,%46,%47,%48,%49,%50,%51,%52,%53,%54,%55,%56,%57,%58,%59,%60,%61,%62,%63}, %65, %69, 1, 1, 1, 0, 1;\n"
        "wgmma.mma_async.sync.aligned.m64n128k16.f32.bf16.bf16 {%0,%1,%2,%3,%4,%5,%6,%7,%8,%9,%10,%11,%12,%13,%14,%15,%16,%17,%18,%19,%20,%21,%22,%23,%24,%25,%26,%27,%28,%29,%30,%31,%32,%33,%34,%35,%36,%37,%38,%39,%40,%41,%42,%43,%44,%45,%46,%47,%48,%49,%50,%51,%52,%53,%54,%55,%56,%57,%58,%59,%60,%61,%62,%63}, %66, %70, 1, 1, 1, 0, 1;\n"
        "wgmma.mma_async.sync.aligned.m64n128k16.f32.bf16.bf16 {%0,%1,%2,%3,%4,%5,%6,%7,%8,%9,%10,%11,%12,%13,%14,%15,%16,%17,%18,%19,%20,%21,%22,%23,%24,%25,%26,%27,%28,%29,%30,%31,%32,%33,%34,%35,%36,%37,%38,%39,%40,%41,%42,%43,%44,%45,%46,%47,%48,%49,%50,%51,%52,%53,%54,%55,%56,%57,%58,%59,%60,%61,%62,%63}, %67, %71, 1, 1, 1, 0, 1;\n"
        "}\n"
        : R8(a, 0), R8(a, 8), R8(a, 16), R8(a, 24), R8(a, 32), R8(a, 40), R8(a, 48), R8(a, 56)
        : "l"(da0), "l"(da1), "l"(da2), "l"(da3), "l"(db0), "l"(db1), "l"(db2), "l"(db3), "r"(scale_d));
}

__device__ __forceinline__ float bf16_round(float x) {
    uint32_t p; asm("cvt.rn.bf16x2.f32 %0, %1, %2;" : "=r"(p) : "f"(x), "f"(0.0f));
    return __uint_as_float(p);
}
__device__ __forceinline__ uint32_t pack_bf16(float lo, float hi) {
    __nv_bfloat162 v = __floats2bfloat162_rn(lo, hi);
    return *reinterpret_cast<uint32_t*>(&v);
}
__device__ __forceinline__ float bf_lo(uint32_t v) { return __uint_as_float(v << 16); }
__device__ __forceinline__ float bf_hi(uint32_t v) { return __uint_as_float(v & 0xFFFF0000u); }

struct cplx { float r, i; };
__device__ __forceinline__ cplx cmul(cplx a, cplx b) {
    cplx c; c.r = a.r * b.r - a.i * b.i; c.i = a.r * b.i + a.i * b.r; return c;
}
__device__ __forceinline__ cplx csq(cplx a) {
    cplx c; c.r = a.r * a.r - a.i * a.i; c.i = 2.0f * a.r * a.i; return c;
}
__device__ __forceinline__ cplx cexp_m(float ar2, float ai2, float m) {
    float mag;
    asm("ex2.approx.ftz.f32 %0, %1;" : "=f"(mag) : "f"(ar2 * m));
    float rr = ai2 * m;
    rr -= (rr + 12582912.0f) - 12582912.0f;
    float th = rr * 6.283185307179586f;
    cplx c; c.r = mag * __cosf(th); c.i = mag * __sinf(th);
    return c;
}
__device__ __forceinline__ uint32_t to_tf32(float x) { return __float_as_uint(x) + 0x1000u; }
__device__ __forceinline__ void mma_tf32(float* c, uint32_t a0, uint32_t a1, uint32_t a2, uint32_t a3, uint32_t b0, uint32_t b1) {
    asm volatile("mma.sync.aligned.m16n8k8.row.col.f32.tf32.tf32.f32 {%0,%1,%2,%3}, {%4,%5,%6,%7}, {%8,%9}, {%0,%1,%2,%3};"
                 : "+f"(c[0]), "+f"(c[1]), "+f"(c[2]), "+f"(c[3])
                 : "r"(a0), "r"(a1), "r"(a2), "r"(a3), "r"(b0), "r"(b1));
}
__device__ __forceinline__ void mma_bf16(float* c, uint32_t a0, uint32_t a1, uint32_t a2, uint32_t a3, uint32_t b0, uint32_t b1) {
    asm volatile("mma.sync.aligned.m16n8k16.row.col.f32.bf16.bf16.f32 {%0,%1,%2,%3}, {%4,%5,%6,%7}, {%8,%9}, {%0,%1,%2,%3};"
                 : "+f"(c[0]), "+f"(c[1]), "+f"(c[2]), "+f"(c[3])
                 : "r"(a0), "r"(a1), "r"(a2), "r"(a3), "r"(b0), "r"(b1));
}
__device__ __forceinline__ void named_bar(int id, int n) { asm volatile("bar.sync %0, %1;" ::"r"(id), "r"(n) : "memory"); }
__device__ __forceinline__ void ldsm_x4(uint32_t addr, uint32_t& r0, uint32_t& r1, uint32_t& r2, uint32_t& r3) {
    asm volatile("ldmatrix.sync.aligned.m8n8.x4.shared.b16 {%0,%1,%2,%3}, [%4];" : "=r"(r0), "=r"(r1), "=r"(r2), "=r"(r3) : "r"(addr));
}
__device__ __forceinline__ void ldsm_x4_t(uint32_t addr, uint32_t& r0, uint32_t& r1, uint32_t& r2, uint32_t& r3) {
    asm volatile("ldmatrix.sync.aligned.m8n8.x4.trans.shared.b16 {%0,%1,%2,%3}, [%4];" : "=r"(r0), "=r"(r1), "=r"(r2), "=r"(r3) : "r"(addr));
}

constexpr int CV_CH = 4;
constexpr int CV_O_CONST = 0;
constexpr int CV_O_KP = 12288;
constexpr int CV_O_Q = CV_O_KP + 10368;
constexpr int CV_O_Q2 = CV_O_Q + 2304;
constexpr int CV_O_Q3 = CV_O_Q2 + 1024;
constexpr int CV_O_Q4X = CV_O_Q3 + 768;
constexpr int CV_O_W3 = CV_O_Q4X + 256;
constexpr int CV_O_W5 = CV_O_W3 + 3104;
constexpr int CV_O_W7 = CV_O_W5 + 3104;
constexpr int CV_O_W9 = CV_O_W7 + 2048;
constexpr int CV_O_STG = 32768;
constexpr int CV_O_U = CV_O_W9 + 2048;
constexpr int CV_PER_CH = CV_O_U + 4352;
static_assert(CV_O_U >= CV_O_STG + 4096, "staging overlaps u");
constexpr int CV_SMEM = CV_CH * CV_PER_CH;

constexpr int LN_ROWS = 16;

__global__ void __launch_bounds__(512, 1) front_kernel(const __nv_bfloat16* __restrict__ x,
                                                        const __nv_bfloat16* __restrict__ A_re, const __nv_bfloat16* __restrict__ A_im,
                                                        const __nv_bfloat16* __restrict__ B_re, const __nv_bfloat16* __restrict__ B_im,
                                                        const __nv_bfloat16* __restrict__ C_re, const __nv_bfloat16* __restrict__ C_im,
                                                        const __nv_bfloat16* __restrict__ log_dt, const __nv_bfloat16* __restrict__ Dskip,
                                                        const __nv_bfloat16* __restrict__ wg, const __nv_bfloat16* __restrict__ wu,
                                                        const __nv_bfloat16* __restrict__ wd) {
    pdl_launch();
    if (threadIdx.x == 0) STAMP(1, 0);
    extern __shared__ __align__(16) uint8_t smem[];
    const int warp = threadIdx.x >> 5, lane = threadIdx.x & 31;
    const int ch = warp >> 2, w = warp & 3, tc = threadIdx.x & 127;
    const int d = blockIdx.x * CV_CH + ch;
    const int g = lane >> 2, t = lane & 3;
    uint8_t* base = smem + ch * CV_PER_CH;
    float4* s_const = reinterpret_cast<float4*>(base + CV_O_CONST);
    float* s_kp = reinterpret_cast<float*>(base + CV_O_KP);
    uint32_t* s_q = reinterpret_cast<uint32_t*>(base + CV_O_Q);
    uint32_t* s_q2 = reinterpret_cast<uint32_t*>(base + CV_O_Q2);
    uint32_t* s_q3 = reinterpret_cast<uint32_t*>(base + CV_O_Q3);
    uint32_t* s_q4 = reinterpret_cast<uint32_t*>(base + CV_O_Q4X);
    __nv_bfloat16* s_u = reinterpret_cast<__nv_bfloat16*>(base + CV_O_U);
    const int bar_id = 1 + ch;

    const int row = blockIdx.x * LN_ROWS + warp;
    const uint4 xv0 = *reinterpret_cast<const uint4*>(x + (size_t)row * D_ + lane * 8);
    const uint4 xv1 = *reinterpret_cast<const uint4*>(x + (size_t)row * D_ + 256 + lane * 8);
    const size_t poff = (size_t)d * NS_ + tc;
    const __nv_bfloat16 p_ar = A_re[poff], p_ai = A_im[poff], p_br = B_re[poff], p_bi = B_im[poff], p_cr = C_re[poff], p_ci = C_im[poff];
    const __nv_bfloat16 p_ldt = log_dt[d], p_dsk = Dskip[d];
    {
        __nv_bfloat16 (*tile)[D_ + 8] = reinterpret_cast<__nv_bfloat16 (*)[D_ + 8]>(smem);
        float f[16];
        const uint32_t wv[8] = {xv0.x, xv0.y, xv0.z, xv0.w, xv1.x, xv1.y, xv1.z, xv1.w};
#pragma unroll
        for (int i = 0; i < 8; i++) { f[2 * i] = bf_lo(wv[i]); f[2 * i + 1] = bf_hi(wv[i]); }
        float sm = 0.f;
#pragma unroll
        for (int i = 0; i < 16; i++) sm += f[i];
#pragma unroll
        for (int o = 16; o > 0; o >>= 1) sm += __shfl_xor_sync(0xffffffffu, sm, o);
        const float mean = sm * (1.0f / D_);
        float q = 0.f;
#pragma unroll
        for (int i = 0; i < 16; i++) { float dd = f[i] - mean; q += dd * dd; }
#pragma unroll
        for (int o = 16; o > 0; o >>= 1) q += __shfl_xor_sync(0xffffffffu, q, o);
        const float mb = bf16_round(mean);
        const float vb = bf16_round(q * (1.0f / D_));
        const float den = bf16_round(sqrtf(bf16_round(vb + 1e-5f)));
        uint32_t o[8];
#pragma unroll
        for (int i = 0; i < 8; i++) {
            float a = __fdiv_rn(bf16_round(f[2 * i] - mb), den);
            float b = __fdiv_rn(bf16_round(f[2 * i + 1] - mb), den);
            o[i] = pack_bf16(a, b);
        }
        __nv_bfloat16* dst = g_xn + (size_t)row * D_;
        *reinterpret_cast<uint4*>(dst + lane * 8) = make_uint4(o[0], o[1], o[2], o[3]);
        *reinterpret_cast<uint4*>(dst + 256 + lane * 8) = make_uint4(o[4], o[5], o[6], o[7]);
        *reinterpret_cast<uint4*>(&tile[warp][lane * 8]) = make_uint4(o[0], o[1], o[2], o[3]);
        *reinterpret_cast<uint4*>(&tile[warp][256 + lane * 8]) = make_uint4(o[4], o[5], o[6], o[7]);
        __syncthreads();
        {
            const int c = threadIdx.x;
            uint32_t ot[8];
#pragma unroll
            for (int i = 0; i < 8; i++) {
                uint32_t lo = *reinterpret_cast<const uint16_t*>(&tile[2 * i][c]);
                uint32_t hi = *reinterpret_cast<const uint16_t*>(&tile[2 * i + 1][c]);
                ot[i] = lo | (hi << 16);
            }
            __nv_bfloat16* dT = g_xnT + (size_t)c * L_ + blockIdx.x * LN_ROWS;
            *reinterpret_cast<uint4*>(dT) = make_uint4(ot[0], ot[1], ot[2], ot[3]);
            *reinterpret_cast<uint4*>(dT + 8) = make_uint4(ot[4], ot[5], ot[6], ot[7]);
        }
        __threadfence();
        __syncthreads();
        if (threadIdx.x == 0) {
            asm volatile("red.release.gpu.global.add.u32 [%0], 1;" ::"l"(&g_ln_count) : "memory");
            STAMP(0, 0);
        }
        if (threadIdx.x < 336) {
            const int m = threadIdx.x / 112, i = threadIdx.x - m * 112;
            const char* wp = (const char*)(m == 0 ? wg : (m == 1 ? wu : wd));
            asm volatile("prefetch.global.L2 [%0];" ::"l"(wp + ((size_t)blockIdx.x * 112 + i) * 128));
        }
    }

    float tail;
    {
        const float dt = bf16_round(expf(__bfloat162float(p_ldt)));
        const float ar = dt * __bfloat162float(p_ar), ai = dt * __bfloat162float(p_ai);
        const cplx db = {dt * __bfloat162float(p_br), dt * __bfloat162float(p_bi)};
        const cplx cc = {__bfloat162float(p_cr), __bfloat162float(p_ci)};
        const cplx cb = cmul(cc, db);
        const float ar2 = ar * 1.4426950408889634f, ai2 = ai * 0.15915494309189535f;
        const cplx e8 = cexp_m(ar2, ai2, 8.f), e128 = cexp_m(ar2, ai2, 128.f);
        const cplx cb8 = cmul(cb, e8);
        const cplx e256 = cexp_m(ar2, ai2, 256.f), e512 = cexp_m(ar2, ai2, 512.f), e1024 = cexp_m(ar2, ai2, 1024.f);
        const cplx c256 = cmul(cb, e256), c512 = cmul(cb, e512), c1024 = cmul(cb, e1024);
        const cplx c768 = cmul(c512, e256), c1280 = cmul(c1024, e256), c1536 = cmul(c1024, e512);
        const cplx c1792 = cmul(c1536, e256);
        tail = cmul(c1024, e1024).r;
        float4* c = s_const + tc * 6;
        c[0] = make_float4(ar2, ai2, cb.r, cb.i);
        c[1] = make_float4(e128.r, e128.i, cb8.r, cb8.i);
        c[2] = make_float4(c256.r, c256.i, e8.r, e8.i);
        c[3] = make_float4(c512.r, c512.i, c768.r, c768.i);
        c[4] = make_float4(c1024.r, c1024.i, c1280.r, c1280.i);
        c[5] = make_float4(c1536.r, c1536.i, c1792.r, c1792.i);
#pragma unroll
        for (int o = 16; o > 0; o >>= 1) tail += __shfl_xor_sync(0xffffffffu, tail, o);
    }
    __syncwarp();
    if (threadIdx.x == 0) STAMP(1, 1);
    {
        float acc[5][4];
#pragma unroll
        for (int i = 0; i < 5; i++) { acc[i][0] = acc[i][1] = acc[i][2] = acc[i][3] = 0.f; }
        const float gf = (float)g;
        const int src4 = ((g & 3) << 2) | t;
#pragma unroll 2
        for (int s = 0; s < 8; s++) {
            const float4* c = s_const + (w * 32 + s * 4 + t) * 6;
            const float4 k0 = c[0], k1 = c[1], k2 = c[2];
            const float2 k3 = reinterpret_cast<const float2*>(c + 3)[g >> 2];
            const float2 k4 = reinterpret_cast<const float2*>(c + 4)[g >> 1];
            const cplx cb = {k0.z, k0.w}, e128 = {k1.x, k1.y}, cb8 = {k1.z, k1.w}, c256 = {k2.x, k2.y}, e8 = {k2.z, k2.w};
            const cplx c2 = {k3.x, k3.y}, c3 = {k4.x, k4.y};
            const cplx p1 = cexp_m(k0.x, k0.y, gf);
            const cplx p2 = csq(p1), p4 = csq(p2);
            const cplx r16a = csq(csq(p4));
            cplx q4;
            q4.r = __shfl_sync(0xffffffffu, p4.r, src4);
            q4.i = __shfl_sync(0xffffffffu, p4.i, src4);
            const cplx r16b = cmul(r16a, e128);
            const cplx f0a = cmul(cb, p1), f0b = cmul(cb8, p1), f1 = cmul(c256, p2), f2 = cmul(c2, q4);
            cplx f3 = cmul(c3, e8);
            if (!(g & 1)) f3 = c3;
            const uint32_t a0 = to_tf32(r16a.r), a1 = to_tf32(r16b.r), a2 = to_tf32(-r16a.i), a3 = to_tf32(-r16b.i);
            mma_tf32(acc[0], a0, a1, a2, a3, to_tf32(f0a.r), to_tf32(f0a.i));
            mma_tf32(acc[1], a0, a1, a2, a3, to_tf32(f0b.r), to_tf32(f0b.i));
            mma_tf32(acc[2], a0, a1, a2, a3, to_tf32(f1.r), to_tf32(f1.i));
            mma_tf32(acc[3], a0, a1, a2, a3, to_tf32(f2.r), to_tf32(f2.i));
            mma_tf32(acc[4], a0, a1, a2, a3, to_tf32(f3.r), to_tf32(f3.i));
        }
        float* kv = s_kp + w * 648;
#pragma unroll
        for (int hh = 0; hh < 2; hh++) {
            const int i = g + 8 * hh;
            *reinterpret_cast<float2*>(kv + 16 * i + 2 * t) = make_float2(acc[0][2 * hh], acc[0][2 * hh + 1]);
            *reinterpret_cast<float2*>(kv + 16 * i + 8 + 2 * t) = make_float2(acc[1][2 * hh], acc[1][2 * hh + 1]);
            *reinterpret_cast<float2*>(kv + 256 + 8 * i + 2 * t) = make_float2(acc[2][2 * hh], acc[2][2 * hh + 1]);
            *reinterpret_cast<float2*>(kv + 384 + 64 * (t >> 1) + 2 * (t & 1) + 4 * i) = make_float2(acc[3][2 * hh], acc[3][2 * hh + 1]);
            *reinterpret_cast<float2*>(kv + 512 + 32 * t + 2 * i) = make_float2(acc[4][2 * hh], acc[4][2 * hh + 1]);
        }
        if (lane == 0) kv[640] = tail;
    }
    named_bar(bar_id, 128);
    if (threadIdx.x == 0) STAMP(1, 2);
#pragma unroll
    for (int i = 0; i < 6; i++) {
        const int idx = tc + 128 * i;
        if (idx < 641) s_kp[idx] = (s_kp[idx] + s_kp[648 + idx]) + (s_kp[1296 + idx] + s_kp[1944 + idx]);
    }
    named_bar(bar_id, 128);
    {
        auto kdir = [&](int l) -> float {
            if (l < 0 || l > 514) return 0.f;
            const int idx = (l < 256) ? l : (l > 512 ? 384 : 128 + ((l + ((l >> 1) & 1)) >> 1));
            return s_kp[idx];
        };
#pragma unroll
        for (int i = 0; i < 5; i++) {
            const int e = tc + 128 * i;
            if (e < 576) s_q[e] = pack_bf16(kdir(e - 16), kdir(e - 17));
        }
        if (tc < 64) {
            const int xx = 1008 + tc;
            const float k1024 = s_kp[512];
            s_q4[tc] = pack_bf16((xx == 1027 || xx == 1028) ? k1024 : 0.f, (xx == 1028 || xx == 1029) ? k1024 : 0.f);
        }
#pragma unroll
        for (int i = 0; i < 2; i++) {
            const int e = tc + 128 * i, a = e >> 6, ii = (e & 63) - 16;
            const int b = 385 + (a >> 1) + 2 * (a & 1);
            const float v0 = (ii >= 0 && ii < 32) ? s_kp[b + 4 * ii] : 0.f;
            const float v1 = (ii >= 1 && ii < 33) ? s_kp[b + 4 * (ii - 1)] : 0.f;
            s_q2[e] = pack_bf16(v0, v1);
        }
#pragma unroll
        for (int i = 0; i < 2; i++) {
            const int e = tc + 128 * i;
            if (e < 192) {
                const int a = e >= 96, jj = e - 96 * a - 16;
                const float v0 = (jj >= 0 && jj < 64) ? s_kp[513 + a + 2 * jj] : 0.f;
                const float v1 = (jj >= 1 && jj < 65) ? s_kp[513 + a + 2 * (jj - 1)] : 0.f;
                s_q3[e] = pack_bf16(v0, v1);
            }
        }
    }
    if (threadIdx.x == 0) STAMP(1, 3);
    if (threadIdx.x == 0) {
        unsigned int v = 0;
        for (int spin = 0; spin < (1 << 22); spin++) {
            asm volatile("ld.acquire.gpu.global.u32 %0, [%1];" : "=r"(v) : "l"(&g_ln_count) : "memory");
            if (v >= gridDim.x) break;
        }
    }
    __syncthreads();
    if (threadIdx.x == 0) STAMP(1, 4);
    {
        if (tc < 16) *reinterpret_cast<uint4*>(s_u + tc * 8) = make_uint4(0, 0, 0, 0);
        const uint4* src = reinterpret_cast<const uint4*>(g_xnT + (size_t)d * L_);
        const uint4 v0 = src[tc], v1 = src[tc + 128];
        *reinterpret_cast<uint4*>(s_u + 128 + tc * 8) = v0;
        *reinterpret_cast<uint4*>(s_u + 128 + (tc + 128) * 8) = v1;
        if (tc < 2) *reinterpret_cast<uint4*>(base + (tc ? CV_O_W5 : CV_O_W3)) = make_uint4(0, 0, 0, 0);
    }
    named_bar(bar_id, 128);
#pragma unroll
    for (int rep = 0; rep < 2; rep++) {
        const int m = tc + 128 * rep;
        if (m < 192) {
            float P[30];
            const uint4* up = reinterpret_cast<const uint4*>(s_u + 128 + 8 * m - 24);
            P[0] = 0.f;
#pragma unroll
            for (int c4 = 0; c4 < 4; c4++) {
                const uint4 v = up[c4];
                const uint32_t ww[4] = {v.x, v.y, v.z, v.w};
#pragma unroll
                for (int j = 0; j < 4; j++) {
                    const int k = c4 * 8 + 2 * j;
                    if (k + 1 <= 29) P[k + 1] = P[k] + bf_lo(ww[j]);
                    if (k + 2 <= 29) P[k + 2] = P[k + 1] + bf_hi(ww[j]);
                }
            }
            uint32_t o3[4], o5[4], o7[4], o9[4];
#pragma unroll
            for (int j = 0; j < 4; j++) {
                const int i = 2 * j;
                o3[j] = pack_bf16(P[i + 22] - P[i + 19], P[i + 23] - P[i + 20]);
                o5[j] = pack_bf16(P[i + 19] - P[i + 14], P[i + 20] - P[i + 15]);
                o7[j] = pack_bf16(P[i + 20] - P[i + 13], P[i + 21] - P[i + 14]);
                o9[j] = pack_bf16(P[i + 13] - P[i + 4], P[i + 14] - P[i + 5]);
            }
            *reinterpret_cast<uint4*>(base + CV_O_W3 + 16 + m * 16) = make_uint4(o3[0], o3[1], o3[2], o3[3]);
            *reinterpret_cast<uint4*>(base + CV_O_W5 + 16 + m * 16) = make_uint4(o5[0], o5[1], o5[2], o5[3]);
            if (m < 128) {
                *reinterpret_cast<uint4*>(base + CV_O_W7 + m * 16) = make_uint4(o7[0], o7[1], o7[2], o7[3]);
                *reinterpret_cast<uint4*>(base + CV_O_W9 + m * 16) = make_uint4(o9[0], o9[1], o9[2], o9[3]);
            }
        }
    }
    if (threadIdx.x == 0) STAMP(1, 5);
    float acc[16][4];
#pragma unroll
    for (int i = 0; i < 16; i++) { acc[i][0] = acc[i][1] = acc[i][2] = acc[i][3] = 0.f; }
    const uint32_t sb_addr = smem_u32(base);
    const int mi = lane >> 3, rowi = lane & 7;
#pragma unroll 1
    for (int rr = 0; rr < 2; rr++) {
        const int r = 2 * w + rr;
        uint32_t ub[16][2];
        {
            const uint32_t addr = sb_addr + CV_O_U + (uint32_t)((128 + 16 * (8 * (mi >> 1) + rowi - r) + 8 * (mi & 1)) * 2);
#pragma unroll
            for (int j = 0; j < 16; j += 2) ldsm_x4(addr + (uint32_t)(j * 256), ub[j][0], ub[j][1], ub[j + 1][0], ub[j + 1][1]);
        }
        const uint32_t* qp = s_q + 16 + 16 * r + g - 2 * t;
#pragma unroll
        for (int q = 0; q < 4; q++) {
            const uint32_t a0 = qp[128 * q], a1 = qp[128 * q + 8], a2 = qp[128 * q - 8];
#pragma unroll
            for (int nt = q; nt < 16; nt++) mma_bf16(acc[nt], a0, a1, a2, a0, ub[nt - q][0], ub[nt - q][1]);
        }
        if (w == 0) {
            {
                const uint32_t a0 = qp[512], a1 = qp[520], a2 = qp[504];
#pragma unroll
                for (int nt = 4; nt < 16; nt++) mma_bf16(acc[nt], a0, a1, a2, a0, ub[nt - 4][0], ub[nt - 4][1]);
            }
            {
                const uint32_t* q4p = s_q4 + 16 + 16 * r + g - 2 * t;
                const uint32_t a0 = q4p[0], a1 = q4p[8], a2 = q4p[-8];
#pragma unroll
                for (int nt = 8; nt < 16; nt++) mma_bf16(acc[nt], a0, a1, a2, a0, ub[nt - 8][0], ub[nt - 8][1]);
            }
        }
    }
    named_bar(bar_id, 128);
    if (w >= 1) {
#pragma unroll 1
        for (int a = (w == 1 ? 0 : w); a <= w; a++) {
            uint32_t bq[7];
            const uint32_t* q2 = s_q2 + a * 64 + 16 + g - 2 * t - 32;
#pragma unroll
            for (int dlt = 3; dlt <= 9; dlt++) bq[dlt - 3] = q2[8 * dlt];
            const uint32_t addr = sb_addr + ((a >> 1) ? CV_O_W5 : CV_O_W3) + (uint32_t)((8 + 16 * (8 * (mi >> 1) + rowi) + 8 * (mi & 1) - 8 * (a & 1)) * 2);
#pragma unroll
            for (int kp = 0; kp < 6; kp++) {
                uint32_t a0, a1, a2, a3;
                ldsm_x4_t(addr + kp * 512, a0, a1, a2, a3);
#pragma unroll
                for (int dlt = 4; dlt <= 9; dlt++) {
                    if (2 * kp + dlt < 16) mma_bf16(acc[2 * kp + dlt], a0, a1, a2, a3, bq[dlt - 3], bq[dlt - 4]);
                }
            }
        }
    }
    if (w >= 2) {
        uint32_t bq[9];
        const uint32_t* q3 = s_q3 + (w - 2) * 96 + 16 + g - 2 * t - 64;
#pragma unroll
        for (int dlt = 7; dlt <= 15; dlt++) bq[dlt - 7] = q3[8 * dlt];
        const uint32_t addr = sb_addr + ((w - 2) ? CV_O_W9 : CV_O_W7) + (uint32_t)((16 * (8 * (mi >> 1) + rowi) + 8 * (mi & 1)) * 2);
#pragma unroll
        for (int kp = 0; kp < 4; kp++) {
            uint32_t a0, a1, a2, a3;
            ldsm_x4_t(addr + kp * 512, a0, a1, a2, a3);
#pragma unroll
            for (int dlt = 8; dlt <= 15; dlt++) {
                if (2 * kp + dlt < 16) mma_bf16(acc[2 * kp + dlt], a0, a1, a2, a3, bq[dlt - 7], bq[dlt - 8]);
            }
        }
    }
    if (threadIdx.x == 0) STAMP(1, 6);
    named_bar(bar_id, 128);
    {
        float4* xch = reinterpret_cast<float4*>(base) + w * 512;
#pragma unroll
        for (int i = 0; i < 16; i++) xch[i * 32 + lane] = make_float4(acc[i][0], acc[i][1], acc[i][2], acc[i][3]);
    }
    named_bar(bar_id, 128);
    {
        const float4* xch = reinterpret_cast<const float4*>(base) + (4 * w) * 32 + lane;
        const float dsk = __bfloat162float(p_dsk);
        uint16_t* stg = reinterpret_cast<uint16_t*>(base + CV_O_STG);
        const uint16_t* uu = reinterpret_cast<const uint16_t*>(s_u) + 128;
#pragma unroll
        for (int i = 0; i < 4; i++) {
            const float4 p0 = xch[i * 32], p1 = xch[512 + i * 32], p2 = xch[1024 + i * 32], p3 = xch[1536 + i * 32];
            const float y[4] = {(p0.x + p1.x) + (p2.x + p3.x), (p0.y + p1.y) + (p2.y + p3.y), (p0.z + p1.z) + (p2.z + p3.z), (p0.w + p1.w) + (p2.w + p3.w)};
            const int nt = 4 * w + i;
#pragma unroll
            for (int e = 0; e < 4; e++) {
                const int tau = 16 * (8 * nt + 2 * t + (e & 1)) + g + 8 * (e >> 1);
                const float sv = bf16_round(y[e]) + bf16_round(__uint_as_float((uint32_t)uu[tau] << 16) * dsk);
                stg[tau] = (uint16_t)(__float_as_uint(bf16_round(sv)) >> 16);
            }
        }
        __syncwarp();
        uint4* dst = reinterpret_cast<uint4*>(g_sT + (size_t)d * L_ + w * 512);
        const uint4* srcp = reinterpret_cast<const uint4*>(stg + w * 512);
        dst[lane] = srcp[lane];
        dst[32 + lane] = srcp[32 + lane];
    }
    if (threadIdx.x == 0) STAMP(1, 7);
}

__device__ __forceinline__ uint32_t cluster_rank() { uint32_t r; asm volatile("mov.u32 %0, %%cluster_ctarank;" : "=r"(r)); return r; }
__device__ __forceinline__ void cluster_sync_all() {
    asm volatile("barrier.cluster.arrive.release.aligned;\nbarrier.cluster.wait.acquire.aligned;" ::: "memory");
}
__device__ __forceinline__ void mbar_arrive_remote(uint32_t bar, uint32_t cta) {
    asm volatile("{\n.reg .b32 ra;\nmapa.shared::cluster.u32 ra, %0, %1;\n"
                 "mbarrier.arrive.shared::cluster.b64 _, [ra];\n}\n" ::"r"(bar), "r"(cta) : "memory");
}
__device__ __forceinline__ void tma_load_2d_mc(uint32_t dst, const CUtensorMap* tm, int c0, int c1, uint32_t bar, uint16_t mask) {
    asm volatile(
        "cp.async.bulk.tensor.2d.shared::cluster.global.mbarrier::complete_tx::bytes.multicast::cluster [%0], [%1, {%3, %4}], [%2], %5;"
        ::"r"(dst), "l"((uint64_t)tm), "r"(bar), "r"(c0), "r"(c1), "h"(mask) : "memory");
}
__device__ __forceinline__ void tma_store_2d(const CUtensorMap* tm, uint32_t src, int c0, int c1) {
    asm volatile("cp.async.bulk.tensor.2d.global.shared::cta.bulk_group [%0, {%2, %3}], [%1];"
                 ::"l"((uint64_t)tm), "r"(src), "r"(c0), "r"(c1) : "memory");
}
__device__ __forceinline__ void bulk_commit() { asm volatile("cp.async.bulk.commit_group;" ::: "memory"); }
template <int N> __device__ __forceinline__ void bulk_wait_read() { asm volatile("cp.async.bulk.wait_group.read %0;" ::"n"(N) : "memory"); }
template <int N> __device__ __forceinline__ void bulk_wait() { asm volatile("cp.async.bulk.wait_group %0;" ::"n"(N) : "memory"); }
__device__ __forceinline__ void fence_async_smem() { asm volatile("fence.proxy.async.shared::cta;" ::: "memory"); }
__device__ __forceinline__ void stmatrix_x4(uint32_t addr, uint32_t r0, uint32_t r1, uint32_t r2, uint32_t r3) {
    asm volatile("stmatrix.sync.aligned.m8n8.x4.shared.b16 [%0], {%1,%2,%3,%4};" ::"r"(addr), "r"(r0), "r"(r1), "r"(r2), "r"(r3) : "memory");
}

constexpr int G1_STAGES = 5;
constexpr int G1_A_BYTES = 8 * 16384;
constexpr int G1_B_STAGE = 16384;
constexpr int G1_STG = 8 * 1024;
constexpr int G1_SMEM = G1_A_BYTES + G1_STAGES * G1_B_STAGE + G1_STG + 1024 + 256;
constexpr int G1_ITERS = 32;

__device__ __forceinline__ void tma_load_3d(uint32_t dst, const CUtensorMap* tm, int c0, int c1, int c2, uint32_t bar) {
    asm volatile(
        "cp.async.bulk.tensor.3d.shared::cluster.global.mbarrier::complete_tx::bytes [%0], [%1, {%3, %4, %5}], [%2];"
        ::"r"(dst), "l"((uint64_t)tm), "r"(bar), "r"(c0), "r"(c1), "r"(c2) : "memory");
}

__device__ __forceinline__ float gelu_tanh(float x) {
    float u = x * (0.7978845608028654f + 0.035677408136300125f * x * x);
    float t; asm("tanh.approx.f32 %0, %1;" : "=f"(t) : "f"(u));
    float hx = 0.5f * x;
    return fmaf(hx, t, hx);
}
__device__ __forceinline__ uint32_t geglu_pair(uint32_t g2, uint32_t u2) {
    uint32_t a = pack_bf16(gelu_tanh(bf_lo(g2)), gelu_tanh(bf_hi(g2)));
    uint32_t r; asm("mul.rn.bf16x2 %0, %1, %2;" : "=r"(r) : "r"(a), "r"(u2));
    return r;
}

__global__ void __launch_bounds__(384, 1) gemm1_kernel(const __grid_constant__ CUtensorMap tm_xn,
                                                        const __grid_constant__ CUtensorMap tm_wg4,
                                                        const __grid_constant__ CUtensorMap tm_wu4,
                                                        const __grid_constant__ CUtensorMap tm_wg3,
                                                        const __grid_constant__ CUtensorMap tm_wu3,
                                                        const __grid_constant__ CUtensorMap tm_hst,
                                                        const __grid_constant__ CUtensorMap tm_hst96) {
    pdl_launch();
    if (threadIdx.x == 0) STAMP(2, 0);
    extern __shared__ uint8_t smem_raw[];
    const uint32_t sbase = (smem_u32(smem_raw) + 1023) & ~1023u;
    const uint32_t sA = sbase, sB = sbase + G1_A_BYTES, sStg = sB + G1_STAGES * G1_B_STAGE, sBar = sStg + G1_STG;
    const uint32_t bar_a = sBar, bar_full = sBar + 64, bar_empty = sBar + 64 + 8 * G1_STAGES;
    const int rb = blockIdx.x >> 3, cj = blockIdx.x & 7;
    const int warp = threadIdx.x >> 5, lane = threadIdx.x & 31;

    if (threadIdx.x == 0) {
        for (int i = 0; i < 8; i++) mbar_init(bar_a + 8 * i, 1);
        for (int i = 0; i < G1_STAGES; i++) { mbar_init(bar_full + 8 * i, 1); mbar_init(bar_empty + 8 * i, 8); }
        asm volatile("fence.mbarrier_init.release.cluster;" ::: "memory");
    }
    __syncthreads();

    if (warp >= 8) {
        asm volatile("setmaxnreg.dec.sync.aligned.u32 40;");
        if (lane == 0) {
            const int pw = warp - 8;
            if (pw == 0) { prefetch_tmap(&tm_wg4); prefetch_tmap(&tm_wu4); prefetch_tmap(&tm_xn); }
            if (pw == 1) { prefetch_tmap(&tm_wg3); prefetch_tmap(&tm_wu3); prefetch_tmap(&tm_hst); prefetch_tmap(&tm_hst96); }
            for (int it = pw; it < G1_ITERS; it += 4) {
                const int s = it % G1_STAGES, kb = it & 15;
                if (it >= G1_STAGES) mbar_wait(bar_empty + 8 * s, ((it / G1_STAGES) - 1) & 1);
                const uint32_t dst = sB + s * G1_B_STAGE;
                if (it < 16) {
                    mbar_expect_tx(bar_full + 8 * s, 16384);
                    tma_load_3d(dst, &tm_wg4, 0, kb * 32, cj * 7, bar_full + 8 * s);
                    tma_load_3d(dst + 8192, &tm_wu4, 0, kb * 32, cj * 7, bar_full + 8 * s);
                } else {
                    mbar_expect_tx(bar_full + 8 * s, 12288);
                    tma_load_3d(dst, &tm_wg3, 0, kb * 32, cj * 7 + 4, bar_full + 8 * s);
                    tma_load_3d(dst + 6144, &tm_wu3, 0, kb * 32, cj * 7 + 4, bar_full + 8 * s);
                }
                if (it < 4) {
                    pdl_wait();
                    if (pw == 0) { STAMP(2, 1); if (blockIdx.x == 0) g_ln_count = 0; }
                    for (int k = pw; k < 8; k += 4) {
                        mbar_expect_tx(bar_a + 8 * k, 16384);
                        tma_load_2d(sA + k * 16384, &tm_xn, k * 64, rb * 128, bar_a + 8 * k);
                    }
                }
            }
        }
    } else {
        asm volatile("setmaxnreg.inc.sync.aligned.u32 232;");
        const int wg = __shfl_sync(0xffffffffu, (int)(threadIdx.x >> 7), 0);
        float r[160];
        const int row0 = rb * 128 + wg * 64 + (warp & 3) * 16;
        const uint64_t descA = make_desc(sA + wg * 8192, 16, 1024);
        const uint64_t descB = make_desc(sB, 2048, 512, 2);
        const uint32_t stg = sStg + warp * 1024;
        const uint32_t st_off = (uint32_t)(((lane & 7) + ((lane >> 3) & 1) * 8) * 32 + (lane >> 4) * 16);
        __nv_bfloat16* hrow = g_h + (size_t)(row0 + (lane >> 1)) * F_ + (lane & 1) * 8 + cj * 224;
#pragma unroll
        for (int kb = 0; kb < 16; kb++) {
            const int it = kb, s = it % G1_STAGES;
            if ((kb & 1) == 0) mbar_wait(bar_a + 8 * (kb >> 1), 0);
            mbar_wait(bar_full + 8 * s, (it / G1_STAGES) & 1);
            if (threadIdx.x == 0 && (it & 7) == 0) STAMP(2, 2 + it / 8);
            wgmma_fence();
            const uint64_t da = descA + (uint64_t)(((kb >> 1) * 16384 + (kb & 1) * 64) >> 4);
            const uint64_t db = descB + (uint64_t)((s * G1_B_STAGE) >> 4);
            wgmma_n256_k32(r, da, da + 2, db, db + 64, kb != 0);
            wgmma_commit();
            if (kb > 0) {
                wgmma_wait<1>();
                if (lane == 0) mbar_arrive(bar_empty + 8 * ((it - 1) % G1_STAGES));
            }
        }
        wgmma_wait<0>();
        if (lane == 0) mbar_arrive(bar_empty + 8 * (15 % G1_STAGES));
#pragma unroll
        for (int i = 0; i < 32; i++) r[128 + i] = __uint_as_float(pack_bf16(r[2 * i], r[2 * i + 1]));
#pragma unroll
        for (int i = 31; i >= 0; i--) r[96 + i] = __uint_as_float(pack_bf16(r[64 + 2 * i], r[65 + 2 * i]));
        uint32_t eo[4];
        uint4 pv = make_uint4(0, 0, 0, 0);
#pragma unroll
        for (int kb = 0; kb < 16; kb++) {
            const int it = 16 + kb, s = it % G1_STAGES;
            mbar_wait(bar_full + 8 * s, (it / G1_STAGES) & 1);
            if (threadIdx.x == 0 && (it & 7) == 0) STAMP(2, 2 + it / 8);
            wgmma_fence();
            const uint64_t da = descA + (uint64_t)(((kb >> 1) * 16384 + (kb & 1) * 64) >> 4);
            const uint64_t db = descB + (uint64_t)((s * G1_B_STAGE) >> 4);
            const int jj = kb >> 1;
            wgmma_n192(r, da, db, kb != 0);
            eo[(kb & 1) * 2] = geglu_pair(__float_as_uint(r[128 + 2 * kb]), __float_as_uint(r[96 + 2 * kb]));
            wgmma_n192(r, da + 2, db + 64, 1);
            wgmma_commit();
            eo[(kb & 1) * 2 + 1] = geglu_pair(__float_as_uint(r[129 + 2 * kb]), __float_as_uint(r[97 + 2 * kb]));
            if (kb & 1) {
                if (jj > 0) *reinterpret_cast<uint4*>(hrow + (jj - 1) * 16) = pv;
                stmatrix_x4(stg + (jj & 1) * 512 + st_off, eo[0], eo[1], eo[2], eo[3]);
            } else if (jj > 0) {
                __syncwarp();
                asm volatile("ld.shared.v4.u32 {%0,%1,%2,%3}, [%4];" : "=r"(pv.x), "=r"(pv.y), "=r"(pv.z), "=r"(pv.w)
                             : "r"(stg + ((jj - 1) & 1) * 512 + lane * 16));
            }
            if (kb > 0 && it - 1 + G1_STAGES < G1_ITERS) {
                wgmma_wait<1>();
                if (lane == 0) mbar_arrive(bar_empty + 8 * ((it - 1) % G1_STAGES));
            }
        }
        __syncwarp();
        asm volatile("ld.shared.v4.u32 {%0,%1,%2,%3}, [%4];" : "=r"(pv.x), "=r"(pv.y), "=r"(pv.z), "=r"(pv.w) : "r"(stg + 512 + lane * 16));
        wgmma_wait<0>();
        *reinterpret_cast<uint4*>(hrow + 7 * 16) = pv;
        if (threadIdx.x == 0) STAMP(2, 6);
        {
            uint32_t o[24];
#pragma unroll
            for (int i = 0; i < 24; i++) o[i] = geglu_pair(pack_bf16(r[2 * i], r[2 * i + 1]), pack_bf16(r[48 + 2 * i], r[49 + 2 * i]));
            named_bar(1 + wg, 128);
            const uint32_t fbuf = sA + ((warp & 3) >> 1) * 16384 + wg * 8192 + (warp & 1) * 4096;
#pragma unroll
            for (int jj = 0; jj < 6; jj++) stmatrix_x4(fbuf + jj * 512 + st_off, o[4 * jj], o[4 * jj + 1], o[4 * jj + 2], o[4 * jj + 3]);
            __syncwarp();
            uint4 v[6];
#pragma unroll
            for (int jj = 0; jj < 6; jj++)
                asm volatile("ld.shared.v4.u32 {%0,%1,%2,%3}, [%4];" : "=r"(v[jj].x), "=r"(v[jj].y), "=r"(v[jj].z), "=r"(v[jj].w)
                             : "r"(fbuf + jj * 512 + lane * 16));
#pragma unroll
            for (int jj = 0; jj < 6; jj++) *reinterpret_cast<uint4*>(hrow + 128 + jj * 16) = v[jj];
        }
        if (threadIdx.x == 0) STAMP(2, 7);
    }
}

constexpr int G2_STAGES = 5;
constexpr int G2_STAGE = 16384 + 16384;
constexpr int G2_XCH = 32768;
constexpr int G2_EPI = 16384 + 16384;
constexpr int G2_SMEM = G2_STAGES * G2_STAGE + G2_XCH + G2_EPI + 1024 + 256;
constexpr int G2_KB = F_ / 64 / 2;

__global__ void __launch_bounds__(384, 1) gemm2_kernel(const __grid_constant__ CUtensorMap tm_h,
                                                        const __grid_constant__ CUtensorMap tm_wd,
                                                        const __grid_constant__ CUtensorMap tm_x,
                                                        const __grid_constant__ CUtensorMap tm_sT,
                                                        const __grid_constant__ CUtensorMap tm_out) {
    if (threadIdx.x == 0) STAMP(3, 0);
    extern __shared__ uint8_t smem_raw[];
    const uint32_t sbase = (smem_u32(smem_raw) + 1023) & ~1023u;
    const uint32_t sXch = sbase + G2_STAGES * G2_STAGE, sX = sXch + G2_XCH, sS = sX + 16384, sBar = sX + G2_EPI;
    const uint32_t bar_full = sBar, bar_empty = sBar + 8 * G2_STAGES, bar_epi = sBar + 16 * G2_STAGES, bar_xch = bar_epi + 8;
    const uint32_t kh = cluster_rank();
    const int cid = blockIdx.x >> 1;
    const int rb = cid >> 2, nb = cid & 3;
    const int col_fin = nb * 128 + kh * 64;
    const int warp = threadIdx.x >> 5, lane = threadIdx.x & 31;

    if (threadIdx.x == 0) {
        for (int i = 0; i < G2_STAGES; i++) { mbar_init(bar_full + 8 * i, 1); mbar_init(bar_empty + 8 * i, 8); }
        mbar_init(bar_epi, 1);
        mbar_init(bar_xch, 1);
        asm volatile("fence.mbarrier_init.release.cluster;" ::: "memory");
        mbar_expect_tx(bar_xch, G2_XCH);
    }
    cluster_sync_all();

    if (warp >= 8) {
        if (lane == 0) {
            const int pw = warp - 8;
            const int k0 = kh * G2_KB;
            if (pw == 0) { prefetch_tmap(&tm_wd); prefetch_tmap(&tm_h); }
            if (pw == 1) { prefetch_tmap(&tm_x); prefetch_tmap(&tm_sT); prefetch_tmap(&tm_out); }
            for (int it = pw; it < G2_STAGES; it += 4) {
                mbar_expect_tx(bar_full + 8 * it, G2_STAGE);
                tma_load_3d(sbase + it * G2_STAGE + 16384, &tm_wd, 0, (k0 + it) * 64, nb * 2, bar_full + 8 * it);
            }
            if (pw == 3) {
                mbar_expect_tx(bar_epi, G2_EPI);
                tma_load_2d(sX, &tm_x, col_fin, rb * 128, bar_epi);
            }
            pdl_wait();
            if (pw == 0) STAMP(3, 1);
            for (int it = pw; it < G2_STAGES; it += 4)
                tma_load_2d(sbase + it * G2_STAGE, &tm_h, (k0 + it) * 64, rb * 128, bar_full + 8 * it);
            if (pw == 3) {
                tma_load_2d(sS, &tm_sT, rb * 128, col_fin, bar_epi);
                tma_load_2d(sS + 8192, &tm_sT, rb * 128 + 64, col_fin, bar_epi);
            }
            for (int it = G2_STAGES + ((pw + 4 - (G2_STAGES & 3)) & 3); it < G2_KB; it += 4) {
                const int s = it % G2_STAGES;
                mbar_wait(bar_empty + 8 * s, ((it / G2_STAGES) - 1) & 1);
                mbar_expect_tx(bar_full + 8 * s, G2_STAGE);
                tma_load_2d(sbase + s * G2_STAGE, &tm_h, (k0 + it) * 64, rb * 128, bar_full + 8 * s);
                tma_load_3d(sbase + s * G2_STAGE + 16384, &tm_wd, 0, (k0 + it) * 64, nb * 2, bar_full + 8 * s);
            }
        }
    } else {
        const int wg = __shfl_sync(0xffffffffu, (int)(threadIdx.x >> 7), 0);
        const int g = lane >> 2, t = lane & 3;
        float acc[64];
        const uint64_t descA = make_desc(sbase + wg * 8192, 16, 1024);
        const uint64_t descB = make_desc(sbase + 16384, 8192, 1024);
#pragma unroll
        for (int it = 0; it < G2_KB; it++) {
            const int s = it % G2_STAGES;
            mbar_wait(bar_full + 8 * s, (it / G2_STAGES) & 1);
            if (threadIdx.x == 0 && (it == 0 || it == 7)) STAMP(3, 2 + it / 7);
            wgmma_fence();
            {
                const uint64_t da = descA + (uint64_t)((s * G2_STAGE) >> 4);
                const uint64_t db = descB + (uint64_t)((s * G2_STAGE) >> 4);
                wgmma_n128_k64(acc, da, da + 2, da + 4, da + 6, db, db + 128, db + 256, db + 384, it != 0);
            }
            wgmma_commit();
            if (it > 0 && it - 1 + G2_STAGES < G2_KB) {
                wgmma_wait<1>();
                if (lane == 0) mbar_arrive(bar_empty + 8 * ((it - 1) % G2_STAGES));
            }
        }
        const int lr = wg * 64 + (warp & 3) * 16 + g;
        uint32_t xv[16], sv[16];
        mbar_wait(bar_epi, 0);
#pragma unroll
        for (int j = 0; j < 8; j++) {
#pragma unroll
            for (int hh = 0; hh < 2; hh++) {
                const int r = lr + 8 * hh;
                asm volatile("ld.shared.u32 %0, [%1];" : "=r"(xv[2 * j + hh]) : "r"(sX + r * 128 + ((j ^ (r & 7)) << 4) + 4 * t));
                const int c0 = 8 * j + 2 * t;
                const uint32_t sa = sS + (r >> 6) * 8192 + (((r & 63) >> 3) << 4) + (r & 7) * 2;
                uint16_t s0r, s1r;
                asm volatile("ld.shared.u16 %0, [%1];" : "=h"(s0r) : "r"((sa + c0 * 128) ^ ((c0 & 7) << 4)));
                asm volatile("ld.shared.u16 %0, [%1];" : "=h"(s1r) : "r"((sa + (c0 + 1) * 128) ^ (((c0 + 1) & 7) << 4)));
                sv[2 * j + hh] = (uint32_t)s0r | ((uint32_t)s1r << 16);
            }
        }
        wgmma_wait<0>();
        if (threadIdx.x == 0) STAMP(3, 4);
        {
            uint32_t remote, rbar;
            asm volatile("mapa.shared::cluster.u32 %0, %1, %2;" : "=r"(remote) : "r"(sXch + threadIdx.x * 16), "r"(kh ^ 1));
            asm volatile("mapa.shared::cluster.u32 %0, %1, %2;" : "=r"(rbar) : "r"(bar_xch), "r"(kh ^ 1));
            if (kh == 0) {
#pragma unroll
                for (int i = 0; i < 8; i++)
                    asm volatile("st.async.shared::cluster.mbarrier::complete_tx::bytes.v4.f32 [%0], {%1,%2,%3,%4}, [%5];" ::"r"(remote + i * 4096),
                                 "f"(acc[32 + 4 * i]), "f"(acc[33 + 4 * i]), "f"(acc[34 + 4 * i]), "f"(acc[35 + 4 * i]), "r"(rbar) : "memory");
            } else {
#pragma unroll
                for (int i = 0; i < 8; i++)
                    asm volatile("st.async.shared::cluster.mbarrier::complete_tx::bytes.v4.f32 [%0], {%1,%2,%3,%4}, [%5];" ::"r"(remote + i * 4096),
                                 "f"(acc[4 * i]), "f"(acc[1 + 4 * i]), "f"(acc[2 + 4 * i]), "f"(acc[3 + 4 * i]), "r"(rbar) : "memory");
#pragma unroll
                for (int i = 0; i < 32; i++) acc[i] = acc[32 + i];
            }
        }
        if (threadIdx.x == 0) STAMP(3, 6);
        mbar_wait(bar_xch, 0);
        if (threadIdx.x == 0) STAMP(3, 7);
#pragma unroll
        for (int j = 0; j < 8; j++) {
            float4 o;
            asm volatile("ld.shared.v4.f32 {%0,%1,%2,%3}, [%4];" : "=f"(o.x), "=f"(o.y), "=f"(o.z), "=f"(o.w) : "r"(sXch + threadIdx.x * 16 + j * 4096));
            acc[4 * j] += o.x; acc[4 * j + 1] += o.y; acc[4 * j + 2] += o.z; acc[4 * j + 3] += o.w;
        }
#pragma unroll
        for (int i = 0; i < 16; i++) {
            float f0 = bf16_round(acc[2 * i]), f1 = bf16_round(acc[2 * i + 1]);
            float g0 = bf16_round(__fdividef(f0, 1.0f + __expf(-f0)));
            float g1 = bf16_round(__fdividef(f1, 1.0f + __expf(-f1)));
            float o0 = bf_lo(xv[i]) + bf16_round(bf_lo(sv[i]) * g0);
            float o1 = bf_hi(xv[i]) + bf16_round(bf_hi(sv[i]) * g1);
            xv[i] = pack_bf16(o0, o1);
        }
#pragma unroll
        for (int j = 0; j < 8; j++) {
#pragma unroll
            for (int hh = 0; hh < 2; hh++) {
                const int r = lr + 8 * hh;
                asm volatile("st.shared.u32 [%0], %1;" ::"r"(sX + r * 128 + ((j ^ (r & 7)) << 4) + 4 * t), "r"(xv[2 * j + hh]) : "memory");
            }
        }
        if (threadIdx.x == 0) STAMP(3, 9);
        fence_async_smem();
        __syncwarp();
        if (lane == 0) {
            tma_store_2d(&tm_out, sX + (wg * 64 + (warp & 3) * 16) * 128, col_fin, rb * 128 + wg * 64 + (warp & 3) * 16);
            bulk_commit();
            bulk_wait_read<0>();
        }
        if (threadIdx.x == 0) STAMP(3, 5);
    }
}

typedef CUresult (*EncodeFn)(CUtensorMap*, CUtensorMapDataType, cuuint32_t, void*, const cuuint64_t*, const cuuint64_t*,
                             const cuuint32_t*, const cuuint32_t*, CUtensorMapInterleave, CUtensorMapSwizzle,
                             CUtensorMapL2promotion, CUtensorMapFloatOOBfill);

void make_map(EncodeFn fn, CUtensorMap* m, const void* ptr, uint64_t inner, uint64_t outer, uint32_t box_in, uint32_t box_out,
              CUtensorMapSwizzle swz = CU_TENSOR_MAP_SWIZZLE_128B) {
    cuuint64_t dims[2] = {inner, outer};
    cuuint64_t strides[1] = {inner * 2};
    cuuint32_t box[2] = {box_in, box_out};
    cuuint32_t es[2] = {1, 1};
    fn(m, CU_TENSOR_MAP_DATA_TYPE_BFLOAT16, 2, const_cast<void*>(ptr), dims, strides, box, es, CU_TENSOR_MAP_INTERLEAVE_NONE,
       swz, CU_TENSOR_MAP_L2_PROMOTION_L2_256B, CU_TENSOR_MAP_FLOAT_OOB_FILL_NONE);
}
void make_map3(EncodeFn fn, CUtensorMap* m, const void* ptr, uint64_t cols, uint64_t rows, uint32_t atom, uint32_t box_rows,
               uint32_t box_atoms, CUtensorMapSwizzle swz) {
    cuuint64_t dims[3] = {atom, rows, cols / atom};
    cuuint64_t strides[2] = {cols * 2, (cuuint64_t)atom * 2};
    cuuint32_t box[3] = {atom, box_rows, box_atoms};
    cuuint32_t es[3] = {1, 1, 1};
    fn(m, CU_TENSOR_MAP_DATA_TYPE_BFLOAT16, 3, const_cast<void*>(ptr), dims, strides, box, es, CU_TENSOR_MAP_INTERLEAVE_NONE,
       swz, CU_TENSOR_MAP_L2_PROMOTION_L2_256B, CU_TENSOR_MAP_FLOAT_OOB_FILL_NONE);
}

template <typename... Args>
void launch_pdl(void (*kern)(Args...), int grid, int block, int smem, bool pdl, int cluster, Args... args) {
    cudaLaunchConfig_t cfg = {};
    cfg.gridDim = dim3(grid); cfg.blockDim = dim3(block); cfg.dynamicSmemBytes = smem; cfg.stream = cudaStreamPerThread;
    cudaLaunchAttribute at[2];
    int n = 0;
    if (pdl) {
        at[n].id = cudaLaunchAttributeProgrammaticStreamSerialization;
        at[n].val.programmaticStreamSerializationAllowed = 1;
        n++;
    }
    if (cluster > 1) {
        at[n].id = cudaLaunchAttributeClusterDimension;
        at[n].val.clusterDim.x = cluster; at[n].val.clusterDim.y = 1; at[n].val.clusterDim.z = 1;
        n++;
    }
    cfg.attrs = at; cfg.numAttrs = n;
    cudaLaunchKernelEx(&cfg, kern, args...);
}

}

extern "C" void kernel_launch(void* const* d_in, const int* in_sizes, int n_in, void* d_out, int out_size) {
    const __nv_bfloat16* x = (const __nv_bfloat16*)d_in[0];
    const __nv_bfloat16* A_re = (const __nv_bfloat16*)d_in[1];
    const __nv_bfloat16* A_im = (const __nv_bfloat16*)d_in[2];
    const __nv_bfloat16* B_re = (const __nv_bfloat16*)d_in[3];
    const __nv_bfloat16* B_im = (const __nv_bfloat16*)d_in[4];
    const __nv_bfloat16* C_re = (const __nv_bfloat16*)d_in[5];
    const __nv_bfloat16* C_im = (const __nv_bfloat16*)d_in[6];
    const __nv_bfloat16* log_dt = (const __nv_bfloat16*)d_in[7];
    const __nv_bfloat16* Dskip = (const __nv_bfloat16*)d_in[8];
    const __nv_bfloat16* wg = (const __nv_bfloat16*)d_in[10];
    const __nv_bfloat16* wu = (const __nv_bfloat16*)d_in[11];
    const __nv_bfloat16* wd = (const __nv_bfloat16*)d_in[12];
    __nv_bfloat16* out = (__nv_bfloat16*)d_out;

    static bool init = false;
    static CUtensorMap tm_xn, tm_wg4, tm_wu4, tm_wg3, tm_wu3, tm_hst, tm_hst96, tm_h, tm_wd, tm_x, tm_sT, tm_out;
    static const void* last_ptrs[5] = {nullptr, nullptr, nullptr, nullptr, nullptr};
    if (!init || last_ptrs[0] != wg || last_ptrs[1] != wu || last_ptrs[2] != wd || last_ptrs[3] != x || last_ptrs[4] != out) {
        void* fnp = nullptr;
        cudaDriverEntryPointQueryResult qres;
        cudaGetDriverEntryPoint("cuTensorMapEncodeTiled", &fnp, cudaEnableDefault, &qres);
        EncodeFn fn = (EncodeFn)fnp;
        void *p_xn, *p_h, *p_sT;
        cudaGetSymbolAddress(&p_xn, g_xn);
        cudaGetSymbolAddress(&p_h, g_h);
        cudaGetSymbolAddress(&p_sT, g_sT);
        make_map(fn, &tm_xn, p_xn, D_, L_, 64, 128);
        make_map3(fn, &tm_wg4, wg, F_, D_, 32, 32, 4, CU_TENSOR_MAP_SWIZZLE_64B);
        make_map3(fn, &tm_wu4, wu, F_, D_, 32, 32, 4, CU_TENSOR_MAP_SWIZZLE_64B);
        make_map3(fn, &tm_wg3, wg, F_, D_, 32, 32, 3, CU_TENSOR_MAP_SWIZZLE_64B);
        make_map3(fn, &tm_wu3, wu, F_, D_, 32, 32, 3, CU_TENSOR_MAP_SWIZZLE_64B);
        make_map(fn, &tm_hst, p_h, F_, L_, 16, 16, CU_TENSOR_MAP_SWIZZLE_NONE);
        make_map(fn, &tm_hst96, p_h, F_, L_, 96, 16, CU_TENSOR_MAP_SWIZZLE_NONE);
        make_map(fn, &tm_h, p_h, F_, L_, 64, 128);
        make_map3(fn, &tm_wd, wd, D_, F_, 64, 64, 2, CU_TENSOR_MAP_SWIZZLE_128B);
        make_map(fn, &tm_x, x, D_, L_, 64, 128);
        make_map(fn, &tm_sT, p_sT, L_, D_, 64, 64);
        make_map(fn, &tm_out, out, D_, L_, 64, 16);
        cudaFuncSetAttribute(front_kernel, cudaFuncAttributeMaxDynamicSharedMemorySize, CV_SMEM);
        cudaFuncSetAttribute(gemm1_kernel, cudaFuncAttributeMaxDynamicSharedMemorySize, G1_SMEM);
        cudaFuncSetAttribute(gemm2_kernel, cudaFuncAttributeMaxDynamicSharedMemorySize, G2_SMEM);
        last_ptrs[0] = wg; last_ptrs[1] = wu; last_ptrs[2] = wd; last_ptrs[3] = x; last_ptrs[4] = out;
        init = true;
    }
    launch_pdl(front_kernel, D_ / CV_CH, 512, CV_SMEM, false, 1, x, A_re, A_im, B_re, B_im, C_re, C_im, log_dt, Dskip, wg, wu, wd);
    launch_pdl(gemm1_kernel, 128, 384, G1_SMEM, true, 1, tm_xn, tm_wg4, tm_wu4, tm_wg3, tm_wu3, tm_hst, tm_hst96);
    launch_pdl(gemm2_kernel, 128, 384, G2_SMEM, true, 2, tm_h, tm_wd, tm_x, tm_sT, tm_out);
}
```

```cpp
#include <cuda_runtime.h>
#include <cuda_bf16.h>
#include <cuda.h>
#include <stdint.h>

namespace {

constexpr int L_ = 2048, D_ = 512, NS_ = 128, F_ = 1792;

__device__ __align__(1024) __nv_bfloat16 g_xn[L_ * D_];
__device__ __align__(1024) __nv_bfloat16 g_xnT[D_ * L_];
__device__ __align__(1024) __nv_bfloat16 g_sT[D_ * L_];
__device__ __align__(1024) __nv_bfloat16 g_h[L_ * F_];
__device__ unsigned int g_ln_count;

#define STAMP(k, i)

__device__ __forceinline__ uint32_t smem_u32(const void* p) { return (uint32_t)__cvta_generic_to_shared(p); }
__device__ __forceinline__ void pdl_wait() { asm volatile("griddepcontrol.wait;" ::: "memory"); }
__device__ __forceinline__ void pdl_launch() { asm volatile("griddepcontrol.launch_dependents;" ::: "memory"); }

__device__ __forceinline__ void mbar_init(uint32_t bar, uint32_t cnt) {
    asm volatile("mbarrier.init.shared::cta.b64 [%0], %1;" ::"r"(bar), "r"(cnt) : "memory");
}
__device__ __forceinline__ void mbar_expect_tx(uint32_t bar, uint32_t bytes) {
    asm volatile("mbarrier.arrive.expect_tx.shared::cta.b64 _, [%0], %1;" ::"r"(bar), "r"(bytes) : "memory");
}
__device__ __forceinline__ void mbar_arrive(uint32_t bar) {
    asm volatile("mbarrier.arrive.shared::cta.b64 _, [%0];" ::"r"(bar) : "memory");
}
__device__ __forceinline__ void mbar_wait(uint32_t bar, uint32_t parity) {
    asm volatile(
        "{\n.reg .pred p;\n"
        "WAIT_LOOP:\n"
        "mbarrier.try_wait.parity.shared::cta.b64 p, [%0], %1;\n"
        "@p bra WAIT_DONE;\n"
        "bra WAIT_LOOP;\n"
        "WAIT_DONE:\n}\n" ::"r"(bar), "r"(parity) : "memory");
}
__device__ __forceinline__ void tma_load_2d(uint32_t dst, const CUtensorMap* tm, int c0, int c1, uint32_t bar) {
    asm volatile(
        "cp.async.bulk.tensor.2d.shared::cluster.global.mbarrier::complete_tx::bytes [%0], [%1, {%3, %4}], [%2];"
        ::"r"(dst), "l"((uint64_t)tm), "r"(bar), "r"(c0), "r"(c1) : "memory");
}
__device__ __forceinline__ void prefetch_tmap(const CUtensorMap* tm) {
    asm volatile("prefetch.tensormap [%0];" ::"l"((uint64_t)tm) : "memory");
}
__device__ __forceinline__ uint64_t make_desc(uint32_t addr, uint32_t lbo, uint32_t sbo, uint64_t mode = 1) {
    uint64_t d = 0;
    d |= (uint64_t)((addr & 0x3FFFF) >> 4);
    d |= (uint64_t)((lbo >> 4) & 0x3FFF) << 16;
    d |= (uint64_t)((sbo >> 4) & 0x3FFF) << 32;
    d |= mode << 62;
    return d;
}
__device__ __forceinline__ void wgmma_fence() { asm volatile("wgmma.fence.sync.aligned;" ::: "memory"); }
__device__ __forceinline__ void wgmma_commit() { asm volatile("wgmma.commit_group.sync.aligned;" ::: "memory"); }
template <int N> __device__ __forceinline__ void wgmma_wait() {
    asm volatile("wgmma.wait_group.sync.aligned %0;" ::"n"(N) : "memory");
}

#define R8(a, i) "+f"(a[i + 0]), "+f"(a[i + 1]), "+f"(a[i + 2]), "+f"(a[i + 3]), "+f"(a[i + 4]), "+f"(a[i + 5]), "+f"(a[i + 6]), "+f"(a[i + 7])

__device__ __forceinline__ void wgmma_n256_k32(float* a, uint64_t da0, uint64_t da1, uint64_t db0, uint64_t db1, int scale_d) {
    asm volatile(
        "{\n.reg .pred p;\nsetp.ne.b32 p, %132, 0;\n"
        "wgmma.mma_async.sync.aligned.m64n256k16.f32.bf16.bf16 {%0,%1,%2,%3,%4,%5,%6,%7,%8,%9,%10,%11,%12,%13,%14,%15,%16,%17,%18,%19,%20,%21,%22,%23,%24,%25,%26,%27,%28,%29,%30,%31,%32,%33,%34,%35,%36,%37,%38,%39,%40,%41,%42,%43,%44,%45,%46,%47,%48,%49,%50,%51,%52,%53,%54,%55,%56,%57,%58,%59,%60,%61,%62,%63,%64,%65,%66,%67,%68,%69,%70,%71,%72,%73,%74,%75,%76,%77,%78,%79,%80,%81,%82,%83,%84,%85,%86,%87,%88,%89,%90,%91,%92,%93,%94,%95,%96,%97,%98,%99,%100,%101,%102,%103,%104,%105,%106,%107,%108,%109,%110,%111,%112,%113,%114,%115,%116,%117,%118,%119,%120,%121,%122,%123,%124,%125,%126,%127}, %128, %130, p, 1, 1, 0, 1;\n"
        "wgmma.mma_async.sync.aligned.m64n256k16.f32.bf16.bf16 {%0,%1,%2,%3,%4,%5,%6,%7,%8,%9,%10,%11,%12,%13,%14,%15,%16,%17,%18,%19,%20,%21,%22,%23,%24,%25,%26,%27,%28,%29,%30,%31,%32,%33,%34,%35,%36,%37,%38,%39,%40,%41,%42,%43,%44,%45,%46,%47,%48,%49,%50,%51,%52,%53,%54,%55,%56,%57,%58,%59,%60,%61,%62,%63,%64,%65,%66,%67,%68,%69,%70,%71,%72,%73,%74,%75,%76,%77,%78,%79,%80,%81,%82,%83,%84,%85,%86,%87,%88,%89,%90,%91,%92,%93,%94,%95,%96,%97,%98,%99,%100,%101,%102,%103,%104,%105,%106,%107,%108,%109,%110,%111,%112,%113,%114,%115,%116,%117,%118,%119,%120,%121,%122,%123,%124,%125,%126,%127}, %129, %131, 1, 1, 1, 0, 1;\n"
        "}\n"
        : R8(a, 0), R8(a, 8), R8(a, 16), R8(a, 24), R8(a, 32), R8(a, 40), R8(a, 48), R8(a, 56), R8(a, 64), R8(a, 72), R8(a, 80), R8(a, 88), R8(a, 96), R8(a, 104), R8(a, 112), R8(a, 120)
        : "l"(da0), "l"(da1), "l"(db0), "l"(db1), "r"(scale_d));
}
__device__ __forceinline__ void wgmma_n192_k32(float* a, uint64_t da0, uint64_t da1, uint64_t db0, uint64_t db1, int scale_d) {
    asm volatile(
        "{\n.reg .pred p;\nsetp.ne.b32 p, %100, 0;\n"
        "wgmma.mma_async.sync.aligned.m64n192k16.f32.bf16.bf16 {%0,%1,%2,%3,%4,%5,%6,%7,%8,%9,%10,%11,%12,%13,%14,%15,%16,%17,%18,%19,%20,%21,%22,%23,%24,%25,%26,%27,%28,%29,%30,%31,%32,%33,%34,%35,%36,%37,%38,%39,%40,%41,%42,%43,%44,%45,%46,%47,%48,%49,%50,%51,%52,%53,%54,%55,%56,%57,%58,%59,%60,%61,%62,%63,%64,%65,%66,%67,%68,%69,%70,%71,%72,%73,%74,%75,%76,%77,%78,%79,%80,%81,%82,%83,%84,%85,%86,%87,%88,%89,%90,%91,%92,%93,%94,%95}, %96, %98, p, 1, 1, 0, 1;\n"
        "wgmma.mma_async.sync.aligned.m64n192k16.f32.bf16.bf16 {%0,%1,%2,%3,%4,%5,%6,%7,%8,%9,%10,%11,%12,%13,%14,%15,%16,%17,%18,%19,%20,%21,%22,%23,%24,%25,%26,%27,%28,%29,%30,%31,%32,%33,%34,%35,%36,%37,%38,%39,%40,%41,%42,%43,%44,%45,%46,%47,%48,%49,%50,%51,%52,%53,%54,%55,%56,%57,%58,%59,%60,%61,%62,%63,%64,%65,%66,%67,%68,%69,%70,%71,%72,%73,%74,%75,%76,%77,%78,%79,%80,%81,%82,%83,%84,%85,%86,%87,%88,%89,%90,%91,%92,%93,%94,%95}, %97, %99, 1, 1, 1, 0, 1;\n"
        "}\n"
        : R8(a, 0), R8(a, 8), R8(a, 16), R8(a, 24), R8(a, 32), R8(a, 40), R8(a, 48), R8(a, 56), R8(a, 64), R8(a, 72), R8(a, 80), R8(a, 88)
        : "l"(da0), "l"(da1), "l"(db0), "l"(db1), "r"(scale_d));
}
__device__ __forceinline__ void wgmma_n192(float* a, uint64_t da0, uint64_t db0, int scale_d) {
    asm volatile(
        "{\n.reg .pred p;\nsetp.ne.b32 p, %98, 0;\n"
        "wgmma.mma_async.sync.aligned.m64n192k16.f32.bf16.bf16 {%0,%1,%2,%3,%4,%5,%6,%7,%8,%9,%10,%11,%12,%13,%14,%15,%16,%17,%18,%19,%20,%21,%22,%23,%24,%25,%26,%27,%28,%29,%30,%31,%32,%33,%34,%35,%36,%37,%38,%39,%40,%41,%42,%43,%44,%45,%46,%47,%48,%49,%50,%51,%52,%53,%54,%55,%56,%57,%58,%59,%60,%61,%62,%63,%64,%65,%66,%67,%68,%69,%70,%71,%72,%73,%74,%75,%76,%77,%78,%79,%80,%81,%82,%83,%84,%85,%86,%87,%88,%89,%90,%91,%92,%93,%94,%95}, %96, %97, p, 1, 1, 0, 1;\n"
        "}\n"
        : R8(a, 0), R8(a, 8), R8(a, 16), R8(a, 24), R8(a, 32), R8(a, 40), R8(a, 48), R8(a, 56), R8(a, 64), R8(a, 72), R8(a, 80), R8(a, 88)
        : "l"(da0), "l"(db0), "r"(scale_d));
}
__device__ __forceinline__ void wgmma_n128_k64(float* a, uint64_t da0, uint64_t da1, uint64_t da2, uint64_t da3,
                                               uint64_t db0, uint64_t db1, uint64_t db2, uint64_t db3, int scale_d) {
    asm volatile(
        "{\n.reg .pred p;\nsetp.ne.b32 p, %72, 0;\n"
        "wgmma.mma_async.sync.aligned.m64n128k16.f32.bf16.bf16 {%0,%1,%2,%3,%4,%5,%6,%7,%8,%9,%10,%11,%12,%13,%14,%15,%16,%17,%18,%19,%20,%21,%22,%23,%24,%25,%26,%27,%28,%29,%30,%31,%32,%33,%34,%35,%36,%37,%38,%39,%40,%41,%42,%43,%44,%45,%46,%47,%48,%49,%50,%51,%52,%53,%54,%55,%56,%57,%58,%59,%60,%61,%62,%63}, %64, %68, p, 1, 1, 0, 1;\n"
        "wgmma.mma_async.sync.aligned.m64n128k16.f32.bf16.bf16 {%0,%1,%2,%3,%4,%5,%6,%7,%8,%9,%10,%11,%12,%13,%14,%15,%16,%17,%18,%19,%20,%21,%22,%23,%24,%25,%26,%27,%28,%29,%30,%31,%32,%33,%34,%35,%36,%37,%38,%39,%40,%41,%42,%43,%44,%45,%46,%47,%48,%49,%50,%51,%52,%53,%54,%55,%56,%57,%58,%59,%60,%61,%62,%63}, %65, %69, 1, 1, 1, 0, 1;\n"
        "wgmma.mma_async.sync.aligned.m64n128k16.f32.bf16.bf16 {%0,%1,%2,%3,%4,%5,%6,%7,%8,%9,%10,%11,%12,%13,%14,%15,%16,%17,%18,%19,%20,%21,%22,%23,%24,%25,%26,%27,%28,%29,%30,%31,%32,%33,%34,%35,%36,%37,%38,%39,%40,%41,%42,%43,%44,%45,%46,%47,%48,%49,%50,%51,%52,%53,%54,%55,%56,%57,%58,%59,%60,%61,%62,%63}, %66, %70, 1, 1, 1, 0, 1;\n"
        "wgmma.mma_async.sync.aligned.m64n128k16.f32.bf16.bf16 {%0,%1,%2,%3,%4,%5,%6,%7,%8,%9,%10,%11,%12,%13,%14,%15,%16,%17,%18,%19,%20,%21,%22,%23,%24,%25,%26,%27,%28,%29,%30,%31,%32,%33,%34,%35,%36,%37,%38,%39,%40,%41,%42,%43,%44,%45,%46,%47,%48,%49,%50,%51,%52,%53,%54,%55,%56,%57,%58,%59,%60,%61,%62,%63}, %67, %71, 1, 1, 1, 0, 1;\n"
        "}\n"
        : R8(a, 0), R8(a, 8), R8(a, 16), R8(a, 24), R8(a, 32), R8(a, 40), R8(a, 48), R8(a, 56)
        : "l"(da0), "l"(da1), "l"(da2), "l"(da3), "l"(db0), "l"(db1), "l"(db2), "l"(db3), "r"(scale_d));
}

__device__ __forceinline__ float bf16_round(float x) {
    uint32_t p; asm("cvt.rn.bf16x2.f32 %0, %1, %2;" : "=r"(p) : "f"(x), "f"(0.0f));
    return __uint_as_float(p);
}
__device__ __forceinline__ uint32_t pack_bf16(float lo, float hi) {
    __nv_bfloat162 v = __floats2bfloat162_rn(lo, hi);
    return *reinterpret_cast<uint32_t*>(&v);
}
__device__ __forceinline__ float bf_lo(uint32_t v) { return __uint_as_float(v << 16); }
__device__ __forceinline__ float bf_hi(uint32_t v) { return __uint_as_float(v & 0xFFFF0000u); }

struct cplx { float r, i; };
__device__ __forceinline__ cplx cmul(cplx a, cplx b) {
    cplx c; c.r = a.r * b.r - a.i * b.i; c.i = a.r * b.i + a.i * b.r; return c;
}
__device__ __forceinline__ cplx csq(cplx a) {
    cplx c; c.r = a.r * a.r - a.i * a.i; c.i = 2.0f * a.r * a.i; return c;
}
__device__ __forceinline__ cplx cexp_m(float ar2, float ai2, float m) {
    float mag;
    asm("ex2.approx.ftz.f32 %0, %1;" : "=f"(mag) : "f"(ar2 * m));
    float rr = ai2 * m;
    rr -= (rr + 12582912.0f) - 12582912.0f;
    float th = rr * 6.283185307179586f;
    cplx c; c.r = mag * __cosf(th); c.i = mag * __sinf(th);
    return c;
}
__device__ __forceinline__ uint32_t to_tf32(float x) { return __float_as_uint(x) + 0x1000u; }
__device__ __forceinline__ void mma_tf32(float* c, uint32_t a0, uint32_t a1, uint32_t a2, uint32_t a3, uint32_t b0, uint32_t b1) {
    asm volatile("mma.sync.aligned.m16n8k8.row.col.f32.tf32.tf32.f32 {%0,%1,%2,%3}, {%4,%5,%6,%7}, {%8,%9}, {%0,%1,%2,%3};"
                 : "+f"(c[0]), "+f"(c[1]), "+f"(c[2]), "+f"(c[3])
                 : "r"(a0), "r"(a1), "r"(a2), "r"(a3), "r"(b0), "r"(b1));
}
__device__ __forceinline__ void mma_bf16(float* c, uint32_t a0, uint32_t a1, uint32_t a2, uint32_t a3, uint32_t b0, uint32_t b1) {
    asm volatile("mma.sync.aligned.m16n8k16.row.col.f32.bf16.bf16.f32 {%0,%1,%2,%3}, {%4,%5,%6,%7}, {%8,%9}, {%0,%1,%2,%3};"
                 : "+f"(c[0]), "+f"(c[1]), "+f"(c[2]), "+f"(c[3])
                 : "r"(a0), "r"(a1), "r"(a2), "r"(a3), "r"(b0), "r"(b1));
}
__device__ __forceinline__ void named_bar(int id, int n) { asm volatile("bar.sync %0, %1;" ::"r"(id), "r"(n) : "memory"); }
__device__ __forceinline__ void ldsm_x4(uint32_t addr, uint32_t& r0, uint32_t& r1, uint32_t& r2, uint32_t& r3) {
    asm volatile("ldmatrix.sync.aligned.m8n8.x4.shared.b16 {%0,%1,%2,%3}, [%4];" : "=r"(r0), "=r"(r1), "=r"(r2), "=r"(r3) : "r"(addr));
}
__device__ __forceinline__ void ldsm_x4_t(uint32_t addr, uint32_t& r0, uint32_t& r1, uint32_t& r2, uint32_t& r3) {
    asm volatile("ldmatrix.sync.aligned.m8n8.x4.trans.shared.b16 {%0,%1,%2,%3}, [%4];" : "=r"(r0), "=r"(r1), "=r"(r2), "=r"(r3) : "r"(addr));
}

constexpr int CV_CH = 4;
constexpr int CV_O_CONST = 0;
constexpr int CV_O_KP = 12288;
constexpr int CV_O_Q = CV_O_KP + 10368;
constexpr int CV_O_Q2 = CV_O_Q + 2304;
constexpr int CV_O_Q3 = CV_O_Q2 + 1024;
constexpr int CV_O_Q4X = CV_O_Q3 + 768;
constexpr int CV_O_W3 = CV_O_Q4X + 256;
constexpr int CV_O_W5 = CV_O_W3 + 3104;
constexpr int CV_O_W7 = CV_O_W5 + 3104;
constexpr int CV_O_W9 = CV_O_W7 + 2048;
constexpr int CV_O_STG = 32768;
constexpr int CV_O_U = CV_O_W9 + 2048;
constexpr int CV_PER_CH = CV_O_U + 4352;
static_assert(CV_O_U >= CV_O_STG + 4096, "staging overlaps u");
constexpr int CV_SMEM = CV_CH * CV_PER_CH;

constexpr int LN_ROWS = 16;

__global__ void __launch_bounds__(512, 1) front_kernel(const __nv_bfloat16* __restrict__ x,
                                                        const __nv_bfloat16* __restrict__ A_re, const __nv_bfloat16* __restrict__ A_im,
                                                        const __nv_bfloat16* __restrict__ B_re, const __nv_bfloat16* __restrict__ B_im,
                                                        const __nv_bfloat16* __restrict__ C_re, const __nv_bfloat16* __restrict__ C_im,
                                                        const __nv_bfloat16* __restrict__ log_dt, const __nv_bfloat16* __restrict__ Dskip,
                                                        const __nv_bfloat16* __restrict__ wg, const __nv_bfloat16* __restrict__ wu,
                                                        const __nv_bfloat16* __restrict__ wd) {
    pdl_launch();
    if (threadIdx.x == 0) STAMP(1, 0);
    extern __shared__ __align__(16) uint8_t smem[];
    const int warp = threadIdx.x >> 5, lane = threadIdx.x & 31;
    const int ch = warp >> 2, w = warp & 3, tc = threadIdx.x & 127;
    const int d = blockIdx.x * CV_CH + ch;
    const int g = lane >> 2, t = lane & 3;
    uint8_t* base = smem + ch * CV_PER_CH;
    float4* s_const = reinterpret_cast<float4*>(base + CV_O_CONST);
    float* s_kp = reinterpret_cast<float*>(base + CV_O_KP);
    uint32_t* s_q = reinterpret_cast<uint32_t*>(base + CV_O_Q);
    uint32_t* s_q2 = reinterpret_cast<uint32_t*>(base + CV_O_Q2);
    uint32_t* s_q3 = reinterpret_cast<uint32_t*>(base + CV_O_Q3);
    uint32_t* s_q4 = reinterpret_cast<uint32_t*>(base + CV_O_Q4X);
    __nv_bfloat16* s_u = reinterpret_cast<__nv_bfloat16*>(base + CV_O_U);
    const int bar_id = 1 + ch;

    const int row = blockIdx.x * LN_ROWS + warp;
    const uint4 xv0 = *reinterpret_cast<const uint4*>(x + (size_t)row * D_ + lane * 8);
    const uint4 xv1 = *reinterpret_cast<const uint4*>(x + (size_t)row * D_ + 256 + lane * 8);
    const size_t poff = (size_t)d * NS_ + tc;
    const __nv_bfloat16 p_ar = A_re[poff], p_ai = A_im[poff], p_br = B_re[poff], p_bi = B_im[poff], p_cr = C_re[poff], p_ci = C_im[poff];
    const __nv_bfloat16 p_ldt = log_dt[d], p_dsk = Dskip[d];
    {
        __nv_bfloat16 (*tile)[D_ + 8] = reinterpret_cast<__nv_bfloat16 (*)[D_ + 8]>(smem);
        float f[16];
        const uint32_t wv[8] = {xv0.x, xv0.y, xv0.z, xv0.w, xv1.x, xv1.y, xv1.z, xv1.w};
#pragma unroll
        for (int i = 0; i < 8; i++) { f[2 * i] = bf_lo(wv[i]); f[2 * i + 1] = bf_hi(wv[i]); }
        float sm = 0.f;
#pragma unroll
        for (int i = 0; i < 16; i++) sm += f[i];
#pragma unroll
        for (int o = 16; o > 0; o >>= 1) sm += __shfl_xor_sync(0xffffffffu, sm, o);
        const float mean = sm * (1.0f / D_);
        if (threadIdx.x == 0 && mean > -1e30f) STAMP(0, 1);
        float q = 0.f;
#pragma unroll
        for (int i = 0; i < 16; i++) { float dd = f[i] - mean; q += dd * dd; }
#pragma unroll
        for (int o = 16; o > 0; o >>= 1) q += __shfl_xor_sync(0xffffffffu, q, o);
        const float mb = bf16_round(mean);
        const float vb = bf16_round(q * (1.0f / D_));
        const float den = bf16_round(sqrtf(bf16_round(vb + 1e-5f)));
        uint32_t o[8];
#pragma unroll
        for (int i = 0; i < 8; i++) {
            float a = __fdiv_rn(bf16_round(f[2 * i] - mb), den);
            float b = __fdiv_rn(bf16_round(f[2 * i + 1] - mb), den);
            o[i] = pack_bf16(a, b);
        }
        __nv_bfloat16* dst = g_xn + (size_t)row * D_;
        *reinterpret_cast<uint4*>(dst + lane * 8) = make_uint4(o[0], o[1], o[2], o[3]);
        *reinterpret_cast<uint4*>(dst + 256 + lane * 8) = make_uint4(o[4], o[5], o[6], o[7]);
        *reinterpret_cast<uint4*>(&tile[warp][lane * 8]) = make_uint4(o[0], o[1], o[2], o[3]);
        *reinterpret_cast<uint4*>(&tile[warp][256 + lane * 8]) = make_uint4(o[4], o[5], o[6], o[7]);
        if (threadIdx.x == 0) STAMP(0, 2);
        __syncthreads();
        if (threadIdx.x == 0) STAMP(0, 3);
        {
            const int c = threadIdx.x;
            uint32_t ot[8];
#pragma unroll
            for (int i = 0; i < 8; i++) {
                uint32_t lo = *reinterpret_cast<const uint16_t*>(&tile[2 * i][c]);
                uint32_t hi = *reinterpret_cast<const uint16_t*>(&tile[2 * i + 1][c]);
                ot[i] = lo | (hi << 16);
            }
            __nv_bfloat16* dT = g_xnT + (size_t)c * L_ + blockIdx.x * LN_ROWS;
            *reinterpret_cast<uint4*>(dT) = make_uint4(ot[0], ot[1], ot[2], ot[3]);
            *reinterpret_cast<uint4*>(dT + 8) = make_uint4(ot[4], ot[5], ot[6], ot[7]);
        }
        __syncthreads();
        if (threadIdx.x == 0) {
            asm volatile("red.release.gpu.global.add.u32 [%0], 1;" ::"l"(&g_ln_count) : "memory");
            STAMP(0, 0);
        }
        if (threadIdx.x < 336) {
            const int m = threadIdx.x / 112, i = threadIdx.x - m * 112;
            const char* wp = (const char*)(m == 0 ? wg : (m == 1 ? wu : wd));
            asm volatile("prefetch.global.L2 [%0];" ::"l"(wp + ((size_t)blockIdx.x * 112 + i) * 128));
        }
    }

    float tail;
    {
        const float dt = bf16_round(expf(__bfloat162float(p_ldt)));
        const float ar = dt * __bfloat162float(p_ar), ai = dt * __bfloat162float(p_ai);
        const cplx db = {dt * __bfloat162float(p_br), dt * __bfloat162float(p_bi)};
        const cplx cc = {__bfloat162float(p_cr), __bfloat162float(p_ci)};
        const cplx cb = cmul(cc, db);
        const float ar2 = ar * 1.4426950408889634f, ai2 = ai * 0.15915494309189535f;
        const cplx e8 = cexp_m(ar2, ai2, 8.f), e128 = cexp_m(ar2, ai2, 128.f);
        const cplx cb8 = cmul(cb, e8);
        const cplx e256 = cexp_m(ar2, ai2, 256.f), e512 = cexp_m(ar2, ai2, 512.f), e1024 = cexp_m(ar2, ai2, 1024.f);
        const cplx c256 = cmul(cb, e256), c512 = cmul(cb, e512), c1024 = cmul(cb, e1024);
        const cplx c768 = cmul(c512, e256), c1280 = cmul(c1024, e256), c1536 = cmul(c1024, e512);
        const cplx c1792 = cmul(c1536, e256);
        tail = cmul(c1024, e1024).r;
        float4* c = s_const + tc * 6;
        c[0] = make_float4(ar2, ai2, cb.r, cb.i);
        c[1] = make_float4(e128.r, e128.i, cb8.r, cb8.i);
        c[2] = make_float4(c256.r, c256.i, e8.r, e8.i);
        c[3] = make_float4(c512.r, c512.i, c768.r, c768.i);
        c[4] = make_float4(c1024.r, c1024.i, c1280.r, c1280.i);
        c[5] = make_float4(c1536.r, c1536.i, c1792.r, c1792.i);
#pragma unroll
        for (int o = 16; o > 0; o >>= 1) tail += __shfl_xor_sync(0xffffffffu, tail, o);
    }
    __syncwarp();
    if (threadIdx.x == 0) STAMP(1, 1);
    {
        float acc[5][4];
#pragma unroll
        for (int i = 0; i < 5; i++) { acc[i][0] = acc[i][1] = acc[i][2] = acc[i][3] = 0.f; }
        const float gf = (float)g;
        const int src4 = ((g & 3) << 2) | t;
#pragma unroll 2
        for (int s = 0; s < 8; s++) {
            const float4* c = s_const + (w * 32 + s * 4 + t) * 6;
            const float4 k0 = c[0], k1 = c[1], k2 = c[2];
            const float2 k3 = reinterpret_cast<const float2*>(c + 3)[g >> 2];
            const float2 k4 = reinterpret_cast<const float2*>(c + 4)[g >> 1];
            const cplx cb = {k0.z, k0.w}, e128 = {k1.x, k1.y}, cb8 = {k1.z, k1.w}, c256 = {k2.x, k2.y}, e8 = {k2.z, k2.w};
            const cplx c2 = {k3.x, k3.y}, c3 = {k4.x, k4.y};
            const cplx p1 = cexp_m(k0.x, k0.y, gf);
            const cplx p2 = csq(p1), p4 = csq(p2);
            const cplx r16a = csq(csq(p4));
            cplx q4;
            q4.r = __shfl_sync(0xffffffffu, p4.r, src4);
            q4.i = __shfl_sync(0xffffffffu, p4.i, src4);
            const cplx r16b = cmul(r16a, e128);
            const cplx f0a = cmul(cb, p1), f0b = cmul(cb8, p1), f1 = cmul(c256, p2), f2 = cmul(c2, q4);
            cplx f3 = cmul(c3, e8);
            if (!(g & 1)) f3 = c3;
            const uint32_t a0 = to_tf32(r16a.r), a1 = to_tf32(r16b.r), a2 = to_tf32(-r16a.i), a3 = to_tf32(-r16b.i);
            mma_tf32(acc[0], a0, a1, a2, a3, to_tf32(f0a.r), to_tf32(f0a.i));
            mma_tf32(acc[1], a0, a1, a2, a3, to_tf32(f0b.r), to_tf32(f0b.i));
            mma_tf32(acc[2], a0, a1, a2, a3, to_tf32(f1.r), to_tf32(f1.i));
            mma_tf32(acc[3], a0, a1, a2, a3, to_tf32(f2.r), to_tf32(f2.i));
            mma_tf32(acc[4], a0, a1, a2, a3, to_tf32(f3.r), to_tf32(f3.i));
        }
        float* kv = s_kp + w * 648;
#pragma unroll
        for (int hh = 0; hh < 2; hh++) {
            const int i = g + 8 * hh;
            *reinterpret_cast<float2*>(kv + 16 * i + 2 * t) = make_float2(acc[0][2 * hh], acc[0][2 * hh + 1]);
            *reinterpret_cast<float2*>(kv + 16 * i + 8 + 2 * t) = make_float2(acc[1][2 * hh], acc[1][2 * hh + 1]);
            *reinterpret_cast<float2*>(kv + 256 + 8 * i + 2 * t) = make_float2(acc[2][2 * hh], acc[2][2 * hh + 1]);
            *reinterpret_cast<float2*>(kv + 384 + 64 * (t >> 1) + 2 * (t & 1) + 4 * i) = make_float2(acc[3][2 * hh], acc[3][2 * hh + 1]);
            *reinterpret_cast<float2*>(kv + 512 + 32 * t + 2 * i) = make_float2(acc[4][2 * hh], acc[4][2 * hh + 1]);
        }
        if (lane == 0) kv[640] = tail;
    }
    named_bar(bar_id, 128);
    if (threadIdx.x == 0) STAMP(1, 2);
#pragma unroll
    for (int i = 0; i < 6; i++) {
        const int idx = tc + 128 * i;
        if (idx < 641) s_kp[idx] = (s_kp[idx] + s_kp[648 + idx]) + (s_kp[1296 + idx] + s_kp[1944 + idx]);
    }
    named_bar(bar_id, 128);
    {
        auto kdir = [&](int l) -> float {
            if (l < 0 || l > 514) return 0.f;
            const int idx = (l < 256) ? l : (l > 512 ? 384 : 128 + ((l + ((l >> 1) & 1)) >> 1));
            return s_kp[idx];
        };
#pragma unroll
        for (int i = 0; i < 5; i++) {
            const int e = tc + 128 * i;
            if (e < 576) s_q[e] = pack_bf16(kdir(e - 16), kdir(e - 17));
        }
        if (tc < 64) {
            const int xx = 1008 + tc;
            const float k1024 = s_kp[512];
            s_q4[tc] = pack_bf16((xx == 1027 || xx == 1028) ? k1024 : 0.f, (xx == 1028 || xx == 1029) ? k1024 : 0.f);
        }
#pragma unroll
        for (int i = 0; i < 2; i++) {
            const int e = tc + 128 * i, a = e >> 6, ii = (e & 63) - 16;
            const int b = 385 + (a >> 1) + 2 * (a & 1);
            const float v0 = (ii >= 0 && ii < 32) ? s_kp[b + 4 * ii] : 0.f;
            const float v1 = (ii >= 1 && ii < 33) ? s_kp[b + 4 * (ii - 1)] : 0.f;
            s_q2[e] = pack_bf16(v0, v1);
        }
#pragma unroll
        for (int i = 0; i < 2; i++) {
            const int e = tc + 128 * i;
            if (e < 192) {
                const int a = e >= 96, jj = e - 96 * a - 16;
                const float v0 = (jj >= 0 && jj < 64) ? s_kp[513 + a + 2 * jj] : 0.f;
                const float v1 = (jj >= 1 && jj < 65) ? s_kp[513 + a + 2 * (jj - 1)] : 0.f;
                s_q3[e] = pack_bf16(v0, v1);
            }
        }
    }
    if (threadIdx.x == 0) STAMP(1, 3);
    if (threadIdx.x == 0) {
        unsigned int v = 0;
        for (int spin = 0; spin < (1 << 22); spin++) {
            asm volatile("ld.acquire.gpu.global.u32 %0, [%1];" : "=r"(v) : "l"(&g_ln_count) : "memory");
            if (v >= gridDim.x) break;
        }
    }
    __syncthreads();
    if (threadIdx.x == 0) STAMP(1, 4);
    {
        if (tc < 16) *reinterpret_cast<uint4*>(s_u + tc * 8) = make_uint4(0, 0, 0, 0);
        const uint4* src = reinterpret_cast<const uint4*>(g_xnT + (size_t)d * L_);
        const uint4 v0 = src[tc], v1 = src[tc + 128];
        *reinterpret_cast<uint4*>(s_u + 128 + tc * 8) = v0;
        *reinterpret_cast<uint4*>(s_u + 128 + (tc + 128) * 8) = v1;
        if (tc < 2) *reinterpret_cast<uint4*>(base + (tc ? CV_O_W5 : CV_O_W3)) = make_uint4(0, 0, 0, 0);
    }
    named_bar(bar_id, 128);
#pragma unroll
    for (int rep = 0; rep < 2; rep++) {
        const int m = tc + 128 * rep;
        if (m < 192) {
            float P[30];
            const uint4* up = reinterpret_cast<const uint4*>(s_u + 128 + 8 * m - 24);
            P[0] = 0.f;
#pragma unroll
            for (int c4 = 0; c4 < 4; c4++) {
                const uint4 v = up[c4];
                const uint32_t ww[4] = {v.x, v.y, v.z, v.w};
#pragma unroll
                for (int j = 0; j < 4; j++) {
                    const int k = c4 * 8 + 2 * j;
                    if (k + 1 <= 29) P[k + 1] = P[k] + bf_lo(ww[j]);
                    if (k + 2 <= 29) P[k + 2] = P[k + 1] + bf_hi(ww[j]);
                }
            }
            uint32_t o3[4], o5[4], o7[4], o9[4];
#pragma unroll
            for (int j = 0; j < 4; j++) {
                const int i = 2 * j;
                o3[j] = pack_bf16(P[i + 22] - P[i + 19], P[i + 23] - P[i + 20]);
                o5[j] = pack_bf16(P[i + 19] - P[i + 14], P[i + 20] - P[i + 15]);
                o7[j] = pack_bf16(P[i + 20] - P[i + 13], P[i + 21] - P[i + 14]);
                o9[j] = pack_bf16(P[i + 13] - P[i + 4], P[i + 14] - P[i + 5]);
            }
            *reinterpret_cast<uint4*>(base + CV_O_W3 + 16 + m * 16) = make_uint4(o3[0], o3[1], o3[2], o3[3]);
            *reinterpret_cast<uint4*>(base + CV_O_W5 + 16 + m * 16) = make_uint4(o5[0], o5[1], o5[2], o5[3]);
            if (m < 128) {
                *reinterpret_cast<uint4*>(base + CV_O_W7 + m * 16) = make_uint4(o7[0], o7[1], o7[2], o7[3]);
                *reinterpret_cast<uint4*>(base + CV_O_W9 + m * 16) = make_uint4(o9[0], o9[1], o9[2], o9[3]);
            }
        }
    }
    if (threadIdx.x == 0) STAMP(1, 5);
    named_bar(bar_id, 128);
    const int wsel = (w - ch) & 3;
    if (wsel & 1) return;
    const int hb = wsel >> 1;
    float acc[16][4];
#pragma unroll
    for (int i = 0; i < 16; i++) { acc[i][0] = acc[i][1] = acc[i][2] = acc[i][3] = 0.f; }
    const uint32_t sb_addr = smem_u32(base);
    const int mi = lane >> 3, rowi = lane & 7;
#pragma unroll 1
    for (int rr = 0; rr < 4; rr++) {
        const int r = 4 * hb + rr;
        uint32_t ub[16][2];
        {
            const uint32_t addr = sb_addr + CV_O_U + (uint32_t)((128 + 16 * (8 * (mi >> 1) + rowi - r) + 8 * (mi & 1)) * 2);
#pragma unroll
            for (int j = 0; j < 16; j += 2) ldsm_x4(addr + (uint32_t)(j * 256), ub[j][0], ub[j][1], ub[j + 1][0], ub[j + 1][1]);
        }
        const uint32_t* qp = s_q + 16 + 16 * r + g - 2 * t;
        uint32_t af[4][3];
#pragma unroll
        for (int q = 0; q < 4; q++) { af[q][0] = qp[128 * q]; af[q][1] = qp[128 * q + 8]; af[q][2] = qp[128 * q - 8]; }
#pragma unroll
        for (int q = 0; q < 4; q++) {
#pragma unroll
            for (int nt = q; nt < 16; nt++) mma_bf16(acc[nt], af[q][0], af[q][1], af[q][2], af[q][0], ub[nt - q][0], ub[nt - q][1]);
        }
        if (r < 2) {
            {
                const uint32_t a0 = qp[512], a1 = qp[520], a2 = qp[504];
#pragma unroll
                for (int nt = 4; nt < 16; nt++) mma_bf16(acc[nt], a0, a1, a2, a0, ub[nt - 4][0], ub[nt - 4][1]);
            }
            {
                const uint32_t* q4p = s_q4 + 16 + 16 * r + g - 2 * t;
                const uint32_t a0 = q4p[0], a1 = q4p[8], a2 = q4p[-8];
#pragma unroll
                for (int nt = 8; nt < 16; nt++) mma_bf16(acc[nt], a0, a1, a2, a0, ub[nt - 8][0], ub[nt - 8][1]);
            }
        }
    }
#pragma unroll 1
    for (int a = hb; a <= 3 * hb; a++) {
        uint32_t bq[7];
        const uint32_t* q2 = s_q2 + a * 64 + 16 + g - 2 * t - 32;
#pragma unroll
        for (int dlt = 3; dlt <= 9; dlt++) bq[dlt - 3] = q2[8 * dlt];
        const uint32_t addr = sb_addr + ((a >> 1) ? CV_O_W5 : CV_O_W3) + (uint32_t)((8 + 16 * (8 * (mi >> 1) + rowi) + 8 * (mi & 1) - 8 * (a & 1)) * 2);
        uint32_t aa[6][4];
#pragma unroll
        for (int kp = 0; kp < 6; kp++) ldsm_x4_t(addr + kp * 512, aa[kp][0], aa[kp][1], aa[kp][2], aa[kp][3]);
#pragma unroll
        for (int kp = 0; kp < 6; kp++) {
#pragma unroll
            for (int dlt = 4; dlt <= 9; dlt++) {
                if (2 * kp + dlt < 16) mma_bf16(acc[2 * kp + dlt], aa[kp][0], aa[kp][1], aa[kp][2], aa[kp][3], bq[dlt - 3], bq[dlt - 4]);
            }
        }
    }
    if (hb == 0) {
#pragma unroll 1
        for (int a = 0; a < 2; a++) {
            uint32_t bq[9];
            const uint32_t* q3 = s_q3 + a * 96 + 16 + g - 2 * t - 64;
#pragma unroll
            for (int dlt = 7; dlt <= 15; dlt++) bq[dlt - 7] = q3[8 * dlt];
            const uint32_t addr = sb_addr + (a ? CV_O_W9 : CV_O_W7) + (uint32_t)((16 * (8 * (mi >> 1) + rowi) + 8 * (mi & 1)) * 2);
            uint32_t aa[4][4];
#pragma unroll
            for (int kp = 0; kp < 4; kp++) ldsm_x4_t(addr + kp * 512, aa[kp][0], aa[kp][1], aa[kp][2], aa[kp][3]);
#pragma unroll
            for (int kp = 0; kp < 4; kp++) {
#pragma unroll
                for (int dlt = 8; dlt <= 15; dlt++) {
                    if (2 * kp + dlt < 16) mma_bf16(acc[2 * kp + dlt], aa[kp][0], aa[kp][1], aa[kp][2], aa[kp][3], bq[dlt - 7], bq[dlt - 8]);
                }
            }
        }
    }
    if (threadIdx.x == 0) STAMP(1, 6);
    {
        float4* xch = reinterpret_cast<float4*>(base + CV_O_CONST) + hb * 256;
        if (hb) {
#pragma unroll
            for (int i = 0; i < 8; i++) xch[i * 32 + lane] = make_float4(acc[i][0], acc[i][1], acc[i][2], acc[i][3]);
#pragma unroll
            for (int i = 0; i < 8; i++) { acc[i][0] = acc[8 + i][0]; acc[i][1] = acc[8 + i][1]; acc[i][2] = acc[8 + i][2]; acc[i][3] = acc[8 + i][3]; }
        } else {
#pragma unroll
            for (int i = 0; i < 8; i++) xch[i * 32 + lane] = make_float4(acc[8 + i][0], acc[8 + i][1], acc[8 + i][2], acc[8 + i][3]);
        }
    }
    named_bar(bar_id, 64);
    if (threadIdx.x == 0) STAMP(1, 10);
    {
        const float4* xch = reinterpret_cast<const float4*>(base + CV_O_CONST) + (hb ^ 1) * 256 + lane;
        const float dsk = __bfloat162float(p_dsk);
        uint16_t* stg = reinterpret_cast<uint16_t*>(base + CV_O_KP);
        const uint16_t* uu = reinterpret_cast<const uint16_t*>(s_u) + 128;
#pragma unroll
        for (int i = 0; i < 8; i++) {
            const float4 p0 = xch[i * 32];
            const float y[4] = {acc[i][0] + p0.x, acc[i][1] + p0.y, acc[i][2] + p0.z, acc[i][3] + p0.w};
            const int nt = 8 * hb + i;
#pragma unroll
            for (int e = 0; e < 4; e++) {
                const int tau = 16 * (8 * nt + 2 * t + (e & 1)) + g + 8 * (e >> 1);
                const float sv = bf16_round(y[e]) + bf16_round(__uint_as_float((uint32_t)uu[tau] << 16) * dsk);
                stg[tau] = (uint16_t)(__float_as_uint(bf16_round(sv)) >> 16);
            }
        }
        __syncwarp();
        if (threadIdx.x == 0) STAMP(1, 11);
        uint4* dst = reinterpret_cast<uint4*>(g_sT + (size_t)d * L_ + hb * 1024);
        const uint4* srcp = reinterpret_cast<const uint4*>(stg + hb * 1024);
#pragma unroll
        for (int i = 0; i < 4; i++) dst[i * 32 + lane] = srcp[i * 32 + lane];
    }
    if (threadIdx.x == 0) STAMP(1, 7);
}

__device__ __forceinline__ uint32_t cluster_rank() { uint32_t r; asm volatile("mov.u32 %0, %%cluster_ctarank;" : "=r"(r)); return r; }
__device__ __forceinline__ void cluster_sync_all() {
    asm volatile("barrier.cluster.arrive.release.aligned;\nbarrier.cluster.wait.acquire.aligned;" ::: "memory");
}
__device__ __forceinline__ void mbar_arrive_remote(uint32_t bar, uint32_t cta) {
    asm volatile("{\n.reg .b32 ra;\nmapa.shared::cluster.u32 ra, %0, %1;\n"
                 "mbarrier.arrive.shared::cluster.b64 _, [ra];\n}\n" ::"r"(bar), "r"(cta) : "memory");
}
__device__ __forceinline__ void tma_load_2d_mc(uint32_t dst, const CUtensorMap* tm, int c0, int c1, uint32_t bar, uint16_t mask) {
    asm volatile(
        "cp.async.bulk.tensor.2d.shared::cluster.global.mbarrier::complete_tx::bytes.multicast::cluster [%0], [%1, {%3, %4}], [%2], %5;"
        ::"r"(dst), "l"((uint64_t)tm), "r"(bar), "r"(c0), "r"(c1), "h"(mask) : "memory");
}
__device__ __forceinline__ void tma_store_2d(const CUtensorMap* tm, uint32_t src, int c0, int c1) {
    asm volatile("cp.async.bulk.tensor.2d.global.shared::cta.bulk_group [%0, {%2, %3}], [%1];"
                 ::"l"((uint64_t)tm), "r"(src), "r"(c0), "r"(c1) : "memory");
}
__device__ __forceinline__ void bulk_commit() { asm volatile("cp.async.bulk.commit_group;" ::: "memory"); }
template <int N> __device__ __forceinline__ void bulk_wait_read() { asm volatile("cp.async.bulk.wait_group.read %0;" ::"n"(N) : "memory"); }
template <int N> __device__ __forceinline__ void bulk_wait() { asm volatile("cp.async.bulk.wait_group %0;" ::"n"(N) : "memory"); }
__device__ __forceinline__ void fence_async_smem() { asm volatile("fence.proxy.async.shared::cta;" ::: "memory"); }
__device__ __forceinline__ void stmatrix_x4(uint32_t addr, uint32_t r0, uint32_t r1, uint32_t r2, uint32_t r3) {
    asm volatile("stmatrix.sync.aligned.m8n8.x4.shared.b16 [%0], {%1,%2,%3,%4};" ::"r"(addr), "r"(r0), "r"(r1), "r"(r2), "r"(r3) : "memory");
}

constexpr int G1_STAGES = 5;
constexpr int G1_A_BYTES = 8 * 16384;
constexpr int G1_B_STAGE = 16384;
constexpr int G1_STG = 8 * 1024;
constexpr int G1_SMEM = G1_A_BYTES + G1_STAGES * G1_B_STAGE + G1_STG + 1024 + 256;
constexpr int G1_ITERS = 32;

__device__ __forceinline__ void tma_load_3d(uint32_t dst, const CUtensorMap* tm, int c0, int c1, int c2, uint32_t bar) {
    asm volatile(
        "cp.async.bulk.tensor.3d.shared::cluster.global.mbarrier::complete_tx::bytes [%0], [%1, {%3, %4, %5}], [%2];"
        ::"r"(dst), "l"((uint64_t)tm), "r"(bar), "r"(c0), "r"(c1), "r"(c2) : "memory");
}

__device__ __forceinline__ float gelu_tanh(float x) {
    float u = x * (0.7978845608028654f + 0.035677408136300125f * x * x);
    float t; asm("tanh.approx.f32 %0, %1;" : "=f"(t) : "f"(u));
    float hx = 0.5f * x;
    return fmaf(hx, t, hx);
}
__device__ __forceinline__ uint32_t geglu_pair(uint32_t g2, uint32_t u2) {
    uint32_t a = pack_bf16(gelu_tanh(bf_lo(g2)), gelu_tanh(bf_hi(g2)));
    uint32_t r; asm("mul.rn.bf16x2 %0, %1, %2;" : "=r"(r) : "r"(a), "r"(u2));
    return r;
}

__global__ void __launch_bounds__(384, 1) gemm1_kernel(const __grid_constant__ CUtensorMap tm_xn,
                                                        const __grid_constant__ CUtensorMap tm_wg4,
                                                        const __grid_constant__ CUtensorMap tm_wu4,
                                                        const __grid_constant__ CUtensorMap tm_wg3,
                                                        const __grid_constant__ CUtensorMap tm_wu3,
                                                        const __grid_constant__ CUtensorMap tm_hst,
                                                        const __grid_constant__ CUtensorMap tm_hst96) {
    pdl_launch();
    if (threadIdx.x == 0) STAMP(2, 0);
    extern __shared__ uint8_t smem_raw[];
    const uint32_t sbase = (smem_u32(smem_raw) + 1023) & ~1023u;
    const uint32_t sA = sbase, sB = sbase + G1_A_BYTES, sStg = sB + G1_STAGES * G1_B_STAGE, sBar = sStg + G1_STG;
    const uint32_t bar_a = sBar, bar_full = sBar + 64, bar_empty = sBar + 64 + 8 * G1_STAGES;
    const int rb = blockIdx.x >> 3, cj = blockIdx.x & 7;
    const int warp = threadIdx.x >> 5, lane = threadIdx.x & 31;

    if (threadIdx.x == 0) {
        for (int i = 0; i < 8; i++) mbar_init(bar_a + 8 * i, 1);
        for (int i = 0; i < G1_STAGES; i++) { mbar_init(bar_full + 8 * i, 1); mbar_init(bar_empty + 8 * i, 8); }
        asm volatile("fence.mbarrier_init.release.cluster;" ::: "memory");
    }
    __syncthreads();

    if (warp >= 8) {
        asm volatile("setmaxnreg.dec.sync.aligned.u32 40;");
        if (lane == 0) {
            const int pw = warp - 8;
            if (pw == 0) { prefetch_tmap(&tm_wg4); prefetch_tmap(&tm_wu4); prefetch_tmap(&tm_xn); }
            if (pw == 1) { prefetch_tmap(&tm_wg3); prefetch_tmap(&tm_wu3); prefetch_tmap(&tm_hst); prefetch_tmap(&tm_hst96); }
            for (int it = pw; it < G1_ITERS; it += 4) {
                const int s = it % G1_STAGES, kb = it & 15;
                if (it >= G1_STAGES) mbar_wait(bar_empty + 8 * s, ((it / G1_STAGES) - 1) & 1);
                const uint32_t dst = sB + s * G1_B_STAGE;
                if (it < 16) {
                    mbar_expect_tx(bar_full + 8 * s, 16384);
                    tma_load_3d(dst, &tm_wg4, 0, kb * 32, cj * 7, bar_full + 8 * s);
                    tma_load_3d(dst + 8192, &tm_wu4, 0, kb * 32, cj * 7, bar_full + 8 * s);
                } else {
                    mbar_expect_tx(bar_full + 8 * s, 12288);
                    tma_load_3d(dst, &tm_wg3, 0, kb * 32, cj * 7 + 4, bar_full + 8 * s);
                    tma_load_3d(dst + 6144, &tm_wu3, 0, kb * 32, cj * 7 + 4, bar_full + 8 * s);
                }
                if (it < 4) {
                    pdl_wait();
                    if (pw == 0) { STAMP(2, 1); if (blockIdx.x == 0) g_ln_count = 0; }
                    for (int k = pw; k < 8; k += 4) {
                        mbar_expect_tx(bar_a + 8 * k, 16384);
                        tma_load_2d(sA + k * 16384, &tm_xn, k * 64, rb * 128, bar_a + 8 * k);
                    }
                }
            }
        }
    } else {
        asm volatile("setmaxnreg.inc.sync.aligned.u32 232;");
        const int wg = __shfl_sync(0xffffffffu, (int)(threadIdx.x >> 7), 0);
        float r[160];
        const int row0 = rb * 128 + wg * 64 + (warp & 3) * 16;
        const uint64_t descA = make_desc(sA + wg * 8192, 16, 1024);
        const uint64_t descB = make_desc(sB, 2048, 512, 2);
        const uint32_t stg = sStg + warp * 1024;
        const uint32_t st_off = (uint32_t)(((lane & 7) + ((lane >> 3) & 1) * 8) * 32 + (lane >> 4) * 16);
        __nv_bfloat16* hrow = g_h + (size_t)(row0 + (lane >> 1)) * F_ + (lane & 1) * 8 + cj * 224;
#pragma unroll
        for (int kb = 0; kb < 16; kb++) {
            const int it = kb, s = it % G1_STAGES;
            if ((kb & 1) == 0) mbar_wait(bar_a + 8 * (kb >> 1), 0);
            mbar_wait(bar_full + 8 * s, (it / G1_STAGES) & 1);
            if (threadIdx.x == 0 && (it & 7) == 0) STAMP(2, 2 + it / 8);
            wgmma_fence();
            const uint64_t da = descA + (uint64_t)(((kb >> 1) * 16384 + (kb & 1) * 64) >> 4);
            const uint64_t db = descB + (uint64_t)((s * G1_B_STAGE) >> 4);
            wgmma_n256_k32(r, da, da + 2, db, db + 64, kb != 0);
            wgmma_commit();
            if (kb > 0) {
                wgmma_wait<1>();
                if (lane == 0) mbar_arrive(bar_empty + 8 * ((it - 1) % G1_STAGES));
            }
        }
        wgmma_wait<0>();
        if (lane == 0) mbar_arrive(bar_empty + 8 * (15 % G1_STAGES));
#pragma unroll
        for (int i = 0; i < 32; i++) r[128 + i] = __uint_as_float(pack_bf16(r[2 * i], r[2 * i + 1]));
#pragma unroll
        for (int i = 31; i >= 0; i--) r[96 + i] = __uint_as_float(pack_bf16(r[64 + 2 * i], r[65 + 2 * i]));
        uint32_t eo[4];
        uint4 pv = make_uint4(0, 0, 0, 0);
#pragma unroll
        for (int kb = 0; kb < 16; kb++) {
            const int it = 16 + kb, s = it % G1_STAGES;
            mbar_wait(bar_full + 8 * s, (it / G1_STAGES) & 1);
            if (threadIdx.x == 0 && (it & 7) == 0) STAMP(2, 2 + it / 8);
            wgmma_fence();
            const uint64_t da = descA + (uint64_t)(((kb >> 1) * 16384 + (kb & 1) * 64) >> 4);
            const uint64_t db = descB + (uint64_t)((s * G1_B_STAGE) >> 4);
            const int jj = kb >> 1;
            wgmma_n192(r, da, db, kb != 0);
            eo[(kb & 1) * 2] = geglu_pair(__float_as_uint(r[128 + 2 * kb]), __float_as_uint(r[96 + 2 * kb]));
            wgmma_n192(r, da + 2, db + 64, 1);
            wgmma_commit();
            eo[(kb & 1) * 2 + 1] = geglu_pair(__float_as_uint(r[129 + 2 * kb]), __float_as_uint(r[97 + 2 * kb]));
            if (kb & 1) {
                if (jj > 0) *reinterpret_cast<uint4*>(hrow + (jj - 1) * 16) = pv;
                stmatrix_x4(stg + (jj & 1) * 512 + st_off, eo[0], eo[1], eo[2], eo[3]);
            } else if (jj > 0) {
                __syncwarp();
                asm volatile("ld.shared.v4.u32 {%0,%1,%2,%3}, [%4];" : "=r"(pv.x), "=r"(pv.y), "=r"(pv.z), "=r"(pv.w)
                             : "r"(stg + ((jj - 1) & 1) * 512 + lane * 16));
            }
            if (kb > 0 && it - 1 + G1_STAGES < G1_ITERS) {
                wgmma_wait<1>();
                if (lane == 0) mbar_arrive(bar_empty + 8 * ((it - 1) % G1_STAGES));
            }
        }
        __syncwarp();
        asm volatile("ld.shared.v4.u32 {%0,%1,%2,%3}, [%4];" : "=r"(pv.x), "=r"(pv.y), "=r"(pv.z), "=r"(pv.w) : "r"(stg + 512 + lane * 16));
        wgmma_wait<0>();
        *reinterpret_cast<uint4*>(hrow + 7 * 16) = pv;
        if (threadIdx.x == 0) STAMP(2, 6);
        {
            uint32_t o[24];
#pragma unroll
            for (int i = 0; i < 24; i++) o[i] = geglu_pair(pack_bf16(r[2 * i], r[2 * i + 1]), pack_bf16(r[48 + 2 * i], r[49 + 2 * i]));
            named_bar(1 + wg, 128);
            const uint32_t fbuf = sA + ((warp & 3) >> 1) * 16384 + wg * 8192 + (warp & 1) * 4096;
#pragma unroll
            for (int jj = 0; jj < 6; jj++) stmatrix_x4(fbuf + jj * 512 + st_off, o[4 * jj], o[4 * jj + 1], o[4 * jj + 2], o[4 * jj + 3]);
            __syncwarp();
            uint4 v[6];
#pragma unroll
            for (int jj = 0; jj < 6; jj++)
                asm volatile("ld.shared.v4.u32 {%0,%1,%2,%3}, [%4];" : "=r"(v[jj].x), "=r"(v[jj].y), "=r"(v[jj].z), "=r"(v[jj].w)
                             : "r"(fbuf + jj * 512 + lane * 16));
#pragma unroll
            for (int jj = 0; jj < 6; jj++) *reinterpret_cast<uint4*>(hrow + 128 + jj * 16) = v[jj];
        }
        if (threadIdx.x == 0) STAMP(2, 7);
    }
}

constexpr int G2_STAGES = 5;
constexpr int G2_STAGE = 16384 + 16384;
constexpr int G2_XCH = 32768;
constexpr int G2_EPI = 16384 + 16384;
constexpr int G2_SMEM = G2_STAGES * G2_STAGE + G2_XCH + G2_EPI + 1024 + 256;
constexpr int G2_KB = F_ / 64 / 2;

__global__ void __launch_bounds__(384, 1) gemm2_kernel(const __grid_constant__ CUtensorMap tm_h,
                                                        const __grid_constant__ CUtensorMap tm_wd,
                                                        const __grid_constant__ CUtensorMap tm_x,
                                                        const __grid_constant__ CUtensorMap tm_sT,
                                                        const __grid_constant__ CUtensorMap tm_out) {
    if (threadIdx.x == 0) STAMP(3, 0);
    extern __shared__ uint8_t smem_raw[];
    const uint32_t sbase = (smem_u32(smem_raw) + 1023) & ~1023u;
    const uint32_t sXch = sbase + G2_STAGES * G2_STAGE, sX = sXch + G2_XCH, sS = sX + 16384, sBar = sX + G2_EPI;
    const uint32_t bar_full = sBar, bar_empty = sBar + 8 * G2_STAGES, bar_epi = sBar + 16 * G2_STAGES, bar_xch = bar_epi + 8;
    const uint32_t kh = cluster_rank();
    const int cid = blockIdx.x >> 1;
    const int rb = cid >> 2, nb = cid & 3;
    const int col_fin = nb * 128 + kh * 64;
    const int warp = threadIdx.x >> 5, lane = threadIdx.x & 31;

    if (threadIdx.x == 0) {
        for (int i = 0; i < G2_STAGES; i++) { mbar_init(bar_full + 8 * i, 1); mbar_init(bar_empty + 8 * i, 8); }
        mbar_init(bar_epi, 1);
        mbar_init(bar_xch, 1);
        asm volatile("fence.mbarrier_init.release.cluster;" ::: "memory");
        mbar_expect_tx(bar_xch, G2_XCH);
    }
    cluster_sync_all();

    if (warp >= 8) {
        if (lane == 0) {
            const int pw = warp - 8;
            const int k0 = kh * G2_KB;
            if (pw == 0) { prefetch_tmap(&tm_wd); prefetch_tmap(&tm_h); }
            if (pw == 1) { prefetch_tmap(&tm_x); prefetch_tmap(&tm_sT); prefetch_tmap(&tm_out); }
            for (int it = pw; it < G2_STAGES; it += 4) {
                mbar_expect_tx(bar_full + 8 * it, G2_STAGE);
                tma_load_3d(sbase + it * G2_STAGE + 16384, &tm_wd, 0, (k0 + it) * 64, nb * 2, bar_full + 8 * it);
            }
            if (pw == 3) {
                mbar_expect_tx(bar_epi, G2_EPI);
                tma_load_2d(sX, &tm_x, col_fin, rb * 128, bar_epi);
            }
            pdl_wait();
            if (pw == 0) STAMP(3, 1);
            for (int it = pw; it < G2_STAGES; it += 4)
                tma_load_2d(sbase + it * G2_STAGE, &tm_h, (k0 + it) * 64, rb * 128, bar_full + 8 * it);
            if (pw == 3) {
                tma_load_2d(sS, &tm_sT, rb * 128, col_fin, bar_epi);
                tma_load_2d(sS + 8192, &tm_sT, rb * 128 + 64, col_fin, bar_epi);
            }
            for (int it = G2_STAGES + ((pw + 4 - (G2_STAGES & 3)) & 3); it < G2_KB; it += 4) {
                const int s = it % G2_STAGES;
                mbar_wait(bar_empty + 8 * s, ((it / G2_STAGES) - 1) & 1);
                mbar_expect_tx(bar_full + 8 * s, G2_STAGE);
                tma_load_2d(sbase + s * G2_STAGE, &tm_h, (k0 + it) * 64, rb * 128, bar_full + 8 * s);
                tma_load_3d(sbase + s * G2_STAGE + 16384, &tm_wd, 0, (k0 + it) * 64, nb * 2, bar_full + 8 * s);
            }
        }
    } else {
        const int wg = __shfl_sync(0xffffffffu, (int)(threadIdx.x >> 7), 0);
        const int g = lane >> 2, t = lane & 3;
        float acc[64];
        const uint64_t descA = make_desc(sbase + wg * 8192, 16, 1024);
        const uint64_t descB = make_desc(sbase + 16384, 8192, 1024);
#pragma unroll
        for (int it = 0; it < G2_KB; it++) {
            const int s = it % G2_STAGES;
            mbar_wait(bar_full + 8 * s, (it / G2_STAGES) & 1);
            if (threadIdx.x == 0 && (it == 0 || it == 7)) STAMP(3, 2 + it / 7);
            wgmma_fence();
            {
                const uint64_t da = descA + (uint64_t)((s * G2_STAGE) >> 4);
                const uint64_t db = descB + (uint64_t)((s * G2_STAGE) >> 4);
                wgmma_n128_k64(acc, da, da + 2, da + 4, da + 6, db, db + 128, db + 256, db + 384, it != 0);
            }
            wgmma_commit();
            if (it > 0 && it - 1 + G2_STAGES < G2_KB) {
                wgmma_wait<1>();
                if (lane == 0) mbar_arrive(bar_empty + 8 * ((it - 1) % G2_STAGES));
            }
        }
        const int lr = wg * 64 + (warp & 3) * 16 + g;
        uint32_t xv[16], sv[16];
        mbar_wait(bar_epi, 0);
#pragma unroll
        for (int j = 0; j < 8; j++) {
#pragma unroll
            for (int hh = 0; hh < 2; hh++) {
                const int r = lr + 8 * hh;
                asm volatile("ld.shared.u32 %0, [%1];" : "=r"(xv[2 * j + hh]) : "r"(sX + r * 128 + ((j ^ (r & 7)) << 4) + 4 * t));
                const int c0 = 8 * j + 2 * t;
                const uint32_t sa = sS + (r >> 6) * 8192 + (((r & 63) >> 3) << 4) + (r & 7) * 2;
                uint16_t s0r, s1r;
                asm volatile("ld.shared.u16 %0, [%1];" : "=h"(s0r) : "r"((sa + c0 * 128) ^ ((c0 & 7) << 4)));
                asm volatile("ld.shared.u16 %0, [%1];" : "=h"(s1r) : "r"((sa + (c0 + 1) * 128) ^ (((c0 + 1) & 7) << 4)));
                sv[2 * j + hh] = (uint32_t)s0r | ((uint32_t)s1r << 16);
            }
        }
        wgmma_wait<0>();
        if (threadIdx.x == 0) STAMP(3, 4);
        {
            uint32_t remote, rbar;
            asm volatile("mapa.shared::cluster.u32 %0, %1, %2;" : "=r"(remote) : "r"(sXch + threadIdx.x * 16), "r"(kh ^ 1));
            asm volatile("mapa.shared::cluster.u32 %0, %1, %2;" : "=r"(rbar) : "r"(bar_xch), "r"(kh ^ 1));
            if (kh == 0) {
#pragma unroll
                for (int i = 0; i < 8; i++)
                    asm volatile("st.async.shared::cluster.mbarrier::complete_tx::bytes.v4.f32 [%0], {%1,%2,%3,%4}, [%5];" ::"r"(remote + i * 4096),
                                 "f"(acc[32 + 4 * i]), "f"(acc[33 + 4 * i]), "f"(acc[34 + 4 * i]), "f"(acc[35 + 4 * i]), "r"(rbar) : "memory");
            } else {
#pragma unroll
                for (int i = 0; i < 8; i++)
                    asm volatile("st.async.shared::cluster.mbarrier::complete_tx::bytes.v4.f32 [%0], {%1,%2,%3,%4}, [%5];" ::"r"(remote + i * 4096),
                                 "f"(acc[4 * i]), "f"(acc[1 + 4 * i]), "f"(acc[2 + 4 * i]), "f"(acc[3 + 4 * i]), "r"(rbar) : "memory");
#pragma unroll
                for (int i = 0; i < 32; i++) acc[i] = acc[32 + i];
            }
        }
        if (threadIdx.x == 0) STAMP(3, 6);
        mbar_wait(bar_xch, 0);
        if (threadIdx.x == 0) STAMP(3, 7);
#pragma unroll
        for (int j = 0; j < 8; j++) {
            float4 o;
            asm volatile("ld.shared.v4.f32 {%0,%1,%2,%3}, [%4];" : "=f"(o.x), "=f"(o.y), "=f"(o.z), "=f"(o.w) : "r"(sXch + threadIdx.x * 16 + j * 4096));
            acc[4 * j] += o.x; acc[4 * j + 1] += o.y; acc[4 * j + 2] += o.z; acc[4 * j + 3] += o.w;
        }
#pragma unroll
        for (int i = 0; i < 16; i++) {
            float f0 = bf16_round(acc[2 * i]), f1 = bf16_round(acc[2 * i + 1]);
            float g0 = bf16_round(__fdividef(f0, 1.0f + __expf(-f0)));
            float g1 = bf16_round(__fdividef(f1, 1.0f + __expf(-f1)));
            float o0 = bf_lo(xv[i]) + bf16_round(bf_lo(sv[i]) * g0);
            float o1 = bf_hi(xv[i]) + bf16_round(bf_hi(sv[i]) * g1);
            xv[i] = pack_bf16(o0, o1);
        }
#pragma unroll
        for (int j = 0; j < 8; j++) {
#pragma unroll
            for (int hh = 0; hh < 2; hh++) {
                const int r = lr + 8 * hh;
                asm volatile("st.shared.u32 [%0], %1;" ::"r"(sX + r * 128 + ((j ^ (r & 7)) << 4) + 4 * t), "r"(xv[2 * j + hh]) : "memory");
            }
        }
        if (threadIdx.x == 0) STAMP(3, 9);
        fence_async_smem();
        __syncwarp();
        if (lane == 0) {
            tma_store_2d(&tm_out, sX + (wg * 64 + (warp & 3) * 16) * 128, col_fin, rb * 128 + wg * 64 + (warp & 3) * 16);
            bulk_commit();
            bulk_wait_read<0>();
        }
        if (threadIdx.x == 0) STAMP(3, 5);
    }
}

typedef CUresult (*EncodeFn)(CUtensorMap*, CUtensorMapDataType, cuuint32_t, void*, const cuuint64_t*, const cuuint64_t*,
                             const cuuint32_t*, const cuuint32_t*, CUtensorMapInterleave, CUtensorMapSwizzle,
                             CUtensorMapL2promotion, CUtensorMapFloatOOBfill);

void make_map(EncodeFn fn, CUtensorMap* m, const void* ptr, uint64_t inner, uint64_t outer, uint32_t box_in, uint32_t box_out,
              CUtensorMapSwizzle swz = CU_TENSOR_MAP_SWIZZLE_128B) {
    cuuint64_t dims[2] = {inner, outer};
    cuuint64_t strides[1] = {inner * 2};
    cuuint32_t box[2] = {box_in, box_out};
    cuuint32_t es[2] = {1, 1};
    fn(m, CU_TENSOR_MAP_DATA_TYPE_BFLOAT16, 2, const_cast<void*>(ptr), dims, strides, box, es, CU_TENSOR_MAP_INTERLEAVE_NONE,
       swz, CU_TENSOR_MAP_L2_PROMOTION_L2_256B, CU_TENSOR_MAP_FLOAT_OOB_FILL_NONE);
}
void make_map3(EncodeFn fn, CUtensorMap* m, const void* ptr, uint64_t cols, uint64_t rows, uint32_t atom, uint32_t box_rows,
               uint32_t box_atoms, CUtensorMapSwizzle swz) {
    cuuint64_t dims[3] = {atom, rows, cols / atom};
    cuuint64_t strides[2] = {cols * 2, (cuuint64_t)atom * 2};
    cuuint32_t box[3] = {atom, box_rows, box_atoms};
    cuuint32_t es[3] = {1, 1, 1};
    fn(m, CU_TENSOR_MAP_DATA_TYPE_BFLOAT16, 3, const_cast<void*>(ptr), dims, strides, box, es, CU_TENSOR_MAP_INTERLEAVE_NONE,
       swz, CU_TENSOR_MAP_L2_PROMOTION_L2_256B, CU_TENSOR_MAP_FLOAT_OOB_FILL_NONE);
}

template <typename... Args>
void launch_pdl(void (*kern)(Args...), int grid, int block, int smem, bool pdl, int cluster, Args... args) {
    cudaLaunchConfig_t cfg = {};
    cfg.gridDim = dim3(grid); cfg.blockDim = dim3(block); cfg.dynamicSmemBytes = smem; cfg.stream = cudaStreamPerThread;
    cudaLaunchAttribute at[2];
    int n = 0;
    if (pdl) {
        at[n].id = cudaLaunchAttributeProgrammaticStreamSerialization;
        at[n].val.programmaticStreamSerializationAllowed = 1;
        n++;
    }
    if (cluster > 1) {
        at[n].id = cudaLaunchAttributeClusterDimension;
        at[n].val.clusterDim.x = cluster; at[n].val.clusterDim.y = 1; at[n].val.clusterDim.z = 1;
        n++;
    }
    cfg.attrs = at; cfg.numAttrs = n;
    cudaLaunchKernelEx(&cfg, kern, args...);
}

}

extern "C" void kernel_launch(void* const* d_in, const int* in_sizes, int n_in, void* d_out, int out_size) {
    const __nv_bfloat16* x = (const __nv_bfloat16*)d_in[0];
    const __nv_bfloat16* A_re = (const __nv_bfloat16*)d_in[1];
    const __nv_bfloat16* A_im = (const __nv_bfloat16*)d_in[2];
    const __nv_bfloat16* B_re = (const __nv_bfloat16*)d_in[3];
    const __nv_bfloat16* B_im = (const __nv_bfloat16*)d_in[4];
    const __nv_bfloat16* C_re = (const __nv_bfloat16*)d_in[5];
    const __nv_bfloat16* C_im = (const __nv_bfloat16*)d_in[6];
    const __nv_bfloat16* log_dt = (const __nv_bfloat16*)d_in[7];
    const __nv_bfloat16* Dskip = (const __nv_bfloat16*)d_in[8];
    const __nv_bfloat16* wg = (const __nv_bfloat16*)d_in[10];
    const __nv_bfloat16* wu = (const __nv_bfloat16*)d_in[11];
    const __nv_bfloat16* wd = (const __nv_bfloat16*)d_in[12];
    __nv_bfloat16* out = (__nv_bfloat16*)d_out;

    static bool init = false;
    static CUtensorMap tm_xn, tm_wg4, tm_wu4, tm_wg3, tm_wu3, tm_hst, tm_hst96, tm_h, tm_wd, tm_x, tm_sT, tm_out;
    static const void* last_ptrs[5] = {nullptr, nullptr, nullptr, nullptr, nullptr};
    if (!init || last_ptrs[0] != wg || last_ptrs[1] != wu || last_ptrs[2] != wd || last_ptrs[3] != x || last_ptrs[4] != out) {
        void* fnp = nullptr;
        cudaDriverEntryPointQueryResult qres;
        cudaGetDriverEntryPoint("cuTensorMapEncodeTiled", &fnp, cudaEnableDefault, &qres);
        EncodeFn fn = (EncodeFn)fnp;
        void *p_xn, *p_h, *p_sT;
        cudaGetSymbolAddress(&p_xn, g_xn);
        cudaGetSymbolAddress(&p_h, g_h);
        cudaGetSymbolAddress(&p_sT, g_sT);
        make_map(fn, &tm_xn, p_xn, D_, L_, 64, 128);
        make_map3(fn, &tm_wg4, wg, F_, D_, 32, 32, 4, CU_TENSOR_MAP_SWIZZLE_64B);
        make_map3(fn, &tm_wu4, wu, F_, D_, 32, 32, 4, CU_TENSOR_MAP_SWIZZLE_64B);
        make_map3(fn, &tm_wg3, wg, F_, D_, 32, 32, 3, CU_TENSOR_MAP_SWIZZLE_64B);
        make_map3(fn, &tm_wu3, wu, F_, D_, 32, 32, 3, CU_TENSOR_MAP_SWIZZLE_64B);
        make_map(fn, &tm_hst, p_h, F_, L_, 16, 16, CU_TENSOR_MAP_SWIZZLE_NONE);
        make_map(fn, &tm_hst96, p_h, F_, L_, 96, 16, CU_TENSOR_MAP_SWIZZLE_NONE);
        make_map(fn, &tm_h, p_h, F_, L_, 64, 128);
        make_map3(fn, &tm_wd, wd, D_, F_, 64, 64, 2, CU_TENSOR_MAP_SWIZZLE_128B);
        make_map(fn, &tm_x, x, D_, L_, 64, 128);
        make_map(fn, &tm_sT, p_sT, L_, D_, 64, 64);
        make_map(fn, &tm_out, out, D_, L_, 64, 16);
        cudaFuncSetAttribute(front_kernel, cudaFuncAttributeMaxDynamicSharedMemorySize, CV_SMEM);
        cudaFuncSetAttribute(gemm1_kernel, cudaFuncAttributeMaxDynamicSharedMemorySize, G1_SMEM);
        cudaFuncSetAttribute(gemm2_kernel, cudaFuncAttributeMaxDynamicSharedMemorySize, G2_SMEM);
        last_ptrs[0] = wg; last_ptrs[1] = wu; last_ptrs[2] = wd; last_ptrs[3] = x; last_ptrs[4] = out;
        init = true;
    }
    launch_pdl(front_kernel, D_ / CV_CH, 512, CV_SMEM, false, 1, x, A_re, A_im, B_re, B_im, C_re, C_im, log_dt, Dskip, wg, wu, wd);
    launch_pdl(gemm1_kernel, 128, 384, G1_SMEM, true, 1, tm_xn, tm_wg4, tm_wu4, tm_wg3, tm_wu3, tm_hst, tm_hst96);
    launch_pdl(gemm2_kernel, 128, 384, G2_SMEM, true, 2, tm_h, tm_wd, tm_x, tm_sT, tm_out);
}
```

```cpp
#include <cuda_runtime.h>
#include <cuda_bf16.h>
#include <cuda.h>
#include <stdint.h>

namespace {

constexpr int L_ = 2048, D_ = 512, NS_ = 128, F_ = 1792;

__device__ __align__(1024) __nv_bfloat16 g_xn[L_ * D_];
__device__ __align__(1024) __nv_bfloat16 g_xnT[D_ * L_];
__device__ __align__(1024) __nv_bfloat16 g_sT[D_ * L_];
__device__ __align__(1024) __nv_bfloat16 g_h[L_ * F_];
__device__ unsigned int g_ln_count;

#define STAMP(k, i)

__device__ __forceinline__ uint32_t smem_u32(const void* p) { return (uint32_t)__cvta_generic_to_shared(p); }
__device__ __forceinline__ void pdl_wait() { asm volatile("griddepcontrol.wait;" ::: "memory"); }
__device__ __forceinline__ void pdl_launch() { asm volatile("griddepcontrol.launch_dependents;" ::: "memory"); }

__device__ __forceinline__ void mbar_init(uint32_t bar, uint32_t cnt) {
    asm volatile("mbarrier.init.shared::cta.b64 [%0], %1;" ::"r"(bar), "r"(cnt) : "memory");
}
__device__ __forceinline__ void mbar_expect_tx(uint32_t bar, uint32_t bytes) {
    asm volatile("mbarrier.arrive.expect_tx.shared::cta.b64 _, [%0], %1;" ::"r"(bar), "r"(bytes) : "memory");
}
__device__ __forceinline__ void mbar_arrive(uint32_t bar) {
    asm volatile("mbarrier.arrive.shared::cta.b64 _, [%0];" ::"r"(bar) : "memory");
}
__device__ __forceinline__ void mbar_wait(uint32_t bar, uint32_t parity) {
    asm volatile(
        "{\n.reg .pred p;\n"
        "WAIT_LOOP:\n"
        "mbarrier.try_wait.parity.shared::cta.b64 p, [%0], %1;\n"
        "@p bra WAIT_DONE;\n"
        "bra WAIT_LOOP;\n"
        "WAIT_DONE:\n}\n" ::"r"(bar), "r"(parity) : "memory");
}
__device__ __forceinline__ void tma_load_2d(uint32_t dst, const CUtensorMap* tm, int c0, int c1, uint32_t bar) {
    asm volatile(
        "cp.async.bulk.tensor.2d.shared::cluster.global.mbarrier::complete_tx::bytes [%0], [%1, {%3, %4}], [%2];"
        ::"r"(dst), "l"((uint64_t)tm), "r"(bar), "r"(c0), "r"(c1) : "memory");
}
__device__ __forceinline__ void prefetch_tmap(const CUtensorMap* tm) {
    asm volatile("prefetch.tensormap [%0];" ::"l"((uint64_t)tm) : "memory");
}
__device__ __forceinline__ uint64_t make_desc(uint32_t addr, uint32_t lbo, uint32_t sbo, uint64_t mode = 1) {
    uint64_t d = 0;
    d |= (uint64_t)((addr & 0x3FFFF) >> 4);
    d |= (uint64_t)((lbo >> 4) & 0x3FFF) << 16;
    d |= (uint64_t)((sbo >> 4) & 0x3FFF) << 32;
    d |= mode << 62;
    return d;
}
__device__ __forceinline__ void wgmma_fence() { asm volatile("wgmma.fence.sync.aligned;" ::: "memory"); }
__device__ __forceinline__ void wgmma_commit() { asm volatile("wgmma.commit_group.sync.aligned;" ::: "memory"); }
template <int N> __device__ __forceinline__ void wgmma_wait() {
    asm volatile("wgmma.wait_group.sync.aligned %0;" ::"n"(N) : "memory");
}

#define R8(a, i) "+f"(a[i + 0]), "+f"(a[i + 1]), "+f"(a[i + 2]), "+f"(a[i + 3]), "+f"(a[i + 4]), "+f"(a[i + 5]), "+f"(a[i + 6]), "+f"(a[i + 7])

__device__ __forceinline__ void wgmma_n256_k32(float* a, uint64_t da0, uint64_t da1, uint64_t db0, uint64_t db1, int scale_d) {
    asm volatile(
        "{\n.reg .pred p;\nsetp.ne.b32 p, %132, 0;\n"
        "wgmma.mma_async.sync.aligned.m64n256k16.f32.bf16.bf16 {%0,%1,%2,%3,%4,%5,%6,%7,%8,%9,%10,%11,%12,%13,%14,%15,%16,%17,%18,%19,%20,%21,%22,%23,%24,%25,%26,%27,%28,%29,%30,%31,%32,%33,%34,%35,%36,%37,%38,%39,%40,%41,%42,%43,%44,%45,%46,%47,%48,%49,%50,%51,%52,%53,%54,%55,%56,%57,%58,%59,%60,%61,%62,%63,%64,%65,%66,%67,%68,%69,%70,%71,%72,%73,%74,%75,%76,%77,%78,%79,%80,%81,%82,%83,%84,%85,%86,%87,%88,%89,%90,%91,%92,%93,%94,%95,%96,%97,%98,%99,%100,%101,%102,%103,%104,%105,%106,%107,%108,%109,%110,%111,%112,%113,%114,%115,%116,%117,%118,%119,%120,%121,%122,%123,%124,%125,%126,%127}, %128, %130, p, 1, 1, 0, 1;\n"
        "wgmma.mma_async.sync.aligned.m64n256k16.f32.bf16.bf16 {%0,%1,%2,%3,%4,%5,%6,%7,%8,%9,%10,%11,%12,%13,%14,%15,%16,%17,%18,%19,%20,%21,%22,%23,%24,%25,%26,%27,%28,%29,%30,%31,%32,%33,%34,%35,%36,%37,%38,%39,%40,%41,%42,%43,%44,%45,%46,%47,%48,%49,%50,%51,%52,%53,%54,%55,%56,%57,%58,%59,%60,%61,%62,%63,%64,%65,%66,%67,%68,%69,%70,%71,%72,%73,%74,%75,%76,%77,%78,%79,%80,%81,%82,%83,%84,%85,%86,%87,%88,%89,%90,%91,%92,%93,%94,%95,%96,%97,%98,%99,%100,%101,%102,%103,%104,%105,%106,%107,%108,%109,%110,%111,%112,%113,%114,%115,%116,%117,%118,%119,%120,%121,%122,%123,%124,%125,%126,%127}, %129, %131, 1, 1, 1, 0, 1;\n"
        "}\n"
        : R8(a, 0), R8(a, 8), R8(a, 16), R8(a, 24), R8(a, 32), R8(a, 40), R8(a, 48), R8(a, 56), R8(a, 64), R8(a, 72), R8(a, 80), R8(a, 88), R8(a, 96), R8(a, 104), R8(a, 112), R8(a, 120)
        : "l"(da0), "l"(da1), "l"(db0), "l"(db1), "r"(scale_d));
}
__device__ __forceinline__ void wgmma_n192_k32(float* a, uint64_t da0, uint64_t da1, uint64_t db0, uint64_t db1, int scale_d) {
    asm volatile(
        "{\n.reg .pred p;\nsetp.ne.b32 p, %100, 0;\n"
        "wgmma.mma_async.sync.aligned.m64n192k16.f32.bf16.bf16 {%0,%1,%2,%3,%4,%5,%6,%7,%8,%9,%10,%11,%12,%13,%14,%15,%16,%17,%18,%19,%20,%21,%22,%23,%24,%25,%26,%27,%28,%29,%30,%31,%32,%33,%34,%35,%36,%37,%38,%39,%40,%41,%42,%43,%44,%45,%46,%47,%48,%49,%50,%51,%52,%53,%54,%55,%56,%57,%58,%59,%60,%61,%62,%63,%64,%65,%66,%67,%68,%69,%70,%71,%72,%73,%74,%75,%76,%77,%78,%79,%80,%81,%82,%83,%84,%85,%86,%87,%88,%89,%90,%91,%92,%93,%94,%95}, %96, %98, p, 1, 1, 0, 1;\n"
        "wgmma.mma_async.sync.aligned.m64n192k16.f32.bf16.bf16 {%0,%1,%2,%3,%4,%5,%6,%7,%8,%9,%10,%11,%12,%13,%14,%15,%16,%17,%18,%19,%20,%21,%22,%23,%24,%25,%26,%27,%28,%29,%30,%31,%32,%33,%34,%35,%36,%37,%38,%39,%40,%41,%42,%43,%44,%45,%46,%47,%48,%49,%50,%51,%52,%53,%54,%55,%56,%57,%58,%59,%60,%61,%62,%63,%64,%65,%66,%67,%68,%69,%70,%71,%72,%73,%74,%75,%76,%77,%78,%79,%80,%81,%82,%83,%84,%85,%86,%87,%88,%89,%90,%91,%92,%93,%94,%95}, %97, %99, 1, 1, 1, 0, 1;\n"
        "}\n"
        : R8(a, 0), R8(a, 8), R8(a, 16), R8(a, 24), R8(a, 32), R8(a, 40), R8(a, 48), R8(a, 56), R8(a, 64), R8(a, 72), R8(a, 80), R8(a, 88)
        : "l"(da0), "l"(da1), "l"(db0), "l"(db1), "r"(scale_d));
}
__device__ __forceinline__ void wgmma_n192(float* a, uint64_t da0, uint64_t db0, int scale_d) {
    asm volatile(
        "{\n.reg .pred p;\nsetp.ne.b32 p, %98, 0;\n"
        "wgmma.mma_async.sync.aligned.m64n192k16.f32.bf16.bf16 {%0,%1,%2,%3,%4,%5,%6,%7,%8,%9,%10,%11,%12,%13,%14,%15,%16,%17,%18,%19,%20,%21,%22,%23,%24,%25,%26,%27,%28,%29,%30,%31,%32,%33,%34,%35,%36,%37,%38,%39,%40,%41,%42,%43,%44,%45,%46,%47,%48,%49,%50,%51,%52,%53,%54,%55,%56,%57,%58,%59,%60,%61,%62,%63,%64,%65,%66,%67,%68,%69,%70,%71,%72,%73,%74,%75,%76,%77,%78,%79,%80,%81,%82,%83,%84,%85,%86,%87,%88,%89,%90,%91,%92,%93,%94,%95}, %96, %97, p, 1, 1, 0, 1;\n"
        "}\n"
        : R8(a, 0), R8(a, 8), R8(a, 16), R8(a, 24), R8(a, 32), R8(a, 40), R8(a, 48), R8(a, 56), R8(a, 64), R8(a, 72), R8(a, 80), R8(a, 88)
        : "l"(da0), "l"(db0), "r"(scale_d));
}
__device__ __forceinline__ void wgmma_n128_k64(float* a, uint64_t da0, uint64_t da1, uint64_t da2, uint64_t da3,
                                               uint64_t db0, uint64_t db1, uint64_t db2, uint64_t db3, int scale_d) {
    asm volatile(
        "{\n.reg .pred p;\nsetp.ne.b32 p, %72, 0;\n"
        "wgmma.mma_async.sync.aligned.m64n128k16.f32.bf16.bf16 {%0,%1,%2,%3,%4,%5,%6,%7,%8,%9,%10,%11,%12,%13,%14,%15,%16,%17,%18,%19,%20,%21,%22,%23,%24,%25,%26,%27,%28,%29,%30,%31,%32,%33,%34,%35,%36,%37,%38,%39,%40,%41,%42,%43,%44,%45,%46,%47,%48,%49,%50,%51,%52,%53,%54,%55,%56,%57,%58,%59,%60,%61,%62,%63}, %64, %68, p, 1, 1, 0, 1;\n"
        "wgmma.mma_async.sync.aligned.m64n128k16.f32.bf16.bf16 {%0,%1,%2,%3,%4,%5,%6,%7,%8,%9,%10,%11,%12,%13,%14,%15,%16,%17,%18,%19,%20,%21,%22,%23,%24,%25,%26,%27,%28,%29,%30,%31,%32,%33,%34,%35,%36,%37,%38,%39,%40,%41,%42,%43,%44,%45,%46,%47,%48,%49,%50,%51,%52,%53,%54,%55,%56,%57,%58,%59,%60,%61,%62,%63}, %65, %69, 1, 1, 1, 0, 1;\n"
        "wgmma.mma_async.sync.aligned.m64n128k16.f32.bf16.bf16 {%0,%1,%2,%3,%4,%5,%6,%7,%8,%9,%10,%11,%12,%13,%14,%15,%16,%17,%18,%19,%20,%21,%22,%23,%24,%25,%26,%27,%28,%29,%30,%31,%32,%33,%34,%35,%36,%37,%38,%39,%40,%41,%42,%43,%44,%45,%46,%47,%48,%49,%50,%51,%52,%53,%54,%55,%56,%57,%58,%59,%60,%61,%62,%63}, %66, %70, 1, 1, 1, 0, 1;\n"
        "wgmma.mma_async.sync.aligned.m64n128k16.f32.bf16.bf16 {%0,%1,%2,%3,%4,%5,%6,%7,%8,%9,%10,%11,%12,%13,%14,%15,%16,%17,%18,%19,%20,%21,%22,%23,%24,%25,%26,%27,%28,%29,%30,%31,%32,%33,%34,%35,%36,%37,%38,%39,%40,%41,%42,%43,%44,%45,%46,%47,%48,%49,%50,%51,%52,%53,%54,%55,%56,%57,%58,%59,%60,%61,%62,%63}, %67, %71, 1, 1, 1, 0, 1;\n"
        "}\n"
        : R8(a, 0), R8(a, 8), R8(a, 16), R8(a, 24), R8(a, 32), R8(a, 40), R8(a, 48), R8(a, 56)
        : "l"(da0), "l"(da1), "l"(da2), "l"(da3), "l"(db0), "l"(db1), "l"(db2), "l"(db3), "r"(scale_d));
}

__device__ __forceinline__ float bf16_round(float x) {
    uint32_t p; asm("cvt.rn.bf16x2.f32 %0, %1, %2;" : "=r"(p) : "f"(x), "f"(0.0f));
    return __uint_as_float(p);
}
__device__ __forceinline__ uint32_t pack_bf16(float lo, float hi) {
    __nv_bfloat162 v = __floats2bfloat162_rn(lo, hi);
    return *reinterpret_cast<uint32_t*>(&v);
}
__device__ __forceinline__ float bf_lo(uint32_t v) { return __uint_as_float(v << 16); }
__device__ __forceinline__ float bf_hi(uint32_t v) { return __uint_as_float(v & 0xFFFF0000u); }

struct cplx { float r, i; };
__device__ __forceinline__ cplx cmul(cplx a, cplx b) {
    cplx c; c.r = a.r * b.r - a.i * b.i; c.i = a.r * b.i + a.i * b.r; return c;
}
__device__ __forceinline__ cplx csq(cplx a) {
    cplx c; c.r = a.r * a.r - a.i * a.i; c.i = 2.0f * a.r * a.i; return c;
}
__device__ __forceinline__ cplx cexp_m(float ar2, float ai2, float m) {
    float mag;
    asm("ex2.approx.ftz.f32 %0, %1;" : "=f"(mag) : "f"(ar2 * m));
    float rr = ai2 * m;
    rr -= (rr + 12582912.0f) - 12582912.0f;
    float th = rr * 6.283185307179586f;
    cplx c; c.r = mag * __cosf(th); c.i = mag * __sinf(th);
    return c;
}
__device__ __forceinline__ uint32_t to_tf32(float x) { return __float_as_uint(x) + 0x1000u; }
__device__ __forceinline__ void mma_tf32(float* c, uint32_t a0, uint32_t a1, uint32_t a2, uint32_t a3, uint32_t b0, uint32_t b1) {
    asm volatile("mma.sync.aligned.m16n8k8.row.col.f32.tf32.tf32.f32 {%0,%1,%2,%3}, {%4,%5,%6,%7}, {%8,%9}, {%0,%1,%2,%3};"
                 : "+f"(c[0]), "+f"(c[1]), "+f"(c[2]), "+f"(c[3])
                 : "r"(a0), "r"(a1), "r"(a2), "r"(a3), "r"(b0), "r"(b1));
}
__device__ __forceinline__ void mma_bf16(float* c, uint32_t a0, uint32_t a1, uint32_t a2, uint32_t a3, uint32_t b0, uint32_t b1) {
    asm volatile("mma.sync.aligned.m16n8k16.row.col.f32.bf16.bf16.f32 {%0,%1,%2,%3}, {%4,%5,%6,%7}, {%8,%9}, {%0,%1,%2,%3};"
                 : "+f"(c[0]), "+f"(c[1]), "+f"(c[2]), "+f"(c[3])
                 : "r"(a0), "r"(a1), "r"(a2), "r"(a3), "r"(b0), "r"(b1));
}
__device__ __forceinline__ void named_bar(int id, int n) { asm volatile("bar.sync %0, %1;" ::"r"(id), "r"(n) : "memory"); }
__device__ __forceinline__ void ldsm_x4(uint32_t addr, uint32_t& r0, uint32_t& r1, uint32_t& r2, uint32_t& r3) {
    asm volatile("ldmatrix.sync.aligned.m8n8.x4.shared.b16 {%0,%1,%2,%3}, [%4];" : "=r"(r0), "=r"(r1), "=r"(r2), "=r"(r3) : "r"(addr));
}
__device__ __forceinline__ void ldsm_x4_t(uint32_t addr, uint32_t& r0, uint32_t& r1, uint32_t& r2, uint32_t& r3) {
    asm volatile("ldmatrix.sync.aligned.m8n8.x4.trans.shared.b16 {%0,%1,%2,%3}, [%4];" : "=r"(r0), "=r"(r1), "=r"(r2), "=r"(r3) : "r"(addr));
}

constexpr int CV_CH = 4;
constexpr int CV_O_CONST = 0;
constexpr int CV_O_KP = 12288;
constexpr int CV_O_Q = CV_O_KP + 10368;
constexpr int CV_O_Q2 = CV_O_Q + 2304;
constexpr int CV_O_Q3 = CV_O_Q2 + 1024;
constexpr int CV_O_Q4X = CV_O_Q3 + 768;
constexpr int CV_O_W3 = CV_O_Q4X + 256;
constexpr int CV_O_W5 = CV_O_W3 + 3104;
constexpr int CV_O_W7 = CV_O_W5 + 3104;
constexpr int CV_O_W9 = CV_O_W7 + 2048;
constexpr int CV_O_STG = 32768;
constexpr int CV_O_U = CV_O_W9 + 2048;
constexpr int CV_PER_CH = CV_O_U + 4352;
static_assert(CV_O_U >= CV_O_STG + 4096, "staging overlaps u");
constexpr int CV_SMEM = CV_CH * CV_PER_CH;

constexpr int LN_ROWS = 16;

__global__ void __launch_bounds__(544, 1) front_kernel(const __nv_bfloat16* __restrict__ x,
                                                        const __nv_bfloat16* __restrict__ A_re, const __nv_bfloat16* __restrict__ A_im,
                                                        const __nv_bfloat16* __restrict__ B_re, const __nv_bfloat16* __restrict__ B_im,
                                                        const __nv_bfloat16* __restrict__ C_re, const __nv_bfloat16* __restrict__ C_im,
                                                        const __nv_bfloat16* __restrict__ log_dt, const __nv_bfloat16* __restrict__ Dskip,
                                                        const __nv_bfloat16* __restrict__ wg, const __nv_bfloat16* __restrict__ wu,
                                                        const __nv_bfloat16* __restrict__ wd) {
    pdl_launch();
    if (threadIdx.x == 0) STAMP(1, 0);
    extern __shared__ __align__(16) uint8_t smem[];
    const int warp = threadIdx.x >> 5, lane = threadIdx.x & 31;
    const int ch = warp >> 2, w = warp & 3, tc = threadIdx.x & 127;
    const int d = blockIdx.x * CV_CH + ch;
    const int g = lane >> 2, t = lane & 3;
    uint8_t* base = smem + ch * CV_PER_CH;
    float4* s_const = reinterpret_cast<float4*>(base + CV_O_CONST);
    float* s_kp = reinterpret_cast<float*>(base + CV_O_KP);
    uint32_t* s_q = reinterpret_cast<uint32_t*>(base + CV_O_Q);
    uint32_t* s_q2 = reinterpret_cast<uint32_t*>(base + CV_O_Q2);
    uint32_t* s_q3 = reinterpret_cast<uint32_t*>(base + CV_O_Q3);
    uint32_t* s_q4 = reinterpret_cast<uint32_t*>(base + CV_O_Q4X);
    __nv_bfloat16* s_u = reinterpret_cast<__nv_bfloat16*>(base + CV_O_U);
    const int bar_id = 1 + ch;

    if (warp == 16) {
        __syncthreads();
        __syncthreads();
        if (lane == 0) asm volatile("red.release.gpu.global.add.u32 [%0], 1;" ::"l"(&g_ln_count) : "memory");
        for (int i = lane; i < 336; i += 32) {
            const int m = i / 112, j = i - m * 112;
            const char* wp = (const char*)(m == 0 ? wg : (m == 1 ? wu : wd));
            asm volatile("prefetch.global.L2 [%0];" ::"l"(wp + ((size_t)blockIdx.x * 112 + j) * 128));
        }
        if (lane == 0) {
            unsigned int v = 0;
            for (int spin = 0; spin < (1 << 22); spin++) {
                asm volatile("ld.acquire.gpu.global.u32 %0, [%1];" : "=r"(v) : "l"(&g_ln_count) : "memory");
                if (v >= gridDim.x) break;
            }
        }
        __syncthreads();
        return;
    }
    const int row = blockIdx.x * LN_ROWS + warp;
    const uint4 xv0 = *reinterpret_cast<const uint4*>(x + (size_t)row * D_ + lane * 8);
    const uint4 xv1 = *reinterpret_cast<const uint4*>(x + (size_t)row * D_ + 256 + lane * 8);
    const size_t poff = (size_t)d * NS_ + tc;
    const __nv_bfloat16 p_ar = A_re[poff], p_ai = A_im[poff], p_br = B_re[poff], p_bi = B_im[poff], p_cr = C_re[poff], p_ci = C_im[poff];
    const __nv_bfloat16 p_ldt = log_dt[d], p_dsk = Dskip[d];
    {
        __nv_bfloat16 (*tile)[D_ + 8] = reinterpret_cast<__nv_bfloat16 (*)[D_ + 8]>(smem);
        float f[16];
        const uint32_t wv[8] = {xv0.x, xv0.y, xv0.z, xv0.w, xv1.x, xv1.y, xv1.z, xv1.w};
#pragma unroll
        for (int i = 0; i < 8; i++) { f[2 * i] = bf_lo(wv[i]); f[2 * i + 1] = bf_hi(wv[i]); }
        float sm = 0.f;
#pragma unroll
        for (int i = 0; i < 16; i++) sm += f[i];
#pragma unroll
        for (int o = 16; o > 0; o >>= 1) sm += __shfl_xor_sync(0xffffffffu, sm, o);
        const float mean = sm * (1.0f / D_);
        if (threadIdx.x == 0 && mean > -1e30f) STAMP(0, 1);
        float q = 0.f;
#pragma unroll
        for (int i = 0; i < 16; i++) { float dd = f[i] - mean; q += dd * dd; }
#pragma unroll
        for (int o = 16; o > 0; o >>= 1) q += __shfl_xor_sync(0xffffffffu, q, o);
        const float mb = bf16_round(mean);
        const float vb = bf16_round(q * (1.0f / D_));
        const float den = bf16_round(sqrtf(bf16_round(vb + 1e-5f)));
        uint32_t o[8];
#pragma unroll
        for (int i = 0; i < 8; i++) {
            float a = __fdiv_rn(bf16_round(f[2 * i] - mb), den);
            float b = __fdiv_rn(bf16_round(f[2 * i + 1] - mb), den);
            o[i] = pack_bf16(a, b);
        }
        __nv_bfloat16* dst = g_xn + (size_t)row * D_;
        *reinterpret_cast<uint4*>(dst + lane * 8) = make_uint4(o[0], o[1], o[2], o[3]);
        *reinterpret_cast<uint4*>(dst + 256 + lane * 8) = make_uint4(o[4], o[5], o[6], o[7]);
        *reinterpret_cast<uint4*>(&tile[warp][lane * 8]) = make_uint4(o[0], o[1], o[2], o[3]);
        *reinterpret_cast<uint4*>(&tile[warp][256 + lane * 8]) = make_uint4(o[4], o[5], o[6], o[7]);
        if (threadIdx.x == 0) STAMP(0, 2);
        __syncthreads();
        if (threadIdx.x == 0) STAMP(0, 3);
        {
            const int c = threadIdx.x;
            uint32_t ot[8];
#pragma unroll
            for (int i = 0; i < 8; i++) {
                uint32_t lo = *reinterpret_cast<const uint16_t*>(&tile[2 * i][c]);
                uint32_t hi = *reinterpret_cast<const uint16_t*>(&tile[2 * i + 1][c]);
                ot[i] = lo | (hi << 16);
            }
            __nv_bfloat16* dT = g_xnT + (size_t)c * L_ + blockIdx.x * LN_ROWS;
            *reinterpret_cast<uint4*>(dT) = make_uint4(ot[0], ot[1], ot[2], ot[3]);
            *reinterpret_cast<uint4*>(dT + 8) = make_uint4(ot[4], ot[5], ot[6], ot[7]);
        }
        __syncthreads();
        if (threadIdx.x == 0) STAMP(0, 0);
    }

    float tail;
    {
        const float dt = bf16_round(expf(__bfloat162float(p_ldt)));
        const float ar = dt * __bfloat162float(p_ar), ai = dt * __bfloat162float(p_ai);
        const cplx db = {dt * __bfloat162float(p_br), dt * __bfloat162float(p_bi)};
        const cplx cc = {__bfloat162float(p_cr), __bfloat162float(p_ci)};
        const cplx cb = cmul(cc, db);
        const float ar2 = ar * 1.4426950408889634f, ai2 = ai * 0.15915494309189535f;
        const cplx e8 = cexp_m(ar2, ai2, 8.f), e128 = cexp_m(ar2, ai2, 128.f);
        const cplx cb8 = cmul(cb, e8);
        const cplx e256 = cexp_m(ar2, ai2, 256.f), e512 = cexp_m(ar2, ai2, 512.f), e1024 = cexp_m(ar2, ai2, 1024.f);
        const cplx c256 = cmul(cb, e256), c512 = cmul(cb, e512), c1024 = cmul(cb, e1024);
        const cplx c768 = cmul(c512, e256), c1280 = cmul(c1024, e256), c1536 = cmul(c1024, e512);
        const cplx c1792 = cmul(c1536, e256);
        tail = cmul(c1024, e1024).r;
        float4* c = s_const + tc * 6;
        c[0] = make_float4(ar2, ai2, cb.r, cb.i);
        c[1] = make_float4(e128.r, e128.i, cb8.r, cb8.i);
        c[2] = make_float4(c256.r, c256.i, e8.r, e8.i);
        c[3] = make_float4(c512.r, c512.i, c768.r, c768.i);
        c[4] = make_float4(c1024.r, c1024.i, c1280.r, c1280.i);
        c[5] = make_float4(c1536.r, c1536.i, c1792.r, c1792.i);
#pragma unroll
        for (int o = 16; o > 0; o >>= 1) tail += __shfl_xor_sync(0xffffffffu, tail, o);
    }
    __syncwarp();
    if (threadIdx.x == 0) STAMP(1, 1);
    {
        float acc[5][4];
#pragma unroll
        for (int i = 0; i < 5; i++) { acc[i][0] = acc[i][1] = acc[i][2] = acc[i][3] = 0.f; }
        const float gf = (float)g;
        const int src4 = ((g & 3) << 2) | t;
#pragma unroll 2
        for (int s = 0; s < 8; s++) {
            const float4* c = s_const + (w * 32 + s * 4 + t) * 6;
            const float4 k0 = c[0], k1 = c[1], k2 = c[2];
            const float2 k3 = reinterpret_cast<const float2*>(c + 3)[g >> 2];
            const float2 k4 = reinterpret_cast<const float2*>(c + 4)[g >> 1];
            const cplx cb = {k0.z, k0.w}, e128 = {k1.x, k1.y}, cb8 = {k1.z, k1.w}, c256 = {k2.x, k2.y}, e8 = {k2.z, k2.w};
            const cplx c2 = {k3.x, k3.y}, c3 = {k4.x, k4.y};
            const cplx p1 = cexp_m(k0.x, k0.y, gf);
            const cplx p2 = csq(p1), p4 = csq(p2);
            const cplx r16a = csq(csq(p4));
            cplx q4;
            q4.r = __shfl_sync(0xffffffffu, p4.r, src4);
            q4.i = __shfl_sync(0xffffffffu, p4.i, src4);
            const cplx r16b = cmul(r16a, e128);
            const cplx f0a = cmul(cb, p1), f0b = cmul(cb8, p1), f1 = cmul(c256, p2), f2 = cmul(c2, q4);
            cplx f3 = cmul(c3, e8);
            if (!(g & 1)) f3 = c3;
            const uint32_t a0 = to_tf32(r16a.r), a1 = to_tf32(r16b.r), a2 = to_tf32(-r16a.i), a3 = to_tf32(-r16b.i);
            mma_tf32(acc[0], a0, a1, a2, a3, to_tf32(f0a.r), to_tf32(f0a.i));
            mma_tf32(acc[1], a0, a1, a2, a3, to_tf32(f0b.r), to_tf32(f0b.i));
            mma_tf32(acc[2], a0, a1, a2, a3, to_tf32(f1.r), to_tf32(f1.i));
            mma_tf32(acc[3], a0, a1, a2, a3, to_tf32(f2.r), to_tf32(f2.i));
            mma_tf32(acc[4], a0, a1, a2, a3, to_tf32(f3.r), to_tf32(f3.i));
        }
        float* kv = s_kp + w * 648;
#pragma unroll
        for (int hh = 0; hh < 2; hh++) {
            const int i = g + 8 * hh;
            *reinterpret_cast<float2*>(kv + 16 * i + 2 * t) = make_float2(acc[0][2 * hh], acc[0][2 * hh + 1]);
            *reinterpret_cast<float2*>(kv + 16 * i + 8 + 2 * t) = make_float2(acc[1][2 * hh], acc[1][2 * hh + 1]);
            *reinterpret_cast<float2*>(kv + 256 + 8 * i + 2 * t) = make_float2(acc[2][2 * hh], acc[2][2 * hh + 1]);
            *reinterpret_cast<float2*>(kv + 384 + 64 * (t >> 1) + 2 * (t & 1) + 4 * i) = make_float2(acc[3][2 * hh], acc[3][2 * hh + 1]);
            *reinterpret_cast<float2*>(kv + 512 + 32 * t + 2 * i) = make_float2(acc[4][2 * hh], acc[4][2 * hh + 1]);
        }
        if (lane == 0) kv[640] = tail;
    }

    named_bar(bar_id, 128);
    if (threadIdx.x == 0) STAMP(1, 2);
#pragma unroll
    for (int i = 0; i < 6; i++) {
        const int idx = tc + 128 * i;
        if (idx < 641) s_kp[idx] = (s_kp[idx] + s_kp[648 + idx]) + (s_kp[1296 + idx] + s_kp[1944 + idx]);
    }
    named_bar(bar_id, 128);
    {
        auto kdir = [&](int l) -> float {
            if (l < 0 || l > 514) return 0.f;
            const int idx = (l < 256) ? l : (l > 512 ? 384 : 128 + ((l + ((l >> 1) & 1)) >> 1));
            return s_kp[idx];
        };
#pragma unroll
        for (int i = 0; i < 5; i++) {
            const int e = tc + 128 * i;
            if (e < 576) s_q[e] = pack_bf16(kdir(e - 16), kdir(e - 17));
        }
        if (tc < 64) {
            const int xx = 1008 + tc;
            const float k1024 = s_kp[512];
            s_q4[tc] = pack_bf16((xx == 1027 || xx == 1028) ? k1024 : 0.f, (xx == 1028 || xx == 1029) ? k1024 : 0.f);
        }
#pragma unroll
        for (int i = 0; i < 2; i++) {
            const int e = tc + 128 * i, a = e >> 6, ii = (e & 63) - 16;
            const int b = 385 + (a >> 1) + 2 * (a & 1);
            const float v0 = (ii >= 0 && ii < 32) ? s_kp[b + 4 * ii] : 0.f;
            const float v1 = (ii >= 1 && ii < 33) ? s_kp[b + 4 * (ii - 1)] : 0.f;
            s_q2[e] = pack_bf16(v0, v1);
        }
#pragma unroll
        for (int i = 0; i < 2; i++) {
            const int e = tc + 128 * i;
            if (e < 192) {
                const int a = e >= 96, jj = e - 96 * a - 16;
                const float v0 = (jj >= 0 && jj < 64) ? s_kp[513 + a + 2 * jj] : 0.f;
                const float v1 = (jj >= 1 && jj < 65) ? s_kp[513 + a + 2 * (jj - 1)] : 0.f;
                s_q3[e] = pack_bf16(v0, v1);
            }
        }
    }
    if (threadIdx.x == 0) STAMP(1, 3);
    __syncthreads();
    if (threadIdx.x == 0) STAMP(1, 4);
    {
        if (tc < 16) *reinterpret_cast<uint4*>(s_u + tc * 8) = make_uint4(0, 0, 0, 0);
        const uint4* src = reinterpret_cast<const uint4*>(g_xnT + (size_t)d * L_);
        const uint4 v0 = src[tc], v1 = src[tc + 128];
        *reinterpret_cast<uint4*>(s_u + 128 + tc * 8) = v0;
        *reinterpret_cast<uint4*>(s_u + 128 + (tc + 128) * 8) = v1;
        if (tc < 2) *reinterpret_cast<uint4*>(base + (tc ? CV_O_W5 : CV_O_W3)) = make_uint4(0, 0, 0, 0);
    }
    named_bar(bar_id, 128);
#pragma unroll
    for (int rep = 0; rep < 2; rep++) {
        const int m = tc + 128 * rep;
        if (m < 192) {
            float P[30];
            const uint4* up = reinterpret_cast<const uint4*>(s_u + 128 + 8 * m - 24);
            P[0] = 0.f;
#pragma unroll
            for (int c4 = 0; c4 < 4; c4++) {
                const uint4 v = up[c4];
                const uint32_t ww[4] = {v.x, v.y, v.z, v.w};
#pragma unroll
                for (int j = 0; j < 4; j++) {
                    const int k = c4 * 8 + 2 * j;
                    if (k + 1 <= 29) P[k + 1] = P[k] + bf_lo(ww[j]);
                    if (k + 2 <= 29) P[k + 2] = P[k + 1] + bf_hi(ww[j]);
                }
            }
            uint32_t o3[4], o5[4], o7[4], o9[4];
#pragma unroll
            for (int j = 0; j < 4; j++) {
                const int i = 2 * j;
                o3[j] = pack_bf16(P[i + 22] - P[i + 19], P[i + 23] - P[i + 20]);
                o5[j] = pack_bf16(P[i + 19] - P[i + 14], P[i + 20] - P[i + 15]);
                o7[j] = pack_bf16(P[i + 20] - P[i + 13], P[i + 21] - P[i + 14]);
                o9[j] = pack_bf16(P[i + 13] - P[i + 4], P[i + 14] - P[i + 5]);
            }
            *reinterpret_cast<uint4*>(base + CV_O_W3 + 16 + m * 16) = make_uint4(o3[0], o3[1], o3[2], o3[3]);
            *reinterpret_cast<uint4*>(base + CV_O_W5 + 16 + m * 16) = make_uint4(o5[0], o5[1], o5[2], o5[3]);
            if (m < 128) {
                *reinterpret_cast<uint4*>(base + CV_O_W7 + m * 16) = make_uint4(o7[0], o7[1], o7[2], o7[3]);
                *reinterpret_cast<uint4*>(base + CV_O_W9 + m * 16) = make_uint4(o9[0], o9[1], o9[2], o9[3]);
            }
        }
    }
    if (threadIdx.x == 0) STAMP(1, 5);
    named_bar(bar_id, 128);
    const int wsel = (w - ch) & 3;
    if (wsel & 1) return;
    const int hb = wsel >> 1;
    float acc[16][4];
#pragma unroll
    for (int i = 0; i < 16; i++) { acc[i][0] = acc[i][1] = acc[i][2] = acc[i][3] = 0.f; }
    const uint32_t sb_addr = smem_u32(base);
    const int mi = lane >> 3, rowi = lane & 7;
#pragma unroll 1
    for (int rr = 0; rr < 4; rr++) {
        const int r = 4 * hb + rr;
        uint32_t ub[16][2];
        {
            const uint32_t addr = sb_addr + CV_O_U + (uint32_t)((128 + 16 * (8 * (mi >> 1) + rowi - r) + 8 * (mi & 1)) * 2);
#pragma unroll
            for (int j = 0; j < 16; j += 2) ldsm_x4(addr + (uint32_t)(j * 256), ub[j][0], ub[j][1], ub[j + 1][0], ub[j + 1][1]);
        }
        const uint32_t* qp = s_q + 16 + 16 * r + g - 2 * t;
        uint32_t af[4][3];
#pragma unroll
        for (int q = 0; q < 4; q++) { af[q][0] = qp[128 * q]; af[q][1] = qp[128 * q + 8]; af[q][2] = qp[128 * q - 8]; }
#pragma unroll
        for (int q = 0; q < 4; q++) {
#pragma unroll
            for (int nt = q; nt < 16; nt++) mma_bf16(acc[nt], af[q][0], af[q][1], af[q][2], af[q][0], ub[nt - q][0], ub[nt - q][1]);
        }
        if (r < 2) {
            {
                const uint32_t a0 = qp[512], a1 = qp[520], a2 = qp[504];
#pragma unroll
                for (int nt = 4; nt < 16; nt++) mma_bf16(acc[nt], a0, a1, a2, a0, ub[nt - 4][0], ub[nt - 4][1]);
            }
            {
                const uint32_t* q4p = s_q4 + 16 + 16 * r + g - 2 * t;
                const uint32_t a0 = q4p[0], a1 = q4p[8], a2 = q4p[-8];
#pragma unroll
                for (int nt = 8; nt < 16; nt++) mma_bf16(acc[nt], a0, a1, a2, a0, ub[nt - 8][0], ub[nt - 8][1]);
            }
        }
    }
#pragma unroll 1
    for (int a = hb; a <= 3 * hb; a++) {
        uint32_t bq[7];
        const uint32_t* q2 = s_q2 + a * 64 + 16 + g - 2 * t - 32;
#pragma unroll
        for (int dlt = 3; dlt <= 9; dlt++) bq[dlt - 3] = q2[8 * dlt];
        const uint32_t addr = sb_addr + ((a >> 1) ? CV_O_W5 : CV_O_W3) + (uint32_t)((8 + 16 * (8 * (mi >> 1) + rowi) + 8 * (mi & 1) - 8 * (a & 1)) * 2);
        uint32_t aa[6][4];
#pragma unroll
        for (int kp = 0; kp < 6; kp++) ldsm_x4_t(addr + kp * 512, aa[kp][0], aa[kp][1], aa[kp][2], aa[kp][3]);
#pragma unroll
        for (int kp = 0; kp < 6; kp++) {
#pragma unroll
            for (int dlt = 4; dlt <= 9; dlt++) {
                if (2 * kp + dlt < 16) mma_bf16(acc[2 * kp + dlt], aa[kp][0], aa[kp][1], aa[kp][2], aa[kp][3], bq[dlt - 3], bq[dlt - 4]);
            }
        }
    }
    if (hb == 0) {
#pragma unroll 1
        for (int a = 0; a < 2; a++) {
            uint32_t bq[9];
            const uint32_t* q3 = s_q3 + a * 96 + 16 + g - 2 * t - 64;
#pragma unroll
            for (int dlt = 7; dlt <= 15; dlt++) bq[dlt - 7] = q3[8 * dlt];
            const uint32_t addr = sb_addr + (a ? CV_O_W9 : CV_O_W7) + (uint32_t)((16 * (8 * (mi >> 1) + rowi) + 8 * (mi & 1)) * 2);
            uint32_t aa[4][4];
#pragma unroll
            for (int kp = 0; kp < 4; kp++) ldsm_x4_t(addr + kp * 512, aa[kp][0], aa[kp][1], aa[kp][2], aa[kp][3]);
#pragma unroll
            for (int kp = 0; kp < 4; kp++) {
#pragma unroll
                for (int dlt = 8; dlt <= 15; dlt++) {
                    if (2 * kp + dlt < 16) mma_bf16(acc[2 * kp + dlt], aa[kp][0], aa[kp][1], aa[kp][2], aa[kp][3], bq[dlt - 7], bq[dlt - 8]);
                }
            }
        }
    }
    if (threadIdx.x == 0) STAMP(1, 6);
    {
        float4* xch = reinterpret_cast<float4*>(base + CV_O_CONST) + hb * 256;
        if (hb) {
#pragma unroll
            for (int i = 0; i < 8; i++) xch[i * 32 + lane] = make_float4(acc[i][0], acc[i][1], acc[i][2], acc[i][3]);
#pragma unroll
            for (int i = 0; i < 8; i++) { acc[i][0] = acc[8 + i][0]; acc[i][1] = acc[8 + i][1]; acc[i][2] = acc[8 + i][2]; acc[i][3] = acc[8 + i][3]; }
        } else {
#pragma unroll
            for (int i = 0; i < 8; i++) xch[i * 32 + lane] = make_float4(acc[8 + i][0], acc[8 + i][1], acc[8 + i][2], acc[8 + i][3]);
        }
    }
    named_bar(bar_id, 64);
    if (threadIdx.x == 0) STAMP(1, 10);
    {
        const float4* xch = reinterpret_cast<const float4*>(base + CV_O_CONST) + (hb ^ 1) * 256 + lane;
        const float dsk = __bfloat162float(p_dsk);
        uint16_t* stg = reinterpret_cast<uint16_t*>(base + CV_O_KP);
        const uint16_t* uu = reinterpret_cast<const uint16_t*>(s_u) + 128;
#pragma unroll
        for (int i = 0; i < 8; i++) {
            const float4 p0 = xch[i * 32];
            const float y[4] = {acc[i][0] + p0.x, acc[i][1] + p0.y, acc[i][2] + p0.z, acc[i][3] + p0.w};
            const int nt = 8 * hb + i;
#pragma unroll
            for (int e = 0; e < 4; e++) {
                const int tau = 16 * (8 * nt + 2 * t + (e & 1)) + g + 8 * (e >> 1);
                const float sv = bf16_round(y[e]) + bf16_round(__uint_as_float((uint32_t)uu[tau] << 16) * dsk);
                stg[tau] = (uint16_t)(__float_as_uint(bf16_round(sv)) >> 16);
            }
        }
        __syncwarp();
        if (threadIdx.x == 0) STAMP(1, 11);
        uint4* dst = reinterpret_cast<uint4*>(g_sT + (size_t)d * L_ + hb * 1024);
        const uint4* srcp = reinterpret_cast<const uint4*>(stg + hb * 1024);
#pragma unroll
        for (int i = 0; i < 4; i++) dst[i * 32 + lane] = srcp[i * 32 + lane];
    }
    if (threadIdx.x == 0) STAMP(1, 7);
}

__device__ __forceinline__ uint32_t cluster_rank() { uint32_t r; asm volatile("mov.u32 %0, %%cluster_ctarank;" : "=r"(r)); return r; }
__device__ __forceinline__ void cluster_sync_all() {
    asm volatile("barrier.cluster.arrive.release.aligned;\nbarrier.cluster.wait.acquire.aligned;" ::: "memory");
}
__device__ __forceinline__ void mbar_arrive_remote(uint32_t bar, uint32_t cta) {
    asm volatile("{\n.reg .b32 ra;\nmapa.shared::cluster.u32 ra, %0, %1;\n"
                 "mbarrier.arrive.shared::cluster.b64 _, [ra];\n}\n" ::"r"(bar), "r"(cta) : "memory");
}
__device__ __forceinline__ void tma_load_2d_mc(uint32_t dst, const CUtensorMap* tm, int c0, int c1, uint32_t bar, uint16_t mask) {
    asm volatile(
        "cp.async.bulk.tensor.2d.shared::cluster.global.mbarrier::complete_tx::bytes.multicast::cluster [%0], [%1, {%3, %4}], [%2], %5;"
        ::"r"(dst), "l"((uint64_t)tm), "r"(bar), "r"(c0), "r"(c1), "h"(mask) : "memory");
}
__device__ __forceinline__ void tma_store_2d(const CUtensorMap* tm, uint32_t src, int c0, int c1) {
    asm volatile("cp.async.bulk.tensor.2d.global.shared::cta.bulk_group [%0, {%2, %3}], [%1];"
                 ::"l"((uint64_t)tm), "r"(src), "r"(c0), "r"(c1) : "memory");
}
__device__ __forceinline__ void bulk_commit() { asm volatile("cp.async.bulk.commit_group;" ::: "memory"); }
template <int N> __device__ __forceinline__ void bulk_wait_read() { asm volatile("cp.async.bulk.wait_group.read %0;" ::"n"(N) : "memory"); }
template <int N> __device__ __forceinline__ void bulk_wait() { asm volatile("cp.async.bulk.wait_group %0;" ::"n"(N) : "memory"); }
__device__ __forceinline__ void fence_async_smem() { asm volatile("fence.proxy.async.shared::cta;" ::: "memory"); }
__device__ __forceinline__ void stmatrix_x4(uint32_t addr, uint32_t r0, uint32_t r1, uint32_t r2, uint32_t r3) {
    asm volatile("stmatrix.sync.aligned.m8n8.x4.shared.b16 [%0], {%1,%2,%3,%4};" ::"r"(addr), "r"(r0), "r"(r1), "r"(r2), "r"(r3) : "memory");
}

constexpr int G1_STAGES = 5;
constexpr int G1_A_BYTES = 8 * 16384;
constexpr int G1_B_STAGE = 16384;
constexpr int G1_STG = 8 * 1024;
constexpr int G1_SMEM = G1_A_BYTES + G1_STAGES * G1_B_STAGE + G1_STG + 1024 + 256;
constexpr int G1_ITERS = 32;

__device__ __forceinline__ void tma_load_3d(uint32_t dst, const CUtensorMap* tm, int c0, int c1, int c2, uint32_t bar) {
    asm volatile(
        "cp.async.bulk.tensor.3d.shared::cluster.global.mbarrier::complete_tx::bytes [%0], [%1, {%3, %4, %5}], [%2];"
        ::"r"(dst), "l"((uint64_t)tm), "r"(bar), "r"(c0), "r"(c1), "r"(c2) : "memory");
}

__device__ __forceinline__ float gelu_tanh(float x) {
    float u = x * (0.7978845608028654f + 0.035677408136300125f * x * x);
    float t; asm("tanh.approx.f32 %0, %1;" : "=f"(t) : "f"(u));
    float hx = 0.5f * x;
    return fmaf(hx, t, hx);
}
__device__ __forceinline__ uint32_t geglu_pair(uint32_t g2, uint32_t u2) {
    uint32_t a = pack_bf16(gelu_tanh(bf_lo(g2)), gelu_tanh(bf_hi(g2)));
    uint32_t r; asm("mul.rn.bf16x2 %0, %1, %2;" : "=r"(r) : "r"(a), "r"(u2));
    return r;
}

__global__ void __launch_bounds__(384, 1) gemm1_kernel(const __grid_constant__ CUtensorMap tm_xn,
                                                        const __grid_constant__ CUtensorMap tm_wg4,
                                                        const __grid_constant__ CUtensorMap tm_wu4,
                                                        const __grid_constant__ CUtensorMap tm_wg3,
                                                        const __grid_constant__ CUtensorMap tm_wu3,
                                                        const __grid_constant__ CUtensorMap tm_hst,
                                                        const __grid_constant__ CUtensorMap tm_hst96) {
    pdl_launch();
    if (threadIdx.x == 0) STAMP(2, 0);
    extern __shared__ uint8_t smem_raw[];
    const uint32_t sbase = (smem_u32(smem_raw) + 1023) & ~1023u;
    const uint32_t sA = sbase, sB = sbase + G1_A_BYTES, sStg = sB + G1_STAGES * G1_B_STAGE, sBar = sStg + G1_STG;
    const uint32_t bar_a = sBar, bar_full = sBar + 64, bar_empty = sBar + 64 + 8 * G1_STAGES;
    const int rb = blockIdx.x >> 3, cj = blockIdx.x & 7;
    const int warp = threadIdx.x >> 5, lane = threadIdx.x & 31;

    if (threadIdx.x == 0) {
        for (int i = 0; i < 8; i++) mbar_init(bar_a + 8 * i, 1);
        for (int i = 0; i < G1_STAGES; i++) { mbar_init(bar_full + 8 * i, 1); mbar_init(bar_empty + 8 * i, 8); }
        asm volatile("fence.mbarrier_init.release.cluster;" ::: "memory");
    }
    __syncthreads();

    if (warp >= 8) {
        asm volatile("setmaxnreg.dec.sync.aligned.u32 40;");
        if (lane == 0) {
            const int pw = warp - 8;
            if (pw == 0) { prefetch_tmap(&tm_wg4); prefetch_tmap(&tm_wu4); prefetch_tmap(&tm_xn); }
            if (pw == 1) { prefetch_tmap(&tm_wg3); prefetch_tmap(&tm_wu3); prefetch_tmap(&tm_hst); prefetch_tmap(&tm_hst96); }
            for (int it = pw; it < G1_ITERS; it += 4) {
                const int s = it % G1_STAGES, kb = it & 15;
                if (it >= G1_STAGES) mbar_wait(bar_empty + 8 * s, ((it / G1_STAGES) - 1) & 1);
                const uint32_t dst = sB + s * G1_B_STAGE;
                if (it < 16) {
                    mbar_expect_tx(bar_full + 8 * s, 16384);
                    tma_load_3d(dst, &tm_wg4, 0, kb * 32, cj * 7, bar_full + 8 * s);
                    tma_load_3d(dst + 8192, &tm_wu4, 0, kb * 32, cj * 7, bar_full + 8 * s);
                } else {
                    mbar_expect_tx(bar_full + 8 * s, 12288);
                    tma_load_3d(dst, &tm_wg3, 0, kb * 32, cj * 7 + 4, bar_full + 8 * s);
                    tma_load_3d(dst + 6144, &tm_wu3, 0, kb * 32, cj * 7 + 4, bar_full + 8 * s);
                }
                if (it < 4) {
                    pdl_wait();
                    if (pw == 0) { STAMP(2, 1); if (blockIdx.x == 0) g_ln_count = 0; }
                    for (int k = pw; k < 8; k += 4) {
                        mbar_expect_tx(bar_a + 8 * k, 16384);
                        tma_load_2d(sA + k * 16384, &tm_xn, k * 64, rb * 128, bar_a + 8 * k);
                    }
                }
            }
        }
    } else {
        asm volatile("setmaxnreg.inc.sync.aligned.u32 232;");
        const int wg = __shfl_sync(0xffffffffu, (int)(threadIdx.x >> 7), 0);
        float r[160];
        const int row0 = rb * 128 + wg * 64 + (warp & 3) * 16;
        const uint64_t descA = make_desc(sA + wg * 8192, 16, 1024);
        const uint64_t descB = make_desc(sB, 2048, 512, 2);
        const uint32_t stg = sStg + warp * 1024;
        const uint32_t st_off = (uint32_t)(((lane & 7) + ((lane >> 3) & 1) * 8) * 32 + (lane >> 4) * 16);
        __nv_bfloat16* hrow = g_h + (size_t)(row0 + (lane >> 1)) * F_ + (lane & 1) * 8 + cj * 224;
#pragma unroll
        for (int kb = 0; kb < 16; kb++) {
            const int it = kb, s = it % G1_STAGES;
            if ((kb & 1) == 0) mbar_wait(bar_a + 8 * (kb >> 1), 0);
            mbar_wait(bar_full + 8 * s, (it / G1_STAGES) & 1);
            if (threadIdx.x == 0 && (it & 7) == 0) STAMP(2, 2 + it / 8);
            wgmma_fence();
            const uint64_t da = descA + (uint64_t)(((kb >> 1) * 16384 + (kb & 1) * 64) >> 4);
            const uint64_t db = descB + (uint64_t)((s * G1_B_STAGE) >> 4);
            wgmma_n256_k32(r, da, da + 2, db, db + 64, kb != 0);
            wgmma_commit();
            if (kb > 0) {
                wgmma_wait<1>();
                if (lane == 0) mbar_arrive(bar_empty + 8 * ((it - 1) % G1_STAGES));
            }
        }
        wgmma_wait<0>();
        if (lane == 0) mbar_arrive(bar_empty + 8 * (15 % G1_STAGES));
#pragma unroll
        for (int i = 0; i < 32; i++) r[128 + i] = __uint_as_float(pack_bf16(r[2 * i], r[2 * i + 1]));
#pragma unroll
        for (int i = 31; i >= 0; i--) r[96 + i] = __uint_as_float(pack_bf16(r[64 + 2 * i], r[65 + 2 * i]));
        uint32_t eo[4];
        uint4 pv = make_uint4(0, 0, 0, 0);
#pragma unroll
        for (int kb = 0; kb < 16; kb++) {
            const int it = 16 + kb, s = it % G1_STAGES;
            mbar_wait(bar_full + 8 * s, (it / G1_STAGES) & 1);
            if (threadIdx.x == 0 && (it & 7) == 0) STAMP(2, 2 + it / 8);
            wgmma_fence();
            const uint64_t da = descA + (uint64_t)(((kb >> 1) * 16384 + (kb & 1) * 64) >> 4);
            const uint64_t db = descB + (uint64_t)((s * G1_B_STAGE) >> 4);
            const int jj = kb >> 1;
            wgmma_n192(r, da, db, kb != 0);
            eo[(kb & 1) * 2] = geglu_pair(__float_as_uint(r[128 + 2 * kb]), __float_as_uint(r[96 + 2 * kb]));
            wgmma_n192(r, da + 2, db + 64, 1);
            wgmma_commit();
            eo[(kb & 1) * 2 + 1] = geglu_pair(__float_as_uint(r[129 + 2 * kb]), __float_as_uint(r[97 + 2 * kb]));
            if (kb & 1) {
                if (jj > 0) *reinterpret_cast<uint4*>(hrow + (jj - 1) * 16) = pv;
                stmatrix_x4(stg + (jj & 1) * 512 + st_off, eo[0], eo[1], eo[2], eo[3]);
            } else if (jj > 0) {
                __syncwarp();
                asm volatile("ld.shared.v4.u32 {%0,%1,%2,%3}, [%4];" : "=r"(pv.x), "=r"(pv.y), "=r"(pv.z), "=r"(pv.w)
                             : "r"(stg + ((jj - 1) & 1) * 512 + lane * 16));
            }
            if (kb > 0 && it - 1 + G1_STAGES < G1_ITERS) {
                wgmma_wait<1>();
                if (lane == 0) mbar_arrive(bar_empty + 8 * ((it - 1) % G1_STAGES));
            }
        }
        __syncwarp();
        asm volatile("ld.shared.v4.u32 {%0,%1,%2,%3}, [%4];" : "=r"(pv.x), "=r"(pv.y), "=r"(pv.z), "=r"(pv.w) : "r"(stg + 512 + lane * 16));
        wgmma_wait<0>();
        *reinterpret_cast<uint4*>(hrow + 7 * 16) = pv;
        if (threadIdx.x == 0) STAMP(2, 6);
        {
            uint32_t o[24];
#pragma unroll
            for (int i = 0; i < 24; i++) o[i] = geglu_pair(pack_bf16(r[2 * i], r[2 * i + 1]), pack_bf16(r[48 + 2 * i], r[49 + 2 * i]));
            named_bar(1 + wg, 128);
            const uint32_t fbuf = sA + ((warp & 3) >> 1) * 16384 + wg * 8192 + (warp & 1) * 4096;
#pragma unroll
            for (int jj = 0; jj < 6; jj++) stmatrix_x4(fbuf + jj * 512 + st_off, o[4 * jj], o[4 * jj + 1], o[4 * jj + 2], o[4 * jj + 3]);
            __syncwarp();
            uint4 v[6];
#pragma unroll
            for (int jj = 0; jj < 6; jj++)
                asm volatile("ld.shared.v4.u32 {%0,%1,%2,%3}, [%4];" : "=r"(v[jj].x), "=r"(v[jj].y), "=r"(v[jj].z), "=r"(v[jj].w)
                             : "r"(fbuf + jj * 512 + lane * 16));
#pragma unroll
            for (int jj = 0; jj < 6; jj++) *reinterpret_cast<uint4*>(hrow + 128 + jj * 16) = v[jj];
        }
        if (threadIdx.x == 0) STAMP(2, 7);
    }
}

constexpr int G2_STAGES = 5;
constexpr int G2_STAGE = 16384 + 16384;
constexpr int G2_XCH = 32768;
constexpr int G2_EPI = 16384 + 16384;
constexpr int G2_SMEM = G2_STAGES * G2_STAGE + G2_XCH + G2_EPI + 1024 + 256;
constexpr int G2_KB = F_ / 64 / 2;

__global__ void __launch_bounds__(384, 1) gemm2_kernel(const __grid_constant__ CUtensorMap tm_h,
                                                        const __grid_constant__ CUtensorMap tm_wd,
                                                        const __grid_constant__ CUtensorMap tm_x,
                                                        const __grid_constant__ CUtensorMap tm_sT,
                                                        const __grid_constant__ CUtensorMap tm_out) {
    if (threadIdx.x == 0) STAMP(3, 0);
    extern __shared__ uint8_t smem_raw[];
    const uint32_t sbase = (smem_u32(smem_raw) + 1023) & ~1023u;
    const uint32_t sXch = sbase + G2_STAGES * G2_STAGE, sX = sXch + G2_XCH, sS = sX + 16384, sBar = sX + G2_EPI;
    const uint32_t bar_full = sBar, bar_empty = sBar + 8 * G2_STAGES, bar_epi = sBar + 16 * G2_STAGES, bar_xch = bar_epi + 8;
    const uint32_t kh = cluster_rank();
    const int cid = blockIdx.x >> 1;
    const int rb = cid >> 2, nb = cid & 3;
    const int col_fin = nb * 128 + kh * 64;
    const int warp = threadIdx.x >> 5, lane = threadIdx.x & 31;

    if (threadIdx.x == 0) {
        for (int i = 0; i < G2_STAGES; i++) { mbar_init(bar_full + 8 * i, 1); mbar_init(bar_empty + 8 * i, 8); }
        mbar_init(bar_epi, 1);
        mbar_init(bar_xch, 1);
        asm volatile("fence.mbarrier_init.release.cluster;" ::: "memory");
        mbar_expect_tx(bar_xch, G2_XCH);
    }
    cluster_sync_all();

    if (warp >= 8) {
        if (lane == 0) {
            const int pw = warp - 8;
            const int k0 = kh * G2_KB;
            if (pw == 0) { prefetch_tmap(&tm_wd); prefetch_tmap(&tm_h); }
            if (pw == 1) { prefetch_tmap(&tm_x); prefetch_tmap(&tm_sT); prefetch_tmap(&tm_out); }
            for (int it = pw; it < G2_STAGES; it += 4) {
                mbar_expect_tx(bar_full + 8 * it, G2_STAGE);
                tma_load_3d(sbase + it * G2_STAGE + 16384, &tm_wd, 0, (k0 + it) * 64, nb * 2, bar_full + 8 * it);
            }
            if (pw == 3) {
                mbar_expect_tx(bar_epi, G2_EPI);
                tma_load_2d(sX, &tm_x, col_fin, rb * 128, bar_epi);
            }
            pdl_wait();
            if (pw == 0) STAMP(3, 1);
            for (int it = pw; it < G2_STAGES; it += 4)
                tma_load_2d(sbase + it * G2_STAGE, &tm_h, (k0 + it) * 64, rb * 128, bar_full + 8 * it);
            if (pw == 3) {
                tma_load_2d(sS, &tm_sT, rb * 128, col_fin, bar_epi);
                tma_load_2d(sS + 8192, &tm_sT, rb * 128 + 64, col_fin, bar_epi);
            }
            for (int it = G2_STAGES + ((pw + 4 - (G2_STAGES & 3)) & 3); it < G2_KB; it += 4) {
                const int s = it % G2_STAGES;
                mbar_wait(bar_empty + 8 * s, ((it / G2_STAGES) - 1) & 1);
                mbar_expect_tx(bar_full + 8 * s, G2_STAGE);
                tma_load_2d(sbase + s * G2_STAGE, &tm_h, (k0 + it) * 64, rb * 128, bar_full + 8 * s);
                tma_load_3d(sbase + s * G2_STAGE + 16384, &tm_wd, 0, (k0 + it) * 64, nb * 2, bar_full + 8 * s);
            }
        }
    } else {
        const int wg = __shfl_sync(0xffffffffu, (int)(threadIdx.x >> 7), 0);
        const int g = lane >> 2, t = lane & 3;
        float acc[64];
        const uint64_t descA = make_desc(sbase + wg * 8192, 16, 1024);
        const uint64_t descB = make_desc(sbase + 16384, 8192, 1024);
#pragma unroll
        for (int it = 0; it < G2_KB; it++) {
            const int s = it % G2_STAGES;
            mbar_wait(bar_full + 8 * s, (it / G2_STAGES) & 1);
            if (threadIdx.x == 0 && (it == 0 || it == 7)) STAMP(3, 2 + it / 7);
            wgmma_fence();
            {
                const uint64_t da = descA + (uint64_t)((s * G2_STAGE) >> 4);
                const uint64_t db = descB + (uint64_t)((s * G2_STAGE) >> 4);
                wgmma_n128_k64(acc, da, da + 2, da + 4, da + 6, db, db + 128, db + 256, db + 384, it != 0);
            }
            wgmma_commit();
            if (it > 0 && it - 1 + G2_STAGES < G2_KB) {
                wgmma_wait<1>();
                if (lane == 0) mbar_arrive(bar_empty + 8 * ((it - 1) % G2_STAGES));
            }
        }
        const int lr = wg * 64 + (warp & 3) * 16 + g;
        uint32_t xv[16], sv[16];
        mbar_wait(bar_epi, 0);
#pragma unroll
        for (int j = 0; j < 8; j++) {
#pragma unroll
            for (int hh = 0; hh < 2; hh++) {
                const int r = lr + 8 * hh;
                asm volatile("ld.shared.u32 %0, [%1];" : "=r"(xv[2 * j + hh]) : "r"(sX + r * 128 + ((j ^ (r & 7)) << 4) + 4 * t));
                const int c0 = 8 * j + 2 * t;
                const uint32_t sa = sS + (r >> 6) * 8192 + (((r & 63) >> 3) << 4) + (r & 7) * 2;
                uint16_t s0r, s1r;
                asm volatile("ld.shared.u16 %0, [%1];" : "=h"(s0r) : "r"((sa + c0 * 128) ^ ((c0 & 7) << 4)));
                asm volatile("ld.shared.u16 %0, [%1];" : "=h"(s1r) : "r"((sa + (c0 + 1) * 128) ^ (((c0 + 1) & 7) << 4)));
                sv[2 * j + hh] = (uint32_t)s0r | ((uint32_t)s1r << 16);
            }
        }
        wgmma_wait<0>();
        if (threadIdx.x == 0) STAMP(3, 4);
        {
            uint32_t remote, rbar;
            asm volatile("mapa.shared::cluster.u32 %0, %1, %2;" : "=r"(remote) : "r"(sXch + threadIdx.x * 16), "r"(kh ^ 1));
            asm volatile("mapa.shared::cluster.u32 %0, %1, %2;" : "=r"(rbar) : "r"(bar_xch), "r"(kh ^ 1));
            if (kh == 0) {
#pragma unroll
                for (int i = 0; i < 8; i++)
                    asm volatile("st.async.shared::cluster.mbarrier::complete_tx::bytes.v4.f32 [%0], {%1,%2,%3,%4}, [%5];" ::"r"(remote + i * 4096),
                                 "f"(acc[32 + 4 * i]), "f"(acc[33 + 4 * i]), "f"(acc[34 + 4 * i]), "f"(acc[35 + 4 * i]), "r"(rbar) : "memory");
            } else {
#pragma unroll
                for (int i = 0; i < 8; i++)
                    asm volatile("st.async.shared::cluster.mbarrier::complete_tx::bytes.v4.f32 [%0], {%1,%2,%3,%4}, [%5];" ::"r"(remote + i * 4096),
                                 "f"(acc[4 * i]), "f"(acc[1 + 4 * i]), "f"(acc[2 + 4 * i]), "f"(acc[3 + 4 * i]), "r"(rbar) : "memory");
#pragma unroll
                for (int i = 0; i < 32; i++) acc[i] = acc[32 + i];
            }
        }
        if (threadIdx.x == 0) STAMP(3, 6);
        mbar_wait(bar_xch, 0);
        if (threadIdx.x == 0) STAMP(3, 7);
#pragma unroll
        for (int j = 0; j < 8; j++) {
            float4 o;
            asm volatile("ld.shared.v4.f32 {%0,%1,%2,%3}, [%4];" : "=f"(o.x), "=f"(o.y), "=f"(o.z), "=f"(o.w) : "r"(sXch + threadIdx.x * 16 + j * 4096));
            acc[4 * j] += o.x; acc[4 * j + 1] += o.y; acc[4 * j + 2] += o.z; acc[4 * j + 3] += o.w;
        }
#pragma unroll
        for (int i = 0; i < 16; i++) {
            float f0 = bf16_round(acc[2 * i]), f1 = bf16_round(acc[2 * i + 1]);
            float g0 = bf16_round(__fdividef(f0, 1.0f + __expf(-f0)));
            float g1 = bf16_round(__fdividef(f1, 1.0f + __expf(-f1)));
            float o0 = bf_lo(xv[i]) + bf16_round(bf_lo(sv[i]) * g0);
            float o1 = bf_hi(xv[i]) + bf16_round(bf_hi(sv[i]) * g1);
            xv[i] = pack_bf16(o0, o1);
        }
#pragma unroll
        for (int j = 0; j < 8; j++) {
#pragma unroll
            for (int hh = 0; hh < 2; hh++) {
                const int r = lr + 8 * hh;
                asm volatile("st.shared.u32 [%0], %1;" ::"r"(sX + r * 128 + ((j ^ (r & 7)) << 4) + 4 * t), "r"(xv[2 * j + hh]) : "memory");
            }
        }
        if (threadIdx.x == 0) STAMP(3, 9);
        fence_async_smem();
        __syncwarp();
        if (lane == 0) {
            tma_store_2d(&tm_out, sX + (wg * 64 + (warp & 3) * 16) * 128, col_fin, rb * 128 + wg * 64 + (warp & 3) * 16);
            bulk_commit();
            bulk_wait_read<0>();
        }
        if (threadIdx.x == 0) STAMP(3, 5);
    }
}

typedef CUresult (*EncodeFn)(CUtensorMap*, CUtensorMapDataType, cuuint32_t, void*, const cuuint64_t*, const cuuint64_t*,
                             const cuuint32_t*, const cuuint32_t*, CUtensorMapInterleave, CUtensorMapSwizzle,
                             CUtensorMapL2promotion, CUtensorMapFloatOOBfill);

void make_map(EncodeFn fn, CUtensorMap* m, const void* ptr, uint64_t inner, uint64_t outer, uint32_t box_in, uint32_t box_out,
              CUtensorMapSwizzle swz = CU_TENSOR_MAP_SWIZZLE_128B) {
    cuuint64_t dims[2] = {inner, outer};
    cuuint64_t strides[1] = {inner * 2};
    cuuint32_t box[2] = {box_in, box_out};
    cuuint32_t es[2] = {1, 1};
    fn(m, CU_TENSOR_MAP_DATA_TYPE_BFLOAT16, 2, const_cast<void*>(ptr), dims, strides, box, es, CU_TENSOR_MAP_INTERLEAVE_NONE,
       swz, CU_TENSOR_MAP_L2_PROMOTION_L2_256B, CU_TENSOR_MAP_FLOAT_OOB_FILL_NONE);
}
void make_map3(EncodeFn fn, CUtensorMap* m, const void* ptr, uint64_t cols, uint64_t rows, uint32_t atom, uint32_t box_rows,
               uint32_t box_atoms, CUtensorMapSwizzle swz) {
    cuuint64_t dims[3] = {atom, rows, cols / atom};
    cuuint64_t strides[2] = {cols * 2, (cuuint64_t)atom * 2};
    cuuint32_t box[3] = {atom, box_rows, box_atoms};
    cuuint32_t es[3] = {1, 1, 1};
    fn(m, CU_TENSOR_MAP_DATA_TYPE_BFLOAT16, 3, const_cast<void*>(ptr), dims, strides, box, es, CU_TENSOR_MAP_INTERLEAVE_NONE,
       swz, CU_TENSOR_MAP_L2_PROMOTION_L2_256B, CU_TENSOR_MAP_FLOAT_OOB_FILL_NONE);
}

template <typename... Args>
void launch_pdl(void (*kern)(Args...), int grid, int block, int smem, bool pdl, int cluster, Args... args) {
    cudaLaunchConfig_t cfg = {};
    cfg.gridDim = dim3(grid); cfg.blockDim = dim3(block); cfg.dynamicSmemBytes = smem; cfg.stream = cudaStreamPerThread;
    cudaLaunchAttribute at[2];
    int n = 0;
    if (pdl) {
        at[n].id = cudaLaunchAttributeProgrammaticStreamSerialization;
        at[n].val.programmaticStreamSerializationAllowed = 1;
        n++;
    }
    if (cluster > 1) {
        at[n].id = cudaLaunchAttributeClusterDimension;
        at[n].val.clusterDim.x = cluster; at[n].val.clusterDim.y = 1; at[n].val.clusterDim.z = 1;
        n++;
    }
    cfg.attrs = at; cfg.numAttrs = n;
    cudaLaunchKernelEx(&cfg, kern, args...);
}

}

extern "C" void kernel_launch(void* const* d_in, const int* in_sizes, int n_in, void* d_out, int out_size) {
    const __nv_bfloat16* x = (const __nv_bfloat16*)d_in[0];
    const __nv_bfloat16* A_re = (const __nv_bfloat16*)d_in[1];
    const __nv_bfloat16* A_im = (const __nv_bfloat16*)d_in[2];
    const __nv_bfloat16* B_re = (const __nv_bfloat16*)d_in[3];
    const __nv_bfloat16* B_im = (const __nv_bfloat16*)d_in[4];
    const __nv_bfloat16* C_re = (const __nv_bfloat16*)d_in[5];
    const __nv_bfloat16* C_im = (const __nv_bfloat16*)d_in[6];
    const __nv_bfloat16* log_dt = (const __nv_bfloat16*)d_in[7];
    const __nv_bfloat16* Dskip = (const __nv_bfloat16*)d_in[8];
    const __nv_bfloat16* wg = (const __nv_bfloat16*)d_in[10];
    const __nv_bfloat16* wu = (const __nv_bfloat16*)d_in[11];
    const __nv_bfloat16* wd = (const __nv_bfloat16*)d_in[12];
    __nv_bfloat16* out = (__nv_bfloat16*)d_out;

    static bool init = false;
    static CUtensorMap tm_xn, tm_wg4, tm_wu4, tm_wg3, tm_wu3, tm_hst, tm_hst96, tm_h, tm_wd, tm_x, tm_sT, tm_out;
    static const void* last_ptrs[5] = {nullptr, nullptr, nullptr, nullptr, nullptr};
    if (!init || last_ptrs[0] != wg || last_ptrs[1] != wu || last_ptrs[2] != wd || last_ptrs[3] != x || last_ptrs[4] != out) {
        void* fnp = nullptr;
        cudaDriverEntryPointQueryResult qres;
        cudaGetDriverEntryPoint("cuTensorMapEncodeTiled", &fnp, cudaEnableDefault, &qres);
        EncodeFn fn = (EncodeFn)fnp;
        void *p_xn, *p_h, *p_sT;
        cudaGetSymbolAddress(&p_xn, g_xn);
        cudaGetSymbolAddress(&p_h, g_h);
        cudaGetSymbolAddress(&p_sT, g_sT);
        make_map(fn, &tm_xn, p_xn, D_, L_, 64, 128);
        make_map3(fn, &tm_wg4, wg, F_, D_, 32, 32, 4, CU_TENSOR_MAP_SWIZZLE_64B);
        make_map3(fn, &tm_wu4, wu, F_, D_, 32, 32, 4, CU_TENSOR_MAP_SWIZZLE_64B);
        make_map3(fn, &tm_wg3, wg, F_, D_, 32, 32, 3, CU_TENSOR_MAP_SWIZZLE_64B);
        make_map3(fn, &tm_wu3, wu, F_, D_, 32, 32, 3, CU_TENSOR_MAP_SWIZZLE_64B);
        make_map(fn, &tm_hst, p_h, F_, L_, 16, 16, CU_TENSOR_MAP_SWIZZLE_NONE);
        make_map(fn, &tm_hst96, p_h, F_, L_, 96, 16, CU_TENSOR_MAP_SWIZZLE_NONE);
        make_map(fn, &tm_h, p_h, F_, L_, 64, 128);
        make_map3(fn, &tm_wd, wd, D_, F_, 64, 64, 2, CU_TENSOR_MAP_SWIZZLE_128B);
        make_map(fn, &tm_x, x, D_, L_, 64, 128);
        make_map(fn, &tm_sT, p_sT, L_, D_, 64, 64);
        make_map(fn, &tm_out, out, D_, L_, 64, 16);
        cudaFuncSetAttribute(front_kernel, cudaFuncAttributeMaxDynamicSharedMemorySize, CV_SMEM);
        cudaFuncSetAttribute(gemm1_kernel, cudaFuncAttributeMaxDynamicSharedMemorySize, G1_SMEM);
        cudaFuncSetAttribute(gemm2_kernel, cudaFuncAttributeMaxDynamicSharedMemorySize, G2_SMEM);
        last_ptrs[0] = wg; last_ptrs[1] = wu; last_ptrs[2] = wd; last_ptrs[3] = x; last_ptrs[4] = out;
        init = true;
    }
    launch_pdl(front_kernel, D_ / CV_CH, 544, CV_SMEM, false, 1, x, A_re, A_im, B_re, B_im, C_re, C_im, log_dt, Dskip, wg, wu, wd);
    launch_pdl(gemm1_kernel, 128, 384, G1_SMEM, true, 1, tm_xn, tm_wg4, tm_wu4, tm_wg3, tm_wu3, tm_hst, tm_hst96);
    launch_pdl(gemm2_kernel, 128, 384, G2_SMEM, true, 2, tm_h, tm_wd, tm_x, tm_sT, tm_out);
}
```

```cpp
#include <cuda_runtime.h>
#include <cuda_bf16.h>
#include <cuda.h>
#include <stdint.h>

namespace {

constexpr int L_ = 2048, D_ = 512, NS_ = 128, F_ = 1792;

__device__ __align__(1024) __nv_bfloat16 g_xn[L_ * D_];
__device__ __align__(1024) __nv_bfloat16 g_xnT[D_ * L_];
__device__ __align__(1024) __nv_bfloat16 g_sT[D_ * L_];
__device__ __align__(1024) __nv_bfloat16 g_h[L_ * F_];
__device__ unsigned int g_ln_count;

#define STAMP(k, i)

__device__ __forceinline__ uint32_t smem_u32(const void* p) { return (uint32_t)__cvta_generic_to_shared(p); }
__device__ __forceinline__ void pdl_wait() { asm volatile("griddepcontrol.wait;" ::: "memory"); }
__device__ __forceinline__ void pdl_launch() { asm volatile("griddepcontrol.launch_dependents;" ::: "memory"); }

__device__ __forceinline__ void mbar_init(uint32_t bar, uint32_t cnt) {
    asm volatile("mbarrier.init.shared::cta.b64 [%0], %1;" ::"r"(bar), "r"(cnt) : "memory");
}
__device__ __forceinline__ void mbar_expect_tx(uint32_t bar, uint32_t bytes) {
    asm volatile("mbarrier.arrive.expect_tx.shared::cta.b64 _, [%0], %1;" ::"r"(bar), "r"(bytes) : "memory");
}
__device__ __forceinline__ void mbar_arrive(uint32_t bar) {
    asm volatile("mbarrier.arrive.shared::cta.b64 _, [%0];" ::"r"(bar) : "memory");
}
__device__ __forceinline__ void mbar_wait(uint32_t bar, uint32_t parity) {
    asm volatile(
        "{\n.reg .pred p;\n"
        "WAIT_LOOP:\n"
        "mbarrier.try_wait.parity.shared::cta.b64 p, [%0], %1;\n"
        "@p bra WAIT_DONE;\n"
        "bra WAIT_LOOP;\n"
        "WAIT_DONE:\n}\n" ::"r"(bar), "r"(parity) : "memory");
}
__device__ __forceinline__ void tma_load_2d(uint32_t dst, const CUtensorMap* tm, int c0, int c1, uint32_t bar) {
    asm volatile(
        "cp.async.bulk.tensor.2d.shared::cluster.global.mbarrier::complete_tx::bytes [%0], [%1, {%3, %4}], [%2];"
        ::"r"(dst), "l"((uint64_t)tm), "r"(bar), "r"(c0), "r"(c1) : "memory");
}
__device__ __forceinline__ void prefetch_tmap(const CUtensorMap* tm) {
    asm volatile("prefetch.tensormap [%0];" ::"l"((uint64_t)tm) : "memory");
}
__device__ __forceinline__ uint64_t make_desc(uint32_t addr, uint32_t lbo, uint32_t sbo, uint64_t mode = 1) {
    uint64_t d = 0;
    d |= (uint64_t)((addr & 0x3FFFF) >> 4);
    d |= (uint64_t)((lbo >> 4) & 0x3FFF) << 16;
    d |= (uint64_t)((sbo >> 4) & 0x3FFF) << 32;
    d |= mode << 62;
    return d;
}
__device__ __forceinline__ void wgmma_fence() { asm volatile("wgmma.fence.sync.aligned;" ::: "memory"); }
__device__ __forceinline__ void wgmma_commit() { asm volatile("wgmma.commit_group.sync.aligned;" ::: "memory"); }
template <int N> __device__ __forceinline__ void wgmma_wait() {
    asm volatile("wgmma.wait_group.sync.aligned %0;" ::"n"(N) : "memory");
}

#define R8(a, i) "+f"(a[i + 0]), "+f"(a[i + 1]), "+f"(a[i + 2]), "+f"(a[i + 3]), "+f"(a[i + 4]), "+f"(a[i + 5]), "+f"(a[i + 6]), "+f"(a[i + 7])

__device__ __forceinline__ void wgmma_n256_k32(float* a, uint64_t da0, uint64_t da1, uint64_t db0, uint64_t db1, int scale_d) {
    asm volatile(
        "{\n.reg .pred p;\nsetp.ne.b32 p, %132, 0;\n"
        "wgmma.mma_async.sync.aligned.m64n256k16.f32.bf16.bf16 {%0,%1,%2,%3,%4,%5,%6,%7,%8,%9,%10,%11,%12,%13,%14,%15,%16,%17,%18,%19,%20,%21,%22,%23,%24,%25,%26,%27,%28,%29,%30,%31,%32,%33,%34,%35,%36,%37,%38,%39,%40,%41,%42,%43,%44,%45,%46,%47,%48,%49,%50,%51,%52,%53,%54,%55,%56,%57,%58,%59,%60,%61,%62,%63,%64,%65,%66,%67,%68,%69,%70,%71,%72,%73,%74,%75,%76,%77,%78,%79,%80,%81,%82,%83,%84,%85,%86,%87,%88,%89,%90,%91,%92,%93,%94,%95,%96,%97,%98,%99,%100,%101,%102,%103,%104,%105,%106,%107,%108,%109,%110,%111,%112,%113,%114,%115,%116,%117,%118,%119,%120,%121,%122,%123,%124,%125,%126,%127}, %128, %130, p, 1, 1, 0, 1;\n"
        "wgmma.mma_async.sync.aligned.m64n256k16.f32.bf16.bf16 {%0,%1,%2,%3,%4,%5,%6,%7,%8,%9,%10,%11,%12,%13,%14,%15,%16,%17,%18,%19,%20,%21,%22,%23,%24,%25,%26,%27,%28,%29,%30,%31,%32,%33,%34,%35,%36,%37,%38,%39,%40,%41,%42,%43,%44,%45,%46,%47,%48,%49,%50,%51,%52,%53,%54,%55,%56,%57,%58,%59,%60,%61,%62,%63,%64,%65,%66,%67,%68,%69,%70,%71,%72,%73,%74,%75,%76,%77,%78,%79,%80,%81,%82,%83,%84,%85,%86,%87,%88,%89,%90,%91,%92,%93,%94,%95,%96,%97,%98,%99,%100,%101,%102,%103,%104,%105,%106,%107,%108,%109,%110,%111,%112,%113,%114,%115,%116,%117,%118,%119,%120,%121,%122,%123,%124,%125,%126,%127}, %129, %131, 1, 1, 1, 0, 1;\n"
        "}\n"
        : R8(a, 0), R8(a, 8), R8(a, 16), R8(a, 24), R8(a, 32), R8(a, 40), R8(a, 48), R8(a, 56), R8(a, 64), R8(a, 72), R8(a, 80), R8(a, 88), R8(a, 96), R8(a, 104), R8(a, 112), R8(a, 120)
        : "l"(da0), "l"(da1), "l"(db0), "l"(db1), "r"(scale_d));
}
__device__ __forceinline__ void wgmma_n192_k32(float* a, uint64_t da0, uint64_t da1, uint64_t db0, uint64_t db1, int scale_d) {
    asm volatile(
        "{\n.reg .pred p;\nsetp.ne.b32 p, %100, 0;\n"
        "wgmma.mma_async.sync.aligned.m64n192k16.f32.bf16.bf16 {%0,%1,%2,%3,%4,%5,%6,%7,%8,%9,%10,%11,%12,%13,%14,%15,%16,%17,%18,%19,%20,%21,%22,%23,%24,%25,%26,%27,%28,%29,%30,%31,%32,%33,%34,%35,%36,%37,%38,%39,%40,%41,%42,%43,%44,%45,%46,%47,%48,%49,%50,%51,%52,%53,%54,%55,%56,%57,%58,%59,%60,%61,%62,%63,%64,%65,%66,%67,%68,%69,%70,%71,%72,%73,%74,%75,%76,%77,%78,%79,%80,%81,%82,%83,%84,%85,%86,%87,%88,%89,%90,%91,%92,%93,%94,%95}, %96, %98, p, 1, 1, 0, 1;\n"
        "wgmma.mma_async.sync.aligned.m64n192k16.f32.bf16.bf16 {%0,%1,%2,%3,%4,%5,%6,%7,%8,%9,%10,%11,%12,%13,%14,%15,%16,%17,%18,%19,%20,%21,%22,%23,%24,%25,%26,%27,%28,%29,%30,%31,%32,%33,%34,%35,%36,%37,%38,%39,%40,%41,%42,%43,%44,%45,%46,%47,%48,%49,%50,%51,%52,%53,%54,%55,%56,%57,%58,%59,%60,%61,%62,%63,%64,%65,%66,%67,%68,%69,%70,%71,%72,%73,%74,%75,%76,%77,%78,%79,%80,%81,%82,%83,%84,%85,%86,%87,%88,%89,%90,%91,%92,%93,%94,%95}, %97, %99, 1, 1, 1, 0, 1;\n"
        "}\n"
        : R8(a, 0), R8(a, 8), R8(a, 16), R8(a, 24), R8(a, 32), R8(a, 40), R8(a, 48), R8(a, 56), R8(a, 64), R8(a, 72), R8(a, 80), R8(a, 88)
        : "l"(da0), "l"(da1), "l"(db0), "l"(db1), "r"(scale_d));
}
__device__ __forceinline__ void wgmma_n192(float* a, uint64_t da0, uint64_t db0, int scale_d) {
    asm volatile(
        "{\n.reg .pred p;\nsetp.ne.b32 p, %98, 0;\n"
        "wgmma.mma_async.sync.aligned.m64n192k16.f32.bf16.bf16 {%0,%1,%2,%3,%4,%5,%6,%7,%8,%9,%10,%11,%12,%13,%14,%15,%16,%17,%18,%19,%20,%21,%22,%23,%24,%25,%26,%27,%28,%29,%30,%31,%32,%33,%34,%35,%36,%37,%38,%39,%40,%41,%42,%43,%44,%45,%46,%47,%48,%49,%50,%51,%52,%53,%54,%55,%56,%57,%58,%59,%60,%61,%62,%63,%64,%65,%66,%67,%68,%69,%70,%71,%72,%73,%74,%75,%76,%77,%78,%79,%80,%81,%82,%83,%84,%85,%86,%87,%88,%89,%90,%91,%92,%93,%94,%95}, %96, %97, p, 1, 1, 0, 1;\n"
        "}\n"
        : R8(a, 0), R8(a, 8), R8(a, 16), R8(a, 24), R8(a, 32), R8(a, 40), R8(a, 48), R8(a, 56), R8(a, 64), R8(a, 72), R8(a, 80), R8(a, 88)
        : "l"(da0), "l"(db0), "r"(scale_d));
}
__device__ __forceinline__ void wgmma_n128_k64(float* a, uint64_t da0, uint64_t da1, uint64_t da2, uint64_t da3,
                                               uint64_t db0, uint64_t db1, uint64_t db2, uint64_t db3, int scale_d) {
    asm volatile(
        "{\n.reg .pred p;\nsetp.ne.b32 p, %72, 0;\n"
        "wgmma.mma_async.sync.aligned.m64n128k16.f32.bf16.bf16 {%0,%1,%2,%3,%4,%5,%6,%7,%8,%9,%10,%11,%12,%13,%14,%15,%16,%17,%18,%19,%20,%21,%22,%23,%24,%25,%26,%27,%28,%29,%30,%31,%32,%33,%34,%35,%36,%37,%38,%39,%40,%41,%42,%43,%44,%45,%46,%47,%48,%49,%50,%51,%52,%53,%54,%55,%56,%57,%58,%59,%60,%61,%62,%63}, %64, %68, p, 1, 1, 0, 1;\n"
        "wgmma.mma_async.sync.aligned.m64n128k16.f32.bf16.bf16 {%0,%1,%2,%3,%4,%5,%6,%7,%8,%9,%10,%11,%12,%13,%14,%15,%16,%17,%18,%19,%20,%21,%22,%23,%24,%25,%26,%27,%28,%29,%30,%31,%32,%33,%34,%35,%36,%37,%38,%39,%40,%41,%42,%43,%44,%45,%46,%47,%48,%49,%50,%51,%52,%53,%54,%55,%56,%57,%58,%59,%60,%61,%62,%63}, %65, %69, 1, 1, 1, 0, 1;\n"
        "wgmma.mma_async.sync.aligned.m64n128k16.f32.bf16.bf16 {%0,%1,%2,%3,%4,%5,%6,%7,%8,%9,%10,%11,%12,%13,%14,%15,%16,%17,%18,%19,%20,%21,%22,%23,%24,%25,%26,%27,%28,%29,%30,%31,%32,%33,%34,%35,%36,%37,%38,%39,%40,%41,%42,%43,%44,%45,%46,%47,%48,%49,%50,%51,%52,%53,%54,%55,%56,%57,%58,%59,%60,%61,%62,%63}, %66, %70, 1, 1, 1, 0, 1;\n"
        "wgmma.mma_async.sync.aligned.m64n128k16.f32.bf16.bf16 {%0,%1,%2,%3,%4,%5,%6,%7,%8,%9,%10,%11,%12,%13,%14,%15,%16,%17,%18,%19,%20,%21,%22,%23,%24,%25,%26,%27,%28,%29,%30,%31,%32,%33,%34,%35,%36,%37,%38,%39,%40,%41,%42,%43,%44,%45,%46,%47,%48,%49,%50,%51,%52,%53,%54,%55,%56,%57,%58,%59,%60,%61,%62,%63}, %67, %71, 1, 1, 1, 0, 1;\n"
        "}\n"
        : R8(a, 0), R8(a, 8), R8(a, 16), R8(a, 24), R8(a, 32), R8(a, 40), R8(a, 48), R8(a, 56)
        : "l"(da0), "l"(da1), "l"(da2), "l"(da3), "l"(db0), "l"(db1), "l"(db2), "l"(db3), "r"(scale_d));
}

__device__ __forceinline__ float bf16_round(float x) {
    uint32_t p; asm("cvt.rn.bf16x2.f32 %0, %1, %2;" : "=r"(p) : "f"(x), "f"(0.0f));
    return __uint_as_float(p);
}
__device__ __forceinline__ uint32_t pack_bf16(float lo, float hi) {
    __nv_bfloat162 v = __floats2bfloat162_rn(lo, hi);
    return *reinterpret_cast<uint32_t*>(&v);
}
__device__ __forceinline__ float bf_lo(uint32_t v) { return __uint_as_float(v << 16); }
__device__ __forceinline__ float bf_hi(uint32_t v) { return __uint_as_float(v & 0xFFFF0000u); }

struct cplx { float r, i; };
__device__ __forceinline__ cplx cmul(cplx a, cplx b) {
    cplx c; c.r = a.r * b.r - a.i * b.i; c.i = a.r * b.i + a.i * b.r; return c;
}
__device__ __forceinline__ cplx csq(cplx a) {
    cplx c; c.r = a.r * a.r - a.i * a.i; c.i = 2.0f * a.r * a.i; return c;
}
__device__ __forceinline__ cplx cexp_m(float ar2, float ai2, float m) {
    float mag;
    asm("ex2.approx.ftz.f32 %0, %1;" : "=f"(mag) : "f"(ar2 * m));
    float rr = ai2 * m;
    rr -= (rr + 12582912.0f) - 12582912.0f;
    float th = rr * 6.283185307179586f;
    cplx c; c.r = mag * __cosf(th); c.i = mag * __sinf(th);
    return c;
}
__device__ __forceinline__ uint32_t to_tf32(float x) { return __float_as_uint(x) + 0x1000u; }
__device__ __forceinline__ void mma_tf32(float* c, uint32_t a0, uint32_t a1, uint32_t a2, uint32_t a3, uint32_t b0, uint32_t b1) {
    asm volatile("mma.sync.aligned.m16n8k8.row.col.f32.tf32.tf32.f32 {%0,%1,%2,%3}, {%4,%5,%6,%7}, {%8,%9}, {%0,%1,%2,%3};"
                 : "+f"(c[0]), "+f"(c[1]), "+f"(c[2]), "+f"(c[3])
                 : "r"(a0), "r"(a1), "r"(a2), "r"(a3), "r"(b0), "r"(b1));
}
__device__ __forceinline__ void mma_bf16(float* c, uint32_t a0, uint32_t a1, uint32_t a2, uint32_t a3, uint32_t b0, uint32_t b1) {
    asm volatile("mma.sync.aligned.m16n8k16.row.col.f32.bf16.bf16.f32 {%0,%1,%2,%3}, {%4,%5,%6,%7}, {%8,%9}, {%0,%1,%2,%3};"
                 : "+f"(c[0]), "+f"(c[1]), "+f"(c[2]), "+f"(c[3])
                 : "r"(a0), "r"(a1), "r"(a2), "r"(a3), "r"(b0), "r"(b1));
}
__device__ __forceinline__ void named_bar(int id, int n) { asm volatile("bar.sync %0, %1;" ::"r"(id), "r"(n) : "memory"); }
__device__ __forceinline__ void ldsm_x4(uint32_t addr, uint32_t& r0, uint32_t& r1, uint32_t& r2, uint32_t& r3) {
    asm volatile("ldmatrix.sync.aligned.m8n8.x4.shared.b16 {%0,%1,%2,%3}, [%4];" : "=r"(r0), "=r"(r1), "=r"(r2), "=r"(r3) : "r"(addr));
}
__device__ __forceinline__ void ldsm_x4_t(uint32_t addr, uint32_t& r0, uint32_t& r1, uint32_t& r2, uint32_t& r3) {
    asm volatile("ldmatrix.sync.aligned.m8n8.x4.trans.shared.b16 {%0,%1,%2,%3}, [%4];" : "=r"(r0), "=r"(r1), "=r"(r2), "=r"(r3) : "r"(addr));
}

constexpr int CV_CH = 4;
constexpr int CV_O_CONST = 0;
constexpr int CV_O_KP = 12288;
constexpr int CV_O_Q = CV_O_KP + 10368;
constexpr int CV_O_Q2 = CV_O_Q + 2304;
constexpr int CV_O_Q3 = CV_O_Q2 + 1024;
constexpr int CV_O_Q4X = CV_O_Q3 + 768;
constexpr int CV_O_W3 = CV_O_Q4X + 256;
constexpr int CV_O_W5 = CV_O_W3 + 3104;
constexpr int CV_O_W7 = CV_O_W5 + 3104;
constexpr int CV_O_W9 = CV_O_W7 + 2048;
constexpr int CV_O_STG = 32768;
constexpr int CV_O_U = CV_O_W9 + 2048;
constexpr int CV_PER_CH = CV_O_U + 4352;
static_assert(CV_O_U >= CV_O_STG + 4096, "staging overlaps u");
constexpr int CV_SMEM = CV_CH * CV_PER_CH;

constexpr int LN_ROWS = 16;

__global__ void __launch_bounds__(512, 1) front_kernel(const __nv_bfloat16* __restrict__ x,
                                                        const __nv_bfloat16* __restrict__ A_re, const __nv_bfloat16* __restrict__ A_im,
                                                        const __nv_bfloat16* __restrict__ B_re, const __nv_bfloat16* __restrict__ B_im,
                                                        const __nv_bfloat16* __restrict__ C_re, const __nv_bfloat16* __restrict__ C_im,
                                                        const __nv_bfloat16* __restrict__ log_dt, const __nv_bfloat16* __restrict__ Dskip,
                                                        const __nv_bfloat16* __restrict__ wg, const __nv_bfloat16* __restrict__ wu,
                                                        const __nv_bfloat16* __restrict__ wd) {
    pdl_launch();
    if (threadIdx.x == 0) STAMP(1, 0);
    extern __shared__ __align__(16) uint8_t smem[];
    const int warp = threadIdx.x >> 5, lane = threadIdx.x & 31;
    const int ch = warp >> 2, w = warp & 3, tc = threadIdx.x & 127;
    const int d = blockIdx.x * CV_CH + ch;
    const int g = lane >> 2, t = lane & 3;
    uint8_t* base = smem + ch * CV_PER_CH;
    float4* s_const = reinterpret_cast<float4*>(base + CV_O_CONST);
    float* s_kp = reinterpret_cast<float*>(base + CV_O_KP);
    uint32_t* s_q = reinterpret_cast<uint32_t*>(base + CV_O_Q);
    uint32_t* s_q2 = reinterpret_cast<uint32_t*>(base + CV_O_Q2);
    uint32_t* s_q3 = reinterpret_cast<uint32_t*>(base + CV_O_Q3);
    uint32_t* s_q4 = reinterpret_cast<uint32_t*>(base + CV_O_Q4X);
    __nv_bfloat16* s_u = reinterpret_cast<__nv_bfloat16*>(base + CV_O_U);
    const int bar_id = 1 + ch;

    const int row = blockIdx.x * LN_ROWS + warp;
    const uint4 xv0 = *reinterpret_cast<const uint4*>(x + (size_t)row * D_ + lane * 8);
    const uint4 xv1 = *reinterpret_cast<const uint4*>(x + (size_t)row * D_ + 256 + lane * 8);
    const size_t poff = (size_t)d * NS_ + tc;
    const __nv_bfloat16 p_ar = A_re[poff], p_ai = A_im[poff], p_br = B_re[poff], p_bi = B_im[poff], p_cr = C_re[poff], p_ci = C_im[poff];
    const __nv_bfloat16 p_ldt = log_dt[d], p_dsk = Dskip[d];
    {
        __nv_bfloat16 (*tile)[D_ + 8] = reinterpret_cast<__nv_bfloat16 (*)[D_ + 8]>(smem);
        float f[16];
        const uint32_t wv[8] = {xv0.x, xv0.y, xv0.z, xv0.w, xv1.x, xv1.y, xv1.z, xv1.w};
#pragma unroll
        for (int i = 0; i < 8; i++) { f[2 * i] = bf_lo(wv[i]); f[2 * i + 1] = bf_hi(wv[i]); }
        float sm = 0.f;
#pragma unroll
        for (int i = 0; i < 16; i++) sm += f[i];
#pragma unroll
        for (int o = 16; o > 0; o >>= 1) sm += __shfl_xor_sync(0xffffffffu, sm, o);
        const float mean = sm * (1.0f / D_);
        if (threadIdx.x == 0 && mean > -1e30f) STAMP(0, 1);
        float q = 0.f;
#pragma unroll
        for (int i = 0; i < 16; i++) { float dd = f[i] - mean; q += dd * dd; }
#pragma unroll
        for (int o = 16; o > 0; o >>= 1) q += __shfl_xor_sync(0xffffffffu, q, o);
        const float mb = bf16_round(mean);
        const float vb = bf16_round(q * (1.0f / D_));
        const float den = bf16_round(sqrtf(bf16_round(vb + 1e-5f)));
        uint32_t o[8];
#pragma unroll
        for (int i = 0; i < 8; i++) {
            float a = __fdiv_rn(bf16_round(f[2 * i] - mb), den);
            float b = __fdiv_rn(bf16_round(f[2 * i + 1] - mb), den);
            o[i] = pack_bf16(a, b);
        }
        __nv_bfloat16* dst = g_xn + (size_t)row * D_;
        *reinterpret_cast<uint4*>(dst + lane * 8) = make_uint4(o[0], o[1], o[2], o[3]);
        *reinterpret_cast<uint4*>(dst + 256 + lane * 8) = make_uint4(o[4], o[5], o[6], o[7]);
        *reinterpret_cast<uint4*>(&tile[warp][lane * 8]) = make_uint4(o[0], o[1], o[2], o[3]);
        *reinterpret_cast<uint4*>(&tile[warp][256 + lane * 8]) = make_uint4(o[4], o[5], o[6], o[7]);
        if (threadIdx.x == 0) STAMP(0, 2);
        __syncthreads();
        if (threadIdx.x == 0) STAMP(0, 3);
        {
            const int c = threadIdx.x;
            uint32_t ot[8];
#pragma unroll
            for (int i = 0; i < 8; i++) {
                uint32_t lo = *reinterpret_cast<const uint16_t*>(&tile[2 * i][c]);
                uint32_t hi = *reinterpret_cast<const uint16_t*>(&tile[2 * i + 1][c]);
                ot[i] = lo | (hi << 16);
            }
            __nv_bfloat16* dT = g_xnT + (size_t)c * L_ + blockIdx.x * LN_ROWS;
            *reinterpret_cast<uint4*>(dT) = make_uint4(ot[0], ot[1], ot[2], ot[3]);
            *reinterpret_cast<uint4*>(dT + 8) = make_uint4(ot[4], ot[5], ot[6], ot[7]);
        }
        __syncthreads();
        if (threadIdx.x == 0) STAMP(0, 0);
        if (threadIdx.x < 336) {
            const int m = threadIdx.x / 112, i = threadIdx.x - m * 112;
            const char* wp = (const char*)(m == 0 ? wg : (m == 1 ? wu : wd));
            asm volatile("prefetch.global.L2 [%0];" ::"l"(wp + ((size_t)blockIdx.x * 112 + i) * 128));
        }
    }

    float tail;
    {
        const float dt = bf16_round(expf(__bfloat162float(p_ldt)));
        const float ar = dt * __bfloat162float(p_ar), ai = dt * __bfloat162float(p_ai);
        const cplx db = {dt * __bfloat162float(p_br), dt * __bfloat162float(p_bi)};
        const cplx cc = {__bfloat162float(p_cr), __bfloat162float(p_ci)};
        const cplx cb = cmul(cc, db);
        const float ar2 = ar * 1.4426950408889634f, ai2 = ai * 0.15915494309189535f;
        const cplx e8 = cexp_m(ar2, ai2, 8.f), e128 = cexp_m(ar2, ai2, 128.f);
        const cplx cb8 = cmul(cb, e8);
        const cplx e256 = cexp_m(ar2, ai2, 256.f), e512 = cexp_m(ar2, ai2, 512.f), e1024 = cexp_m(ar2, ai2, 1024.f);
        const cplx c256 = cmul(cb, e256), c512 = cmul(cb, e512), c1024 = cmul(cb, e1024);
        const cplx c768 = cmul(c512, e256), c1280 = cmul(c1024, e256), c1536 = cmul(c1024, e512);
        const cplx c1792 = cmul(c1536, e256);
        tail = cmul(c1024, e1024).r;
        float4* c = s_const + tc * 6;
        c[0] = make_float4(ar2, ai2, cb.r, cb.i);
        c[1] = make_float4(e128.r, e128.i, cb8.r, cb8.i);
        c[2] = make_float4(c256.r, c256.i, e8.r, e8.i);
        c[3] = make_float4(c512.r, c512.i, c768.r, c768.i);
        c[4] = make_float4(c1024.r, c1024.i, c1280.r, c1280.i);
        c[5] = make_float4(c1536.r, c1536.i, c1792.r, c1792.i);
#pragma unroll
        for (int o = 16; o > 0; o >>= 1) tail += __shfl_xor_sync(0xffffffffu, tail, o);
    }
    __syncwarp();
    if (threadIdx.x == 0) STAMP(1, 1);
    {
        float acc[5][4];
#pragma unroll
        for (int i = 0; i < 5; i++) { acc[i][0] = acc[i][1] = acc[i][2] = acc[i][3] = 0.f; }
        const float gf = (float)g;
        const int src4 = ((g & 3) << 2) | t;
#pragma unroll 2
        for (int s = 0; s < 8; s++) {
            if (s == 4 && threadIdx.x == 480) asm volatile("red.release.gpu.global.add.u32 [%0], 1;" ::"l"(&g_ln_count) : "memory");
            const float4* c = s_const + (w * 32 + s * 4 + t) * 6;
            const float4 k0 = c[0], k1 = c[1], k2 = c[2];
            const float2 k3 = reinterpret_cast<const float2*>(c + 3)[g >> 2];
            const float2 k4 = reinterpret_cast<const float2*>(c + 4)[g >> 1];
            const cplx cb = {k0.z, k0.w}, e128 = {k1.x, k1.y}, cb8 = {k1.z, k1.w}, c256 = {k2.x, k2.y}, e8 = {k2.z, k2.w};
            const cplx c2 = {k3.x, k3.y}, c3 = {k4.x, k4.y};
            const cplx p1 = cexp_m(k0.x, k0.y, gf);
            const cplx p2 = csq(p1), p4 = csq(p2);
            const cplx r16a = csq(csq(p4));
            cplx q4;
            q4.r = __shfl_sync(0xffffffffu, p4.r, src4);
            q4.i = __shfl_sync(0xffffffffu, p4.i, src4);
            const cplx r16b = cmul(r16a, e128);
            const cplx f0a = cmul(cb, p1), f0b = cmul(cb8, p1), f1 = cmul(c256, p2), f2 = cmul(c2, q4);
            cplx f3 = cmul(c3, e8);
            if (!(g & 1)) f3 = c3;
            const uint32_t a0 = to_tf32(r16a.r), a1 = to_tf32(r16b.r), a2 = to_tf32(-r16a.i), a3 = to_tf32(-r16b.i);
            mma_tf32(acc[0], a0, a1, a2, a3, to_tf32(f0a.r), to_tf32(f0a.i));
            mma_tf32(acc[1], a0, a1, a2, a3, to_tf32(f0b.r), to_tf32(f0b.i));
            mma_tf32(acc[2], a0, a1, a2, a3, to_tf32(f1.r), to_tf32(f1.i));
            mma_tf32(acc[3], a0, a1, a2, a3, to_tf32(f2.r), to_tf32(f2.i));
            mma_tf32(acc[4], a0, a1, a2, a3, to_tf32(f3.r), to_tf32(f3.i));
        }
        float* kv = s_kp + w * 648;
#pragma unroll
        for (int hh = 0; hh < 2; hh++) {
            const int i = g + 8 * hh;
            *reinterpret_cast<float2*>(kv + 16 * i + 2 * t) = make_float2(acc[0][2 * hh], acc[0][2 * hh + 1]);
            *reinterpret_cast<float2*>(kv + 16 * i + 8 + 2 * t) = make_float2(acc[1][2 * hh], acc[1][2 * hh + 1]);
            *reinterpret_cast<float2*>(kv + 256 + 8 * i + 2 * t) = make_float2(acc[2][2 * hh], acc[2][2 * hh + 1]);
            *reinterpret_cast<float2*>(kv + 384 + 64 * (t >> 1) + 2 * (t & 1) + 4 * i) = make_float2(acc[3][2 * hh], acc[3][2 * hh + 1]);
            *reinterpret_cast<float2*>(kv + 512 + 32 * t + 2 * i) = make_float2(acc[4][2 * hh], acc[4][2 * hh + 1]);
        }
        if (lane == 0) kv[640] = tail;
    }

    named_bar(bar_id, 128);
    if (threadIdx.x == 0) STAMP(1, 2);
#pragma unroll
    for (int i = 0; i < 6; i++) {
        const int idx = tc + 128 * i;
        if (idx < 641) s_kp[idx] = (s_kp[idx] + s_kp[648 + idx]) + (s_kp[1296 + idx] + s_kp[1944 + idx]);
    }
    named_bar(bar_id, 128);
    {
        auto kdir = [&](int l) -> float {
            if (l < 0 || l > 514) return 0.f;
            const int idx = (l < 256) ? l : (l > 512 ? 384 : 128 + ((l + ((l >> 1) & 1)) >> 1));
            return s_kp[idx];
        };
#pragma unroll
        for (int i = 0; i < 5; i++) {
            const int e = tc + 128 * i;
            if (e < 576) s_q[e] = pack_bf16(kdir(e - 16), kdir(e - 17));
        }
        if (tc < 64) {
            const int xx = 1008 + tc;
            const float k1024 = s_kp[512];
            s_q4[tc] = pack_bf16((xx == 1027 || xx == 1028) ? k1024 : 0.f, (xx == 1028 || xx == 1029) ? k1024 : 0.f);
        }
#pragma unroll
        for (int i = 0; i < 2; i++) {
            const int e = tc + 128 * i, a = e >> 6, ii = (e & 63) - 16;
            const int b = 385 + (a >> 1) + 2 * (a & 1);
            const float v0 = (ii >= 0 && ii < 32) ? s_kp[b + 4 * ii] : 0.f;
            const float v1 = (ii >= 1 && ii < 33) ? s_kp[b + 4 * (ii - 1)] : 0.f;
            s_q2[e] = pack_bf16(v0, v1);
        }
#pragma unroll
        for (int i = 0; i < 2; i++) {
            const int e = tc + 128 * i;
            if (e < 192) {
                const int a = e >= 96, jj = e - 96 * a - 16;
                const float v0 = (jj >= 0 && jj < 64) ? s_kp[513 + a + 2 * jj] : 0.f;
                const float v1 = (jj >= 1 && jj < 65) ? s_kp[513 + a + 2 * (jj - 1)] : 0.f;
                s_q3[e] = pack_bf16(v0, v1);
            }
        }
    }
    if (threadIdx.x == 0) STAMP(1, 3);
    if (threadIdx.x == 0) {
        unsigned int v = 0;
        for (int spin = 0; spin < (1 << 22); spin++) {
            asm volatile("ld.acquire.gpu.global.u32 %0, [%1];" : "=r"(v) : "l"(&g_ln_count) : "memory");
            if (v >= gridDim.x) break;
        }
    }
    __syncthreads();
    if (threadIdx.x == 0) STAMP(1, 4);
    {
        if (tc < 16) *reinterpret_cast<uint4*>(s_u + tc * 8) = make_uint4(0, 0, 0, 0);
        const uint4* src = reinterpret_cast<const uint4*>(g_xnT + (size_t)d * L_);
        const uint4 v0 = src[tc], v1 = src[tc + 128];
        *reinterpret_cast<uint4*>(s_u + 128 + tc * 8) = v0;
        *reinterpret_cast<uint4*>(s_u + 128 + (tc + 128) * 8) = v1;
        if (tc < 2) *reinterpret_cast<uint4*>(base + (tc ? CV_O_W5 : CV_O_W3)) = make_uint4(0, 0, 0, 0);
    }
    named_bar(bar_id, 128);
#pragma unroll
    for (int rep = 0; rep < 2; rep++) {
        const int m = tc + 128 * rep;
        if (m < 192) {
            float P[30];
            const uint4* up = reinterpret_cast<const uint4*>(s_u + 128 + 8 * m - 24);
            P[0] = 0.f;
#pragma unroll
            for (int c4 = 0; c4 < 4; c4++) {
                const uint4 v = up[c4];
                const uint32_t ww[4] = {v.x, v.y, v.z, v.w};
#pragma unroll
                for (int j = 0; j < 4; j++) {
                    const int k = c4 * 8 + 2 * j;
                    if (k + 1 <= 29) P[k + 1] = P[k] + bf_lo(ww[j]);
                    if (k + 2 <= 29) P[k + 2] = P[k + 1] + bf_hi(ww[j]);
                }
            }
            uint32_t o3[4], o5[4], o7[4], o9[4];
#pragma unroll
            for (int j = 0; j < 4; j++) {
                const int i = 2 * j;
                o3[j] = pack_bf16(P[i + 22] - P[i + 19], P[i + 23] - P[i + 20]);
                o5[j] = pack_bf16(P[i + 19] - P[i + 14], P[i + 20] - P[i + 15]);
                o7[j] = pack_bf16(P[i + 20] - P[i + 13], P[i + 21] - P[i + 14]);
                o9[j] = pack_bf16(P[i + 13] - P[i + 4], P[i + 14] - P[i + 5]);
            }
            *reinterpret_cast<uint4*>(base + CV_O_W3 + 16 + m * 16) = make_uint4(o3[0], o3[1], o3[2], o3[3]);
            *reinterpret_cast<uint4*>(base + CV_O_W5 + 16 + m * 16) = make_uint4(o5[0], o5[1], o5[2], o5[3]);
            if (m < 128) {
                *reinterpret_cast<uint4*>(base + CV_O_W7 + m * 16) = make_uint4(o7[0], o7[1], o7[2], o7[3]);
                *reinterpret_cast<uint4*>(base + CV_O_W9 + m * 16) = make_uint4(o9[0], o9[1], o9[2], o9[3]);
            }
        }
    }
    if (threadIdx.x == 0) STAMP(1, 5);
    named_bar(bar_id, 128);
    const int wsel = (w - ch) & 3;
    if (wsel & 1) return;
    const int hb = wsel >> 1;
    float acc[16][4];
#pragma unroll
    for (int i = 0; i < 16; i++) { acc[i][0] = acc[i][1] = acc[i][2] = acc[i][3] = 0.f; }
    const uint32_t sb_addr = smem_u32(base);
    const int mi = lane >> 3, rowi = lane & 7;
#pragma unroll 1
    for (int rr = 0; rr < 4; rr++) {
        const int r = 4 * hb + rr;
        uint32_t ub[16][2];
        {
            const uint32_t addr = sb_addr + CV_O_U + (uint32_t)((128 + 16 * (8 * (mi >> 1) + rowi - r) + 8 * (mi & 1)) * 2);
#pragma unroll
            for (int j = 0; j < 16; j += 2) ldsm_x4(addr + (uint32_t)(j * 256), ub[j][0], ub[j][1], ub[j + 1][0], ub[j + 1][1]);
        }
        const uint32_t* qp = s_q + 16 + 16 * r + g - 2 * t;
        uint32_t af[4][3];
#pragma unroll
        for (int q = 0; q < 4; q++) { af[q][0] = qp[128 * q]; af[q][1] = qp[128 * q + 8]; af[q][2] = qp[128 * q - 8]; }
#pragma unroll
        for (int q = 0; q < 4; q++) {
#pragma unroll
            for (int nt = q; nt < 16; nt++) mma_bf16(acc[nt], af[q][0], af[q][1], af[q][2], af[q][0], ub[nt - q][0], ub[nt - q][1]);
        }
        if (r < 2) {
            {
                const uint32_t a0 = qp[512], a1 = qp[520], a2 = qp[504];
#pragma unroll
                for (int nt = 4; nt < 16; nt++) mma_bf16(acc[nt], a0, a1, a2, a0, ub[nt - 4][0], ub[nt - 4][1]);
            }
            {
                const uint32_t* q4p = s_q4 + 16 + 16 * r + g - 2 * t;
                const uint32_t a0 = q4p[0], a1 = q4p[8], a2 = q4p[-8];
#pragma unroll
                for (int nt = 8; nt < 16; nt++) mma_bf16(acc[nt], a0, a1, a2, a0, ub[nt - 8][0], ub[nt - 8][1]);
            }
        }
    }
#pragma unroll 1
    for (int a = hb; a <= 3 * hb; a++) {
        uint32_t bq[7];
        const uint32_t* q2 = s_q2 + a * 64 + 16 + g - 2 * t - 32;
#pragma unroll
        for (int dlt = 3; dlt <= 9; dlt++) bq[dlt - 3] = q2[8 * dlt];
        const uint32_t addr = sb_addr + ((a >> 1) ? CV_O_W5 : CV_O_W3) + (uint32_t)((8 + 16 * (8 * (mi >> 1) + rowi) + 8 * (mi & 1) - 8 * (a & 1)) * 2);
        uint32_t aa[6][4];
#pragma unroll
        for (int kp = 0; kp < 6; kp++) ldsm_x4_t(addr + kp * 512, aa[kp][0], aa[kp][1], aa[kp][2], aa[kp][3]);
#pragma unroll
        for (int kp = 0; kp < 6; kp++) {
#pragma unroll
            for (int dlt = 4; dlt <= 9; dlt++) {
                if (2 * kp + dlt < 16) mma_bf16(acc[2 * kp + dlt], aa[kp][0], aa[kp][1], aa[kp][2], aa[kp][3], bq[dlt - 3], bq[dlt - 4]);
            }
        }
    }
    if (hb == 0) {
#pragma unroll 1
        for (int a = 0; a < 2; a++) {
            uint32_t bq[9];
            const uint32_t* q3 = s_q3 + a * 96 + 16 + g - 2 * t - 64;
#pragma unroll
            for (int dlt = 7; dlt <= 15; dlt++) bq[dlt - 7] = q3[8 * dlt];
            const uint32_t addr = sb_addr + (a ? CV_O_W9 : CV_O_W7) + (uint32_t)((16 * (8 * (mi >> 1) + rowi) + 8 * (mi & 1)) * 2);
            uint32_t aa[4][4];
#pragma unroll
            for (int kp = 0; kp < 4; kp++) ldsm_x4_t(addr + kp * 512, aa[kp][0], aa[kp][1], aa[kp][2], aa[kp][3]);
#pragma unroll
            for (int kp = 0; kp < 4; kp++) {
#pragma unroll
                for (int dlt = 8; dlt <= 15; dlt++) {
                    if (2 * kp + dlt < 16) mma_bf16(acc[2 * kp + dlt], aa[kp][0], aa[kp][1], aa[kp][2], aa[kp][3], bq[dlt - 7], bq[dlt - 8]);
                }
            }
        }
    }
    if (threadIdx.x == 0) STAMP(1, 6);
    {
        float4* xch = reinterpret_cast<float4*>(base + CV_O_CONST) + hb * 256;
        if (hb) {
#pragma unroll
            for (int i = 0; i < 8; i++) xch[i * 32 + lane] = make_float4(acc[i][0], acc[i][1], acc[i][2], acc[i][3]);
#pragma unroll
            for (int i = 0; i < 8; i++) { acc[i][0] = acc[8 + i][0]; acc[i][1] = acc[8 + i][1]; acc[i][2] = acc[8 + i][2]; acc[i][3] = acc[8 + i][3]; }
        } else {
#pragma unroll
            for (int i = 0; i < 8; i++) xch[i * 32 + lane] = make_float4(acc[8 + i][0], acc[8 + i][1], acc[8 + i][2], acc[8 + i][3]);
        }
    }
    named_bar(bar_id, 64);
    if (threadIdx.x == 0) STAMP(1, 10);
    {
        const float4* xch = reinterpret_cast<const float4*>(base + CV_O_CONST) + (hb ^ 1) * 256 + lane;
        const float dsk = __bfloat162float(p_dsk);
        uint16_t* stg = reinterpret_cast<uint16_t*>(base + CV_O_KP);
        const uint16_t* uu = reinterpret_cast<const uint16_t*>(s_u) + 128;
#pragma unroll
        for (int i = 0; i < 8; i++) {
            const float4 p0 = xch[i * 32];
            const float y[4] = {acc[i][0] + p0.x, acc[i][1] + p0.y, acc[i][2] + p0.z, acc[i][3] + p0.w};
            const int nt = 8 * hb + i;
#pragma unroll
            for (int e = 0; e < 4; e++) {
                const int tau = 16 * (8 * nt + 2 * t + (e & 1)) + g + 8 * (e >> 1);
                const float sv = bf16_round(y[e]) + bf16_round(__uint_as_float((uint32_t)uu[tau] << 16) * dsk);
                stg[tau] = (uint16_t)(__float_as_uint(bf16_round(sv)) >> 16);
            }
        }
        __syncwarp();
        if (threadIdx.x == 0) STAMP(1, 11);
        uint4* dst = reinterpret_cast<uint4*>(g_sT + (size_t)d * L_ + hb * 1024);
        const uint4* srcp = reinterpret_cast<const uint4*>(stg + hb * 1024);
#pragma unroll
        for (int i = 0; i < 4; i++) dst[i * 32 + lane] = srcp[i * 32 + lane];
    }
    if (threadIdx.x == 0) STAMP(1, 7);
}

__device__ __forceinline__ uint32_t cluster_rank() { uint32_t r; asm volatile("mov.u32 %0, %%cluster_ctarank;" : "=r"(r)); return r; }
__device__ __forceinline__ void cluster_sync_all() {
    asm volatile("barrier.cluster.arrive.release.aligned;\nbarrier.cluster.wait.acquire.aligned;" ::: "memory");
}
__device__ __forceinline__ void mbar_arrive_remote(uint32_t bar, uint32_t cta) {
    asm volatile("{\n.reg .b32 ra;\nmapa.shared::cluster.u32 ra, %0, %1;\n"
                 "mbarrier.arrive.shared::cluster.b64 _, [ra];\n}\n" ::"r"(bar), "r"(cta) : "memory");
}
__device__ __forceinline__ void tma_load_2d_mc(uint32_t dst, const CUtensorMap* tm, int c0, int c1, uint32_t bar, uint16_t mask) {
    asm volatile(
        "cp.async.bulk.tensor.2d.shared::cluster.global.mbarrier::complete_tx::bytes.multicast::cluster [%0], [%1, {%3, %4}], [%2], %5;"
        ::"r"(dst), "l"((uint64_t)tm), "r"(bar), "r"(c0), "r"(c1), "h"(mask) : "memory");
}
__device__ __forceinline__ void tma_store_2d(const CUtensorMap* tm, uint32_t src, int c0, int c1) {
    asm volatile("cp.async.bulk.tensor.2d.global.shared::cta.bulk_group [%0, {%2, %3}], [%1];"
                 ::"l"((uint64_t)tm), "r"(src), "r"(c0), "r"(c1) : "memory");
}
__device__ __forceinline__ void bulk_commit() { asm volatile("cp.async.bulk.commit_group;" ::: "memory"); }
template <int N> __device__ __forceinline__ void bulk_wait_read() { asm volatile("cp.async.bulk.wait_group.read %0;" ::"n"(N) : "memory"); }
template <int N> __device__ __forceinline__ void bulk_wait() { asm volatile("cp.async.bulk.wait_group %0;" ::"n"(N) : "memory"); }
__device__ __forceinline__ void fence_async_smem() { asm volatile("fence.proxy.async.shared::cta;" ::: "memory"); }
__device__ __forceinline__ void stmatrix_x4(uint32_t addr, uint32_t r0, uint32_t r1, uint32_t r2, uint32_t r3) {
    asm volatile("stmatrix.sync.aligned.m8n8.x4.shared.b16 [%0], {%1,%2,%3,%4};" ::"r"(addr), "r"(r0), "r"(r1), "r"(r2), "r"(r3) : "memory");
}

constexpr int G1_STAGES = 5;
constexpr int G1_A_BYTES = 8 * 16384;
constexpr int G1_B_STAGE = 16384;
constexpr int G1_STG = 8 * 1024;
constexpr int G1_SMEM = G1_A_BYTES + G1_STAGES * G1_B_STAGE + G1_STG + 1024 + 256;
constexpr int G1_ITERS = 32;

__device__ __forceinline__ void tma_load_3d(uint32_t dst, const CUtensorMap* tm, int c0, int c1, int c2, uint32_t bar) {
    asm volatile(
        "cp.async.bulk.tensor.3d.shared::cluster.global.mbarrier::complete_tx::bytes [%0], [%1, {%3, %4, %5}], [%2];"
        ::"r"(dst), "l"((uint64_t)tm), "r"(bar), "r"(c0), "r"(c1), "r"(c2) : "memory");
}

__device__ __forceinline__ float gelu_tanh(float x) {
    float u = x * (0.7978845608028654f + 0.035677408136300125f * x * x);
    float t; asm("tanh.approx.f32 %0, %1;" : "=f"(t) : "f"(u));
    float hx = 0.5f * x;
    return fmaf(hx, t, hx);
}
__device__ __forceinline__ uint32_t geglu_pair(uint32_t g2, uint32_t u2) {
    uint32_t a = pack_bf16(gelu_tanh(bf_lo(g2)), gelu_tanh(bf_hi(g2)));
    uint32_t r; asm("mul.rn.bf16x2 %0, %1, %2;" : "=r"(r) : "r"(a), "r"(u2));
    return r;
}

__global__ void __launch_bounds__(384, 1) gemm1_kernel(const __grid_constant__ CUtensorMap tm_xn,
                                                        const __grid_constant__ CUtensorMap tm_wg4,
                                                        const __grid_constant__ CUtensorMap tm_wu4,
                                                        const __grid_constant__ CUtensorMap tm_wg3,
                                                        const __grid_constant__ CUtensorMap tm_wu3,
                                                        const __grid_constant__ CUtensorMap tm_hst,
                                                        const __grid_constant__ CUtensorMap tm_hst96) {
    pdl_launch();
    if (threadIdx.x == 0) STAMP(2, 0);
    extern __shared__ uint8_t smem_raw[];
    const uint32_t sbase = (smem_u32(smem_raw) + 1023) & ~1023u;
    const uint32_t sA = sbase, sB = sbase + G1_A_BYTES, sStg = sB + G1_STAGES * G1_B_STAGE, sBar = sStg + G1_STG;
    const uint32_t bar_a = sBar, bar_full = sBar + 64, bar_empty = sBar + 64 + 8 * G1_STAGES;
    const int rb = blockIdx.x >> 3, cj = blockIdx.x & 7;
    const int warp = threadIdx.x >> 5, lane = threadIdx.x & 31;

    if (threadIdx.x == 0) {
        for (int i = 0; i < 8; i++) mbar_init(bar_a + 8 * i, 1);
        for (int i = 0; i < G1_STAGES; i++) { mbar_init(bar_full + 8 * i, 1); mbar_init(bar_empty + 8 * i, 8); }
        asm volatile("fence.mbarrier_init.release.cluster;" ::: "memory");
    }
    __syncthreads();

    if (warp >= 8) {
        asm volatile("setmaxnreg.dec.sync.aligned.u32 40;");
        if (lane == 0) {
            const int pw = warp - 8;
            if (pw == 0) { prefetch_tmap(&tm_wg4); prefetch_tmap(&tm_wu4); prefetch_tmap(&tm_xn); }
            if (pw == 1) { prefetch_tmap(&tm_wg3); prefetch_tmap(&tm_wu3); prefetch_tmap(&tm_hst); prefetch_tmap(&tm_hst96); }
            for (int it = pw; it < G1_ITERS; it += 4) {
                const int s = it % G1_STAGES, kb = it & 15;
                if (it >= G1_STAGES) mbar_wait(bar_empty + 8 * s, ((it / G1_STAGES) - 1) & 1);
                const uint32_t dst = sB + s * G1_B_STAGE;
                if (it < 16) {
                    mbar_expect_tx(bar_full + 8 * s, 16384);
                    tma_load_3d(dst, &tm_wg4, 0, kb * 32, cj * 7, bar_full + 8 * s);
                    tma_load_3d(dst + 8192, &tm_wu4, 0, kb * 32, cj * 7, bar_full + 8 * s);
                } else {
                    mbar_expect_tx(bar_full + 8 * s, 12288);
                    tma_load_3d(dst, &tm_wg3, 0, kb * 32, cj * 7 + 4, bar_full + 8 * s);
                    tma_load_3d(dst + 6144, &tm_wu3, 0, kb * 32, cj * 7 + 4, bar_full + 8 * s);
                }
                if (it < 4) {
                    pdl_wait();
                    if (pw == 0) { STAMP(2, 1); if (blockIdx.x == 0) g_ln_count = 0; }
                    for (int k = pw; k < 8; k += 4) {
                        mbar_expect_tx(bar_a + 8 * k, 16384);
                        tma_load_2d(sA + k * 16384, &tm_xn, k * 64, rb * 128, bar_a + 8 * k);
                    }
                }
            }
        }
    } else {
        asm volatile("setmaxnreg.inc.sync.aligned.u32 232;");
        const int wg = __shfl_sync(0xffffffffu, (int)(threadIdx.x >> 7), 0);
        float r[160];
        const int row0 = rb * 128 + wg * 64 + (warp & 3) * 16;
        const uint64_t descA = make_desc(sA + wg * 8192, 16, 1024);
        const uint64_t descB = make_desc(sB, 2048, 512, 2);
        const uint32_t stg = sStg + warp * 1024;
        const uint32_t st_off = (uint32_t)(((lane & 7) + ((lane >> 3) & 1) * 8) * 32 + (lane >> 4) * 16);
        __nv_bfloat16* hrow = g_h + (size_t)(row0 + (lane >> 1)) * F_ + (lane & 1) * 8 + cj * 224;
#pragma unroll
        for (int kb = 0; kb < 16; kb++) {
            const int it = kb, s = it % G1_STAGES;
            if ((kb & 1) == 0) mbar_wait(bar_a + 8 * (kb >> 1), 0);
            mbar_wait(bar_full + 8 * s, (it / G1_STAGES) & 1);
            if (threadIdx.x == 0 && (it & 7) == 0) STAMP(2, 2 + it / 8);
            wgmma_fence();
            const uint64_t da = descA + (uint64_t)(((kb >> 1) * 16384 + (kb & 1) * 64) >> 4);
            const uint64_t db = descB + (uint64_t)((s * G1_B_STAGE) >> 4);
            wgmma_n256_k32(r, da, da + 2, db, db + 64, kb != 0);
            wgmma_commit();
            if (kb > 0) {
                wgmma_wait<1>();
                if (lane == 0) mbar_arrive(bar_empty + 8 * ((it - 1) % G1_STAGES));
            }
        }
        wgmma_wait<0>();
        if (lane == 0) mbar_arrive(bar_empty + 8 * (15 % G1_STAGES));
#pragma unroll
        for (int i = 0; i < 32; i++) r[128 + i] = __uint_as_float(pack_bf16(r[2 * i], r[2 * i + 1]));
#pragma unroll
        for (int i = 31; i >= 0; i--) r[96 + i] = __uint_as_float(pack_bf16(r[64 + 2 * i], r[65 + 2 * i]));
        uint32_t eo[4];
        uint4 pv = make_uint4(0, 0, 0, 0);
#pragma unroll
        for (int kb = 0; kb < 16; kb++) {
            const int it = 16 + kb, s = it % G1_STAGES;
            mbar_wait(bar_full + 8 * s, (it / G1_STAGES) & 1);
            if (threadIdx.x == 0 && (it & 7) == 0) STAMP(2, 2 + it / 8);
            wgmma_fence();
            const uint64_t da = descA + (uint64_t)(((kb >> 1) * 16384 + (kb & 1) * 64) >> 4);
            const uint64_t db = descB + (uint64_t)((s * G1_B_STAGE) >> 4);
            const int jj = kb >> 1;
            wgmma_n192(r, da, db, kb != 0);
            eo[(kb & 1) * 2] = geglu_pair(__float_as_uint(r[128 + 2 * kb]), __float_as_uint(r[96 + 2 * kb]));
            wgmma_n192(r, da + 2, db + 64, 1);
            wgmma_commit();
            eo[(kb & 1) * 2 + 1] = geglu_pair(__float_as_uint(r[129 + 2 * kb]), __float_as_uint(r[97 + 2 * kb]));
            if (kb & 1) {
                if (jj > 0) *reinterpret_cast<uint4*>(hrow + (jj - 1) * 16) = pv;
                stmatrix_x4(stg + (jj & 1) * 512 + st_off, eo[0], eo[1], eo[2], eo[3]);
            } else if (jj > 0) {
                __syncwarp();
                asm volatile("ld.shared.v4.u32 {%0,%1,%2,%3}, [%4];" : "=r"(pv.x), "=r"(pv.y), "=r"(pv.z), "=r"(pv.w)
                             : "r"(stg + ((jj - 1) & 1) * 512 + lane * 16));
            }
            if (kb > 0 && it - 1 + G1_STAGES < G1_ITERS) {
                wgmma_wait<1>();
                if (lane == 0) mbar_arrive(bar_empty + 8 * ((it - 1) % G1_STAGES));
            }
        }
        __syncwarp();
        asm volatile("ld.shared.v4.u32 {%0,%1,%2,%3}, [%4];" : "=r"(pv.x), "=r"(pv.y), "=r"(pv.z), "=r"(pv.w) : "r"(stg + 512 + lane * 16));
        wgmma_wait<0>();
        *reinterpret_cast<uint4*>(hrow + 7 * 16) = pv;
        if (threadIdx.x == 0) STAMP(2, 6);
        {
            uint32_t o[24];
#pragma unroll
            for (int i = 0; i < 24; i++) o[i] = geglu_pair(pack_bf16(r[2 * i], r[2 * i + 1]), pack_bf16(r[48 + 2 * i], r[49 + 2 * i]));
            named_bar(1 + wg, 128);
            const uint32_t fbuf = sA + ((warp & 3) >> 1) * 16384 + wg * 8192 + (warp & 1) * 4096;
#pragma unroll
            for (int jj = 0; jj < 6; jj++) stmatrix_x4(fbuf + jj * 512 + st_off, o[4 * jj], o[4 * jj + 1], o[4 * jj + 2], o[4 * jj + 3]);
            __syncwarp();
            uint4 v[6];
#pragma unroll
            for (int jj = 0; jj < 6; jj++)
                asm volatile("ld.shared.v4.u32 {%0,%1,%2,%3}, [%4];" : "=r"(v[jj].x), "=r"(v[jj].y), "=r"(v[jj].z), "=r"(v[jj].w)
                             : "r"(fbuf + jj * 512 + lane * 16));
#pragma unroll
            for (int jj = 0; jj < 6; jj++) *reinterpret_cast<uint4*>(hrow + 128 + jj * 16) = v[jj];
        }
        if (threadIdx.x == 0) STAMP(2, 7);
    }
}

constexpr int G2_STAGES = 5;
constexpr int G2_STAGE = 16384 + 16384;
constexpr int G2_XCH = 32768;
constexpr int G2_EPI = 16384 + 16384;
constexpr int G2_SMEM = G2_STAGES * G2_STAGE + G2_XCH + G2_EPI + 1024 + 256;
constexpr int G2_KB = F_ / 64 / 2;

__global__ void __launch_bounds__(384, 1) gemm2_kernel(const __grid_constant__ CUtensorMap tm_h,
                                                        const __grid_constant__ CUtensorMap tm_wd,
                                                        const __grid_constant__ CUtensorMap tm_x,
                                                        const __grid_constant__ CUtensorMap tm_sT,
                                                        const __grid_constant__ CUtensorMap tm_out) {
    if (threadIdx.x == 0) STAMP(3, 0);
    extern __shared__ uint8_t smem_raw[];
    const uint32_t sbase = (smem_u32(smem_raw) + 1023) & ~1023u;
    const uint32_t sXch = sbase + G2_STAGES * G2_STAGE, sX = sXch + G2_XCH, sS = sX + 16384, sBar = sX + G2_EPI;
    const uint32_t bar_full = sBar, bar_empty = sBar + 8 * G2_STAGES, bar_epi = sBar + 16 * G2_STAGES, bar_xch = bar_epi + 8;
    const uint32_t kh = cluster_rank();
    const int cid = blockIdx.x >> 1;
    const int rb = cid >> 2, nb = cid & 3;
    const int col_fin = nb * 128 + kh * 64;
    const int warp = threadIdx.x >> 5, lane = threadIdx.x & 31;

    if (threadIdx.x == 0) {
        for (int i = 0; i < G2_STAGES; i++) { mbar_init(bar_full + 8 * i, 1); mbar_init(bar_empty + 8 * i, 8); }
        mbar_init(bar_epi, 1);
        mbar_init(bar_xch, 1);
        asm volatile("fence.mbarrier_init.release.cluster;" ::: "memory");
        mbar_expect_tx(bar_xch, G2_XCH);
    }
    cluster_sync_all();

    if (warp >= 8) {
        if (lane == 0) {
            const int pw = warp - 8;
            const int k0 = kh * G2_KB;
            if (pw == 0) { prefetch_tmap(&tm_wd); prefetch_tmap(&tm_h); }
            if (pw == 1) { prefetch_tmap(&tm_x); prefetch_tmap(&tm_sT); prefetch_tmap(&tm_out); }
            for (int it = pw; it < G2_STAGES; it += 4) {
                mbar_expect_tx(bar_full + 8 * it, G2_STAGE);
                tma_load_3d(sbase + it * G2_STAGE + 16384, &tm_wd, 0, (k0 + it) * 64, nb * 2, bar_full + 8 * it);
            }
            if (pw == 3) {
                mbar_expect_tx(bar_epi, G2_EPI);
                tma_load_2d(sX, &tm_x, col_fin, rb * 128, bar_epi);
            }
            pdl_wait();
            if (pw == 0) STAMP(3, 1);
            for (int it = pw; it < G2_STAGES; it += 4)
                tma_load_2d(sbase + it * G2_STAGE, &tm_h, (k0 + it) * 64, rb * 128, bar_full + 8 * it);
            if (pw == 3) {
                tma_load_2d(sS, &tm_sT, rb * 128, col_fin, bar_epi);
                tma_load_2d(sS + 8192, &tm_sT, rb * 128 + 64, col_fin, bar_epi);
            }
            for (int it = G2_STAGES + ((pw + 4 - (G2_STAGES & 3)) & 3); it < G2_KB; it += 4) {
                const int s = it % G2_STAGES;
                mbar_wait(bar_empty + 8 * s, ((it / G2_STAGES) - 1) & 1);
                mbar_expect_tx(bar_full + 8 * s, G2_STAGE);
                tma_load_2d(sbase + s * G2_STAGE, &tm_h, (k0 + it) * 64, rb * 128, bar_full + 8 * s);
                tma_load_3d(sbase + s * G2_STAGE + 16384, &tm_wd, 0, (k0 + it) * 64, nb * 2, bar_full + 8 * s);
            }
        }
    } else {
        const int wg = __shfl_sync(0xffffffffu, (int)(threadIdx.x >> 7), 0);
        const int g = lane >> 2, t = lane & 3;
        float acc[64];
        const uint64_t descA = make_desc(sbase + wg * 8192, 16, 1024);
        const uint64_t descB = make_desc(sbase + 16384, 8192, 1024);
#pragma unroll
        for (int it = 0; it < G2_KB; it++) {
            const int s = it % G2_STAGES;
            mbar_wait(bar_full + 8 * s, (it / G2_STAGES) & 1);
            if (threadIdx.x == 0 && (it == 0 || it == 7)) STAMP(3, 2 + it / 7);
            wgmma_fence();
            {
                const uint64_t da = descA + (uint64_t)((s * G2_STAGE) >> 4);
                const uint64_t db = descB + (uint64_t)((s * G2_STAGE) >> 4);
                wgmma_n128_k64(acc, da, da + 2, da + 4, da + 6, db, db + 128, db + 256, db + 384, it != 0);
            }
            wgmma_commit();
            if (it > 0 && it - 1 + G2_STAGES < G2_KB) {
                wgmma_wait<1>();
                if (lane == 0) mbar_arrive(bar_empty + 8 * ((it - 1) % G2_STAGES));
            }
        }
        const int lr = wg * 64 + (warp & 3) * 16 + g;
        uint32_t xv[16], sv[16];
        mbar_wait(bar_epi, 0);
#pragma unroll
        for (int j = 0; j < 8; j++) {
#pragma unroll
            for (int hh = 0; hh < 2; hh++) {
                const int r = lr + 8 * hh;
                asm volatile("ld.shared.u32 %0, [%1];" : "=r"(xv[2 * j + hh]) : "r"(sX + r * 128 + ((j ^ (r & 7)) << 4) + 4 * t));
                const int c0 = 8 * j + 2 * t;
                const uint32_t sa = sS + (r >> 6) * 8192 + (((r & 63) >> 3) << 4) + (r & 7) * 2;
                uint16_t s0r, s1r;
                asm volatile("ld.shared.u16 %0, [%1];" : "=h"(s0r) : "r"((sa + c0 * 128) ^ ((c0 & 7) << 4)));
                asm volatile("ld.shared.u16 %0, [%1];" : "=h"(s1r) : "r"((sa + (c0 + 1) * 128) ^ (((c0 + 1) & 7) << 4)));
                sv[2 * j + hh] = (uint32_t)s0r | ((uint32_t)s1r << 16);
            }
        }
        wgmma_wait<0>();
        if (threadIdx.x == 0) STAMP(3, 4);
        {
            uint32_t remote, rbar;
            asm volatile("mapa.shared::cluster.u32 %0, %1, %2;" : "=r"(remote) : "r"(sXch + threadIdx.x * 16), "r"(kh ^ 1));
            asm volatile("mapa.shared::cluster.u32 %0, %1, %2;" : "=r"(rbar) : "r"(bar_xch), "r"(kh ^ 1));
            if (kh == 0) {
#pragma unroll
                for (int i = 0; i < 8; i++)
                    asm volatile("st.async.shared::cluster.mbarrier::complete_tx::bytes.v4.f32 [%0], {%1,%2,%3,%4}, [%5];" ::"r"(remote + i * 4096),
                                 "f"(acc[32 + 4 * i]), "f"(acc[33 + 4 * i]), "f"(acc[34 + 4 * i]), "f"(acc[35 + 4 * i]), "r"(rbar) : "memory");
            } else {
#pragma unroll
                for (int i = 0; i < 8; i++)
                    asm volatile("st.async.shared::cluster.mbarrier::complete_tx::bytes.v4.f32 [%0], {%1,%2,%3,%4}, [%5];" ::"r"(remote + i * 4096),
                                 "f"(acc[4 * i]), "f"(acc[1 + 4 * i]), "f"(acc[2 + 4 * i]), "f"(acc[3 + 4 * i]), "r"(rbar) : "memory");
#pragma unroll
                for (int i = 0; i < 32; i++) acc[i] = acc[32 + i];
            }
        }
        if (threadIdx.x == 0) STAMP(3, 6);
        mbar_wait(bar_xch, 0);
        if (threadIdx.x == 0) STAMP(3, 7);
#pragma unroll
        for (int j = 0; j < 8; j++) {
            float4 o;
            asm volatile("ld.shared.v4.f32 {%0,%1,%2,%3}, [%4];" : "=f"(o.x), "=f"(o.y), "=f"(o.z), "=f"(o.w) : "r"(sXch + threadIdx.x * 16 + j * 4096));
            acc[4 * j] += o.x; acc[4 * j + 1] += o.y; acc[4 * j + 2] += o.z; acc[4 * j + 3] += o.w;
        }
#pragma unroll
        for (int i = 0; i < 16; i++) {
            float f0 = bf16_round(acc[2 * i]), f1 = bf16_round(acc[2 * i + 1]);
            float g0 = bf16_round(__fdividef(f0, 1.0f + __expf(-f0)));
            float g1 = bf16_round(__fdividef(f1, 1.0f + __expf(-f1)));
            float o0 = bf_lo(xv[i]) + bf16_round(bf_lo(sv[i]) * g0);
            float o1 = bf_hi(xv[i]) + bf16_round(bf_hi(sv[i]) * g1);
            xv[i] = pack_bf16(o0, o1);
        }
#pragma unroll
        for (int j = 0; j < 8; j++) {
#pragma unroll
            for (int hh = 0; hh < 2; hh++) {
                const int r = lr + 8 * hh;
                asm volatile("st.shared.u32 [%0], %1;" ::"r"(sX + r * 128 + ((j ^ (r & 7)) << 4) + 4 * t), "r"(xv[2 * j + hh]) : "memory");
            }
        }
        if (threadIdx.x == 0) STAMP(3, 9);
        fence_async_smem();
        __syncwarp();
        if (lane == 0) {
            tma_store_2d(&tm_out, sX + (wg * 64 + (warp & 3) * 16) * 128, col_fin, rb * 128 + wg * 64 + (warp & 3) * 16);
            bulk_commit();
            bulk_wait_read<0>();
        }
        if (threadIdx.x == 0) STAMP(3, 5);
    }
}

typedef CUresult (*EncodeFn)(CUtensorMap*, CUtensorMapDataType, cuuint32_t, void*, const cuuint64_t*, const cuuint64_t*,
                             const cuuint32_t*, const cuuint32_t*, CUtensorMapInterleave, CUtensorMapSwizzle,
                             CUtensorMapL2promotion, CUtensorMapFloatOOBfill);

void make_map(EncodeFn fn, CUtensorMap* m, const void* ptr, uint64_t inner, uint64_t outer, uint32_t box_in, uint32_t box_out,
              CUtensorMapSwizzle swz = CU_TENSOR_MAP_SWIZZLE_128B) {
    cuuint64_t dims[2] = {inner, outer};
    cuuint64_t strides[1] = {inner * 2};
    cuuint32_t box[2] = {box_in, box_out};
    cuuint32_t es[2] = {1, 1};
    fn(m, CU_TENSOR_MAP_DATA_TYPE_BFLOAT16, 2, const_cast<void*>(ptr), dims, strides, box, es, CU_TENSOR_MAP_INTERLEAVE_NONE,
       swz, CU_TENSOR_MAP_L2_PROMOTION_L2_256B, CU_TENSOR_MAP_FLOAT_OOB_FILL_NONE);
}
void make_map3(EncodeFn fn, CUtensorMap* m, const void* ptr, uint64_t cols, uint64_t rows, uint32_t atom, uint32_t box_rows,
               uint32_t box_atoms, CUtensorMapSwizzle swz) {
    cuuint64_t dims[3] = {atom, rows, cols / atom};
    cuuint64_t strides[2] = {cols * 2, (cuuint64_t)atom * 2};
    cuuint32_t box[3] = {atom, box_rows, box_atoms};
    cuuint32_t es[3] = {1, 1, 1};
    fn(m, CU_TENSOR_MAP_DATA_TYPE_BFLOAT16, 3, const_cast<void*>(ptr), dims, strides, box, es, CU_TENSOR_MAP_INTERLEAVE_NONE,
       swz, CU_TENSOR_MAP_L2_PROMOTION_L2_256B, CU_TENSOR_MAP_FLOAT_OOB_FILL_NONE);
}

template <typename... Args>
void launch_pdl(void (*kern)(Args...), int grid, int block, int smem, bool pdl, int cluster, Args... args) {
    cudaLaunchConfig_t cfg = {};
    cfg.gridDim = dim3(grid); cfg.blockDim = dim3(block); cfg.dynamicSmemBytes = smem; cfg.stream = cudaStreamPerThread;
    cudaLaunchAttribute at[2];
    int n = 0;
    if (pdl) {
        at[n].id = cudaLaunchAttributeProgrammaticStreamSerialization;
        at[n].val.programmaticStreamSerializationAllowed = 1;
        n++;
    }
    if (cluster > 1) {
        at[n].id = cudaLaunchAttributeClusterDimension;
        at[n].val.clusterDim.x = cluster; at[n].val.clusterDim.y = 1; at[n].val.clusterDim.z = 1;
        n++;
    }
    cfg.attrs = at; cfg.numAttrs = n;
    cudaLaunchKernelEx(&cfg, kern, args...);
}

}

extern "C" void kernel_launch(void* const* d_in, const int* in_sizes, int n_in, void* d_out, int out_size) {
    const __nv_bfloat16* x = (const __nv_bfloat16*)d_in[0];
    const __nv_bfloat16* A_re = (const __nv_bfloat16*)d_in[1];
    const __nv_bfloat16* A_im = (const __nv_bfloat16*)d_in[2];
    const __nv_bfloat16* B_re = (const __nv_bfloat16*)d_in[3];
    const __nv_bfloat16* B_im = (const __nv_bfloat16*)d_in[4];
    const __nv_bfloat16* C_re = (const __nv_bfloat16*)d_in[5];
    const __nv_bfloat16* C_im = (const __nv_bfloat16*)d_in[6];
    const __nv_bfloat16* log_dt = (const __nv_bfloat16*)d_in[7];
    const __nv_bfloat16* Dskip = (const __nv_bfloat16*)d_in[8];
    const __nv_bfloat16* wg = (const __nv_bfloat16*)d_in[10];
    const __nv_bfloat16* wu = (const __nv_bfloat16*)d_in[11];
    const __nv_bfloat16* wd = (const __nv_bfloat16*)d_in[12];
    __nv_bfloat16* out = (__nv_bfloat16*)d_out;

    static bool init = false;
    static CUtensorMap tm_xn, tm_wg4, tm_wu4, tm_wg3, tm_wu3, tm_hst, tm_hst96, tm_h, tm_wd, tm_x, tm_sT, tm_out;
    static const void* last_ptrs[5] = {nullptr, nullptr, nullptr, nullptr, nullptr};
    if (!init || last_ptrs[0] != wg || last_ptrs[1] != wu || last_ptrs[2] != wd || last_ptrs[3] != x || last_ptrs[4] != out) {
        void* fnp = nullptr;
        cudaDriverEntryPointQueryResult qres;
        cudaGetDriverEntryPoint("cuTensorMapEncodeTiled", &fnp, cudaEnableDefault, &qres);
        EncodeFn fn = (EncodeFn)fnp;
        void *p_xn, *p_h, *p_sT;
        cudaGetSymbolAddress(&p_xn, g_xn);
        cudaGetSymbolAddress(&p_h, g_h);
        cudaGetSymbolAddress(&p_sT, g_sT);
        make_map(fn, &tm_xn, p_xn, D_, L_, 64, 128);
        make_map3(fn, &tm_wg4, wg, F_, D_, 32, 32, 4, CU_TENSOR_MAP_SWIZZLE_64B);
        make_map3(fn, &tm_wu4, wu, F_, D_, 32, 32, 4, CU_TENSOR_MAP_SWIZZLE_64B);
        make_map3(fn, &tm_wg3, wg, F_, D_, 32, 32, 3, CU_TENSOR_MAP_SWIZZLE_64B);
        make_map3(fn, &tm_wu3, wu, F_, D_, 32, 32, 3, CU_TENSOR_MAP_SWIZZLE_64B);
        make_map(fn, &tm_hst, p_h, F_, L_, 16, 16, CU_TENSOR_MAP_SWIZZLE_NONE);
        make_map(fn, &tm_hst96, p_h, F_, L_, 96, 16, CU_TENSOR_MAP_SWIZZLE_NONE);
        make_map(fn, &tm_h, p_h, F_, L_, 64, 128);
        make_map3(fn, &tm_wd, wd, D_, F_, 64, 64, 2, CU_TENSOR_MAP_SWIZZLE_128B);
        make_map(fn, &tm_x, x, D_, L_, 64, 128);
        make_map(fn, &tm_sT, p_sT, L_, D_, 64, 64);
        make_map(fn, &tm_out, out, D_, L_, 64, 16);
        cudaFuncSetAttribute(front_kernel, cudaFuncAttributeMaxDynamicSharedMemorySize, CV_SMEM);
        cudaFuncSetAttribute(gemm1_kernel, cudaFuncAttributeMaxDynamicSharedMemorySize, G1_SMEM);
        cudaFuncSetAttribute(gemm2_kernel, cudaFuncAttributeMaxDynamicSharedMemorySize, G2_SMEM);
        last_ptrs[0] = wg; last_ptrs[1] = wu; last_ptrs[2] = wd; last_ptrs[3] = x; last_ptrs[4] = out;
        init = true;
    }
    launch_pdl(front_kernel, D_ / CV_CH, 512, CV_SMEM, false, 1, x, A_re, A_im, B_re, B_im, C_re, C_im, log_dt, Dskip, wg, wu, wd);
    launch_pdl(gemm1_kernel, 128, 384, G1_SMEM, true, 1, tm_xn, tm_wg4, tm_wu4, tm_wg3, tm_wu3, tm_hst, tm_hst96);
    launch_pdl(gemm2_kernel, 128, 384, G2_SMEM, true, 2, tm_h, tm_wd, tm_x, tm_sT, tm_out);
}
```

```cpp
#include <cuda_runtime.h>
#include <cuda_bf16.h>
#include <cuda.h>
#include <stdint.h>

namespace {

constexpr int L_ = 2048, D_ = 512, NS_ = 128, F_ = 1792;

__device__ __align__(1024) __nv_bfloat16 g_xn[L_ * D_];
__device__ __align__(1024) __nv_bfloat16 g_xnT[D_ * L_];
__device__ __align__(1024) __nv_bfloat16 g_sT[D_ * L_];
__device__ __align__(1024) __nv_bfloat16 g_h[L_ * F_];
__device__ unsigned int g_ln_count, g_conv_count, g_done_count, g_h_count[16];

#define STAMP(k, i)

__device__ __forceinline__ uint32_t smem_u32(const void* p) { return (uint32_t)__cvta_generic_to_shared(p); }
__device__ __forceinline__ void pdl_wait() { asm volatile("griddepcontrol.wait;" ::: "memory"); }
__device__ __forceinline__ void pdl_launch() { asm volatile("griddepcontrol.launch_dependents;" ::: "memory"); }

__device__ __forceinline__ void mbar_init(uint32_t bar, uint32_t cnt) {
    asm volatile("mbarrier.init.shared::cta.b64 [%0], %1;" ::"r"(bar), "r"(cnt) : "memory");
}
__device__ __forceinline__ void mbar_expect_tx(uint32_t bar, uint32_t bytes) {
    asm volatile("mbarrier.arrive.expect_tx.shared::cta.b64 _, [%0], %1;" ::"r"(bar), "r"(bytes) : "memory");
}
__device__ __forceinline__ void mbar_arrive(uint32_t bar) {
    asm volatile("mbarrier.arrive.shared::cta.b64 _, [%0];" ::"r"(bar) : "memory");
}
__device__ __forceinline__ void mbar_wait(uint32_t bar, uint32_t parity) {
    asm volatile(
        "{\n.reg .pred p;\n"
        "WAIT_LOOP:\n"
        "mbarrier.try_wait.parity.shared::cta.b64 p, [%0], %1;\n"
        "@p bra WAIT_DONE;\n"
        "bra WAIT_LOOP;\n"
        "WAIT_DONE:\n}\n" ::"r"(bar), "r"(parity) : "memory");
}
__device__ __forceinline__ void tma_load_2d(uint32_t dst, const CUtensorMap* tm, int c0, int c1, uint32_t bar) {
    asm volatile(
        "cp.async.bulk.tensor.2d.shared::cluster.global.mbarrier::complete_tx::bytes [%0], [%1, {%3, %4}], [%2];"
        ::"r"(dst), "l"((uint64_t)tm), "r"(bar), "r"(c0), "r"(c1) : "memory");
}
__device__ __forceinline__ void prefetch_tmap(const CUtensorMap* tm) {
    asm volatile("prefetch.tensormap [%0];" ::"l"((uint64_t)tm) : "memory");
}
__device__ __forceinline__ uint64_t make_desc(uint32_t addr, uint32_t lbo, uint32_t sbo, uint64_t mode = 1) {
    uint64_t d = 0;
    d |= (uint64_t)((addr & 0x3FFFF) >> 4);
    d |= (uint64_t)((lbo >> 4) & 0x3FFF) << 16;
    d |= (uint64_t)((sbo >> 4) & 0x3FFF) << 32;
    d |= mode << 62;
    return d;
}
__device__ __forceinline__ void wgmma_fence() { asm volatile("wgmma.fence.sync.aligned;" ::: "memory"); }
__device__ __forceinline__ void wgmma_commit() { asm volatile("wgmma.commit_group.sync.aligned;" ::: "memory"); }
template <int N> __device__ __forceinline__ void wgmma_wait() {
    asm volatile("wgmma.wait_group.sync.aligned %0;" ::"n"(N) : "memory");
}

#define R8(a, i) "+f"(a[i + 0]), "+f"(a[i + 1]), "+f"(a[i + 2]), "+f"(a[i + 3]), "+f"(a[i + 4]), "+f"(a[i + 5]), "+f"(a[i + 6]), "+f"(a[i + 7])

__device__ __forceinline__ void wgmma_n256_k32(float* a, uint64_t da0, uint64_t da1, uint64_t db0, uint64_t db1, int scale_d) {
    asm volatile(
        "{\n.reg .pred p;\nsetp.ne.b32 p, %132, 0;\n"
        "wgmma.mma_async.sync.aligned.m64n256k16.f32.bf16.bf16 {%0,%1,%2,%3,%4,%5,%6,%7,%8,%9,%10,%11,%12,%13,%14,%15,%16,%17,%18,%19,%20,%21,%22,%23,%24,%25,%26,%27,%28,%29,%30,%31,%32,%33,%34,%35,%36,%37,%38,%39,%40,%41,%42,%43,%44,%45,%46,%47,%48,%49,%50,%51,%52,%53,%54,%55,%56,%57,%58,%59,%60,%61,%62,%63,%64,%65,%66,%67,%68,%69,%70,%71,%72,%73,%74,%75,%76,%77,%78,%79,%80,%81,%82,%83,%84,%85,%86,%87,%88,%89,%90,%91,%92,%93,%94,%95,%96,%97,%98,%99,%100,%101,%102,%103,%104,%105,%106,%107,%108,%109,%110,%111,%112,%113,%114,%115,%116,%117,%118,%119,%120,%121,%122,%123,%124,%125,%126,%127}, %128, %130, p, 1, 1, 0, 1;\n"
        "wgmma.mma_async.sync.aligned.m64n256k16.f32.bf16.bf16 {%0,%1,%2,%3,%4,%5,%6,%7,%8,%9,%10,%11,%12,%13,%14,%15,%16,%17,%18,%19,%20,%21,%22,%23,%24,%25,%26,%27,%28,%29,%30,%31,%32,%33,%34,%35,%36,%37,%38,%39,%40,%41,%42,%43,%44,%45,%46,%47,%48,%49,%50,%51,%52,%53,%54,%55,%56,%57,%58,%59,%60,%61,%62,%63,%64,%65,%66,%67,%68,%69,%70,%71,%72,%73,%74,%75,%76,%77,%78,%79,%80,%81,%82,%83,%84,%85,%86,%87,%88,%89,%90,%91,%92,%93,%94,%95,%96,%97,%98,%99,%100,%101,%102,%103,%104,%105,%106,%107,%108,%109,%110,%111,%112,%113,%114,%115,%116,%117,%118,%119,%120,%121,%122,%123,%124,%125,%126,%127}, %129, %131, 1, 1, 1, 0, 1;\n"
        "}\n"
        : R8(a, 0), R8(a, 8), R8(a, 16), R8(a, 24), R8(a, 32), R8(a, 40), R8(a, 48), R8(a, 56), R8(a, 64), R8(a, 72), R8(a, 80), R8(a, 88), R8(a, 96), R8(a, 104), R8(a, 112), R8(a, 120)
        : "l"(da0), "l"(da1), "l"(db0), "l"(db1), "r"(scale_d));
}
__device__ __forceinline__ void wgmma_n192_k32(float* a, uint64_t da0, uint64_t da1, uint64_t db0, uint64_t db1, int scale_d) {
    asm volatile(
        "{\n.reg .pred p;\nsetp.ne.b32 p, %100, 0;\n"
        "wgmma.mma_async.sync.aligned.m64n192k16.f32.bf16.bf16 {%0,%1,%2,%3,%4,%5,%6,%7,%8,%9,%10,%11,%12,%13,%14,%15,%16,%17,%18,%19,%20,%21,%22,%23,%24,%25,%26,%27,%28,%29,%30,%31,%32,%33,%34,%35,%36,%37,%38,%39,%40,%41,%42,%43,%44,%45,%46,%47,%48,%49,%50,%51,%52,%53,%54,%55,%56,%57,%58,%59,%60,%61,%62,%63,%64,%65,%66,%67,%68,%69,%70,%71,%72,%73,%74,%75,%76,%77,%78,%79,%80,%81,%82,%83,%84,%85,%86,%87,%88,%89,%90,%91,%92,%93,%94,%95}, %96, %98, p, 1, 1, 0, 1;\n"
        "wgmma.mma_async.sync.aligned.m64n192k16.f32.bf16.bf16 {%0,%1,%2,%3,%4,%5,%6,%7,%8,%9,%10,%11,%12,%13,%14,%15,%16,%17,%18,%19,%20,%21,%22,%23,%24,%25,%26,%27,%28,%29,%30,%31,%32,%33,%34,%35,%36,%37,%38,%39,%40,%41,%42,%43,%44,%45,%46,%47,%48,%49,%50,%51,%52,%53,%54,%55,%56,%57,%58,%59,%60,%61,%62,%63,%64,%65,%66,%67,%68,%69,%70,%71,%72,%73,%74,%75,%76,%77,%78,%79,%80,%81,%82,%83,%84,%85,%86,%87,%88,%89,%90,%91,%92,%93,%94,%95}, %97, %99, 1, 1, 1, 0, 1;\n"
        "}\n"
        : R8(a, 0), R8(a, 8), R8(a, 16), R8(a, 24), R8(a, 32), R8(a, 40), R8(a, 48), R8(a, 56), R8(a, 64), R8(a, 72), R8(a, 80), R8(a, 88)
        : "l"(da0), "l"(da1), "l"(db0), "l"(db1), "r"(scale_d));
}
__device__ __forceinline__ void wgmma_n192(float* a, uint64_t da0, uint64_t db0, int scale_d) {
    asm volatile(
        "{\n.reg .pred p;\nsetp.ne.b32 p, %98, 0;\n"
        "wgmma.mma_async.sync.aligned.m64n192k16.f32.bf16.bf16 {%0,%1,%2,%3,%4,%5,%6,%7,%8,%9,%10,%11,%12,%13,%14,%15,%16,%17,%18,%19,%20,%21,%22,%23,%24,%25,%26,%27,%28,%29,%30,%31,%32,%33,%34,%35,%36,%37,%38,%39,%40,%41,%42,%43,%44,%45,%46,%47,%48,%49,%50,%51,%52,%53,%54,%55,%56,%57,%58,%59,%60,%61,%62,%63,%64,%65,%66,%67,%68,%69,%70,%71,%72,%73,%74,%75,%76,%77,%78,%79,%80,%81,%82,%83,%84,%85,%86,%87,%88,%89,%90,%91,%92,%93,%94,%95}, %96, %97, p, 1, 1, 0, 1;\n"
        "}\n"
        : R8(a, 0), R8(a, 8), R8(a, 16), R8(a, 24), R8(a, 32), R8(a, 40), R8(a, 48), R8(a, 56), R8(a, 64), R8(a, 72), R8(a, 80), R8(a, 88)
        : "l"(da0), "l"(db0), "r"(scale_d));
}
__device__ __forceinline__ void wgmma_n128_k64(float* a, uint64_t da0, uint64_t da1, uint64_t da2, uint64_t da3,
                                               uint64_t db0, uint64_t db1, uint64_t db2, uint64_t db3, int scale_d) {
    asm volatile(
        "{\n.reg .pred p;\nsetp.ne.b32 p, %72, 0;\n"
        "wgmma.mma_async.sync.aligned.m64n128k16.f32.bf16.bf16 {%0,%1,%2,%3,%4,%5,%6,%7,%8,%9,%10,%11,%12,%13,%14,%15,%16,%17,%18,%19,%20,%21,%22,%23,%24,%25,%26,%27,%28,%29,%30,%31,%32,%33,%34,%35,%36,%37,%38,%39,%40,%41,%42,%43,%44,%45,%46,%47,%48,%49,%50,%51,%52,%53,%54,%55,%56,%57,%58,%59,%60,%61,%62,%63}, %64, %68, p, 1, 1, 0, 1;\n"
        "wgmma.mma_async.sync.aligned.m64n128k16.f32.bf16.bf16 {%0,%1,%2,%3,%4,%5,%6,%7,%8,%9,%10,%11,%12,%13,%14,%15,%16,%17,%18,%19,%20,%21,%22,%23,%24,%25,%26,%27,%28,%29,%30,%31,%32,%33,%34,%35,%36,%37,%38,%39,%40,%41,%42,%43,%44,%45,%46,%47,%48,%49,%50,%51,%52,%53,%54,%55,%56,%57,%58,%59,%60,%61,%62,%63}, %65, %69, 1, 1, 1, 0, 1;\n"
        "wgmma.mma_async.sync.aligned.m64n128k16.f32.bf16.bf16 {%0,%1,%2,%3,%4,%5,%6,%7,%8,%9,%10,%11,%12,%13,%14,%15,%16,%17,%18,%19,%20,%21,%22,%23,%24,%25,%26,%27,%28,%29,%30,%31,%32,%33,%34,%35,%36,%37,%38,%39,%40,%41,%42,%43,%44,%45,%46,%47,%48,%49,%50,%51,%52,%53,%54,%55,%56,%57,%58,%59,%60,%61,%62,%63}, %66, %70, 1, 1, 1, 0, 1;\n"
        "wgmma.mma_async.sync.aligned.m64n128k16.f32.bf16.bf16 {%0,%1,%2,%3,%4,%5,%6,%7,%8,%9,%10,%11,%12,%13,%14,%15,%16,%17,%18,%19,%20,%21,%22,%23,%24,%25,%26,%27,%28,%29,%30,%31,%32,%33,%34,%35,%36,%37,%38,%39,%40,%41,%42,%43,%44,%45,%46,%47,%48,%49,%50,%51,%52,%53,%54,%55,%56,%57,%58,%59,%60,%61,%62,%63}, %67, %71, 1, 1, 1, 0, 1;\n"
        "}\n"
        : R8(a, 0), R8(a, 8), R8(a, 16), R8(a, 24), R8(a, 32), R8(a, 40), R8(a, 48), R8(a, 56)
        : "l"(da0), "l"(da1), "l"(da2), "l"(da3), "l"(db0), "l"(db1), "l"(db2), "l"(db3), "r"(scale_d));
}

__device__ __forceinline__ float bf16_round(float x) {
    uint32_t p; asm("cvt.rn.bf16x2.f32 %0, %1, %2;" : "=r"(p) : "f"(x), "f"(0.0f));
    return __uint_as_float(p);
}
__device__ __forceinline__ uint32_t pack_bf16(float lo, float hi) {
    __nv_bfloat162 v = __floats2bfloat162_rn(lo, hi);
    return *reinterpret_cast<uint32_t*>(&v);
}
__device__ __forceinline__ float bf_lo(uint32_t v) { return __uint_as_float(v << 16); }
__device__ __forceinline__ float bf_hi(uint32_t v) { return __uint_as_float(v & 0xFFFF0000u); }

struct cplx { float r, i; };
__device__ __forceinline__ cplx cmul(cplx a, cplx b) {
    cplx c; c.r = a.r * b.r - a.i * b.i; c.i = a.r * b.i + a.i * b.r; return c;
}
__device__ __forceinline__ cplx csq(cplx a) {
    cplx c; c.r = a.r * a.r - a.i * a.i; c.i = 2.0f * a.r * a.i; return c;
}
__device__ __forceinline__ cplx cexp_m(float ar2, float ai2, float m) {
    float mag;
    asm("ex2.approx.ftz.f32 %0, %1;" : "=f"(mag) : "f"(ar2 * m));
    float rr = ai2 * m;
    rr -= (rr + 12582912.0f) - 12582912.0f;
    float th = rr * 6.283185307179586f;
    cplx c; c.r = mag * __cosf(th); c.i = mag * __sinf(th);
    return c;
}
__device__ __forceinline__ uint32_t to_tf32(float x) { return __float_as_uint(x) + 0x1000u; }
__device__ __forceinline__ void mma_tf32(float* c, uint32_t a0, uint32_t a1, uint32_t a2, uint32_t a3, uint32_t b0, uint32_t b1) {
    asm volatile("mma.sync.aligned.m16n8k8.row.col.f32.tf32.tf32.f32 {%0,%1,%2,%3}, {%4,%5,%6,%7}, {%8,%9}, {%0,%1,%2,%3};"
                 : "+f"(c[0]), "+f"(c[1]), "+f"(c[2]), "+f"(c[3])
                 : "r"(a0), "r"(a1), "r"(a2), "r"(a3), "r"(b0), "r"(b1));
}
__device__ __forceinline__ void mma_bf16(float* c, uint32_t a0, uint32_t a1, uint32_t a2, uint32_t a3, uint32_t b0, uint32_t b1) {
    asm volatile("mma.sync.aligned.m16n8k16.row.col.f32.bf16.bf16.f32 {%0,%1,%2,%3}, {%4,%5,%6,%7}, {%8,%9}, {%0,%1,%2,%3};"
                 : "+f"(c[0]), "+f"(c[1]), "+f"(c[2]), "+f"(c[3])
                 : "r"(a0), "r"(a1), "r"(a2), "r"(a3), "r"(b0), "r"(b1));
}
__device__ __forceinline__ void named_bar(int id, int n) { asm volatile("bar.sync %0, %1;" ::"r"(id), "r"(n) : "memory"); }
__device__ __forceinline__ void ldsm_x4(uint32_t addr, uint32_t& r0, uint32_t& r1, uint32_t& r2, uint32_t& r3) {
    asm volatile("ldmatrix.sync.aligned.m8n8.x4.shared.b16 {%0,%1,%2,%3}, [%4];" : "=r"(r0), "=r"(r1), "=r"(r2), "=r"(r3) : "r"(addr));
}
__device__ __forceinline__ void ldsm_x4_t(uint32_t addr, uint32_t& r0, uint32_t& r1, uint32_t& r2, uint32_t& r3) {
    asm volatile("ldmatrix.sync.aligned.m8n8.x4.trans.shared.b16 {%0,%1,%2,%3}, [%4];" : "=r"(r0), "=r"(r1), "=r"(r2), "=r"(r3) : "r"(addr));
}

constexpr int CV_CH = 4;
constexpr int CV_O_CONST = 0;
constexpr int CV_O_KP = 12288;
constexpr int CV_O_Q = CV_O_KP + 10368;
constexpr int CV_O_Q2 = CV_O_Q + 2304;
constexpr int CV_O_Q3 = CV_O_Q2 + 1024;
constexpr int CV_O_Q4X = CV_O_Q3 + 768;
constexpr int CV_O_W3 = CV_O_Q4X + 256;
constexpr int CV_O_W5 = CV_O_W3 + 3104;
constexpr int CV_O_W7 = CV_O_W5 + 3104;
constexpr int CV_O_W9 = CV_O_W7 + 2048;
constexpr int CV_O_STG = 32768;
constexpr int CV_O_U = CV_O_W9 + 2048;
constexpr int CV_PER_CH = CV_O_U + 4352;
static_assert(CV_O_U >= CV_O_STG + 4096, "staging overlaps u");
constexpr int CV_SMEM = CV_CH * CV_PER_CH;

constexpr int LN_ROWS = 16;

__device__ __forceinline__ void front_phase(uint8_t* smem, const __nv_bfloat16* __restrict__ x,
                                            const __nv_bfloat16* __restrict__ A_re, const __nv_bfloat16* __restrict__ A_im,
                                            const __nv_bfloat16* __restrict__ B_re, const __nv_bfloat16* __restrict__ B_im,
                                            const __nv_bfloat16* __restrict__ C_re, const __nv_bfloat16* __restrict__ C_im,
                                            const __nv_bfloat16* __restrict__ log_dt, const __nv_bfloat16* __restrict__ Dskip,
                                            const __nv_bfloat16* __restrict__ wg, const __nv_bfloat16* __restrict__ wu,
                                            const __nv_bfloat16* __restrict__ wd) {
    const int warp = threadIdx.x >> 5, lane = threadIdx.x & 31;
    const int ch = warp / 3, w = warp - 3 * ch, tc = threadIdx.x - 96 * ch;
    const int d = blockIdx.x * CV_CH + ch;
    const int g = lane >> 2, t = lane & 3;
    uint8_t* base = smem + ch * CV_PER_CH;
    float4* s_const = reinterpret_cast<float4*>(base + CV_O_CONST);
    float* s_kp = reinterpret_cast<float*>(base + CV_O_KP);
    uint32_t* s_q = reinterpret_cast<uint32_t*>(base + CV_O_Q);
    uint32_t* s_q2 = reinterpret_cast<uint32_t*>(base + CV_O_Q2);
    uint32_t* s_q3 = reinterpret_cast<uint32_t*>(base + CV_O_Q3);
    uint32_t* s_q4 = reinterpret_cast<uint32_t*>(base + CV_O_Q4X);
    __nv_bfloat16* s_u = reinterpret_cast<__nv_bfloat16*>(base + CV_O_U);
    const int bar_id = 5 + ch;
    const __nv_bfloat16 p_dsk = Dskip[d];
    __nv_bfloat16 (*tile)[D_ + 8] = reinterpret_cast<__nv_bfloat16 (*)[D_ + 8]>(smem + CV_SMEM);

    if (warp < 8) {
        const int row = blockIdx.x * LN_ROWS + warp * 2;
        uint4 xv[2][2];
#pragma unroll
        for (int r = 0; r < 2; r++) {
            xv[r][0] = *reinterpret_cast<const uint4*>(x + (size_t)(row + r) * D_ + lane * 8);
            xv[r][1] = *reinterpret_cast<const uint4*>(x + (size_t)(row + r) * D_ + 256 + lane * 8);
        }
        float f[2][16], sm[2], q[2];
#pragma unroll
        for (int r = 0; r < 2; r++) {
            const uint32_t wv[8] = {xv[r][0].x, xv[r][0].y, xv[r][0].z, xv[r][0].w, xv[r][1].x, xv[r][1].y, xv[r][1].z, xv[r][1].w};
#pragma unroll
            for (int i = 0; i < 8; i++) { f[r][2 * i] = bf_lo(wv[i]); f[r][2 * i + 1] = bf_hi(wv[i]); }
            sm[r] = 0.f;
#pragma unroll
            for (int i = 0; i < 16; i++) sm[r] += f[r][i];
        }
#pragma unroll
        for (int o = 16; o > 0; o >>= 1) { sm[0] += __shfl_xor_sync(0xffffffffu, sm[0], o); sm[1] += __shfl_xor_sync(0xffffffffu, sm[1], o); }
#pragma unroll
        for (int r = 0; r < 2; r++) {
            sm[r] *= (1.0f / D_);
            q[r] = 0.f;
#pragma unroll
            for (int i = 0; i < 16; i++) { float dd = f[r][i] - sm[r]; q[r] += dd * dd; }
        }
#pragma unroll
        for (int o = 16; o > 0; o >>= 1) { q[0] += __shfl_xor_sync(0xffffffffu, q[0], o); q[1] += __shfl_xor_sync(0xffffffffu, q[1], o); }
#pragma unroll
        for (int r = 0; r < 2; r++) {
            const float mb = bf16_round(sm[r]);
            const float vb = bf16_round(q[r] * (1.0f / D_));
            const float den = bf16_round(sqrtf(bf16_round(vb + 1e-5f)));
            uint32_t o[8];
#pragma unroll
            for (int i = 0; i < 8; i++) {
                float a = __fdiv_rn(bf16_round(f[r][2 * i] - mb), den);
                float b = __fdiv_rn(bf16_round(f[r][2 * i + 1] - mb), den);
                o[i] = pack_bf16(a, b);
            }
            __nv_bfloat16* dst = g_xn + (size_t)(row + r) * D_;
            *reinterpret_cast<uint4*>(dst + lane * 8) = make_uint4(o[0], o[1], o[2], o[3]);
            *reinterpret_cast<uint4*>(dst + 256 + lane * 8) = make_uint4(o[4], o[5], o[6], o[7]);
            *reinterpret_cast<uint4*>(&tile[warp * 2 + r][lane * 8]) = make_uint4(o[0], o[1], o[2], o[3]);
            *reinterpret_cast<uint4*>(&tile[warp * 2 + r][256 + lane * 8]) = make_uint4(o[4], o[5], o[6], o[7]);
        }
    } else {
        const int cc_ = warp - 8, dd = blockIdx.x * CV_CH + cc_;
        float4* sc = reinterpret_cast<float4*>(smem + cc_ * CV_PER_CH + CV_O_CONST);
        __nv_bfloat16 pr[4][6];
#pragma unroll
        for (int j = 0; j < 4; j++) {
            const size_t off = (size_t)dd * NS_ + lane + 32 * j;
            pr[j][0] = A_re[off]; pr[j][1] = A_im[off]; pr[j][2] = B_re[off]; pr[j][3] = B_im[off]; pr[j][4] = C_re[off]; pr[j][5] = C_im[off];
        }
        const float dt = bf16_round(expf(__bfloat162float(log_dt[dd])));
        float tail = 0.f;
#pragma unroll
        for (int j = 0; j < 4; j++) {
            const float ar = dt * __bfloat162float(pr[j][0]), ai = dt * __bfloat162float(pr[j][1]);
            const cplx db = {dt * __bfloat162float(pr[j][2]), dt * __bfloat162float(pr[j][3])};
            const cplx cc = {__bfloat162float(pr[j][4]), __bfloat162float(pr[j][5])};
            const cplx cb = cmul(cc, db);
            const float ar2 = ar * 1.4426950408889634f, ai2 = ai * 0.15915494309189535f;
            const cplx e8 = cexp_m(ar2, ai2, 8.f), e128 = cexp_m(ar2, ai2, 128.f);
            const cplx cb8 = cmul(cb, e8);
            const cplx e256 = cexp_m(ar2, ai2, 256.f), e512 = cexp_m(ar2, ai2, 512.f), e1024 = cexp_m(ar2, ai2, 1024.f);
            const cplx c256 = cmul(cb, e256), c512 = cmul(cb, e512), c1024 = cmul(cb, e1024);
            const cplx c768 = cmul(c512, e256), c1280 = cmul(c1024, e256), c1536 = cmul(c1024, e512);
            const cplx c1792 = cmul(c1536, e256);
            tail += cmul(c1024, e1024).r;
            float4* c = sc + (lane + 32 * j) * 6;
            c[0] = make_float4(ar2, ai2, cb.r, cb.i);
            c[1] = make_float4(e128.r, e128.i, cb8.r, cb8.i);
            c[2] = make_float4(c256.r, c256.i, e8.r, e8.i);
            c[3] = make_float4(c512.r, c512.i, c768.r, c768.i);
            c[4] = make_float4(c1024.r, c1024.i, c1280.r, c1280.i);
            c[5] = make_float4(c1536.r, c1536.i, c1792.r, c1792.i);
        }
#pragma unroll
        for (int o = 16; o > 0; o >>= 1) tail += __shfl_xor_sync(0xffffffffu, tail, o);
        if (lane == 0) {
            float* kp = reinterpret_cast<float*>(smem + cc_ * CV_PER_CH + CV_O_KP);
            kp[640] = tail; kp[648 + 640] = 0.f; kp[1296 + 640] = 0.f;
        }
    }
    __syncthreads();
    if (threadIdx.x == 0) STAMP(0, 3);
#pragma unroll
    for (int rep = 0; rep < 2; rep++) {
        const int c = threadIdx.x + 384 * rep;
        if (c < D_) {
            uint32_t ot[8];
#pragma unroll
            for (int i = 0; i < 8; i++) {
                uint32_t lo = *reinterpret_cast<const uint16_t*>(&tile[2 * i][c]);
                uint32_t hi = *reinterpret_cast<const uint16_t*>(&tile[2 * i + 1][c]);
                ot[i] = lo | (hi << 16);
            }
            __nv_bfloat16* dT = g_xnT + (size_t)c * L_ + blockIdx.x * LN_ROWS;
            *reinterpret_cast<uint4*>(dT) = make_uint4(ot[0], ot[1], ot[2], ot[3]);
            *reinterpret_cast<uint4*>(dT + 8) = make_uint4(ot[4], ot[5], ot[6], ot[7]);
        }
    }
    if (threadIdx.x < 336) {
        const int m = threadIdx.x / 112, i = threadIdx.x - m * 112;
        const char* wp = (const char*)(m == 0 ? wg : (m == 1 ? wu : wd));
        asm volatile("prefetch.global.L2 [%0];" ::"l"(wp + ((size_t)blockIdx.x * 112 + i) * 128));
    }
    __syncthreads();
    if (threadIdx.x == 0) STAMP(1, 1);
    {
        float acc[5][4];
#pragma unroll
        for (int i = 0; i < 5; i++) { acc[i][0] = acc[i][1] = acc[i][2] = acc[i][3] = 0.f; }
        const float gf = (float)g;
        const int src4 = ((g & 3) << 2) | t;
#pragma unroll 2
        for (int s = w; s < 32; s += 3) {
            if (s == 17 && threadIdx.x == 352) asm volatile("red.release.gpu.global.add.u32 [%0], 1;" ::"l"(&g_ln_count) : "memory");
            const float4* c = s_const + (s * 4 + t) * 6;
            const float4 k0 = c[0], k1 = c[1], k2 = c[2];
            const float2 k3 = reinterpret_cast<const float2*>(c + 3)[g >> 2];
            const float2 k4 = reinterpret_cast<const float2*>(c + 4)[g >> 1];
            const cplx cb = {k0.z, k0.w}, e128 = {k1.x, k1.y}, cb8 = {k1.z, k1.w}, c256 = {k2.x, k2.y}, e8 = {k2.z, k2.w};
            const cplx c2 = {k3.x, k3.y}, c3 = {k4.x, k4.y};
            const cplx p1 = cexp_m(k0.x, k0.y, gf);
            const cplx p2 = csq(p1), p4 = csq(p2);
            const cplx r16a = csq(csq(p4));
            cplx q4;
            q4.r = __shfl_sync(0xffffffffu, p4.r, src4);
            q4.i = __shfl_sync(0xffffffffu, p4.i, src4);
            const cplx r16b = cmul(r16a, e128);
            const cplx f0a = cmul(cb, p1), f0b = cmul(cb8, p1), f1 = cmul(c256, p2), f2 = cmul(c2, q4);
            cplx f3 = cmul(c3, e8);
            if (!(g & 1)) f3 = c3;
            const uint32_t a0 = to_tf32(r16a.r), a1 = to_tf32(r16b.r), a2 = to_tf32(-r16a.i), a3 = to_tf32(-r16b.i);
            mma_tf32(acc[0], a0, a1, a2, a3, to_tf32(f0a.r), to_tf32(f0a.i));
            mma_tf32(acc[1], a0, a1, a2, a3, to_tf32(f0b.r), to_tf32(f0b.i));
            mma_tf32(acc[2], a0, a1, a2, a3, to_tf32(f1.r), to_tf32(f1.i));
            mma_tf32(acc[3], a0, a1, a2, a3, to_tf32(f2.r), to_tf32(f2.i));
            mma_tf32(acc[4], a0, a1, a2, a3, to_tf32(f3.r), to_tf32(f3.i));
        }
        float* kv = s_kp + w * 648;
#pragma unroll
        for (int hh = 0; hh < 2; hh++) {
            const int i = g + 8 * hh;
            *reinterpret_cast<float2*>(kv + 16 * i + 2 * t) = make_float2(acc[0][2 * hh], acc[0][2 * hh + 1]);
            *reinterpret_cast<float2*>(kv + 16 * i + 8 + 2 * t) = make_float2(acc[1][2 * hh], acc[1][2 * hh + 1]);
            *reinterpret_cast<float2*>(kv + 256 + 8 * i + 2 * t) = make_float2(acc[2][2 * hh], acc[2][2 * hh + 1]);
            *reinterpret_cast<float2*>(kv + 384 + 64 * (t >> 1) + 2 * (t & 1) + 4 * i) = make_float2(acc[3][2 * hh], acc[3][2 * hh + 1]);
            *reinterpret_cast<float2*>(kv + 512 + 32 * t + 2 * i) = make_float2(acc[4][2 * hh], acc[4][2 * hh + 1]);
        }
    }
    named_bar(bar_id, 96);
    if (threadIdx.x == 0) STAMP(1, 2);
#pragma unroll
    for (int i = 0; i < 7; i++) {
        const int idx = tc + 96 * i;
        if (idx < 641) s_kp[idx] = (s_kp[idx] + s_kp[648 + idx]) + s_kp[1296 + idx];
    }
    named_bar(bar_id, 96);
    {
        auto kdir = [&](int l) -> float {
            if (l < 0 || l > 514) return 0.f;
            const int idx = (l < 256) ? l : (l > 512 ? 384 : 128 + ((l + ((l >> 1) & 1)) >> 1));
            return s_kp[idx];
        };
#pragma unroll
        for (int i = 0; i < 6; i++) {
            const int e = tc + 96 * i;
            s_q[e] = pack_bf16(kdir(e - 16), kdir(e - 17));
        }
        if (tc < 64) {
            const int xx = 1008 + tc;
            const float k1024 = s_kp[512];
            s_q4[tc] = pack_bf16((xx == 1027 || xx == 1028) ? k1024 : 0.f, (xx == 1028 || xx == 1029) ? k1024 : 0.f);
        }
#pragma unroll
        for (int i = 0; i < 3; i++) {
            const int e = tc + 96 * i;
            if (e < 256) {
                const int a = e >> 6, ii = (e & 63) - 16;
                const int b = 385 + (a >> 1) + 2 * (a & 1);
                const float v0 = (ii >= 0 && ii < 32) ? s_kp[b + 4 * ii] : 0.f;
                const float v1 = (ii >= 1 && ii < 33) ? s_kp[b + 4 * (ii - 1)] : 0.f;
                s_q2[e] = pack_bf16(v0, v1);
            }
        }
#pragma unroll
        for (int a = 0; a < 2; a++) {
            const int jj = tc - 16;
            const float v0 = (jj >= 0 && jj < 64) ? s_kp[513 + a + 2 * jj] : 0.f;
            const float v1 = (jj >= 1 && jj < 65) ? s_kp[513 + a + 2 * (jj - 1)] : 0.f;
            s_q3[96 * a + tc] = pack_bf16(v0, v1);
        }
    }
    if (threadIdx.x == 0) STAMP(1, 3);
    if (threadIdx.x == 0) {
        unsigned int v = 0;
        for (int spin = 0; spin < (1 << 22); spin++) {
            asm volatile("ld.acquire.gpu.global.u32 %0, [%1];" : "=r"(v) : "l"(&g_ln_count) : "memory");
            if (v >= gridDim.x) break;
        }
    }
    __syncthreads();
    if (threadIdx.x == 0) STAMP(1, 4);
    {
        if (tc < 16) *reinterpret_cast<uint4*>(s_u + tc * 8) = make_uint4(0, 0, 0, 0);
        const uint4* src = reinterpret_cast<const uint4*>(g_xnT + (size_t)d * L_);
        uint4 v[3];
#pragma unroll
        for (int i = 0; i < 3; i++) if (tc + 96 * i < 256) v[i] = src[tc + 96 * i];
#pragma unroll
        for (int i = 0; i < 3; i++) if (tc + 96 * i < 256) *reinterpret_cast<uint4*>(s_u + 128 + (tc + 96 * i) * 8) = v[i];
        if (tc < 2) *reinterpret_cast<uint4*>(base + (tc ? CV_O_W5 : CV_O_W3)) = make_uint4(0, 0, 0, 0);
    }
    named_bar(bar_id, 96);
#pragma unroll
    for (int rep = 0; rep < 2; rep++) {
        const int m = tc + 96 * rep;
        float P[30];
        const uint4* up = reinterpret_cast<const uint4*>(s_u + 128 + 8 * m - 24);
        P[0] = 0.f;
#pragma unroll
        for (int c4 = 0; c4 < 4; c4++) {
            const uint4 v = up[c4];
            const uint32_t ww[4] = {v.x, v.y, v.z, v.w};
#pragma unroll
            for (int j = 0; j < 4; j++) {
                const int k = c4 * 8 + 2 * j;
                if (k + 1 <= 29) P[k + 1] = P[k] + bf_lo(ww[j]);
                if (k + 2 <= 29) P[k + 2] = P[k + 1] + bf_hi(ww[j]);
            }
        }
        uint32_t o3[4], o5[4], o7[4], o9[4];
#pragma unroll
        for (int j = 0; j < 4; j++) {
            const int i = 2 * j;
            o3[j] = pack_bf16(P[i + 22] - P[i + 19], P[i + 23] - P[i + 20]);
            o5[j] = pack_bf16(P[i + 19] - P[i + 14], P[i + 20] - P[i + 15]);
            o7[j] = pack_bf16(P[i + 20] - P[i + 13], P[i + 21] - P[i + 14]);
            o9[j] = pack_bf16(P[i + 13] - P[i + 4], P[i + 14] - P[i + 5]);
        }
        *reinterpret_cast<uint4*>(base + CV_O_W3 + 16 + m * 16) = make_uint4(o3[0], o3[1], o3[2], o3[3]);
        *reinterpret_cast<uint4*>(base + CV_O_W5 + 16 + m * 16) = make_uint4(o5[0], o5[1], o5[2], o5[3]);
        if (m < 128) {
            *reinterpret_cast<uint4*>(base + CV_O_W7 + m * 16) = make_uint4(o7[0], o7[1], o7[2], o7[3]);
            *reinterpret_cast<uint4*>(base + CV_O_W9 + m * 16) = make_uint4(o9[0], o9[1], o9[2], o9[3]);
        }
    }
    if (threadIdx.x == 0) STAMP(1, 5);
    named_bar(bar_id, 96);
    if (w == 2) return;
    const int hb = w;
    float acc[16][4];
#pragma unroll
    for (int i = 0; i < 16; i++) { acc[i][0] = acc[i][1] = acc[i][2] = acc[i][3] = 0.f; }
    const uint32_t sb_addr = smem_u32(base);
    const int mi = lane >> 3, rowi = lane & 7;
#pragma unroll 1
    for (int rr = 0; rr < 4; rr++) {
        const int r = 4 * hb + rr;
        uint32_t ub[16][2];
        {
            const uint32_t addr = sb_addr + CV_O_U + (uint32_t)((128 + 16 * (8 * (mi >> 1) + rowi - r) + 8 * (mi & 1)) * 2);
#pragma unroll
            for (int j = 0; j < 16; j += 2) ldsm_x4(addr + (uint32_t)(j * 256), ub[j][0], ub[j][1], ub[j + 1][0], ub[j + 1][1]);
        }
        const uint32_t* qp = s_q + 16 + 16 * r + g - 2 * t;
        uint32_t af[4][3];
#pragma unroll
        for (int q = 0; q < 4; q++) { af[q][0] = qp[128 * q]; af[q][1] = qp[128 * q + 8]; af[q][2] = qp[128 * q - 8]; }
#pragma unroll
        for (int q = 0; q < 4; q++) {
#pragma unroll
            for (int nt = q; nt < 16; nt++) mma_bf16(acc[nt], af[q][0], af[q][1], af[q][2], af[q][0], ub[nt - q][0], ub[nt - q][1]);
        }
        if (r < 2) {
            {
                const uint32_t a0 = qp[512], a1 = qp[520], a2 = qp[504];
#pragma unroll
                for (int nt = 4; nt < 16; nt++) mma_bf16(acc[nt], a0, a1, a2, a0, ub[nt - 4][0], ub[nt - 4][1]);
            }
            {
                const uint32_t* q4p = s_q4 + 16 + 16 * r + g - 2 * t;
                const uint32_t a0 = q4p[0], a1 = q4p[8], a2 = q4p[-8];
#pragma unroll
                for (int nt = 8; nt < 16; nt++) mma_bf16(acc[nt], a0, a1, a2, a0, ub[nt - 8][0], ub[nt - 8][1]);
            }
        }
    }
#pragma unroll 1
    for (int a = hb; a <= 3 * hb; a++) {
        uint32_t bq[7];
        const uint32_t* q2 = s_q2 + a * 64 + 16 + g - 2 * t - 32;
#pragma unroll
        for (int dlt = 3; dlt <= 9; dlt++) bq[dlt - 3] = q2[8 * dlt];
        const uint32_t addr = sb_addr + ((a >> 1) ? CV_O_W5 : CV_O_W3) + (uint32_t)((8 + 16 * (8 * (mi >> 1) + rowi) + 8 * (mi & 1) - 8 * (a & 1)) * 2);
        uint32_t aa[6][4];
#pragma unroll
        for (int kp = 0; kp < 6; kp++) ldsm_x4_t(addr + kp * 512, aa[kp][0], aa[kp][1], aa[kp][2], aa[kp][3]);
#pragma unroll
        for (int kp = 0; kp < 6; kp++) {
#pragma unroll
            for (int dlt = 4; dlt <= 9; dlt++) {
                if (2 * kp + dlt < 16) mma_bf16(acc[2 * kp + dlt], aa[kp][0], aa[kp][1], aa[kp][2], aa[kp][3], bq[dlt - 3], bq[dlt - 4]);
            }
        }
    }
    if (hb == 0) {
#pragma unroll 1
        for (int a = 0; a < 2; a++) {
            uint32_t bq[9];
            const uint32_t* q3 = s_q3 + a * 96 + 16 + g - 2 * t - 64;
#pragma unroll
            for (int dlt = 7; dlt <= 15; dlt++) bq[dlt - 7] = q3[8 * dlt];
            const uint32_t addr = sb_addr + (a ? CV_O_W9 : CV_O_W7) + (uint32_t)((16 * (8 * (mi >> 1) + rowi) + 8 * (mi & 1)) * 2);
            uint32_t aa[4][4];
#pragma unroll
            for (int kp = 0; kp < 4; kp++) ldsm_x4_t(addr + kp * 512, aa[kp][0], aa[kp][1], aa[kp][2], aa[kp][3]);
#pragma unroll
            for (int kp = 0; kp < 4; kp++) {
#pragma unroll
                for (int dlt = 8; dlt <= 15; dlt++) {
                    if (2 * kp + dlt < 16) mma_bf16(acc[2 * kp + dlt], aa[kp][0], aa[kp][1], aa[kp][2], aa[kp][3], bq[dlt - 7], bq[dlt - 8]);
                }
            }
        }
    }
    if (threadIdx.x == 0) STAMP(1, 6);
    {
        float4* xch = reinterpret_cast<float4*>(base + CV_O_CONST) + hb * 256;
        if (hb) {
#pragma unroll
            for (int i = 0; i < 8; i++) xch[i * 32 + lane] = make_float4(acc[i][0], acc[i][1], acc[i][2], acc[i][3]);
#pragma unroll
            for (int i = 0; i < 8; i++) { acc[i][0] = acc[8 + i][0]; acc[i][1] = acc[8 + i][1]; acc[i][2] = acc[8 + i][2]; acc[i][3] = acc[8 + i][3]; }
        } else {
#pragma unroll
            for (int i = 0; i < 8; i++) xch[i * 32 + lane] = make_float4(acc[8 + i][0], acc[8 + i][1], acc[8 + i][2], acc[8 + i][3]);
        }
    }
    named_bar(bar_id, 64);
    if (threadIdx.x == 0) STAMP(1, 10);
    {
        const float4* xch = reinterpret_cast<const float4*>(base + CV_O_CONST) + (hb ^ 1) * 256 + lane;
        const float dsk = __bfloat162float(p_dsk);
        uint16_t* stg = reinterpret_cast<uint16_t*>(base + CV_O_KP);
        const uint16_t* uu = reinterpret_cast<const uint16_t*>(s_u) + 128;
#pragma unroll
        for (int i = 0; i < 8; i++) {
            const float4 p0 = xch[i * 32];
            const float y[4] = {acc[i][0] + p0.x, acc[i][1] + p0.y, acc[i][2] + p0.z, acc[i][3] + p0.w};
            const int nt = 8 * hb + i;
#pragma unroll
            for (int e = 0; e < 4; e++) {
                const int tau = 16 * (8 * nt + 2 * t + (e & 1)) + g + 8 * (e >> 1);
                const float sv = bf16_round(y[e]) + bf16_round(__uint_as_float((uint32_t)uu[tau] << 16) * dsk);
                stg[tau] = (uint16_t)(__float_as_uint(bf16_round(sv)) >> 16);
            }
        }
        __syncwarp();
        if (threadIdx.x == 0) STAMP(1, 11);
        uint4* dst = reinterpret_cast<uint4*>(g_sT + (size_t)d * L_ + hb * 1024);
        const uint4* srcp = reinterpret_cast<const uint4*>(stg + hb * 1024);
#pragma unroll
        for (int i = 0; i < 4; i++) dst[i * 32 + lane] = srcp[i * 32 + lane];
    }
}

__device__ __forceinline__ uint32_t cluster_rank() { uint32_t r; asm volatile("mov.u32 %0, %%cluster_ctarank;" : "=r"(r)); return r; }
__device__ __forceinline__ void cluster_sync_all() {
    asm volatile("barrier.cluster.arrive.release.aligned;\nbarrier.cluster.wait.acquire.aligned;" ::: "memory");
}
__device__ __forceinline__ void mbar_arrive_remote(uint32_t bar, uint32_t cta) {
    asm volatile("{\n.reg .b32 ra;\nmapa.shared::cluster.u32 ra, %0, %1;\n"
                 "mbarrier.arrive.shared::cluster.b64 _, [ra];\n}\n" ::"r"(bar), "r"(cta) : "memory");
}
__device__ __forceinline__ void tma_load_2d_mc(uint32_t dst, const CUtensorMap* tm, int c0, int c1, uint32_t bar, uint16_t mask) {
    asm volatile(
        "cp.async.bulk.tensor.2d.shared::cluster.global.mbarrier::complete_tx::bytes.multicast::cluster [%0], [%1, {%3, %4}], [%2], %5;"
        ::"r"(dst), "l"((uint64_t)tm), "r"(bar), "r"(c0), "r"(c1), "h"(mask) : "memory");
}
__device__ __forceinline__ void tma_store_2d(const CUtensorMap* tm, uint32_t src, int c0, int c1) {
    asm volatile("cp.async.bulk.tensor.2d.global.shared::cta.bulk_group [%0, {%2, %3}], [%1];"
                 ::"l"((uint64_t)tm), "r"(src), "r"(c0), "r"(c1) : "memory");
}
__device__ __forceinline__ void bulk_commit() { asm volatile("cp.async.bulk.commit_group;" ::: "memory"); }
template <int N> __device__ __forceinline__ void bulk_wait_read() { asm volatile("cp.async.bulk.wait_group.read %0;" ::"n"(N) : "memory"); }
template <int N> __device__ __forceinline__ void bulk_wait() { asm volatile("cp.async.bulk.wait_group %0;" ::"n"(N) : "memory"); }
__device__ __forceinline__ void fence_async_smem() { asm volatile("fence.proxy.async.shared::cta;" ::: "memory"); }
__device__ __forceinline__ void stmatrix_x4(uint32_t addr, uint32_t r0, uint32_t r1, uint32_t r2, uint32_t r3) {
    asm volatile("stmatrix.sync.aligned.m8n8.x4.shared.b16 [%0], {%1,%2,%3,%4};" ::"r"(addr), "r"(r0), "r"(r1), "r"(r2), "r"(r3) : "memory");
}

constexpr int G1_STAGES = 5;
constexpr int G1_A_BYTES = 8 * 16384;
constexpr int G1_B_STAGE = 16384;
constexpr int G1_STG = 8 * 1024;
constexpr int G1_SMEM = G1_A_BYTES + G1_STAGES * G1_B_STAGE + G1_STG + 1024 + 256;
constexpr int G1_ITERS = 32;

__device__ __forceinline__ void tma_load_3d(uint32_t dst, const CUtensorMap* tm, int c0, int c1, int c2, uint32_t bar) {
    asm volatile(
        "cp.async.bulk.tensor.3d.shared::cluster.global.mbarrier::complete_tx::bytes [%0], [%1, {%3, %4, %5}], [%2];"
        ::"r"(dst), "l"((uint64_t)tm), "r"(bar), "r"(c0), "r"(c1), "r"(c2) : "memory");
}

__device__ __forceinline__ float gelu_tanh(float x) {
    float u = x * (0.7978845608028654f + 0.035677408136300125f * x * x);
    float t; asm("tanh.approx.f32 %0, %1;" : "=f"(t) : "f"(u));
    float hx = 0.5f * x;
    return fmaf(hx, t, hx);
}
__device__ __forceinline__ uint32_t geglu_pair(uint32_t g2, uint32_t u2) {
    uint32_t a = pack_bf16(gelu_tanh(bf_lo(g2)), gelu_tanh(bf_hi(g2)));
    uint32_t r; asm("mul.rn.bf16x2 %0, %1, %2;" : "=r"(r) : "r"(a), "r"(u2));
    return r;
}

constexpr int G2_STAGES = 5;
constexpr int G2_STAGE = 16384 + 16384;
constexpr int G2_XCH = 32768;
constexpr int G2_EPI = 16384 + 16384;
constexpr int G2_SMEM = G2_STAGES * G2_STAGE + G2_XCH + G2_EPI + 1024 + 256;
constexpr int G2_KB = F_ / 64 / 2;

constexpr int MG_BAR_OFF = G2_STAGES * G2_STAGE + G2_XCH + G2_EPI;
constexpr int MG_SMEM = MG_BAR_OFF + 256 + 1024;
static_assert(CV_SMEM + 16 * (D_ + 8) * 2 <= MG_BAR_OFF && G1_A_BYTES + G1_STAGES * G1_B_STAGE + G1_STG <= MG_BAR_OFF, "smem layout");

__device__ __forceinline__ void fence_async_all() { asm volatile("fence.proxy.async;" ::: "memory"); }
__device__ __forceinline__ void spin_until(const unsigned int* p, unsigned int target) {
    unsigned int v = 0;
    for (int spin = 0; spin < (1 << 22); spin++) {
        asm volatile("ld.acquire.gpu.global.u32 %0, [%1];" : "=r"(v) : "l"(p) : "memory");
        if (v >= target) break;
    }
}

struct MegaParams {
    const __nv_bfloat16 *x, *A_re, *A_im, *B_re, *B_im, *C_re, *C_im, *log_dt, *Dskip, *wg, *wu, *wd;
};

__global__ void __launch_bounds__(384, 1) mega_kernel(const __grid_constant__ MegaParams P,
                                                       const __grid_constant__ CUtensorMap tm_xn,
                                                       const __grid_constant__ CUtensorMap tm_wg4,
                                                       const __grid_constant__ CUtensorMap tm_wu4,
                                                       const __grid_constant__ CUtensorMap tm_wg3,
                                                       const __grid_constant__ CUtensorMap tm_wu3,
                                                       const __grid_constant__ CUtensorMap tm_h,
                                                       const __grid_constant__ CUtensorMap tm_wd,
                                                       const __grid_constant__ CUtensorMap tm_x,
                                                       const __grid_constant__ CUtensorMap tm_sT,
                                                       const __grid_constant__ CUtensorMap tm_out) {
    if (threadIdx.x == 0) STAMP(1, 0);
    extern __shared__ uint8_t smem_raw[];
    const uint32_t sraw = smem_u32(smem_raw);
    const uint32_t sbase = (sraw + 1023) & ~1023u;
    uint8_t* smem = smem_raw + (sbase - sraw);
    const int warp = threadIdx.x >> 5, lane = threadIdx.x & 31;
    const uint32_t sA = sbase, sB = sbase + G1_A_BYTES, sStg = sB + G1_STAGES * G1_B_STAGE;
    const uint32_t sXch = sbase + G2_STAGES * G2_STAGE, sX = sXch + G2_XCH, sS = sX + 16384;
    const uint32_t sBar = sbase + MG_BAR_OFF;
    const uint32_t bar_a = sBar, bar_full = sBar + 64, bar_empty = bar_full + 8 * G1_STAGES;
    const uint32_t bar_full2 = bar_empty + 8 * G1_STAGES, bar_empty2 = bar_full2 + 8 * G2_STAGES;
    const uint32_t bar_epi = bar_empty2 + 8 * G2_STAGES, bar_xch = bar_epi + 8, bar_g1done = bar_xch + 8;
    const int rb = blockIdx.x >> 3, cj = blockIdx.x & 7;
    const uint32_t kh = blockIdx.x & 1;
    const int nb = (blockIdx.x >> 1) & 3;
    const int col_fin = nb * 128 + kh * 64;

    if (threadIdx.x == 0) {
        for (int i = 0; i < 8; i++) mbar_init(bar_a + 8 * i, 1);
        for (int i = 0; i < G1_STAGES; i++) { mbar_init(bar_full + 8 * i, 1); mbar_init(bar_empty + 8 * i, 8); }
        for (int i = 0; i < G2_STAGES; i++) { mbar_init(bar_full2 + 8 * i, 1); mbar_init(bar_empty2 + 8 * i, 8); }
        mbar_init(bar_epi, 1);
        mbar_init(bar_xch, 1);
        mbar_init(bar_g1done, 8);
        asm volatile("fence.mbarrier_init.release.cluster;" ::: "memory");
        mbar_expect_tx(bar_xch, G2_XCH);
    }
    if (warp == 11 && lane == 0) {
        prefetch_tmap(&tm_wg4); prefetch_tmap(&tm_wu4); prefetch_tmap(&tm_xn); prefetch_tmap(&tm_wg3); prefetch_tmap(&tm_wu3);
        prefetch_tmap(&tm_wd); prefetch_tmap(&tm_h); prefetch_tmap(&tm_x); prefetch_tmap(&tm_sT); prefetch_tmap(&tm_out);
    }
    asm volatile("barrier.cluster.arrive.release.aligned;" ::: "memory");

    front_phase(smem, P.x, P.A_re, P.A_im, P.B_re, P.B_im, P.C_re, P.C_im, P.log_dt, P.Dskip, P.wg, P.wu, P.wd);
    fence_async_all();
    asm volatile("barrier.cluster.wait.acquire.aligned;" ::: "memory");
    __syncthreads();
    if (threadIdx.x == 0) STAMP(1, 7);

    if (warp >= 8) {
        asm volatile("setmaxnreg.dec.sync.aligned.u32 40;");
        if (warp == 11) {
            if (lane == 0) asm volatile("red.release.gpu.global.add.u32 [%0], 1;" ::"l"(&g_conv_count) : "memory");
            named_bar(3, 288);
            if (lane == 0) asm volatile("red.release.gpu.global.add.u32 [%0], 1;" ::"l"(&g_h_count[rb]) : "memory");
        } else if (lane == 0) {
            const int pw = warp - 8;
            fence_async_all();
            for (int k = pw; k < 8; k += 3) {
                mbar_expect_tx(bar_a + 8 * k, 16384);
                tma_load_2d(sA + k * 16384, &tm_xn, k * 64, rb * 128, bar_a + 8 * k);
                if (k < 3) {
                    const uint32_t dst = sB + k * G1_B_STAGE;
                    mbar_expect_tx(bar_full + 8 * k, 16384);
                    tma_load_3d(dst, &tm_wg4, 0, k * 32, cj * 7, bar_full + 8 * k);
                    tma_load_3d(dst + 8192, &tm_wu4, 0, k * 32, cj * 7, bar_full + 8 * k);
                }
            }
            for (int it = 3 + pw; it < G1_ITERS; it += 3) {
                const int s = it % G1_STAGES, kb = it & 15;
                if (it >= G1_STAGES) mbar_wait(bar_empty + 8 * s, ((it / G1_STAGES) - 1) & 1);
                const uint32_t dst = sB + s * G1_B_STAGE;
                if (it < 16) {
                    mbar_expect_tx(bar_full + 8 * s, 16384);
                    tma_load_3d(dst, &tm_wg4, 0, kb * 32, cj * 7, bar_full + 8 * s);
                    tma_load_3d(dst + 8192, &tm_wu4, 0, kb * 32, cj * 7, bar_full + 8 * s);
                } else {
                    mbar_expect_tx(bar_full + 8 * s, 12288);
                    tma_load_3d(dst, &tm_wg3, 0, kb * 32, cj * 7 + 4, bar_full + 8 * s);
                    tma_load_3d(dst + 6144, &tm_wu3, 0, kb * 32, cj * 7 + 4, bar_full + 8 * s);
                }
            }
            const int k0 = kh * G2_KB;
            mbar_wait(bar_g1done, 0);
            fence_async_all();
            for (int it = pw; it < G2_STAGES; it += 3) {
                mbar_expect_tx(bar_full2 + 8 * it, G2_STAGE);
                tma_load_3d(sbase + it * G2_STAGE + 16384, &tm_wd, 0, (k0 + it) * 64, nb * 2, bar_full2 + 8 * it);
            }
            if (pw == 2) {
                mbar_expect_tx(bar_epi, G2_EPI);
                tma_load_2d(sX, &tm_x, col_fin, rb * 128, bar_epi);
            }
            spin_until(&g_h_count[rb], 8);
            fence_async_all();
            if (pw == 0) STAMP(3, 1);
            for (int it = pw; it < G2_STAGES; it += 3)
                tma_load_2d(sbase + it * G2_STAGE, &tm_h, (k0 + it) * 64, rb * 128, bar_full2 + 8 * it);
            if (pw == 2) {
                spin_until(&g_conv_count, gridDim.x);
                fence_async_all();
                tma_load_2d(sS, &tm_sT, rb * 128, col_fin, bar_epi);
                tma_load_2d(sS + 8192, &tm_sT, rb * 128 + 64, col_fin, bar_epi);
            }
            for (int it = G2_STAGES + ((pw + 3 - (G2_STAGES % 3)) % 3); it < G2_KB; it += 3) {
                const int s = it % G2_STAGES;
                mbar_wait(bar_empty2 + 8 * s, ((it / G2_STAGES) - 1) & 1);
                mbar_expect_tx(bar_full2 + 8 * s, G2_STAGE);
                tma_load_2d(sbase + s * G2_STAGE, &tm_h, (k0 + it) * 64, rb * 128, bar_full2 + 8 * s);
                tma_load_3d(sbase + s * G2_STAGE + 16384, &tm_wd, 0, (k0 + it) * 64, nb * 2, bar_full2 + 8 * s);
            }
        }
    } else {
        asm volatile("setmaxnreg.inc.sync.aligned.u32 232;");
        const int wg = __shfl_sync(0xffffffffu, (int)(threadIdx.x >> 7), 0);
        {
        float r[160];
        const int row0 = rb * 128 + wg * 64 + (warp & 3) * 16;
        const uint64_t descA = make_desc(sA + wg * 8192, 16, 1024);
        const uint64_t descB = make_desc(sB, 2048, 512, 2);
        const uint32_t stg = sStg + warp * 1024;
        const uint32_t st_off = (uint32_t)(((lane & 7) + ((lane >> 3) & 1) * 8) * 32 + (lane >> 4) * 16);
        __nv_bfloat16* hrow = g_h + (size_t)(row0 + (lane >> 1)) * F_ + (lane & 1) * 8 + cj * 224;
#pragma unroll
        for (int kb = 0; kb < 16; kb++) {
            const int it = kb, s = it % G1_STAGES;
            if ((kb & 1) == 0) mbar_wait(bar_a + 8 * (kb >> 1), 0);
            mbar_wait(bar_full + 8 * s, (it / G1_STAGES) & 1);
            if (threadIdx.x == 0 && (it & 7) == 0) STAMP(2, 2 + it / 8);
            wgmma_fence();
            const uint64_t da = descA + (uint64_t)(((kb >> 1) * 16384 + (kb & 1) * 64) >> 4);
            const uint64_t db = descB + (uint64_t)((s * G1_B_STAGE) >> 4);
            wgmma_n256_k32(r, da, da + 2, db, db + 64, kb != 0);
            wgmma_commit();
            if (kb > 0) {
                wgmma_wait<1>();
                if (lane == 0) mbar_arrive(bar_empty + 8 * ((it - 1) % G1_STAGES));
            }
        }
        wgmma_wait<0>();
        if (lane == 0) mbar_arrive(bar_empty + 8 * (15 % G1_STAGES));
#pragma unroll
        for (int i = 0; i < 32; i++) r[128 + i] = __uint_as_float(pack_bf16(r[2 * i], r[2 * i + 1]));
#pragma unroll
        for (int i = 31; i >= 0; i--) r[96 + i] = __uint_as_float(pack_bf16(r[64 + 2 * i], r[65 + 2 * i]));
        uint32_t eo[4];
        uint4 pv = make_uint4(0, 0, 0, 0);
#pragma unroll
        for (int kb = 0; kb < 16; kb++) {
            const int it = 16 + kb, s = it % G1_STAGES;
            mbar_wait(bar_full + 8 * s, (it / G1_STAGES) & 1);
            if (threadIdx.x == 0 && (it & 7) == 0) STAMP(2, 2 + it / 8);
            wgmma_fence();
            const uint64_t da = descA + (uint64_t)(((kb >> 1) * 16384 + (kb & 1) * 64) >> 4);
            const uint64_t db = descB + (uint64_t)((s * G1_B_STAGE) >> 4);
            const int jj = kb >> 1;
            wgmma_n192(r, da, db, kb != 0);
            eo[(kb & 1) * 2] = geglu_pair(__float_as_uint(r[128 + 2 * kb]), __float_as_uint(r[96 + 2 * kb]));
            wgmma_n192(r, da + 2, db + 64, 1);
            wgmma_commit();
            eo[(kb & 1) * 2 + 1] = geglu_pair(__float_as_uint(r[129 + 2 * kb]), __float_as_uint(r[97 + 2 * kb]));
            if (kb & 1) {
                if (jj > 0) *reinterpret_cast<uint4*>(hrow + (jj - 1) * 16) = pv;
                stmatrix_x4(stg + (jj & 1) * 512 + st_off, eo[0], eo[1], eo[2], eo[3]);
            } else if (jj > 0) {
                __syncwarp();
                asm volatile("ld.shared.v4.u32 {%0,%1,%2,%3}, [%4];" : "=r"(pv.x), "=r"(pv.y), "=r"(pv.z), "=r"(pv.w)
                             : "r"(stg + ((jj - 1) & 1) * 512 + lane * 16));
            }
            if (kb > 0 && it - 1 + G1_STAGES < G1_ITERS) {
                wgmma_wait<1>();
                if (lane == 0) mbar_arrive(bar_empty + 8 * ((it - 1) % G1_STAGES));
            }
        }
        __syncwarp();
        asm volatile("ld.shared.v4.u32 {%0,%1,%2,%3}, [%4];" : "=r"(pv.x), "=r"(pv.y), "=r"(pv.z), "=r"(pv.w) : "r"(stg + 512 + lane * 16));
        wgmma_wait<0>();
        *reinterpret_cast<uint4*>(hrow + 7 * 16) = pv;
        if (threadIdx.x == 0) STAMP(2, 6);
        {
            uint32_t o[24];
#pragma unroll
            for (int i = 0; i < 24; i++) o[i] = geglu_pair(pack_bf16(r[2 * i], r[2 * i + 1]), pack_bf16(r[48 + 2 * i], r[49 + 2 * i]));
            named_bar(1 + wg, 128);
            const uint32_t fbuf = sA + ((warp & 3) >> 1) * 16384 + wg * 8192 + (warp & 1) * 4096;
#pragma unroll
            for (int jj = 0; jj < 6; jj++) stmatrix_x4(fbuf + jj * 512 + st_off, o[4 * jj], o[4 * jj + 1], o[4 * jj + 2], o[4 * jj + 3]);
            __syncwarp();
            uint4 v[6];
#pragma unroll
            for (int jj = 0; jj < 6; jj++)
                asm volatile("ld.shared.v4.u32 {%0,%1,%2,%3}, [%4];" : "=r"(v[jj].x), "=r"(v[jj].y), "=r"(v[jj].z), "=r"(v[jj].w)
                             : "r"(fbuf + jj * 512 + lane * 16));
#pragma unroll
            for (int jj = 0; jj < 6; jj++) *reinterpret_cast<uint4*>(hrow + 128 + jj * 16) = v[jj];
        }
        }
        fence_async_all();
        __syncwarp();
        if (lane == 0) mbar_arrive(bar_g1done);
        asm volatile("bar.arrive 3, 288;" ::: "memory");
        if (threadIdx.x == 0) STAMP(2, 7);
        {
        const int g = lane >> 2, t = lane & 3;
        float acc[64];
        const uint64_t descA2 = make_desc(sbase + wg * 8192, 16, 1024);
        const uint64_t descB2 = make_desc(sbase + 16384, 8192, 1024);
#pragma unroll
        for (int it = 0; it < G2_KB; it++) {
            const int s = it % G2_STAGES;
            mbar_wait(bar_full2 + 8 * s, (it / G2_STAGES) & 1);
            if (threadIdx.x == 0 && (it == 0 || it == 7)) STAMP(3, 2 + it / 7);
            wgmma_fence();
            {
                const uint64_t da = descA2 + (uint64_t)((s * G2_STAGE) >> 4);
                const uint64_t db = descB2 + (uint64_t)((s * G2_STAGE) >> 4);
                wgmma_n128_k64(acc, da, da + 2, da + 4, da + 6, db, db + 128, db + 256, db + 384, it != 0);
            }
            wgmma_commit();
            if (it > 0 && it - 1 + G2_STAGES < G2_KB) {
                wgmma_wait<1>();
                if (lane == 0) mbar_arrive(bar_empty2 + 8 * ((it - 1) % G2_STAGES));
            }
        }
        const int lr = wg * 64 + (warp & 3) * 16 + g;
        uint32_t xv[16], sv[16];
        mbar_wait(bar_epi, 0);
#pragma unroll
        for (int j = 0; j < 8; j++) {
#pragma unroll
            for (int hh = 0; hh < 2; hh++) {
                const int r = lr + 8 * hh;
                asm volatile("ld.shared.u32 %0, [%1];" : "=r"(xv[2 * j + hh]) : "r"(sX + r * 128 + ((j ^ (r & 7)) << 4) + 4 * t));
                const int c0 = 8 * j + 2 * t;
                const uint32_t sa = sS + (r >> 6) * 8192 + (((r & 63) >> 3) << 4) + (r & 7) * 2;
                uint16_t s0r, s1r;
                asm volatile("ld.shared.u16 %0, [%1];" : "=h"(s0r) : "r"((sa + c0 * 128) ^ ((c0 & 7) << 4)));
                asm volatile("ld.shared.u16 %0, [%1];" : "=h"(s1r) : "r"((sa + (c0 + 1) * 128) ^ (((c0 + 1) & 7) << 4)));
                sv[2 * j + hh] = (uint32_t)s0r | ((uint32_t)s1r << 16);
            }
        }
        wgmma_wait<0>();
        if (threadIdx.x == 0) STAMP(3, 4);
        {
            uint32_t remote, rbar;
            asm volatile("mapa.shared::cluster.u32 %0, %1, %2;" : "=r"(remote) : "r"(sXch + threadIdx.x * 16), "r"(kh ^ 1));
            asm volatile("mapa.shared::cluster.u32 %0, %1, %2;" : "=r"(rbar) : "r"(bar_xch), "r"(kh ^ 1));
            if (kh == 0) {
#pragma unroll
                for (int i = 0; i < 8; i++)
                    asm volatile("st.async.shared::cluster.mbarrier::complete_tx::bytes.v4.f32 [%0], {%1,%2,%3,%4}, [%5];" ::"r"(remote + i * 4096),
                                 "f"(acc[32 + 4 * i]), "f"(acc[33 + 4 * i]), "f"(acc[34 + 4 * i]), "f"(acc[35 + 4 * i]), "r"(rbar) : "memory");
            } else {
#pragma unroll
                for (int i = 0; i < 8; i++)
                    asm volatile("st.async.shared::cluster.mbarrier::complete_tx::bytes.v4.f32 [%0], {%1,%2,%3,%4}, [%5];" ::"r"(remote + i * 4096),
                                 "f"(acc[4 * i]), "f"(acc[1 + 4 * i]), "f"(acc[2 + 4 * i]), "f"(acc[3 + 4 * i]), "r"(rbar) : "memory");
#pragma unroll
                for (int i = 0; i < 32; i++) acc[i] = acc[32 + i];
            }
        }
        if (threadIdx.x == 0) STAMP(3, 6);
        mbar_wait(bar_xch, 0);
        if (threadIdx.x == 0) STAMP(3, 7);
#pragma unroll
        for (int j = 0; j < 8; j++) {
            float4 o;
            asm volatile("ld.shared.v4.f32 {%0,%1,%2,%3}, [%4];" : "=f"(o.x), "=f"(o.y), "=f"(o.z), "=f"(o.w) : "r"(sXch + threadIdx.x * 16 + j * 4096));
            acc[4 * j] += o.x; acc[4 * j + 1] += o.y; acc[4 * j + 2] += o.z; acc[4 * j + 3] += o.w;
        }
#pragma unroll
        for (int i = 0; i < 16; i++) {
            float f0 = bf16_round(acc[2 * i]), f1 = bf16_round(acc[2 * i + 1]);
            float g0 = bf16_round(__fdividef(f0, 1.0f + __expf(-f0)));
            float g1 = bf16_round(__fdividef(f1, 1.0f + __expf(-f1)));
            float o0 = bf_lo(xv[i]) + bf16_round(bf_lo(sv[i]) * g0);
            float o1 = bf_hi(xv[i]) + bf16_round(bf_hi(sv[i]) * g1);
            xv[i] = pack_bf16(o0, o1);
        }
#pragma unroll
        for (int j = 0; j < 8; j++) {
#pragma unroll
            for (int hh = 0; hh < 2; hh++) {
                const int r = lr + 8 * hh;
                asm volatile("st.shared.u32 [%0], %1;" ::"r"(sX + r * 128 + ((j ^ (r & 7)) << 4) + 4 * t), "r"(xv[2 * j + hh]) : "memory");
            }
        }
        if (threadIdx.x == 0) STAMP(3, 9);
        fence_async_smem();
        __syncwarp();
        if (lane == 0) {
            tma_store_2d(&tm_out, sX + (wg * 64 + (warp & 3) * 16) * 128, col_fin, rb * 128 + wg * 64 + (warp & 3) * 16);
            bulk_commit();
            bulk_wait_read<0>();
        }
        }
        if (threadIdx.x == 0) STAMP(3, 5);
        named_bar(4, 256);
        if (threadIdx.x == 0) {
            const unsigned int old = atomicAdd(&g_done_count, 1u);
            if (old == gridDim.x - 1) {
                g_ln_count = 0; g_conv_count = 0; g_done_count = 0;
                for (int i = 0; i < 16; i++) g_h_count[i] = 0;
            }
        }
    }
}

typedef CUresult (*EncodeFn)(CUtensorMap*, CUtensorMapDataType, cuuint32_t, void*, const cuuint64_t*, const cuuint64_t*,
                             const cuuint32_t*, const cuuint32_t*, CUtensorMapInterleave, CUtensorMapSwizzle,
                             CUtensorMapL2promotion, CUtensorMapFloatOOBfill);

void make_map(EncodeFn fn, CUtensorMap* m, const void* ptr, uint64_t inner, uint64_t outer, uint32_t box_in, uint32_t box_out,
              CUtensorMapSwizzle swz = CU_TENSOR_MAP_SWIZZLE_128B) {
    cuuint64_t dims[2] = {inner, outer};
    cuuint64_t strides[1] = {inner * 2};
    cuuint32_t box[2] = {box_in, box_out};
    cuuint32_t es[2] = {1, 1};
    fn(m, CU_TENSOR_MAP_DATA_TYPE_BFLOAT16, 2, const_cast<void*>(ptr), dims, strides, box, es, CU_TENSOR_MAP_INTERLEAVE_NONE,
       swz, CU_TENSOR_MAP_L2_PROMOTION_L2_256B, CU_TENSOR_MAP_FLOAT_OOB_FILL_NONE);
}
void make_map3(EncodeFn fn, CUtensorMap* m, const void* ptr, uint64_t cols, uint64_t rows, uint32_t atom, uint32_t box_rows,
               uint32_t box_atoms, CUtensorMapSwizzle swz) {
    cuuint64_t dims[3] = {atom, rows, cols / atom};
    cuuint64_t strides[2] = {cols * 2, (cuuint64_t)atom * 2};
    cuuint32_t box[3] = {atom, box_rows, box_atoms};
    cuuint32_t es[3] = {1, 1, 1};
    fn(m, CU_TENSOR_MAP_DATA_TYPE_BFLOAT16, 3, const_cast<void*>(ptr), dims, strides, box, es, CU_TENSOR_MAP_INTERLEAVE_NONE,
       swz, CU_TENSOR_MAP_L2_PROMOTION_L2_256B, CU_TENSOR_MAP_FLOAT_OOB_FILL_NONE);
}

template <typename... Args>
void launch_pdl(void (*kern)(Args...), int grid, int block, int smem, bool pdl, int cluster, Args... args) {
    cudaLaunchConfig_t cfg = {};
    cfg.gridDim = dim3(grid); cfg.blockDim = dim3(block); cfg.dynamicSmemBytes = smem; cfg.stream = cudaStreamPerThread;
    cudaLaunchAttribute at[2];
    int n = 0;
    if (pdl) {
        at[n].id = cudaLaunchAttributeProgrammaticStreamSerialization;
        at[n].val.programmaticStreamSerializationAllowed = 1;
        n++;
    }
    if (cluster > 1) {
        at[n].id = cudaLaunchAttributeClusterDimension;
        at[n].val.clusterDim.x = cluster; at[n].val.clusterDim.y = 1; at[n].val.clusterDim.z = 1;
        n++;
    }
    cfg.attrs = at; cfg.numAttrs = n;
    cudaLaunchKernelEx(&cfg, kern, args...);
}

}

extern "C" void kernel_launch(void* const* d_in, const int* in_sizes, int n_in, void* d_out, int out_size) {
    const __nv_bfloat16* x = (const __nv_bfloat16*)d_in[0];
    const __nv_bfloat16* A_re = (const __nv_bfloat16*)d_in[1];
    const __nv_bfloat16* A_im = (const __nv_bfloat16*)d_in[2];
    const __nv_bfloat16* B_re = (const __nv_bfloat16*)d_in[3];
    const __nv_bfloat16* B_im = (const __nv_bfloat16*)d_in[4];
    const __nv_bfloat16* C_re = (const __nv_bfloat16*)d_in[5];
    const __nv_bfloat16* C_im = (const __nv_bfloat16*)d_in[6];
    const __nv_bfloat16* log_dt = (const __nv_bfloat16*)d_in[7];
    const __nv_bfloat16* Dskip = (const __nv_bfloat16*)d_in[8];
    const __nv_bfloat16* wg = (const __nv_bfloat16*)d_in[10];
    const __nv_bfloat16* wu = (const __nv_bfloat16*)d_in[11];
    const __nv_bfloat16* wd = (const __nv_bfloat16*)d_in[12];
    __nv_bfloat16* out = (__nv_bfloat16*)d_out;

    static bool init = false;
    static CUtensorMap tm_xn, tm_wg4, tm_wu4, tm_wg3, tm_wu3, tm_hst, tm_hst96, tm_h, tm_wd, tm_x, tm_sT, tm_out;
    static const void* last_ptrs[5] = {nullptr, nullptr, nullptr, nullptr, nullptr};
    if (!init || last_ptrs[0] != wg || last_ptrs[1] != wu || last_ptrs[2] != wd || last_ptrs[3] != x || last_ptrs[4] != out) {
        void* fnp = nullptr;
        cudaDriverEntryPointQueryResult qres;
        cudaGetDriverEntryPoint("cuTensorMapEncodeTiled", &fnp, cudaEnableDefault, &qres);
        EncodeFn fn = (EncodeFn)fnp;
        void *p_xn, *p_h, *p_sT;
        cudaGetSymbolAddress(&p_xn, g_xn);
        cudaGetSymbolAddress(&p_h, g_h);
        cudaGetSymbolAddress(&p_sT, g_sT);
        make_map(fn, &tm_xn, p_xn, D_, L_, 64, 128);
        make_map3(fn, &tm_wg4, wg, F_, D_, 32, 32, 4, CU_TENSOR_MAP_SWIZZLE_64B);
        make_map3(fn, &tm_wu4, wu, F_, D_, 32, 32, 4, CU_TENSOR_MAP_SWIZZLE_64B);
        make_map3(fn, &tm_wg3, wg, F_, D_, 32, 32, 3, CU_TENSOR_MAP_SWIZZLE_64B);
        make_map3(fn, &tm_wu3, wu, F_, D_, 32, 32, 3, CU_TENSOR_MAP_SWIZZLE_64B);
        make_map(fn, &tm_hst, p_h, F_, L_, 16, 16, CU_TENSOR_MAP_SWIZZLE_NONE);
        make_map(fn, &tm_hst96, p_h, F_, L_, 96, 16, CU_TENSOR_MAP_SWIZZLE_NONE);
        make_map(fn, &tm_h, p_h, F_, L_, 64, 128);
        make_map3(fn, &tm_wd, wd, D_, F_, 64, 64, 2, CU_TENSOR_MAP_SWIZZLE_128B);
        make_map(fn, &tm_x, x, D_, L_, 64, 128);
        make_map(fn, &tm_sT, p_sT, L_, D_, 64, 64);
        make_map(fn, &tm_out, out, D_, L_, 64, 16);
        cudaFuncSetAttribute(mega_kernel, cudaFuncAttributeMaxDynamicSharedMemorySize, MG_SMEM);
        last_ptrs[0] = wg; last_ptrs[1] = wu; last_ptrs[2] = wd; last_ptrs[3] = x; last_ptrs[4] = out;
        init = true;
    }
    MegaParams P = {x, A_re, A_im, B_re, B_im, C_re, C_im, log_dt, Dskip, wg, wu, wd};
    launch_pdl(mega_kernel, 128, 384, MG_SMEM, false, 2, P, tm_xn, tm_wg4, tm_wu4, tm_wg3, tm_wu3, tm_h, tm_wd, tm_x, tm_sT, tm_out);
}
```

```cpp
#include <cuda_runtime.h>
#include <cuda_bf16.h>
#include <cuda.h>
#include <stdint.h>

namespace {

constexpr int L_ = 2048, D_ = 512, NS_ = 128, F_ = 1792;

__device__ __align__(1024) __nv_bfloat16 g_xn[L_ * D_];
__device__ __align__(1024) __nv_bfloat16 g_xnT[D_ * L_];
__device__ __align__(1024) __nv_bfloat16 g_sT[D_ * L_];
__device__ __align__(1024) __nv_bfloat16 g_h[L_ * F_];
__device__ unsigned int g_ln_count, g_conv_count, g_done_count, g_h_count[32];

#define STAMP(k, i)

__device__ __forceinline__ uint32_t smem_u32(const void* p) { return (uint32_t)__cvta_generic_to_shared(p); }
__device__ __forceinline__ void pdl_wait() { asm volatile("griddepcontrol.wait;" ::: "memory"); }
__device__ __forceinline__ void pdl_launch() { asm volatile("griddepcontrol.launch_dependents;" ::: "memory"); }

__device__ __forceinline__ void mbar_init(uint32_t bar, uint32_t cnt) {
    asm volatile("mbarrier.init.shared::cta.b64 [%0], %1;" ::"r"(bar), "r"(cnt) : "memory");
}
__device__ __forceinline__ void mbar_expect_tx(uint32_t bar, uint32_t bytes) {
    asm volatile("mbarrier.arrive.expect_tx.shared::cta.b64 _, [%0], %1;" ::"r"(bar), "r"(bytes) : "memory");
}
__device__ __forceinline__ void mbar_arrive(uint32_t bar) {
    asm volatile("mbarrier.arrive.shared::cta.b64 _, [%0];" ::"r"(bar) : "memory");
}
__device__ __forceinline__ void mbar_wait(uint32_t bar, uint32_t parity) {
    asm volatile(
        "{\n.reg .pred p;\n"
        "WAIT_LOOP:\n"
        "mbarrier.try_wait.parity.shared::cta.b64 p, [%0], %1;\n"
        "@p bra WAIT_DONE;\n"
        "bra WAIT_LOOP;\n"
        "WAIT_DONE:\n}\n" ::"r"(bar), "r"(parity) : "memory");
}
__device__ __forceinline__ void tma_load_2d(uint32_t dst, const CUtensorMap* tm, int c0, int c1, uint32_t bar) {
    asm volatile(
        "cp.async.bulk.tensor.2d.shared::cluster.global.mbarrier::complete_tx::bytes [%0], [%1, {%3, %4}], [%2];"
        ::"r"(dst), "l"((uint64_t)tm), "r"(bar), "r"(c0), "r"(c1) : "memory");
}
__device__ __forceinline__ void prefetch_tmap(const CUtensorMap* tm) {
    asm volatile("prefetch.tensormap [%0];" ::"l"((uint64_t)tm) : "memory");
}
__device__ __forceinline__ uint64_t make_desc(uint32_t addr, uint32_t lbo, uint32_t sbo, uint64_t mode = 1) {
    uint64_t d = 0;
    d |= (uint64_t)((addr & 0x3FFFF) >> 4);
    d |= (uint64_t)((lbo >> 4) & 0x3FFF) << 16;
    d |= (uint64_t)((sbo >> 4) & 0x3FFF) << 32;
    d |= mode << 62;
    return d;
}
__device__ __forceinline__ void wgmma_fence() { asm volatile("wgmma.fence.sync.aligned;" ::: "memory"); }
__device__ __forceinline__ void wgmma_commit() { asm volatile("wgmma.commit_group.sync.aligned;" ::: "memory"); }
template <int N> __device__ __forceinline__ void wgmma_wait() {
    asm volatile("wgmma.wait_group.sync.aligned %0;" ::"n"(N) : "memory");
}

#define R8(a, i) "+f"(a[i + 0]), "+f"(a[i + 1]), "+f"(a[i + 2]), "+f"(a[i + 3]), "+f"(a[i + 4]), "+f"(a[i + 5]), "+f"(a[i + 6]), "+f"(a[i + 7])

__device__ __forceinline__ void wgmma_n256_k32(float* a, uint64_t da0, uint64_t da1, uint64_t db0, uint64_t db1, int scale_d) {
    asm volatile(
        "{\n.reg .pred p;\nsetp.ne.b32 p, %132, 0;\n"
        "wgmma.mma_async.sync.aligned.m64n256k16.f32.bf16.bf16 {%0,%1,%2,%3,%4,%5,%6,%7,%8,%9,%10,%11,%12,%13,%14,%15,%16,%17,%18,%19,%20,%21,%22,%23,%24,%25,%26,%27,%28,%29,%30,%31,%32,%33,%34,%35,%36,%37,%38,%39,%40,%41,%42,%43,%44,%45,%46,%47,%48,%49,%50,%51,%52,%53,%54,%55,%56,%57,%58,%59,%60,%61,%62,%63,%64,%65,%66,%67,%68,%69,%70,%71,%72,%73,%74,%75,%76,%77,%78,%79,%80,%81,%82,%83,%84,%85,%86,%87,%88,%89,%90,%91,%92,%93,%94,%95,%96,%97,%98,%99,%100,%101,%102,%103,%104,%105,%106,%107,%108,%109,%110,%111,%112,%113,%114,%115,%116,%117,%118,%119,%120,%121,%122,%123,%124,%125,%126,%127}, %128, %130, p, 1, 1, 0, 1;\n"
        "wgmma.mma_async.sync.aligned.m64n256k16.f32.bf16.bf16 {%0,%1,%2,%3,%4,%5,%6,%7,%8,%9,%10,%11,%12,%13,%14,%15,%16,%17,%18,%19,%20,%21,%22,%23,%24,%25,%26,%27,%28,%29,%30,%31,%32,%33,%34,%35,%36,%37,%38,%39,%40,%41,%42,%43,%44,%45,%46,%47,%48,%49,%50,%51,%52,%53,%54,%55,%56,%57,%58,%59,%60,%61,%62,%63,%64,%65,%66,%67,%68,%69,%70,%71,%72,%73,%74,%75,%76,%77,%78,%79,%80,%81,%82,%83,%84,%85,%86,%87,%88,%89,%90,%91,%92,%93,%94,%95,%96,%97,%98,%99,%100,%101,%102,%103,%104,%105,%106,%107,%108,%109,%110,%111,%112,%113,%114,%115,%116,%117,%118,%119,%120,%121,%122,%123,%124,%125,%126,%127}, %129, %131, 1, 1, 1, 0, 1;\n"
        "}\n"
        : R8(a, 0), R8(a, 8), R8(a, 16), R8(a, 24), R8(a, 32), R8(a, 40), R8(a, 48), R8(a, 56), R8(a, 64), R8(a, 72), R8(a, 80), R8(a, 88), R8(a, 96), R8(a, 104), R8(a, 112), R8(a, 120)
        : "l"(da0), "l"(da1), "l"(db0), "l"(db1), "r"(scale_d));
}
__device__ __forceinline__ void wgmma_n192_k32(float* a, uint64_t da0, uint64_t da1, uint64_t db0, uint64_t db1, int scale_d) {
    asm volatile(
        "{\n.reg .pred p;\nsetp.ne.b32 p, %100, 0;\n"
        "wgmma.mma_async.sync.aligned.m64n192k16.f32.bf16.bf16 {%0,%1,%2,%3,%4,%5,%6,%7,%8,%9,%10,%11,%12,%13,%14,%15,%16,%17,%18,%19,%20,%21,%22,%23,%24,%25,%26,%27,%28,%29,%30,%31,%32,%33,%34,%35,%36,%37,%38,%39,%40,%41,%42,%43,%44,%45,%46,%47,%48,%49,%50,%51,%52,%53,%54,%55,%56,%57,%58,%59,%60,%61,%62,%63,%64,%65,%66,%67,%68,%69,%70,%71,%72,%73,%74,%75,%76,%77,%78,%79,%80,%81,%82,%83,%84,%85,%86,%87,%88,%89,%90,%91,%92,%93,%94,%95}, %96, %98, p, 1, 1, 0, 1;\n"
        "wgmma.mma_async.sync.aligned.m64n192k16.f32.bf16.bf16 {%0,%1,%2,%3,%4,%5,%6,%7,%8,%9,%10,%11,%12,%13,%14,%15,%16,%17,%18,%19,%20,%21,%22,%23,%24,%25,%26,%27,%28,%29,%30,%31,%32,%33,%34,%35,%36,%37,%38,%39,%40,%41,%42,%43,%44,%45,%46,%47,%48,%49,%50,%51,%52,%53,%54,%55,%56,%57,%58,%59,%60,%61,%62,%63,%64,%65,%66,%67,%68,%69,%70,%71,%72,%73,%74,%75,%76,%77,%78,%79,%80,%81,%82,%83,%84,%85,%86,%87,%88,%89,%90,%91,%92,%93,%94,%95}, %97, %99, 1, 1, 1, 0, 1;\n"
        "}\n"
        : R8(a, 0), R8(a, 8), R8(a, 16), R8(a, 24), R8(a, 32), R8(a, 40), R8(a, 48), R8(a, 56), R8(a, 64), R8(a, 72), R8(a, 80), R8(a, 88)
        : "l"(da0), "l"(da1), "l"(db0), "l"(db1), "r"(scale_d));
}
__device__ __forceinline__ void wgmma_n192(float* a, uint64_t da0, uint64_t db0, int scale_d) {
    asm volatile(
        "{\n.reg .pred p;\nsetp.ne.b32 p, %98, 0;\n"
        "wgmma.mma_async.sync.aligned.m64n192k16.f32.bf16.bf16 {%0,%1,%2,%3,%4,%5,%6,%7,%8,%9,%10,%11,%12,%13,%14,%15,%16,%17,%18,%19,%20,%21,%22,%23,%24,%25,%26,%27,%28,%29,%30,%31,%32,%33,%34,%35,%36,%37,%38,%39,%40,%41,%42,%43,%44,%45,%46,%47,%48,%49,%50,%51,%52,%53,%54,%55,%56,%57,%58,%59,%60,%61,%62,%63,%64,%65,%66,%67,%68,%69,%70,%71,%72,%73,%74,%75,%76,%77,%78,%79,%80,%81,%82,%83,%84,%85,%86,%87,%88,%89,%90,%91,%92,%93,%94,%95}, %96, %97, p, 1, 1, 0, 1;\n"
        "}\n"
        : R8(a, 0), R8(a, 8), R8(a, 16), R8(a, 24), R8(a, 32), R8(a, 40), R8(a, 48), R8(a, 56), R8(a, 64), R8(a, 72), R8(a, 80), R8(a, 88)
        : "l"(da0), "l"(db0), "r"(scale_d));
}
__device__ __forceinline__ void wgmma_n128_k64(float* a, uint64_t da0, uint64_t da1, uint64_t da2, uint64_t da3,
                                               uint64_t db0, uint64_t db1, uint64_t db2, uint64_t db3, int scale_d) {
    asm volatile(
        "{\n.reg .pred p;\nsetp.ne.b32 p, %72, 0;\n"
        "wgmma.mma_async.sync.aligned.m64n128k16.f32.bf16.bf16 {%0,%1,%2,%3,%4,%5,%6,%7,%8,%9,%10,%11,%12,%13,%14,%15,%16,%17,%18,%19,%20,%21,%22,%23,%24,%25,%26,%27,%28,%29,%30,%31,%32,%33,%34,%35,%36,%37,%38,%39,%40,%41,%42,%43,%44,%45,%46,%47,%48,%49,%50,%51,%52,%53,%54,%55,%56,%57,%58,%59,%60,%61,%62,%63}, %64, %68, p, 1, 1, 0, 1;\n"
        "wgmma.mma_async.sync.aligned.m64n128k16.f32.bf16.bf16 {%0,%1,%2,%3,%4,%5,%6,%7,%8,%9,%10,%11,%12,%13,%14,%15,%16,%17,%18,%19,%20,%21,%22,%23,%24,%25,%26,%27,%28,%29,%30,%31,%32,%33,%34,%35,%36,%37,%38,%39,%40,%41,%42,%43,%44,%45,%46,%47,%48,%49,%50,%51,%52,%53,%54,%55,%56,%57,%58,%59,%60,%61,%62,%63}, %65, %69, 1, 1, 1, 0, 1;\n"
        "wgmma.mma_async.sync.aligned.m64n128k16.f32.bf16.bf16 {%0,%1,%2,%3,%4,%5,%6,%7,%8,%9,%10,%11,%12,%13,%14,%15,%16,%17,%18,%19,%20,%21,%22,%23,%24,%25,%26,%27,%28,%29,%30,%31,%32,%33,%34,%35,%36,%37,%38,%39,%40,%41,%42,%43,%44,%45,%46,%47,%48,%49,%50,%51,%52,%53,%54,%55,%56,%57,%58,%59,%60,%61,%62,%63}, %66, %70, 1, 1, 1, 0, 1;\n"
        "wgmma.mma_async.sync.aligned.m64n128k16.f32.bf16.bf16 {%0,%1,%2,%3,%4,%5,%6,%7,%8,%9,%10,%11,%12,%13,%14,%15,%16,%17,%18,%19,%20,%21,%22,%23,%24,%25,%26,%27,%28,%29,%30,%31,%32,%33,%34,%35,%36,%37,%38,%39,%40,%41,%42,%43,%44,%45,%46,%47,%48,%49,%50,%51,%52,%53,%54,%55,%56,%57,%58,%59,%60,%61,%62,%63}, %67, %71, 1, 1, 1, 0, 1;\n"
        "}\n"
        : R8(a, 0), R8(a, 8), R8(a, 16), R8(a, 24), R8(a, 32), R8(a, 40), R8(a, 48), R8(a, 56)
        : "l"(da0), "l"(da1), "l"(da2), "l"(da3), "l"(db0), "l"(db1), "l"(db2), "l"(db3), "r"(scale_d));
}

__device__ __forceinline__ float bf16_round(float x) {
    uint32_t p; asm("cvt.rn.bf16x2.f32 %0, %1, %2;" : "=r"(p) : "f"(x), "f"(0.0f));
    return __uint_as_float(p);
}
__device__ __forceinline__ uint32_t pack_bf16(float lo, float hi) {
    __nv_bfloat162 v = __floats2bfloat162_rn(lo, hi);
    return *reinterpret_cast<uint32_t*>(&v);
}
__device__ __forceinline__ float bf_lo(uint32_t v) { return __uint_as_float(v << 16); }
__device__ __forceinline__ float bf_hi(uint32_t v) { return __uint_as_float(v & 0xFFFF0000u); }

struct cplx { float r, i; };
__device__ __forceinline__ cplx cmul(cplx a, cplx b) {
    cplx c; c.r = a.r * b.r - a.i * b.i; c.i = a.r * b.i + a.i * b.r; return c;
}
__device__ __forceinline__ cplx csq(cplx a) {
    cplx c; c.r = a.r * a.r - a.i * a.i; c.i = 2.0f * a.r * a.i; return c;
}
__device__ __forceinline__ cplx cexp_m(float ar2, float ai2, float m) {
    float mag;
    asm("ex2.approx.ftz.f32 %0, %1;" : "=f"(mag) : "f"(ar2 * m));
    float rr = ai2 * m;
    rr -= (rr + 12582912.0f) - 12582912.0f;
    float th = rr * 6.283185307179586f;
    cplx c; c.r = mag * __cosf(th); c.i = mag * __sinf(th);
    return c;
}
__device__ __forceinline__ uint32_t to_tf32(float x) { return __float_as_uint(x) + 0x1000u; }
__device__ __forceinline__ void mma_tf32(float* c, uint32_t a0, uint32_t a1, uint32_t a2, uint32_t a3, uint32_t b0, uint32_t b1) {
    asm volatile("mma.sync.aligned.m16n8k8.row.col.f32.tf32.tf32.f32 {%0,%1,%2,%3}, {%4,%5,%6,%7}, {%8,%9}, {%0,%1,%2,%3};"
                 : "+f"(c[0]), "+f"(c[1]), "+f"(c[2]), "+f"(c[3])
                 : "r"(a0), "r"(a1), "r"(a2), "r"(a3), "r"(b0), "r"(b1));
}
__device__ __forceinline__ void mma_bf16(float* c, uint32_t a0, uint32_t a1, uint32_t a2, uint32_t a3, uint32_t b0, uint32_t b1) {
    asm volatile("mma.sync.aligned.m16n8k16.row.col.f32.bf16.bf16.f32 {%0,%1,%2,%3}, {%4,%5,%6,%7}, {%8,%9}, {%0,%1,%2,%3};"
                 : "+f"(c[0]), "+f"(c[1]), "+f"(c[2]), "+f"(c[3])
                 : "r"(a0), "r"(a1), "r"(a2), "r"(a3), "r"(b0), "r"(b1));
}
__device__ __forceinline__ void named_bar(int id, int n) { asm volatile("bar.sync %0, %1;" ::"r"(id), "r"(n) : "memory"); }
__device__ __forceinline__ void ldsm_x4(uint32_t addr, uint32_t& r0, uint32_t& r1, uint32_t& r2, uint32_t& r3) {
    asm volatile("ldmatrix.sync.aligned.m8n8.x4.shared.b16 {%0,%1,%2,%3}, [%4];" : "=r"(r0), "=r"(r1), "=r"(r2), "=r"(r3) : "r"(addr));
}
__device__ __forceinline__ void ldsm_x4_t(uint32_t addr, uint32_t& r0, uint32_t& r1, uint32_t& r2, uint32_t& r3) {
    asm volatile("ldmatrix.sync.aligned.m8n8.x4.trans.shared.b16 {%0,%1,%2,%3}, [%4];" : "=r"(r0), "=r"(r1), "=r"(r2), "=r"(r3) : "r"(addr));
}

constexpr int CV_CH = 4;
constexpr int CV_O_CONST = 0;
constexpr int CV_O_KP = 12288;
constexpr int CV_O_Q = CV_O_KP + 10368;
constexpr int CV_O_Q2 = CV_O_Q + 2304;
constexpr int CV_O_Q3 = CV_O_Q2 + 1024;
constexpr int CV_O_Q4X = CV_O_Q3 + 768;
constexpr int CV_O_W3 = CV_O_Q4X + 256;
constexpr int CV_O_W5 = CV_O_W3 + 3104;
constexpr int CV_O_W7 = CV_O_W5 + 3104;
constexpr int CV_O_W9 = CV_O_W7 + 2048;
constexpr int CV_O_STG = 32768;
constexpr int CV_O_U = CV_O_W9 + 2048;
constexpr int CV_PER_CH = CV_O_U + 4352;
static_assert(CV_O_U >= CV_O_STG + 4096, "staging overlaps u");
constexpr int CV_SMEM = CV_CH * CV_PER_CH;

constexpr int LN_ROWS = 16;

__device__ __forceinline__ void front_phase(uint8_t* smem, const __nv_bfloat16* __restrict__ x,
                                            const __nv_bfloat16* __restrict__ A_re, const __nv_bfloat16* __restrict__ A_im,
                                            const __nv_bfloat16* __restrict__ B_re, const __nv_bfloat16* __restrict__ B_im,
                                            const __nv_bfloat16* __restrict__ C_re, const __nv_bfloat16* __restrict__ C_im,
                                            const __nv_bfloat16* __restrict__ log_dt, const __nv_bfloat16* __restrict__ Dskip,
                                            const __nv_bfloat16* __restrict__ wg, const __nv_bfloat16* __restrict__ wu,
                                            const __nv_bfloat16* __restrict__ wd) {
    const int warp = threadIdx.x >> 5, lane = threadIdx.x & 31;
    const int ch = warp / 3, w = warp - 3 * ch, tc = threadIdx.x - 96 * ch;
    const int d = blockIdx.x * CV_CH + ch;
    const int g = lane >> 2, t = lane & 3;
    uint8_t* base = smem + ch * CV_PER_CH;
    float4* s_const = reinterpret_cast<float4*>(base + CV_O_CONST);
    float* s_kp = reinterpret_cast<float*>(base + CV_O_KP);
    uint32_t* s_q = reinterpret_cast<uint32_t*>(base + CV_O_Q);
    uint32_t* s_q2 = reinterpret_cast<uint32_t*>(base + CV_O_Q2);
    uint32_t* s_q3 = reinterpret_cast<uint32_t*>(base + CV_O_Q3);
    uint32_t* s_q4 = reinterpret_cast<uint32_t*>(base + CV_O_Q4X);
    __nv_bfloat16* s_u = reinterpret_cast<__nv_bfloat16*>(base + CV_O_U);
    const int bar_id = 5 + ch;
    const __nv_bfloat16 p_dsk = Dskip[d];
    __nv_bfloat16 (*tile)[D_ + 8] = reinterpret_cast<__nv_bfloat16 (*)[D_ + 8]>(smem + CV_SMEM);

    if (warp < 8) {
        const int row = blockIdx.x * LN_ROWS + warp * 2;
        uint4 xv[2][2];
#pragma unroll
        for (int r = 0; r < 2; r++) {
            xv[r][0] = *reinterpret_cast<const uint4*>(x + (size_t)(row + r) * D_ + lane * 8);
            xv[r][1] = *reinterpret_cast<const uint4*>(x + (size_t)(row + r) * D_ + 256 + lane * 8);
        }
        float f[2][16], sm[2], q[2];
#pragma unroll
        for (int r = 0; r < 2; r++) {
            const uint32_t wv[8] = {xv[r][0].x, xv[r][0].y, xv[r][0].z, xv[r][0].w, xv[r][1].x, xv[r][1].y, xv[r][1].z, xv[r][1].w};
#pragma unroll
            for (int i = 0; i < 8; i++) { f[r][2 * i] = bf_lo(wv[i]); f[r][2 * i + 1] = bf_hi(wv[i]); }
            sm[r] = 0.f;
#pragma unroll
            for (int i = 0; i < 16; i++) sm[r] += f[r][i];
        }
#pragma unroll
        for (int o = 16; o > 0; o >>= 1) { sm[0] += __shfl_xor_sync(0xffffffffu, sm[0], o); sm[1] += __shfl_xor_sync(0xffffffffu, sm[1], o); }
#pragma unroll
        for (int r = 0; r < 2; r++) {
            sm[r] *= (1.0f / D_);
            q[r] = 0.f;
#pragma unroll
            for (int i = 0; i < 16; i++) { float dd = f[r][i] - sm[r]; q[r] += dd * dd; }
        }
#pragma unroll
        for (int o = 16; o > 0; o >>= 1) { q[0] += __shfl_xor_sync(0xffffffffu, q[0], o); q[1] += __shfl_xor_sync(0xffffffffu, q[1], o); }
#pragma unroll
        for (int r = 0; r < 2; r++) {
            const float mb = bf16_round(sm[r]);
            const float vb = bf16_round(q[r] * (1.0f / D_));
            const float den = bf16_round(sqrtf(bf16_round(vb + 1e-5f)));
            uint32_t o[8];
#pragma unroll
            for (int i = 0; i < 8; i++) {
                float a = __fdiv_rn(bf16_round(f[r][2 * i] - mb), den);
                float b = __fdiv_rn(bf16_round(f[r][2 * i + 1] - mb), den);
                o[i] = pack_bf16(a, b);
            }
            __nv_bfloat16* dst = g_xn + (size_t)(row + r) * D_;
            *reinterpret_cast<uint4*>(dst + lane * 8) = make_uint4(o[0], o[1], o[2], o[3]);
            *reinterpret_cast<uint4*>(dst + 256 + lane * 8) = make_uint4(o[4], o[5], o[6], o[7]);
            *reinterpret_cast<uint4*>(&tile[warp * 2 + r][lane * 8]) = make_uint4(o[0], o[1], o[2], o[3]);
            *reinterpret_cast<uint4*>(&tile[warp * 2 + r][256 + lane * 8]) = make_uint4(o[4], o[5], o[6], o[7]);
        }
    } else {
        const int cc_ = warp - 8, dd = blockIdx.x * CV_CH + cc_;
        float4* sc = reinterpret_cast<float4*>(smem + cc_ * CV_PER_CH + CV_O_CONST);
        __nv_bfloat16 pr[4][6];
#pragma unroll
        for (int j = 0; j < 4; j++) {
            const size_t off = (size_t)dd * NS_ + lane + 32 * j;
            pr[j][0] = A_re[off]; pr[j][1] = A_im[off]; pr[j][2] = B_re[off]; pr[j][3] = B_im[off]; pr[j][4] = C_re[off]; pr[j][5] = C_im[off];
        }
        const float dt = bf16_round(expf(__bfloat162float(log_dt[dd])));
        float tail = 0.f;
#pragma unroll
        for (int j = 0; j < 4; j++) {
            const float ar = dt * __bfloat162float(pr[j][0]), ai = dt * __bfloat162float(pr[j][1]);
            const cplx db = {dt * __bfloat162float(pr[j][2]), dt * __bfloat162float(pr[j][3])};
            const cplx cc = {__bfloat162float(pr[j][4]), __bfloat162float(pr[j][5])};
            const cplx cb = cmul(cc, db);
            const float ar2 = ar * 1.4426950408889634f, ai2 = ai * 0.15915494309189535f;
            const cplx e8 = cexp_m(ar2, ai2, 8.f), e128 = cexp_m(ar2, ai2, 128.f);
            const cplx cb8 = cmul(cb, e8);
            const cplx e256 = cexp_m(ar2, ai2, 256.f), e512 = cexp_m(ar2, ai2, 512.f), e1024 = cexp_m(ar2, ai2, 1024.f);
            const cplx c256 = cmul(cb, e256), c512 = cmul(cb, e512), c1024 = cmul(cb, e1024);
            const cplx c768 = cmul(c512, e256), c1280 = cmul(c1024, e256), c1536 = cmul(c1024, e512);
            const cplx c1792 = cmul(c1536, e256);
            tail += cmul(c1024, e1024).r;
            float4* c = sc + (lane + 32 * j) * 6;
            c[0] = make_float4(ar2, ai2, cb.r, cb.i);
            c[1] = make_float4(e128.r, e128.i, cb8.r, cb8.i);
            c[2] = make_float4(c256.r, c256.i, e8.r, e8.i);
            c[3] = make_float4(c512.r, c512.i, c768.r, c768.i);
            c[4] = make_float4(c1024.r, c1024.i, c1280.r, c1280.i);
            c[5] = make_float4(c1536.r, c1536.i, c1792.r, c1792.i);
        }
#pragma unroll
        for (int o = 16; o > 0; o >>= 1) tail += __shfl_xor_sync(0xffffffffu, tail, o);
        if (lane == 0) {
            float* kp = reinterpret_cast<float*>(smem + cc_ * CV_PER_CH + CV_O_KP);
            kp[640] = tail; kp[648 + 640] = 0.f; kp[1296 + 640] = 0.f;
        }
    }
    __syncthreads();
    if (threadIdx.x == 0) STAMP(0, 3);
#pragma unroll
    for (int rep = 0; rep < 2; rep++) {
        const int c = threadIdx.x + 384 * rep;
        if (c < D_) {
            uint32_t ot[8];
#pragma unroll
            for (int i = 0; i < 8; i++) {
                uint32_t lo = *reinterpret_cast<const uint16_t*>(&tile[2 * i][c]);
                uint32_t hi = *reinterpret_cast<const uint16_t*>(&tile[2 * i + 1][c]);
                ot[i] = lo | (hi << 16);
            }
            __nv_bfloat16* dT = g_xnT + (size_t)c * L_ + blockIdx.x * LN_ROWS;
            *reinterpret_cast<uint4*>(dT) = make_uint4(ot[0], ot[1], ot[2], ot[3]);
            *reinterpret_cast<uint4*>(dT + 8) = make_uint4(ot[4], ot[5], ot[6], ot[7]);
        }
    }
    if (threadIdx.x < 336) {
        const int m = threadIdx.x / 112, i = threadIdx.x - m * 112;
        const char* wp = (const char*)(m == 0 ? wg : (m == 1 ? wu : wd));
        asm volatile("prefetch.global.L2 [%0];" ::"l"(wp + ((size_t)blockIdx.x * 112 + i) * 128));
    }
    __syncthreads();
    if (threadIdx.x == 0) STAMP(1, 1);
    {
        float acc[5][4];
#pragma unroll
        for (int i = 0; i < 5; i++) { acc[i][0] = acc[i][1] = acc[i][2] = acc[i][3] = 0.f; }
        const float gf = (float)g;
        const int src4 = ((g & 3) << 2) | t;
#pragma unroll 2
        for (int s = w; s < 32; s += 3) {
            if (s == 17 && threadIdx.x == 352) asm volatile("red.release.gpu.global.add.u32 [%0], 1;" ::"l"(&g_ln_count) : "memory");
            const float4* c = s_const + (s * 4 + t) * 6;
            const float4 k0 = c[0], k1 = c[1], k2 = c[2];
            const float2 k3 = reinterpret_cast<const float2*>(c + 3)[g >> 2];
            const float2 k4 = reinterpret_cast<const float2*>(c + 4)[g >> 1];
            const cplx cb = {k0.z, k0.w}, e128 = {k1.x, k1.y}, cb8 = {k1.z, k1.w}, c256 = {k2.x, k2.y}, e8 = {k2.z, k2.w};
            const cplx c2 = {k3.x, k3.y}, c3 = {k4.x, k4.y};
            const cplx p1 = cexp_m(k0.x, k0.y, gf);
            const cplx p2 = csq(p1), p4 = csq(p2);
            const cplx r16a = csq(csq(p4));
            cplx q4;
            q4.r = __shfl_sync(0xffffffffu, p4.r, src4);
            q4.i = __shfl_sync(0xffffffffu, p4.i, src4);
            const cplx r16b = cmul(r16a, e128);
            const cplx f0a = cmul(cb, p1), f0b = cmul(cb8, p1), f1 = cmul(c256, p2), f2 = cmul(c2, q4);
            cplx f3 = cmul(c3, e8);
            if (!(g & 1)) f3 = c3;
            const uint32_t a0 = to_tf32(r16a.r), a1 = to_tf32(r16b.r), a2 = to_tf32(-r16a.i), a3 = to_tf32(-r16b.i);
            mma_tf32(acc[0], a0, a1, a2, a3, to_tf32(f0a.r), to_tf32(f0a.i));
            mma_tf32(acc[1], a0, a1, a2, a3, to_tf32(f0b.r), to_tf32(f0b.i));
            mma_tf32(acc[2], a0, a1, a2, a3, to_tf32(f1.r), to_tf32(f1.i));
            mma_tf32(acc[3], a0, a1, a2, a3, to_tf32(f2.r), to_tf32(f2.i));
            mma_tf32(acc[4], a0, a1, a2, a3, to_tf32(f3.r), to_tf32(f3.i));
        }
        float* kv = s_kp + w * 648;
#pragma unroll
        for (int hh = 0; hh < 2; hh++) {
            const int i = g + 8 * hh;
            *reinterpret_cast<float2*>(kv + 16 * i + 2 * t) = make_float2(acc[0][2 * hh], acc[0][2 * hh + 1]);
            *reinterpret_cast<float2*>(kv + 16 * i + 8 + 2 * t) = make_float2(acc[1][2 * hh], acc[1][2 * hh + 1]);
            *reinterpret_cast<float2*>(kv + 256 + 8 * i + 2 * t) = make_float2(acc[2][2 * hh], acc[2][2 * hh + 1]);
            *reinterpret_cast<float2*>(kv + 384 + 64 * (t >> 1) + 2 * (t & 1) + 4 * i) = make_float2(acc[3][2 * hh], acc[3][2 * hh + 1]);
            *reinterpret_cast<float2*>(kv + 512 + 32 * t + 2 * i) = make_float2(acc[4][2 * hh], acc[4][2 * hh + 1]);
        }
    }
    named_bar(bar_id, 96);
    if (threadIdx.x == 0) STAMP(1, 2);
#pragma unroll
    for (int i = 0; i < 7; i++) {
        const int idx = tc + 96 * i;
        if (idx < 641) s_kp[idx] = (s_kp[idx] + s_kp[648 + idx]) + s_kp[1296 + idx];
    }
    named_bar(bar_id, 96);
    {
        auto kdir = [&](int l) -> float {
            if (l < 0 || l > 514) return 0.f;
            const int idx = (l < 256) ? l : (l > 512 ? 384 : 128 + ((l + ((l >> 1) & 1)) >> 1));
            return s_kp[idx];
        };
#pragma unroll
        for (int i = 0; i < 6; i++) {
            const int e = tc + 96 * i;
            s_q[e] = pack_bf16(kdir(e - 16), kdir(e - 17));
        }
        if (tc < 64) {
            const int xx = 1008 + tc;
            const float k1024 = s_kp[512];
            s_q4[tc] = pack_bf16((xx == 1027 || xx == 1028) ? k1024 : 0.f, (xx == 1028 || xx == 1029) ? k1024 : 0.f);
        }
#pragma unroll
        for (int i = 0; i < 3; i++) {
            const int e = tc + 96 * i;
            if (e < 256) {
                const int a = e >> 6, ii = (e & 63) - 16;
                const int b = 385 + (a >> 1) + 2 * (a & 1);
                const float v0 = (ii >= 0 && ii < 32) ? s_kp[b + 4 * ii] : 0.f;
                const float v1 = (ii >= 1 && ii < 33) ? s_kp[b + 4 * (ii - 1)] : 0.f;
                s_q2[e] = pack_bf16(v0, v1);
            }
        }
#pragma unroll
        for (int a = 0; a < 2; a++) {
            const int jj = tc - 16;
            const float v0 = (jj >= 0 && jj < 64) ? s_kp[513 + a + 2 * jj] : 0.f;
            const float v1 = (jj >= 1 && jj < 65) ? s_kp[513 + a + 2 * (jj - 1)] : 0.f;
            s_q3[96 * a + tc] = pack_bf16(v0, v1);
        }
    }
    if (threadIdx.x == 0) STAMP(1, 3);
    if (threadIdx.x == 0) {
        unsigned int v = 0;
        for (int spin = 0; spin < (1 << 22); spin++) {
            asm volatile("ld.acquire.gpu.global.u32 %0, [%1];" : "=r"(v) : "l"(&g_ln_count) : "memory");
            if (v >= gridDim.x) break;
        }
    }
    __syncthreads();
    if (threadIdx.x == 0) STAMP(1, 4);
    {
        if (tc < 16) *reinterpret_cast<uint4*>(s_u + tc * 8) = make_uint4(0, 0, 0, 0);
        const uint4* src = reinterpret_cast<const uint4*>(g_xnT + (size_t)d * L_);
        uint4 v[3];
#pragma unroll
        for (int i = 0; i < 3; i++) if (tc + 96 * i < 256) v[i] = src[tc + 96 * i];
#pragma unroll
        for (int i = 0; i < 3; i++) if (tc + 96 * i < 256) *reinterpret_cast<uint4*>(s_u + 128 + (tc + 96 * i) * 8) = v[i];
        if (tc < 2) *reinterpret_cast<uint4*>(base + (tc ? CV_O_W5 : CV_O_W3)) = make_uint4(0, 0, 0, 0);
    }
    named_bar(bar_id, 96);
#pragma unroll
    for (int rep = 0; rep < 2; rep++) {
        const int m = tc + 96 * rep;
        float P[30];
        const uint4* up = reinterpret_cast<const uint4*>(s_u + 128 + 8 * m - 24);
        P[0] = 0.f;
#pragma unroll
        for (int c4 = 0; c4 < 4; c4++) {
            const uint4 v = up[c4];
            const uint32_t ww[4] = {v.x, v.y, v.z, v.w};
#pragma unroll
            for (int j = 0; j < 4; j++) {
                const int k = c4 * 8 + 2 * j;
                if (k + 1 <= 29) P[k + 1] = P[k] + bf_lo(ww[j]);
                if (k + 2 <= 29) P[k + 2] = P[k + 1] + bf_hi(ww[j]);
            }
        }
        uint32_t o3[4], o5[4], o7[4], o9[4];
#pragma unroll
        for (int j = 0; j < 4; j++) {
            const int i = 2 * j;
            o3[j] = pack_bf16(P[i + 22] - P[i + 19], P[i + 23] - P[i + 20]);
            o5[j] = pack_bf16(P[i + 19] - P[i + 14], P[i + 20] - P[i + 15]);
            o7[j] = pack_bf16(P[i + 20] - P[i + 13], P[i + 21] - P[i + 14]);
            o9[j] = pack_bf16(P[i + 13] - P[i + 4], P[i + 14] - P[i + 5]);
        }
        *reinterpret_cast<uint4*>(base + CV_O_W3 + 16 + m * 16) = make_uint4(o3[0], o3[1], o3[2], o3[3]);
        *reinterpret_cast<uint4*>(base + CV_O_W5 + 16 + m * 16) = make_uint4(o5[0], o5[1], o5[2], o5[3]);
        if (m < 128) {
            *reinterpret_cast<uint4*>(base + CV_O_W7 + m * 16) = make_uint4(o7[0], o7[1], o7[2], o7[3]);
            *reinterpret_cast<uint4*>(base + CV_O_W9 + m * 16) = make_uint4(o9[0], o9[1], o9[2], o9[3]);
        }
    }
    if (threadIdx.x == 0) STAMP(1, 5);
    named_bar(bar_id, 96);
    if (w == 2) return;
    const int hb = w;
    float acc[16][4];
#pragma unroll
    for (int i = 0; i < 16; i++) { acc[i][0] = acc[i][1] = acc[i][2] = acc[i][3] = 0.f; }
    const uint32_t sb_addr = smem_u32(base);
    const int mi = lane >> 3, rowi = lane & 7;
#pragma unroll 1
    for (int rr = 0; rr < 4; rr++) {
        const int r = 4 * hb + rr;
        uint32_t ub[16][2];
        {
            const uint32_t addr = sb_addr + CV_O_U + (uint32_t)((128 + 16 * (8 * (mi >> 1) + rowi - r) + 8 * (mi & 1)) * 2);
#pragma unroll
            for (int j = 0; j < 16; j += 2) ldsm_x4(addr + (uint32_t)(j * 256), ub[j][0], ub[j][1], ub[j + 1][0], ub[j + 1][1]);
        }
        const uint32_t* qp = s_q + 16 + 16 * r + g - 2 * t;
        uint32_t af[4][3];
#pragma unroll
        for (int q = 0; q < 4; q++) { af[q][0] = qp[128 * q]; af[q][1] = qp[128 * q + 8]; af[q][2] = qp[128 * q - 8]; }
#pragma unroll
        for (int q = 0; q < 4; q++) {
#pragma unroll
            for (int nt = q; nt < 16; nt++) mma_bf16(acc[nt], af[q][0], af[q][1], af[q][2], af[q][0], ub[nt - q][0], ub[nt - q][1]);
        }
        if (r < 2) {
            {
                const uint32_t a0 = qp[512], a1 = qp[520], a2 = qp[504];
#pragma unroll
                for (int nt = 4; nt < 16; nt++) mma_bf16(acc[nt], a0, a1, a2, a0, ub[nt - 4][0], ub[nt - 4][1]);
            }
            {
                const uint32_t* q4p = s_q4 + 16 + 16 * r + g - 2 * t;
                const uint32_t a0 = q4p[0], a1 = q4p[8], a2 = q4p[-8];
#pragma unroll
                for (int nt = 8; nt < 16; nt++) mma_bf16(acc[nt], a0, a1, a2, a0, ub[nt - 8][0], ub[nt - 8][1]);
            }
        }
    }
#pragma unroll 1
    for (int a = hb; a <= 3 * hb; a++) {
        uint32_t bq[7];
        const uint32_t* q2 = s_q2 + a * 64 + 16 + g - 2 * t - 32;
#pragma unroll
        for (int dlt = 3; dlt <= 9; dlt++) bq[dlt - 3] = q2[8 * dlt];
        const uint32_t addr = sb_addr + ((a >> 1) ? CV_O_W5 : CV_O_W3) + (uint32_t)((8 + 16 * (8 * (mi >> 1) + rowi) + 8 * (mi & 1) - 8 * (a & 1)) * 2);
        uint32_t aa[6][4];
#pragma unroll
        for (int kp = 0; kp < 6; kp++) ldsm_x4_t(addr + kp * 512, aa[kp][0], aa[kp][1], aa[kp][2], aa[kp][3]);
#pragma unroll
        for (int kp = 0; kp < 6; kp++) {
#pragma unroll
            for (int dlt = 4; dlt <= 9; dlt++) {
                if (2 * kp + dlt < 16) mma_bf16(acc[2 * kp + dlt], aa[kp][0], aa[kp][1], aa[kp][2], aa[kp][3], bq[dlt - 3], bq[dlt - 4]);
            }
        }
    }
    if (hb == 0) {
#pragma unroll 1
        for (int a = 0; a < 2; a++) {
            uint32_t bq[9];
            const uint32_t* q3 = s_q3 + a * 96 + 16 + g - 2 * t - 64;
#pragma unroll
            for (int dlt = 7; dlt <= 15; dlt++) bq[dlt - 7] = q3[8 * dlt];
            const uint32_t addr = sb_addr + (a ? CV_O_W9 : CV_O_W7) + (uint32_t)((16 * (8 * (mi >> 1) + rowi) + 8 * (mi & 1)) * 2);
            uint32_t aa[4][4];
#pragma unroll
            for (int kp = 0; kp < 4; kp++) ldsm_x4_t(addr + kp * 512, aa[kp][0], aa[kp][1], aa[kp][2], aa[kp][3]);
#pragma unroll
            for (int kp = 0; kp < 4; kp++) {
#pragma unroll
                for (int dlt = 8; dlt <= 15; dlt++) {
                    if (2 * kp + dlt < 16) mma_bf16(acc[2 * kp + dlt], aa[kp][0], aa[kp][1], aa[kp][2], aa[kp][3], bq[dlt - 7], bq[dlt - 8]);
                }
            }
        }
    }
    if (threadIdx.x == 0) STAMP(1, 6);
    {
        float4* xch = reinterpret_cast<float4*>(base + CV_O_CONST) + hb * 256;
        if (hb) {
#pragma unroll
            for (int i = 0; i < 8; i++) xch[i * 32 + lane] = make_float4(acc[i][0], acc[i][1], acc[i][2], acc[i][3]);
#pragma unroll
            for (int i = 0; i < 8; i++) { acc[i][0] = acc[8 + i][0]; acc[i][1] = acc[8 + i][1]; acc[i][2] = acc[8 + i][2]; acc[i][3] = acc[8 + i][3]; }
        } else {
#pragma unroll
            for (int i = 0; i < 8; i++) xch[i * 32 + lane] = make_float4(acc[8 + i][0], acc[8 + i][1], acc[8 + i][2], acc[8 + i][3]);
        }
    }
    named_bar(bar_id, 64);
    if (threadIdx.x == 0) STAMP(1, 10);
    {
        const float4* xch = reinterpret_cast<const float4*>(base + CV_O_CONST) + (hb ^ 1) * 256 + lane;
        const float dsk = __bfloat162float(p_dsk);
        uint16_t* stg = reinterpret_cast<uint16_t*>(base + CV_O_KP);
        const uint16_t* uu = reinterpret_cast<const uint16_t*>(s_u) + 128;
#pragma unroll
        for (int i = 0; i < 8; i++) {
            const float4 p0 = xch[i * 32];
            const float y[4] = {acc[i][0] + p0.x, acc[i][1] + p0.y, acc[i][2] + p0.z, acc[i][3] + p0.w};
            const int nt = 8 * hb + i;
#pragma unroll
            for (int e = 0; e < 4; e++) {
                const int tau = 16 * (8 * nt + 2 * t + (e & 1)) + g + 8 * (e >> 1);
                const float sv = bf16_round(y[e]) + bf16_round(__uint_as_float((uint32_t)uu[tau] << 16) * dsk);
                stg[tau] = (uint16_t)(__float_as_uint(bf16_round(sv)) >> 16);
            }
        }
        __syncwarp();
        if (threadIdx.x == 0) STAMP(1, 11);
        uint4* dst = reinterpret_cast<uint4*>(g_sT + (size_t)d * L_ + hb * 1024);
        const uint4* srcp = reinterpret_cast<const uint4*>(stg + hb * 1024);
#pragma unroll
        for (int i = 0; i < 4; i++) dst[i * 32 + lane] = srcp[i * 32 + lane];
    }
}

__device__ __forceinline__ uint32_t cluster_rank() { uint32_t r; asm volatile("mov.u32 %0, %%cluster_ctarank;" : "=r"(r)); return r; }
__device__ __forceinline__ void cluster_sync_all() {
    asm volatile("barrier.cluster.arrive.release.aligned;\nbarrier.cluster.wait.acquire.aligned;" ::: "memory");
}
__device__ __forceinline__ void mbar_arrive_remote(uint32_t bar, uint32_t cta) {
    asm volatile("{\n.reg .b32 ra;\nmapa.shared::cluster.u32 ra, %0, %1;\n"
                 "mbarrier.arrive.shared::cluster.b64 _, [ra];\n}\n" ::"r"(bar), "r"(cta) : "memory");
}
__device__ __forceinline__ void tma_load_2d_mc(uint32_t dst, const CUtensorMap* tm, int c0, int c1, uint32_t bar, uint16_t mask) {
    asm volatile(
        "cp.async.bulk.tensor.2d.shared::cluster.global.mbarrier::complete_tx::bytes.multicast::cluster [%0], [%1, {%3, %4}], [%2], %5;"
        ::"r"(dst), "l"((uint64_t)tm), "r"(bar), "r"(c0), "r"(c1), "h"(mask) : "memory");
}
__device__ __forceinline__ void tma_store_2d(const CUtensorMap* tm, uint32_t src, int c0, int c1) {
    asm volatile("cp.async.bulk.tensor.2d.global.shared::cta.bulk_group [%0, {%2, %3}], [%1];"
                 ::"l"((uint64_t)tm), "r"(src), "r"(c0), "r"(c1) : "memory");
}
__device__ __forceinline__ void bulk_commit() { asm volatile("cp.async.bulk.commit_group;" ::: "memory"); }
template <int N> __device__ __forceinline__ void bulk_wait_read() { asm volatile("cp.async.bulk.wait_group.read %0;" ::"n"(N) : "memory"); }
template <int N> __device__ __forceinline__ void bulk_wait() { asm volatile("cp.async.bulk.wait_group %0;" ::"n"(N) : "memory"); }
__device__ __forceinline__ void fence_async_smem() { asm volatile("fence.proxy.async.shared::cta;" ::: "memory"); }
__device__ __forceinline__ void stmatrix_x4(uint32_t addr, uint32_t r0, uint32_t r1, uint32_t r2, uint32_t r3) {
    asm volatile("stmatrix.sync.aligned.m8n8.x4.shared.b16 [%0], {%1,%2,%3,%4};" ::"r"(addr), "r"(r0), "r"(r1), "r"(r2), "r"(r3) : "memory");
}

constexpr int G1_STAGES = 5;
constexpr int G1_A_BYTES = 8 * 16384;
constexpr int G1_B_STAGE = 16384;
constexpr int G1_STG = 8 * 1024;
constexpr int G1_SMEM = G1_A_BYTES + G1_STAGES * G1_B_STAGE + G1_STG + 1024 + 256;
constexpr int G1_ITERS = 32;

__device__ __forceinline__ void tma_load_3d(uint32_t dst, const CUtensorMap* tm, int c0, int c1, int c2, uint32_t bar) {
    asm volatile(
        "cp.async.bulk.tensor.3d.shared::cluster.global.mbarrier::complete_tx::bytes [%0], [%1, {%3, %4, %5}], [%2];"
        ::"r"(dst), "l"((uint64_t)tm), "r"(bar), "r"(c0), "r"(c1), "r"(c2) : "memory");
}

__device__ __forceinline__ float gelu_tanh(float x) {
    float u = x * (0.7978845608028654f + 0.035677408136300125f * x * x);
    float t; asm("tanh.approx.f32 %0, %1;" : "=f"(t) : "f"(u));
    float hx = 0.5f * x;
    return fmaf(hx, t, hx);
}
__device__ __forceinline__ uint32_t geglu_pair(uint32_t g2, uint32_t u2) {
    uint32_t a = pack_bf16(gelu_tanh(bf_lo(g2)), gelu_tanh(bf_hi(g2)));
    uint32_t r; asm("mul.rn.bf16x2 %0, %1, %2;" : "=r"(r) : "r"(a), "r"(u2));
    return r;
}

constexpr int G2_STAGES = 5;
constexpr int G2_STAGE = 16384 + 16384;
constexpr int G2_XCH = 32768;
constexpr int G2_EPI = 16384 + 16384;
constexpr int G2_SMEM = G2_STAGES * G2_STAGE + G2_XCH + G2_EPI + 1024 + 256;
constexpr int G2_KB = F_ / 64 / 2;

constexpr int MG_BAR_OFF = G2_STAGES * G2_STAGE + G2_XCH + G2_EPI;
constexpr int MG_SMEM = MG_BAR_OFF + 256 + 1024;
static_assert(CV_SMEM + 16 * (D_ + 8) * 2 <= MG_BAR_OFF && G1_A_BYTES + G1_STAGES * G1_B_STAGE + G1_STG <= MG_BAR_OFF, "smem layout");

__device__ __forceinline__ void fence_async_all() { asm volatile("fence.proxy.async;" ::: "memory"); }
__device__ __forceinline__ void spin_until(const unsigned int* p, unsigned int target) {
    unsigned int v = 0;
    for (int spin = 0; spin < (1 << 22); spin++) {
        asm volatile("ld.acquire.gpu.global.u32 %0, [%1];" : "=r"(v) : "l"(p) : "memory");
        if (v >= target) break;
    }
}

struct MegaParams {
    const __nv_bfloat16 *x, *A_re, *A_im, *B_re, *B_im, *C_re, *C_im, *log_dt, *Dskip, *wg, *wu, *wd;
};

__global__ void __launch_bounds__(384, 1) mega_kernel(const __grid_constant__ MegaParams P,
                                                       const __grid_constant__ CUtensorMap tm_xn,
                                                       const __grid_constant__ CUtensorMap tm_wg4,
                                                       const __grid_constant__ CUtensorMap tm_wu4,
                                                       const __grid_constant__ CUtensorMap tm_wg3,
                                                       const __grid_constant__ CUtensorMap tm_wu3,
                                                       const __grid_constant__ CUtensorMap tm_h,
                                                       const __grid_constant__ CUtensorMap tm_wd,
                                                       const __grid_constant__ CUtensorMap tm_x,
                                                       const __grid_constant__ CUtensorMap tm_sT,
                                                       const __grid_constant__ CUtensorMap tm_out) {
    if (threadIdx.x == 0) STAMP(1, 0);
    extern __shared__ uint8_t smem_raw[];
    const uint32_t sraw = smem_u32(smem_raw);
    const uint32_t sbase = (sraw + 1023) & ~1023u;
    uint8_t* smem = smem_raw + (sbase - sraw);
    const int warp = threadIdx.x >> 5, lane = threadIdx.x & 31;
    const uint32_t sA = sbase, sB = sbase + G1_A_BYTES, sStg = sB + G1_STAGES * G1_B_STAGE;
    const uint32_t sXch = sbase + G2_STAGES * G2_STAGE, sX = sXch + G2_XCH, sS = sX + 16384;
    const uint32_t sBar = sbase + MG_BAR_OFF;
    const uint32_t bar_a = sBar, bar_full = sBar + 64, bar_empty = bar_full + 8 * G1_STAGES;
    const uint32_t bar_full2 = bar_empty + 8 * G1_STAGES, bar_empty2 = bar_full2 + 8 * G2_STAGES;
    const uint32_t bar_epi = bar_empty2 + 8 * G2_STAGES, bar_xch = bar_epi + 8, bar_g1done = bar_xch + 8, bar_g1mma = bar_g1done + 8;
    const int rb = blockIdx.x >> 3, cj = blockIdx.x & 7;
    const uint32_t kh = blockIdx.x & 1;
    const int nb = (blockIdx.x >> 1) & 3;
    const int col_fin = nb * 128 + kh * 64;

    if (threadIdx.x == 0) {
        for (int i = 0; i < 8; i++) mbar_init(bar_a + 8 * i, 1);
        for (int i = 0; i < G1_STAGES; i++) { mbar_init(bar_full + 8 * i, 1); mbar_init(bar_empty + 8 * i, 8); }
        for (int i = 0; i < G2_STAGES; i++) { mbar_init(bar_full2 + 8 * i, 1); mbar_init(bar_empty2 + 8 * i, 8); }
        mbar_init(bar_epi, 1);
        mbar_init(bar_xch, 1);
        mbar_init(bar_g1done, 8);
        mbar_init(bar_g1mma, 8);
        asm volatile("fence.mbarrier_init.release.cluster;" ::: "memory");
        mbar_expect_tx(bar_xch, G2_XCH);
    }
    if (warp == 11 && lane == 0) {
        prefetch_tmap(&tm_wg4); prefetch_tmap(&tm_wu4); prefetch_tmap(&tm_xn); prefetch_tmap(&tm_wg3); prefetch_tmap(&tm_wu3);
        prefetch_tmap(&tm_wd); prefetch_tmap(&tm_h); prefetch_tmap(&tm_x); prefetch_tmap(&tm_sT); prefetch_tmap(&tm_out);
    }
    asm volatile("barrier.cluster.arrive.release.aligned;" ::: "memory");

    front_phase(smem, P.x, P.A_re, P.A_im, P.B_re, P.B_im, P.C_re, P.C_im, P.log_dt, P.Dskip, P.wg, P.wu, P.wd);
    fence_async_smem();
    asm volatile("barrier.cluster.wait.acquire.aligned;" ::: "memory");
    __syncthreads();
    if (threadIdx.x == 0) STAMP(1, 7);

    if (warp >= 8) {
        asm volatile("setmaxnreg.dec.sync.aligned.u32 40;");
        if (warp == 11) {
            if (lane == 0) asm volatile("red.release.gpu.global.add.u32 [%0], 1;" ::"l"(&g_conv_count) : "memory");
            named_bar(3, 288);
            if (lane == 0) asm volatile("red.release.gpu.global.add.u32 [%0], 1;" ::"l"(&g_h_count[rb]) : "memory");
            named_bar(9, 288);
            if (lane == 0) asm volatile("red.release.gpu.global.add.u32 [%0], 1;" ::"l"(&g_h_count[16 + rb]) : "memory");
        } else if (lane == 0) {
            const int pw = warp - 8;
            fence_async_all();
            for (int k = pw; k < 8; k += 3) {
                mbar_expect_tx(bar_a + 8 * k, 16384);
                tma_load_2d(sA + k * 16384, &tm_xn, k * 64, rb * 128, bar_a + 8 * k);
                if (k < 3) {
                    const uint32_t dst = sB + k * G1_B_STAGE;
                    mbar_expect_tx(bar_full + 8 * k, 16384);
                    tma_load_3d(dst, &tm_wg4, 0, k * 32, cj * 7, bar_full + 8 * k);
                    tma_load_3d(dst + 8192, &tm_wu4, 0, k * 32, cj * 7, bar_full + 8 * k);
                }
            }
            for (int it = 3 + pw; it < G1_ITERS; it += 3) {
                const int s = it % G1_STAGES, kb = it & 15;
                if (it >= G1_STAGES) mbar_wait(bar_empty + 8 * s, ((it / G1_STAGES) - 1) & 1);
                const uint32_t dst = sB + s * G1_B_STAGE;
                if (it < 16) {
                    mbar_expect_tx(bar_full + 8 * s, 16384);
                    tma_load_3d(dst, &tm_wg4, 0, kb * 32, cj * 7, bar_full + 8 * s);
                    tma_load_3d(dst + 8192, &tm_wu4, 0, kb * 32, cj * 7, bar_full + 8 * s);
                } else {
                    mbar_expect_tx(bar_full + 8 * s, 12288);
                    tma_load_3d(dst, &tm_wg3, 0, kb * 32, cj * 7 + 4, bar_full + 8 * s);
                    tma_load_3d(dst + 6144, &tm_wu3, 0, kb * 32, cj * 7 + 4, bar_full + 8 * s);
                }
            }
            const int k0 = kh * G2_KB;
            auto kblk = [&](int it) -> int {
                const unsigned long long tab = 0xDCA96532B87410ull;
                return k0 + (int)((tab >> (4 * it)) & 15);
            };
            mbar_wait(bar_g1mma, 0);
            if (pw == 2) {
                mbar_expect_tx(bar_epi, G2_EPI);
                tma_load_2d(sX, &tm_x, col_fin, rb * 128, bar_epi);
            }
            spin_until(&g_h_count[rb], 8);
            fence_async_all();
            if (pw == 0) STAMP(3, 1);
            for (int it = pw; it < G2_KB; it += 3) {
                const int s = (it + 1) % G2_STAGES;
                if (it == 4) mbar_wait(bar_g1done, 0);
                if (it >= G2_STAGES) mbar_wait(bar_empty2 + 8 * s, ((it / G2_STAGES) - 1) & 1);
                if (it >= 6 && it < 9) { spin_until(&g_h_count[16 + rb], 8); fence_async_all(); }
                mbar_expect_tx(bar_full2 + 8 * s, G2_STAGE);
                const int kb = kblk(it);
                tma_load_3d(sbase + s * G2_STAGE + 16384, &tm_wd, 0, kb * 64, nb * 2, bar_full2 + 8 * s);
                tma_load_2d(sbase + s * G2_STAGE, &tm_h, kb * 64, rb * 128, bar_full2 + 8 * s);
                if (it == 2) {
                    spin_until(&g_conv_count, gridDim.x);
                    fence_async_all();
                    tma_load_2d(sS, &tm_sT, rb * 128, col_fin, bar_epi);
                    tma_load_2d(sS + 8192, &tm_sT, rb * 128 + 64, col_fin, bar_epi);
                }
            }
        }
    } else {
        asm volatile("setmaxnreg.inc.sync.aligned.u32 232;");
        const int wg = __shfl_sync(0xffffffffu, (int)(threadIdx.x >> 7), 0);
        {
        float r[160];
        const int row0 = rb * 128 + wg * 64 + (warp & 3) * 16;
        const uint64_t descA = make_desc(sA + wg * 8192, 16, 1024);
        const uint64_t descB = make_desc(sB, 2048, 512, 2);
        const uint32_t stg = sStg + warp * 1024;
        const uint32_t st_off = (uint32_t)(((lane & 7) + ((lane >> 3) & 1) * 8) * 32 + (lane >> 4) * 16);
        __nv_bfloat16* hrow = g_h + (size_t)(row0 + (lane >> 1)) * F_ + (lane & 1) * 8 + cj * 224;
#pragma unroll
        for (int kb = 0; kb < 16; kb++) {
            const int it = kb, s = it % G1_STAGES;
            if ((kb & 1) == 0) mbar_wait(bar_a + 8 * (kb >> 1), 0);
            mbar_wait(bar_full + 8 * s, (it / G1_STAGES) & 1);
            if (threadIdx.x == 0 && (it & 7) == 0) STAMP(2, 2 + it / 8);
            wgmma_fence();
            const uint64_t da = descA + (uint64_t)(((kb >> 1) * 16384 + (kb & 1) * 64) >> 4);
            const uint64_t db = descB + (uint64_t)((s * G1_B_STAGE) >> 4);
            wgmma_n256_k32(r, da, da + 2, db, db + 64, kb != 0);
            wgmma_commit();
            if (kb > 0) {
                wgmma_wait<1>();
                if (lane == 0) mbar_arrive(bar_empty + 8 * ((it - 1) % G1_STAGES));
            }
        }
        wgmma_wait<0>();
        if (lane == 0) mbar_arrive(bar_empty + 8 * (15 % G1_STAGES));
#pragma unroll
        for (int i = 0; i < 32; i++) r[128 + i] = __uint_as_float(pack_bf16(r[2 * i], r[2 * i + 1]));
#pragma unroll
        for (int i = 31; i >= 0; i--) r[96 + i] = __uint_as_float(pack_bf16(r[64 + 2 * i], r[65 + 2 * i]));
        uint32_t eo[4];
        uint4 pv = make_uint4(0, 0, 0, 0);
#pragma unroll
        for (int kb = 0; kb < 16; kb++) {
            const int it = 16 + kb, s = it % G1_STAGES;
            mbar_wait(bar_full + 8 * s, (it / G1_STAGES) & 1);
            if (threadIdx.x == 0 && (it & 7) == 0) STAMP(2, 2 + it / 8);
            wgmma_fence();
            const uint64_t da = descA + (uint64_t)(((kb >> 1) * 16384 + (kb & 1) * 64) >> 4);
            const uint64_t db = descB + (uint64_t)((s * G1_B_STAGE) >> 4);
            const int jj = kb >> 1;
            wgmma_n192(r, da, db, kb != 0);
            eo[(kb & 1) * 2] = geglu_pair(__float_as_uint(r[128 + 2 * kb]), __float_as_uint(r[96 + 2 * kb]));
            wgmma_n192(r, da + 2, db + 64, 1);
            wgmma_commit();
            eo[(kb & 1) * 2 + 1] = geglu_pair(__float_as_uint(r[129 + 2 * kb]), __float_as_uint(r[97 + 2 * kb]));
            if (kb & 1) {
                if (jj > 0) *reinterpret_cast<uint4*>(hrow + (jj - 1) * 16) = pv;
                stmatrix_x4(stg + (jj & 1) * 512 + st_off, eo[0], eo[1], eo[2], eo[3]);
            } else if (jj > 0) {
                __syncwarp();
                asm volatile("ld.shared.v4.u32 {%0,%1,%2,%3}, [%4];" : "=r"(pv.x), "=r"(pv.y), "=r"(pv.z), "=r"(pv.w)
                             : "r"(stg + ((jj - 1) & 1) * 512 + lane * 16));
            }
            if (kb > 0 && it - 1 + G1_STAGES < G1_ITERS) {
                wgmma_wait<1>();
                if (lane == 0) mbar_arrive(bar_empty + 8 * ((it - 1) % G1_STAGES));
            }
        }
        __syncwarp();
        asm volatile("ld.shared.v4.u32 {%0,%1,%2,%3}, [%4];" : "=r"(pv.x), "=r"(pv.y), "=r"(pv.z), "=r"(pv.w) : "r"(stg + 512 + lane * 16));
        wgmma_wait<0>();
        *reinterpret_cast<uint4*>(hrow + 7 * 16) = pv;
        fence_async_smem();
        __syncwarp();
        if (lane == 0) mbar_arrive(bar_g1mma);
        asm volatile("bar.arrive 3, 288;" ::: "memory");
        if (threadIdx.x == 0) STAMP(2, 6);
        {
            uint32_t o[24];
#pragma unroll
            for (int i = 0; i < 24; i++) o[i] = geglu_pair(pack_bf16(r[2 * i], r[2 * i + 1]), pack_bf16(r[48 + 2 * i], r[49 + 2 * i]));
            named_bar(1 + wg, 128);
            const uint32_t fbuf = sA + ((warp & 3) >> 1) * 16384 + wg * 8192 + (warp & 1) * 4096;
#pragma unroll
            for (int jj = 0; jj < 6; jj++) stmatrix_x4(fbuf + jj * 512 + st_off, o[4 * jj], o[4 * jj + 1], o[4 * jj + 2], o[4 * jj + 3]);
            __syncwarp();
            uint4 v[6];
#pragma unroll
            for (int jj = 0; jj < 6; jj++)
                asm volatile("ld.shared.v4.u32 {%0,%1,%2,%3}, [%4];" : "=r"(v[jj].x), "=r"(v[jj].y), "=r"(v[jj].z), "=r"(v[jj].w)
                             : "r"(fbuf + jj * 512 + lane * 16));
#pragma unroll
            for (int jj = 0; jj < 6; jj++) *reinterpret_cast<uint4*>(hrow + 128 + jj * 16) = v[jj];
        }
        }
        fence_async_smem();
        __syncwarp();
        if (lane == 0) mbar_arrive(bar_g1done);
        asm volatile("bar.arrive 9, 288;" ::: "memory");
        if (threadIdx.x == 0) STAMP(2, 7);
        {
        const int g = lane >> 2, t = lane & 3;
        float acc[64];
        const uint64_t descA2 = make_desc(sbase + wg * 8192, 16, 1024);
        const uint64_t descB2 = make_desc(sbase + 16384, 8192, 1024);
#pragma unroll
        for (int it = 0; it < G2_KB; it++) {
            const int s = (it + 1) % G2_STAGES;
            mbar_wait(bar_full2 + 8 * s, (it / G2_STAGES) & 1);
            if (threadIdx.x == 0 && (it == 0 || it == 7)) STAMP(3, 2 + it / 7);
            wgmma_fence();
            {
                const uint64_t da = descA2 + (uint64_t)((s * G2_STAGE) >> 4);
                const uint64_t db = descB2 + (uint64_t)((s * G2_STAGE) >> 4);
                wgmma_n128_k64(acc, da, da + 2, da + 4, da + 6, db, db + 128, db + 256, db + 384, it != 0);
            }
            wgmma_commit();
            if (it > 0 && it - 1 + G2_STAGES < G2_KB) {
                wgmma_wait<1>();
                if (lane == 0) mbar_arrive(bar_empty2 + 8 * (it % G2_STAGES));
            }
        }
        const int lr = wg * 64 + (warp & 3) * 16 + g;
        uint32_t xv[16], sv[16];
        mbar_wait(bar_epi, 0);
#pragma unroll
        for (int j = 0; j < 8; j++) {
#pragma unroll
            for (int hh = 0; hh < 2; hh++) {
                const int r = lr + 8 * hh;
                asm volatile("ld.shared.u32 %0, [%1];" : "=r"(xv[2 * j + hh]) : "r"(sX + r * 128 + ((j ^ (r & 7)) << 4) + 4 * t));
                const int c0 = 8 * j + 2 * t;
                const uint32_t sa = sS + (r >> 6) * 8192 + (((r & 63) >> 3) << 4) + (r & 7) * 2;
                uint16_t s0r, s1r;
                asm volatile("ld.shared.u16 %0, [%1];" : "=h"(s0r) : "r"((sa + c0 * 128) ^ ((c0 & 7) << 4)));
                asm volatile("ld.shared.u16 %0, [%1];" : "=h"(s1r) : "r"((sa + (c0 + 1) * 128) ^ (((c0 + 1) & 7) << 4)));
                sv[2 * j + hh] = (uint32_t)s0r | ((uint32_t)s1r << 16);
            }
        }
        wgmma_wait<0>();
        if (threadIdx.x == 0) STAMP(3, 4);
        {
            uint32_t remote, rbar;
            asm volatile("mapa.shared::cluster.u32 %0, %1, %2;" : "=r"(remote) : "r"(sXch + threadIdx.x * 16), "r"(kh ^ 1));
            asm volatile("mapa.shared::cluster.u32 %0, %1, %2;" : "=r"(rbar) : "r"(bar_xch), "r"(kh ^ 1));
            if (kh == 0) {
#pragma unroll
                for (int i = 0; i < 8; i++)
                    asm volatile("st.async.shared::cluster.mbarrier::complete_tx::bytes.v4.f32 [%0], {%1,%2,%3,%4}, [%5];" ::"r"(remote + i * 4096),
                                 "f"(acc[32 + 4 * i]), "f"(acc[33 + 4 * i]), "f"(acc[34 + 4 * i]), "f"(acc[35 + 4 * i]), "r"(rbar) : "memory");
            } else {
#pragma unroll
                for (int i = 0; i < 8; i++)
                    asm volatile("st.async.shared::cluster.mbarrier::complete_tx::bytes.v4.f32 [%0], {%1,%2,%3,%4}, [%5];" ::"r"(remote + i * 4096),
                                 "f"(acc[4 * i]), "f"(acc[1 + 4 * i]), "f"(acc[2 + 4 * i]), "f"(acc[3 + 4 * i]), "r"(rbar) : "memory");
#pragma unroll
                for (int i = 0; i < 32; i++) acc[i] = acc[32 + i];
            }
        }
        if (threadIdx.x == 0) STAMP(3, 6);
        mbar_wait(bar_xch, 0);
        if (threadIdx.x == 0) STAMP(3, 7);
#pragma unroll
        for (int j = 0; j < 8; j++) {
            float4 o;
            asm volatile("ld.shared.v4.f32 {%0,%1,%2,%3}, [%4];" : "=f"(o.x), "=f"(o.y), "=f"(o.z), "=f"(o.w) : "r"(sXch + threadIdx.x * 16 + j * 4096));
            acc[4 * j] += o.x; acc[4 * j + 1] += o.y; acc[4 * j + 2] += o.z; acc[4 * j + 3] += o.w;
        }
#pragma unroll
        for (int i = 0; i < 16; i++) {
            float f0 = bf16_round(acc[2 * i]), f1 = bf16_round(acc[2 * i + 1]);
            float g0 = bf16_round(__fdividef(f0, 1.0f + __expf(-f0)));
            float g1 = bf16_round(__fdividef(f1, 1.0f + __expf(-f1)));
            float o0 = bf_lo(xv[i]) + bf16_round(bf_lo(sv[i]) * g0);
            float o1 = bf_hi(xv[i]) + bf16_round(bf_hi(sv[i]) * g1);
            xv[i] = pack_bf16(o0, o1);
        }
#pragma unroll
        for (int j = 0; j < 8; j++) {
#pragma unroll
            for (int hh = 0; hh < 2; hh++) {
                const int r = lr + 8 * hh;
                asm volatile("st.shared.u32 [%0], %1;" ::"r"(sX + r * 128 + ((j ^ (r & 7)) << 4) + 4 * t), "r"(xv[2 * j + hh]) : "memory");
            }
        }
        if (threadIdx.x == 0) STAMP(3, 9);
        fence_async_smem();
        __syncwarp();
        if (lane == 0) {
            tma_store_2d(&tm_out, sX + (wg * 64 + (warp & 3) * 16) * 128, col_fin, rb * 128 + wg * 64 + (warp & 3) * 16);
            bulk_commit();
            bulk_wait_read<0>();
        }
        }
        if (threadIdx.x == 0) STAMP(3, 5);
        named_bar(4, 256);
        if (threadIdx.x == 0) {
            const unsigned int old = atomicAdd(&g_done_count, 1u);
            if (old == gridDim.x - 1) {
                g_ln_count = 0; g_conv_count = 0; g_done_count = 0;
                for (int i = 0; i < 32; i++) g_h_count[i] = 0;
            }
        }
    }
}

typedef CUresult (*EncodeFn)(CUtensorMap*, CUtensorMapDataType, cuuint32_t, void*, const cuuint64_t*, const cuuint64_t*,
                             const cuuint32_t*, const cuuint32_t*, CUtensorMapInterleave, CUtensorMapSwizzle,
                             CUtensorMapL2promotion, CUtensorMapFloatOOBfill);

void make_map(EncodeFn fn, CUtensorMap* m, const void* ptr, uint64_t inner, uint64_t outer, uint32_t box_in, uint32_t box_out,
              CUtensorMapSwizzle swz = CU_TENSOR_MAP_SWIZZLE_128B) {
    cuuint64_t dims[2] = {inner, outer};
    cuuint64_t strides[1] = {inner * 2};
    cuuint32_t box[2] = {box_in, box_out};
    cuuint32_t es[2] = {1, 1};
    fn(m, CU_TENSOR_MAP_DATA_TYPE_BFLOAT16, 2, const_cast<void*>(ptr), dims, strides, box, es, CU_TENSOR_MAP_INTERLEAVE_NONE,
       swz, CU_TENSOR_MAP_L2_PROMOTION_L2_256B, CU_TENSOR_MAP_FLOAT_OOB_FILL_NONE);
}
void make_map3(EncodeFn fn, CUtensorMap* m, const void* ptr, uint64_t cols, uint64_t rows, uint32_t atom, uint32_t box_rows,
               uint32_t box_atoms, CUtensorMapSwizzle swz) {
    cuuint64_t dims[3] = {atom, rows, cols / atom};
    cuuint64_t strides[2] = {cols * 2, (cuuint64_t)atom * 2};
    cuuint32_t box[3] = {atom, box_rows, box_atoms};
    cuuint32_t es[3] = {1, 1, 1};
    fn(m, CU_TENSOR_MAP_DATA_TYPE_BFLOAT16, 3, const_cast<void*>(ptr), dims, strides, box, es, CU_TENSOR_MAP_INTERLEAVE_NONE,
       swz, CU_TENSOR_MAP_L2_PROMOTION_L2_256B, CU_TENSOR_MAP_FLOAT_OOB_FILL_NONE);
}

template <typename... Args>
void launch_pdl(void (*kern)(Args...), int grid, int block, int smem, bool pdl, int cluster, Args... args) {
    cudaLaunchConfig_t cfg = {};
    cfg.gridDim = dim3(grid); cfg.blockDim = dim3(block); cfg.dynamicSmemBytes = smem; cfg.stream = cudaStreamPerThread;
    cudaLaunchAttribute at[2];
    int n = 0;
    if (pdl) {
        at[n].id = cudaLaunchAttributeProgrammaticStreamSerialization;
        at[n].val.programmaticStreamSerializationAllowed = 1;
        n++;
    }
    if (cluster > 1) {
        at[n].id = cudaLaunchAttributeClusterDimension;
        at[n].val.clusterDim.x = cluster; at[n].val.clusterDim.y = 1; at[n].val.clusterDim.z = 1;
        n++;
    }
    cfg.attrs = at; cfg.numAttrs = n;
    cudaLaunchKernelEx(&cfg, kern, args...);
}

}

extern "C" void kernel_launch(void* const* d_in, const int* in_sizes, int n_in, void* d_out, int out_size) {
    const __nv_bfloat16* x = (const __nv_bfloat16*)d_in[0];
    const __nv_bfloat16* A_re = (const __nv_bfloat16*)d_in[1];
    const __nv_bfloat16* A_im = (const __nv_bfloat16*)d_in[2];
    const __nv_bfloat16* B_re = (const __nv_bfloat16*)d_in[3];
    const __nv_bfloat16* B_im = (const __nv_bfloat16*)d_in[4];
    const __nv_bfloat16* C_re = (const __nv_bfloat16*)d_in[5];
    const __nv_bfloat16* C_im = (const __nv_bfloat16*)d_in[6];
    const __nv_bfloat16* log_dt = (const __nv_bfloat16*)d_in[7];
    const __nv_bfloat16* Dskip = (const __nv_bfloat16*)d_in[8];
    const __nv_bfloat16* wg = (const __nv_bfloat16*)d_in[10];
    const __nv_bfloat16* wu = (const __nv_bfloat16*)d_in[11];
    const __nv_bfloat16* wd = (const __nv_bfloat16*)d_in[12];
    __nv_bfloat16* out = (__nv_bfloat16*)d_out;

    static bool init = false;
    static CUtensorMap tm_xn, tm_wg4, tm_wu4, tm_wg3, tm_wu3, tm_hst, tm_hst96, tm_h, tm_wd, tm_x, tm_sT, tm_out;
    static const void* last_ptrs[5] = {nullptr, nullptr, nullptr, nullptr, nullptr};
    if (!init || last_ptrs[0] != wg || last_ptrs[1] != wu || last_ptrs[2] != wd || last_ptrs[3] != x || last_ptrs[4] != out) {
        void* fnp = nullptr;
        cudaDriverEntryPointQueryResult qres;
        cudaGetDriverEntryPoint("cuTensorMapEncodeTiled", &fnp, cudaEnableDefault, &qres);
        EncodeFn fn = (EncodeFn)fnp;
        void *p_xn, *p_h, *p_sT;
        cudaGetSymbolAddress(&p_xn, g_xn);
        cudaGetSymbolAddress(&p_h, g_h);
        cudaGetSymbolAddress(&p_sT, g_sT);
        make_map(fn, &tm_xn, p_xn, D_, L_, 64, 128);
        make_map3(fn, &tm_wg4, wg, F_, D_, 32, 32, 4, CU_TENSOR_MAP_SWIZZLE_64B);
        make_map3(fn, &tm_wu4, wu, F_, D_, 32, 32, 4, CU_TENSOR_MAP_SWIZZLE_64B);
        make_map3(fn, &tm_wg3, wg, F_, D_, 32, 32, 3, CU_TENSOR_MAP_SWIZZLE_64B);
        make_map3(fn, &tm_wu3, wu, F_, D_, 32, 32, 3, CU_TENSOR_MAP_SWIZZLE_64B);
        make_map(fn, &tm_hst, p_h, F_, L_, 16, 16, CU_TENSOR_MAP_SWIZZLE_NONE);
        make_map(fn, &tm_hst96, p_h, F_, L_, 96, 16, CU_TENSOR_MAP_SWIZZLE_NONE);
        make_map(fn, &tm_h, p_h, F_, L_, 64, 128);
        make_map3(fn, &tm_wd, wd, D_, F_, 64, 64, 2, CU_TENSOR_MAP_SWIZZLE_128B);
        make_map(fn, &tm_x, x, D_, L_, 64, 128);
        make_map(fn, &tm_sT, p_sT, L_, D_, 64, 64);
        make_map(fn, &tm_out, out, D_, L_, 64, 16);
        cudaFuncSetAttribute(mega_kernel, cudaFuncAttributeMaxDynamicSharedMemorySize, MG_SMEM);
        last_ptrs[0] = wg; last_ptrs[1] = wu; last_ptrs[2] = wd; last_ptrs[3] = x; last_ptrs[4] = out;
        init = true;
    }
    MegaParams P = {x, A_re, A_im, B_re, B_im, C_re, C_im, log_dt, Dskip, wg, wu, wd};
    launch_pdl(mega_kernel, 128, 384, MG_SMEM, false, 2, P, tm_xn, tm_wg4, tm_wu4, tm_wg3, tm_wu3, tm_h, tm_wd, tm_x, tm_sT, tm_out);
}
```

```cpp
#include <cuda_runtime.h>
#include <cuda_bf16.h>
#include <cuda.h>
#include <stdint.h>

namespace {

constexpr int L_ = 2048, D_ = 512, NS_ = 128, F_ = 1792;

__device__ __align__(1024) __nv_bfloat16 g_xn[L_ * D_];
__device__ __align__(1024) __nv_bfloat16 g_xnT[D_ * L_];
__device__ __align__(1024) __nv_bfloat16 g_sT[D_ * L_];
__device__ __align__(1024) __nv_bfloat16 g_h[L_ * F_];
__device__ unsigned int g_ln_count, g_conv_count, g_done_count, g_h_count[32];

#define STAMP(k, i)

__device__ __forceinline__ uint32_t smem_u32(const void* p) { return (uint32_t)__cvta_generic_to_shared(p); }
__device__ __forceinline__ void pdl_wait() { asm volatile("griddepcontrol.wait;" ::: "memory"); }
__device__ __forceinline__ void pdl_launch() { asm volatile("griddepcontrol.launch_dependents;" ::: "memory"); }

__device__ __forceinline__ void mbar_init(uint32_t bar, uint32_t cnt) {
    asm volatile("mbarrier.init.shared::cta.b64 [%0], %1;" ::"r"(bar), "r"(cnt) : "memory");
}
__device__ __forceinline__ void mbar_expect_tx(uint32_t bar, uint32_t bytes) {
    asm volatile("mbarrier.arrive.expect_tx.shared::cta.b64 _, [%0], %1;" ::"r"(bar), "r"(bytes) : "memory");
}
__device__ __forceinline__ void mbar_arrive(uint32_t bar) {
    asm volatile("mbarrier.arrive.shared::cta.b64 _, [%0];" ::"r"(bar) : "memory");
}
__device__ __forceinline__ void mbar_wait(uint32_t bar, uint32_t parity) {
    asm volatile(
        "{\n.reg .pred p;\n"
        "WAIT_LOOP:\n"
        "mbarrier.try_wait.parity.shared::cta.b64 p, [%0], %1;\n"
        "@p bra WAIT_DONE;\n"
        "bra WAIT_LOOP;\n"
        "WAIT_DONE:\n}\n" ::"r"(bar), "r"(parity) : "memory");
}
__device__ __forceinline__ void tma_load_2d(uint32_t dst, const CUtensorMap* tm, int c0, int c1, uint32_t bar) {
    asm volatile(
        "cp.async.bulk.tensor.2d.shared::cluster.global.mbarrier::complete_tx::bytes [%0], [%1, {%3, %4}], [%2];"
        ::"r"(dst), "l"((uint64_t)tm), "r"(bar), "r"(c0), "r"(c1) : "memory");
}
__device__ __forceinline__ void prefetch_tmap(const CUtensorMap* tm) {
    asm volatile("prefetch.tensormap [%0];" ::"l"((uint64_t)tm) : "memory");
}
__device__ __forceinline__ uint64_t make_desc(uint32_t addr, uint32_t lbo, uint32_t sbo, uint64_t mode = 1) {
    uint64_t d = 0;
    d |= (uint64_t)((addr & 0x3FFFF) >> 4);
    d |= (uint64_t)((lbo >> 4) & 0x3FFF) << 16;
    d |= (uint64_t)((sbo >> 4) & 0x3FFF) << 32;
    d |= mode << 62;
    return d;
}
__device__ __forceinline__ void fence_async_smem() { asm volatile("fence.proxy.async.shared::cta;" ::: "memory"); }
__device__ __forceinline__ void wgmma_fence() { asm volatile("wgmma.fence.sync.aligned;" ::: "memory"); }
__device__ __forceinline__ void wgmma_commit() { asm volatile("wgmma.commit_group.sync.aligned;" ::: "memory"); }
template <int N> __device__ __forceinline__ void wgmma_wait() {
    asm volatile("wgmma.wait_group.sync.aligned %0;" ::"n"(N) : "memory");
}

#define R8(a, i) "+f"(a[i + 0]), "+f"(a[i + 1]), "+f"(a[i + 2]), "+f"(a[i + 3]), "+f"(a[i + 4]), "+f"(a[i + 5]), "+f"(a[i + 6]), "+f"(a[i + 7])

__device__ __forceinline__ void wgmma_n256_k32(float* a, uint64_t da0, uint64_t da1, uint64_t db0, uint64_t db1, int scale_d) {
    asm volatile(
        "{\n.reg .pred p;\nsetp.ne.b32 p, %132, 0;\n"
        "wgmma.mma_async.sync.aligned.m64n256k16.f32.bf16.bf16 {%0,%1,%2,%3,%4,%5,%6,%7,%8,%9,%10,%11,%12,%13,%14,%15,%16,%17,%18,%19,%20,%21,%22,%23,%24,%25,%26,%27,%28,%29,%30,%31,%32,%33,%34,%35,%36,%37,%38,%39,%40,%41,%42,%43,%44,%45,%46,%47,%48,%49,%50,%51,%52,%53,%54,%55,%56,%57,%58,%59,%60,%61,%62,%63,%64,%65,%66,%67,%68,%69,%70,%71,%72,%73,%74,%75,%76,%77,%78,%79,%80,%81,%82,%83,%84,%85,%86,%87,%88,%89,%90,%91,%92,%93,%94,%95,%96,%97,%98,%99,%100,%101,%102,%103,%104,%105,%106,%107,%108,%109,%110,%111,%112,%113,%114,%115,%116,%117,%118,%119,%120,%121,%122,%123,%124,%125,%126,%127}, %128, %130, p, 1, 1, 0, 1;\n"
        "wgmma.mma_async.sync.aligned.m64n256k16.f32.bf16.bf16 {%0,%1,%2,%3,%4,%5,%6,%7,%8,%9,%10,%11,%12,%13,%14,%15,%16,%17,%18,%19,%20,%21,%22,%23,%24,%25,%26,%27,%28,%29,%30,%31,%32,%33,%34,%35,%36,%37,%38,%39,%40,%41,%42,%43,%44,%45,%46,%47,%48,%49,%50,%51,%52,%53,%54,%55,%56,%57,%58,%59,%60,%61,%62,%63,%64,%65,%66,%67,%68,%69,%70,%71,%72,%73,%74,%75,%76,%77,%78,%79,%80,%81,%82,%83,%84,%85,%86,%87,%88,%89,%90,%91,%92,%93,%94,%95,%96,%97,%98,%99,%100,%101,%102,%103,%104,%105,%106,%107,%108,%109,%110,%111,%112,%113,%114,%115,%116,%117,%118,%119,%120,%121,%122,%123,%124,%125,%126,%127}, %129, %131, 1, 1, 1, 0, 1;\n"
        "}\n"
        : R8(a, 0), R8(a, 8), R8(a, 16), R8(a, 24), R8(a, 32), R8(a, 40), R8(a, 48), R8(a, 56), R8(a, 64), R8(a, 72), R8(a, 80), R8(a, 88), R8(a, 96), R8(a, 104), R8(a, 112), R8(a, 120)
        : "l"(da0), "l"(da1), "l"(db0), "l"(db1), "r"(scale_d));
}
__device__ __forceinline__ void wgmma_n192_k32(float* a, uint64_t da0, uint64_t da1, uint64_t db0, uint64_t db1, int scale_d) {
    asm volatile(
        "{\n.reg .pred p;\nsetp.ne.b32 p, %100, 0;\n"
        "wgmma.mma_async.sync.aligned.m64n192k16.f32.bf16.bf16 {%0,%1,%2,%3,%4,%5,%6,%7,%8,%9,%10,%11,%12,%13,%14,%15,%16,%17,%18,%19,%20,%21,%22,%23,%24,%25,%26,%27,%28,%29,%30,%31,%32,%33,%34,%35,%36,%37,%38,%39,%40,%41,%42,%43,%44,%45,%46,%47,%48,%49,%50,%51,%52,%53,%54,%55,%56,%57,%58,%59,%60,%61,%62,%63,%64,%65,%66,%67,%68,%69,%70,%71,%72,%73,%74,%75,%76,%77,%78,%79,%80,%81,%82,%83,%84,%85,%86,%87,%88,%89,%90,%91,%92,%93,%94,%95}, %96, %98, p, 1, 1, 0, 1;\n"
        "wgmma.mma_async.sync.aligned.m64n192k16.f32.bf16.bf16 {%0,%1,%2,%3,%4,%5,%6,%7,%8,%9,%10,%11,%12,%13,%14,%15,%16,%17,%18,%19,%20,%21,%22,%23,%24,%25,%26,%27,%28,%29,%30,%31,%32,%33,%34,%35,%36,%37,%38,%39,%40,%41,%42,%43,%44,%45,%46,%47,%48,%49,%50,%51,%52,%53,%54,%55,%56,%57,%58,%59,%60,%61,%62,%63,%64,%65,%66,%67,%68,%69,%70,%71,%72,%73,%74,%75,%76,%77,%78,%79,%80,%81,%82,%83,%84,%85,%86,%87,%88,%89,%90,%91,%92,%93,%94,%95}, %97, %99, 1, 1, 1, 0, 1;\n"
        "}\n"
        : R8(a, 0), R8(a, 8), R8(a, 16), R8(a, 24), R8(a, 32), R8(a, 40), R8(a, 48), R8(a, 56), R8(a, 64), R8(a, 72), R8(a, 80), R8(a, 88)
        : "l"(da0), "l"(da1), "l"(db0), "l"(db1), "r"(scale_d));
}
__device__ __forceinline__ void wgmma_n192(float* a, uint64_t da0, uint64_t db0, int scale_d) {
    asm volatile(
        "{\n.reg .pred p;\nsetp.ne.b32 p, %98, 0;\n"
        "wgmma.mma_async.sync.aligned.m64n192k16.f32.bf16.bf16 {%0,%1,%2,%3,%4,%5,%6,%7,%8,%9,%10,%11,%12,%13,%14,%15,%16,%17,%18,%19,%20,%21,%22,%23,%24,%25,%26,%27,%28,%29,%30,%31,%32,%33,%34,%35,%36,%37,%38,%39,%40,%41,%42,%43,%44,%45,%46,%47,%48,%49,%50,%51,%52,%53,%54,%55,%56,%57,%58,%59,%60,%61,%62,%63,%64,%65,%66,%67,%68,%69,%70,%71,%72,%73,%74,%75,%76,%77,%78,%79,%80,%81,%82,%83,%84,%85,%86,%87,%88,%89,%90,%91,%92,%93,%94,%95}, %96, %97, p, 1, 1, 0, 1;\n"
        "}\n"
        : R8(a, 0), R8(a, 8), R8(a, 16), R8(a, 24), R8(a, 32), R8(a, 40), R8(a, 48), R8(a, 56), R8(a, 64), R8(a, 72), R8(a, 80), R8(a, 88)
        : "l"(da0), "l"(db0), "r"(scale_d));
}
__device__ __forceinline__ void wgmma_n128_k64(float* a, uint64_t da0, uint64_t da1, uint64_t da2, uint64_t da3,
                                               uint64_t db0, uint64_t db1, uint64_t db2, uint64_t db3, int scale_d) {
    asm volatile(
        "{\n.reg .pred p;\nsetp.ne.b32 p, %72, 0;\n"
        "wgmma.mma_async.sync.aligned.m64n128k16.f32.bf16.bf16 {%0,%1,%2,%3,%4,%5,%6,%7,%8,%9,%10,%11,%12,%13,%14,%15,%16,%17,%18,%19,%20,%21,%22,%23,%24,%25,%26,%27,%28,%29,%30,%31,%32,%33,%34,%35,%36,%37,%38,%39,%40,%41,%42,%43,%44,%45,%46,%47,%48,%49,%50,%51,%52,%53,%54,%55,%56,%57,%58,%59,%60,%61,%62,%63}, %64, %68, p, 1, 1, 0, 1;\n"
        "wgmma.mma_async.sync.aligned.m64n128k16.f32.bf16.bf16 {%0,%1,%2,%3,%4,%5,%6,%7,%8,%9,%10,%11,%12,%13,%14,%15,%16,%17,%18,%19,%20,%21,%22,%23,%24,%25,%26,%27,%28,%29,%30,%31,%32,%33,%34,%35,%36,%37,%38,%39,%40,%41,%42,%43,%44,%45,%46,%47,%48,%49,%50,%51,%52,%53,%54,%55,%56,%57,%58,%59,%60,%61,%62,%63}, %65, %69, 1, 1, 1, 0, 1;\n"
        "wgmma.mma_async.sync.aligned.m64n128k16.f32.bf16.bf16 {%0,%1,%2,%3,%4,%5,%6,%7,%8,%9,%10,%11,%12,%13,%14,%15,%16,%17,%18,%19,%20,%21,%22,%23,%24,%25,%26,%27,%28,%29,%30,%31,%32,%33,%34,%35,%36,%37,%38,%39,%40,%41,%42,%43,%44,%45,%46,%47,%48,%49,%50,%51,%52,%53,%54,%55,%56,%57,%58,%59,%60,%61,%62,%63}, %66, %70, 1, 1, 1, 0, 1;\n"
        "wgmma.mma_async.sync.aligned.m64n128k16.f32.bf16.bf16 {%0,%1,%2,%3,%4,%5,%6,%7,%8,%9,%10,%11,%12,%13,%14,%15,%16,%17,%18,%19,%20,%21,%22,%23,%24,%25,%26,%27,%28,%29,%30,%31,%32,%33,%34,%35,%36,%37,%38,%39,%40,%41,%42,%43,%44,%45,%46,%47,%48,%49,%50,%51,%52,%53,%54,%55,%56,%57,%58,%59,%60,%61,%62,%63}, %67, %71, 1, 1, 1, 0, 1;\n"
        "}\n"
        : R8(a, 0), R8(a, 8), R8(a, 16), R8(a, 24), R8(a, 32), R8(a, 40), R8(a, 48), R8(a, 56)
        : "l"(da0), "l"(da1), "l"(da2), "l"(da3), "l"(db0), "l"(db1), "l"(db2), "l"(db3), "r"(scale_d));
}

__device__ __forceinline__ float bf16_round(float x) {
    uint32_t p; asm("cvt.rn.bf16x2.f32 %0, %1, %2;" : "=r"(p) : "f"(x), "f"(0.0f));
    return __uint_as_float(p);
}
__device__ __forceinline__ uint32_t pack_bf16(float lo, float hi) {
    __nv_bfloat162 v = __floats2bfloat162_rn(lo, hi);
    return *reinterpret_cast<uint32_t*>(&v);
}
__device__ __forceinline__ float bf_lo(uint32_t v) { return __uint_as_float(v << 16); }
__device__ __forceinline__ float bf_hi(uint32_t v) { return __uint_as_float(v & 0xFFFF0000u); }

struct cplx { float r, i; };
__device__ __forceinline__ cplx cmul(cplx a, cplx b) {
    cplx c; c.r = a.r * b.r - a.i * b.i; c.i = a.r * b.i + a.i * b.r; return c;
}
__device__ __forceinline__ cplx csq(cplx a) {
    cplx c; c.r = a.r * a.r - a.i * a.i; c.i = 2.0f * a.r * a.i; return c;
}
__device__ __forceinline__ cplx cexp_m(float ar2, float ai2, float m) {
    float mag;
    asm("ex2.approx.ftz.f32 %0, %1;" : "=f"(mag) : "f"(ar2 * m));
    float rr = ai2 * m;
    rr -= (rr + 12582912.0f) - 12582912.0f;
    float th = rr * 6.283185307179586f;
    cplx c; c.r = mag * __cosf(th); c.i = mag * __sinf(th);
    return c;
}
__device__ __forceinline__ uint32_t to_tf32(float x) { return __float_as_uint(x) + 0x1000u; }
__device__ __forceinline__ void mma_tf32(float* c, uint32_t a0, uint32_t a1, uint32_t a2, uint32_t a3, uint32_t b0, uint32_t b1) {
    asm volatile("mma.sync.aligned.m16n8k8.row.col.f32.tf32.tf32.f32 {%0,%1,%2,%3}, {%4,%5,%6,%7}, {%8,%9}, {%0,%1,%2,%3};"
                 : "+f"(c[0]), "+f"(c[1]), "+f"(c[2]), "+f"(c[3])
                 : "r"(a0), "r"(a1), "r"(a2), "r"(a3), "r"(b0), "r"(b1));
}
__device__ __forceinline__ void mma_bf16(float* c, uint32_t a0, uint32_t a1, uint32_t a2, uint32_t a3, uint32_t b0, uint32_t b1) {
    asm volatile("mma.sync.aligned.m16n8k16.row.col.f32.bf16.bf16.f32 {%0,%1,%2,%3}, {%4,%5,%6,%7}, {%8,%9}, {%0,%1,%2,%3};"
                 : "+f"(c[0]), "+f"(c[1]), "+f"(c[2]), "+f"(c[3])
                 : "r"(a0), "r"(a1), "r"(a2), "r"(a3), "r"(b0), "r"(b1));
}
__device__ __forceinline__ void named_bar(int id, int n) { asm volatile("bar.sync %0, %1;" ::"r"(id), "r"(n) : "memory"); }
__device__ __forceinline__ void ldsm_x4(uint32_t addr, uint32_t& r0, uint32_t& r1, uint32_t& r2, uint32_t& r3) {
    asm volatile("ldmatrix.sync.aligned.m8n8.x4.shared.b16 {%0,%1,%2,%3}, [%4];" : "=r"(r0), "=r"(r1), "=r"(r2), "=r"(r3) : "r"(addr));
}
__device__ __forceinline__ void ldsm_x4_t(uint32_t addr, uint32_t& r0, uint32_t& r1, uint32_t& r2, uint32_t& r3) {
    asm volatile("ldmatrix.sync.aligned.m8n8.x4.trans.shared.b16 {%0,%1,%2,%3}, [%4];" : "=r"(r0), "=r"(r1), "=r"(r2), "=r"(r3) : "r"(addr));
}

constexpr int CV_CH = 4;
constexpr int CV_O_CONST = 0;
constexpr int CV_O_KP = 12288;
constexpr int CV_EARLY = 12288 + 7776;
constexpr int CV_O_Q = 0;
constexpr int CV_O_Q2 = CV_O_Q + 2304;
constexpr int CV_O_Q3 = CV_O_Q2 + 1024;
constexpr int CV_O_Q4X = CV_O_Q3 + 768;
constexpr int CV_O_W3 = CV_O_Q4X + 256;
constexpr int CV_O_W5 = CV_O_W3 + 3104;
constexpr int CV_O_W7 = CV_O_W5 + 3104;
constexpr int CV_O_W9 = CV_O_W7 + 2048;
constexpr int CV_O_U = CV_O_W9 + 2048;
constexpr int CV_LATE = CV_O_U + 4352;
constexpr int CV_LATE_BASE = 229376 - CV_CH * CV_LATE;
constexpr int CV_TILE_OFF = CV_CH * CV_EARLY;
static_assert(CV_TILE_OFF + 16 * (D_ + 8) * 2 <= CV_LATE_BASE && CV_LATE_BASE >= 131072 + 16384, "front layout");
static_assert(CV_O_W3 >= 4096 && CV_O_U - CV_O_W3 >= 8192 && (CV_LATE % 16) == 0 && (CV_EARLY % 16) == 0, "front layout");

constexpr int LN_ROWS = 16;

template <typename PF>
__device__ __forceinline__ void front_phase(PF prefetch_fn, uint8_t* smem, const __nv_bfloat16* __restrict__ x,
                                            const __nv_bfloat16* __restrict__ A_re, const __nv_bfloat16* __restrict__ A_im,
                                            const __nv_bfloat16* __restrict__ B_re, const __nv_bfloat16* __restrict__ B_im,
                                            const __nv_bfloat16* __restrict__ C_re, const __nv_bfloat16* __restrict__ C_im,
                                            const __nv_bfloat16* __restrict__ log_dt, const __nv_bfloat16* __restrict__ Dskip,
                                            const __nv_bfloat16* __restrict__ wg, const __nv_bfloat16* __restrict__ wu,
                                            const __nv_bfloat16* __restrict__ wd) {
    const int warp = threadIdx.x >> 5, lane = threadIdx.x & 31;
    const int ch = warp / 3, w = warp - 3 * ch, tc = threadIdx.x - 96 * ch;
    const int d = blockIdx.x * CV_CH + ch;
    const int g = lane >> 2, t = lane & 3;
    uint8_t* base = smem + CV_LATE_BASE + ch * CV_LATE;
    float4* s_const = reinterpret_cast<float4*>(smem + ch * CV_EARLY + CV_O_CONST);
    float* s_kp = reinterpret_cast<float*>(smem + ch * CV_EARLY + CV_O_KP);
    uint32_t* s_q = reinterpret_cast<uint32_t*>(base + CV_O_Q);
    uint32_t* s_q2 = reinterpret_cast<uint32_t*>(base + CV_O_Q2);
    uint32_t* s_q3 = reinterpret_cast<uint32_t*>(base + CV_O_Q3);
    uint32_t* s_q4 = reinterpret_cast<uint32_t*>(base + CV_O_Q4X);
    __nv_bfloat16* s_u = reinterpret_cast<__nv_bfloat16*>(base + CV_O_U);
    const int bar_id = 5 + ch;
    const __nv_bfloat16 p_dsk = Dskip[d];
    __nv_bfloat16 (*tile)[D_ + 8] = reinterpret_cast<__nv_bfloat16 (*)[D_ + 8]>(smem + CV_TILE_OFF);

    if (warp < 8) {
        const int row = blockIdx.x * LN_ROWS + warp * 2;
        uint4 xv[2][2];
#pragma unroll
        for (int r = 0; r < 2; r++) {
            xv[r][0] = *reinterpret_cast<const uint4*>(x + (size_t)(row + r) * D_ + lane * 8);
            xv[r][1] = *reinterpret_cast<const uint4*>(x + (size_t)(row + r) * D_ + 256 + lane * 8);
        }
        float f[2][16], sm[2], q[2];
#pragma unroll
        for (int r = 0; r < 2; r++) {
            const uint32_t wv[8] = {xv[r][0].x, xv[r][0].y, xv[r][0].z, xv[r][0].w, xv[r][1].x, xv[r][1].y, xv[r][1].z, xv[r][1].w};
#pragma unroll
            for (int i = 0; i < 8; i++) { f[r][2 * i] = bf_lo(wv[i]); f[r][2 * i + 1] = bf_hi(wv[i]); }
            sm[r] = 0.f;
#pragma unroll
            for (int i = 0; i < 16; i++) sm[r] += f[r][i];
        }
#pragma unroll
        for (int o = 16; o > 0; o >>= 1) { sm[0] += __shfl_xor_sync(0xffffffffu, sm[0], o); sm[1] += __shfl_xor_sync(0xffffffffu, sm[1], o); }
#pragma unroll
        for (int r = 0; r < 2; r++) {
            sm[r] *= (1.0f / D_);
            q[r] = 0.f;
#pragma unroll
            for (int i = 0; i < 16; i++) { float dd = f[r][i] - sm[r]; q[r] += dd * dd; }
        }
#pragma unroll
        for (int o = 16; o > 0; o >>= 1) { q[0] += __shfl_xor_sync(0xffffffffu, q[0], o); q[1] += __shfl_xor_sync(0xffffffffu, q[1], o); }
#pragma unroll
        for (int r = 0; r < 2; r++) {
            const float mb = bf16_round(sm[r]);
            const float vb = bf16_round(q[r] * (1.0f / D_));
            const float den = bf16_round(sqrtf(bf16_round(vb + 1e-5f)));
            uint32_t o[8];
#pragma unroll
            for (int i = 0; i < 8; i++) {
                float a = __fdiv_rn(bf16_round(f[r][2 * i] - mb), den);
                float b = __fdiv_rn(bf16_round(f[r][2 * i + 1] - mb), den);
                o[i] = pack_bf16(a, b);
            }
            __nv_bfloat16* dst = g_xn + (size_t)(row + r) * D_;
            *reinterpret_cast<uint4*>(dst + lane * 8) = make_uint4(o[0], o[1], o[2], o[3]);
            *reinterpret_cast<uint4*>(dst + 256 + lane * 8) = make_uint4(o[4], o[5], o[6], o[7]);
            *reinterpret_cast<uint4*>(&tile[warp * 2 + r][lane * 8]) = make_uint4(o[0], o[1], o[2], o[3]);
            *reinterpret_cast<uint4*>(&tile[warp * 2 + r][256 + lane * 8]) = make_uint4(o[4], o[5], o[6], o[7]);
        }
    } else {
        const int cc_ = warp - 8, dd = blockIdx.x * CV_CH + cc_;
        float4* sc = reinterpret_cast<float4*>(smem + cc_ * CV_EARLY + CV_O_CONST);
        __nv_bfloat16 pr[4][6];
#pragma unroll
        for (int j = 0; j < 4; j++) {
            const size_t off = (size_t)dd * NS_ + lane + 32 * j;
            pr[j][0] = A_re[off]; pr[j][1] = A_im[off]; pr[j][2] = B_re[off]; pr[j][3] = B_im[off]; pr[j][4] = C_re[off]; pr[j][5] = C_im[off];
        }
        const float dt = bf16_round(expf(__bfloat162float(log_dt[dd])));
        float tail = 0.f;
#pragma unroll
        for (int j = 0; j < 4; j++) {
            const float ar = dt * __bfloat162float(pr[j][0]), ai = dt * __bfloat162float(pr[j][1]);
            const cplx db = {dt * __bfloat162float(pr[j][2]), dt * __bfloat162float(pr[j][3])};
            const cplx cc = {__bfloat162float(pr[j][4]), __bfloat162float(pr[j][5])};
            const cplx cb = cmul(cc, db);
            const float ar2 = ar * 1.4426950408889634f, ai2 = ai * 0.15915494309189535f;
            const cplx e8 = cexp_m(ar2, ai2, 8.f), e128 = cexp_m(ar2, ai2, 128.f);
            const cplx cb8 = cmul(cb, e8);
            const cplx e256 = cexp_m(ar2, ai2, 256.f), e512 = cexp_m(ar2, ai2, 512.f), e1024 = cexp_m(ar2, ai2, 1024.f);
            const cplx c256 = cmul(cb, e256), c512 = cmul(cb, e512), c1024 = cmul(cb, e1024);
            const cplx c768 = cmul(c512, e256), c1280 = cmul(c1024, e256), c1536 = cmul(c1024, e512);
            const cplx c1792 = cmul(c1536, e256);
            tail += cmul(c1024, e1024).r;
            float4* c = sc + (lane + 32 * j) * 6;
            c[0] = make_float4(ar2, ai2, cb.r, cb.i);
            c[1] = make_float4(e128.r, e128.i, cb8.r, cb8.i);
            c[2] = make_float4(c256.r, c256.i, e8.r, e8.i);
            c[3] = make_float4(c512.r, c512.i, c768.r, c768.i);
            c[4] = make_float4(c1024.r, c1024.i, c1280.r, c1280.i);
            c[5] = make_float4(c1536.r, c1536.i, c1792.r, c1792.i);
        }
#pragma unroll
        for (int o = 16; o > 0; o >>= 1) tail += __shfl_xor_sync(0xffffffffu, tail, o);
        if (lane == 0) {
            float* kp = reinterpret_cast<float*>(smem + cc_ * CV_EARLY + CV_O_KP);
            kp[640] = tail; kp[648 + 640] = 0.f; kp[1296 + 640] = 0.f;
        }
    }
    __syncthreads();
    if (threadIdx.x == 0) STAMP(0, 3);
#pragma unroll
    for (int rep = 0; rep < 2; rep++) {
        const int c = threadIdx.x + 384 * rep;
        if (c < D_) {
            uint32_t ot[8];
#pragma unroll
            for (int i = 0; i < 8; i++) {
                uint32_t lo = *reinterpret_cast<const uint16_t*>(&tile[2 * i][c]);
                uint32_t hi = *reinterpret_cast<const uint16_t*>(&tile[2 * i + 1][c]);
                ot[i] = lo | (hi << 16);
            }
            __nv_bfloat16* dT = g_xnT + (size_t)c * L_ + blockIdx.x * LN_ROWS;
            *reinterpret_cast<uint4*>(dT) = make_uint4(ot[0], ot[1], ot[2], ot[3]);
            *reinterpret_cast<uint4*>(dT + 8) = make_uint4(ot[4], ot[5], ot[6], ot[7]);
        }
    }
    if (threadIdx.x < 336) {
        const int m = threadIdx.x / 112, i = threadIdx.x - m * 112;
        const char* wp = (const char*)(m == 0 ? wg : (m == 1 ? wu : wd));
        asm volatile("prefetch.global.L2 [%0];" ::"l"(wp + ((size_t)blockIdx.x * 112 + i) * 128));
    }
    __syncthreads();
    if (threadIdx.x == 0) STAMP(1, 1);
    {
        float acc[5][4];
#pragma unroll
        for (int i = 0; i < 5; i++) { acc[i][0] = acc[i][1] = acc[i][2] = acc[i][3] = 0.f; }
        const float gf = (float)g;
        const int src4 = ((g & 3) << 2) | t;
#pragma unroll 2
        for (int s = w; s < 32; s += 3) {
            if (s == 17 && threadIdx.x == 352) asm volatile("red.release.gpu.global.add.u32 [%0], 1;" ::"l"(&g_ln_count) : "memory");
            const float4* c = s_const + (s * 4 + t) * 6;
            const float4 k0 = c[0], k1 = c[1], k2 = c[2];
            const float2 k3 = reinterpret_cast<const float2*>(c + 3)[g >> 2];
            const float2 k4 = reinterpret_cast<const float2*>(c + 4)[g >> 1];
            const cplx cb = {k0.z, k0.w}, e128 = {k1.x, k1.y}, cb8 = {k1.z, k1.w}, c256 = {k2.x, k2.y}, e8 = {k2.z, k2.w};
            const cplx c2 = {k3.x, k3.y}, c3 = {k4.x, k4.y};
            const cplx p1 = cexp_m(k0.x, k0.y, gf);
            const cplx p2 = csq(p1), p4 = csq(p2);
            const cplx r16a = csq(csq(p4));
            cplx q4;
            q4.r = __shfl_sync(0xffffffffu, p4.r, src4);
            q4.i = __shfl_sync(0xffffffffu, p4.i, src4);
            const cplx r16b = cmul(r16a, e128);
            const cplx f0a = cmul(cb, p1), f0b = cmul(cb8, p1), f1 = cmul(c256, p2), f2 = cmul(c2, q4);
            cplx f3 = cmul(c3, e8);
            if (!(g & 1)) f3 = c3;
            const uint32_t a0 = to_tf32(r16a.r), a1 = to_tf32(r16b.r), a2 = to_tf32(-r16a.i), a3 = to_tf32(-r16b.i);
            mma_tf32(acc[0], a0, a1, a2, a3, to_tf32(f0a.r), to_tf32(f0a.i));
            mma_tf32(acc[1], a0, a1, a2, a3, to_tf32(f0b.r), to_tf32(f0b.i));
            mma_tf32(acc[2], a0, a1, a2, a3, to_tf32(f1.r), to_tf32(f1.i));
            mma_tf32(acc[3], a0, a1, a2, a3, to_tf32(f2.r), to_tf32(f2.i));
            mma_tf32(acc[4], a0, a1, a2, a3, to_tf32(f3.r), to_tf32(f3.i));
        }
        float* kv = s_kp + w * 648;
#pragma unroll
        for (int hh = 0; hh < 2; hh++) {
            const int i = g + 8 * hh;
            *reinterpret_cast<float2*>(kv + 16 * i + 2 * t) = make_float2(acc[0][2 * hh], acc[0][2 * hh + 1]);
            *reinterpret_cast<float2*>(kv + 16 * i + 8 + 2 * t) = make_float2(acc[1][2 * hh], acc[1][2 * hh + 1]);
            *reinterpret_cast<float2*>(kv + 256 + 8 * i + 2 * t) = make_float2(acc[2][2 * hh], acc[2][2 * hh + 1]);
            *reinterpret_cast<float2*>(kv + 384 + 64 * (t >> 1) + 2 * (t & 1) + 4 * i) = make_float2(acc[3][2 * hh], acc[3][2 * hh + 1]);
            *reinterpret_cast<float2*>(kv + 512 + 32 * t + 2 * i) = make_float2(acc[4][2 * hh], acc[4][2 * hh + 1]);
        }
    }
    named_bar(bar_id, 96);
    if (threadIdx.x == 0) STAMP(1, 2);
#pragma unroll
    for (int i = 0; i < 7; i++) {
        const int idx = tc + 96 * i;
        if (idx < 641) s_kp[idx] = (s_kp[idx] + s_kp[648 + idx]) + s_kp[1296 + idx];
    }
    named_bar(bar_id, 96);
    {
        auto kdir = [&](int l) -> float {
            if (l < 0 || l > 514) return 0.f;
            const int idx = (l < 256) ? l : (l > 512 ? 384 : 128 + ((l + ((l >> 1) & 1)) >> 1));
            return s_kp[idx];
        };
#pragma unroll
        for (int i = 0; i < 6; i++) {
            const int e = tc + 96 * i;
            s_q[e] = pack_bf16(kdir(e - 16), kdir(e - 17));
        }
        if (tc < 64) {
            const int xx = 1008 + tc;
            const float k1024 = s_kp[512];
            s_q4[tc] = pack_bf16((xx == 1027 || xx == 1028) ? k1024 : 0.f, (xx == 1028 || xx == 1029) ? k1024 : 0.f);
        }
#pragma unroll
        for (int i = 0; i < 3; i++) {
            const int e = tc + 96 * i;
            if (e < 256) {
                const int a = e >> 6, ii = (e & 63) - 16;
                const int b = 385 + (a >> 1) + 2 * (a & 1);
                const float v0 = (ii >= 0 && ii < 32) ? s_kp[b + 4 * ii] : 0.f;
                const float v1 = (ii >= 1 && ii < 33) ? s_kp[b + 4 * (ii - 1)] : 0.f;
                s_q2[e] = pack_bf16(v0, v1);
            }
        }
#pragma unroll
        for (int a = 0; a < 2; a++) {
            const int jj = tc - 16;
            const float v0 = (jj >= 0 && jj < 64) ? s_kp[513 + a + 2 * jj] : 0.f;
            const float v1 = (jj >= 1 && jj < 65) ? s_kp[513 + a + 2 * (jj - 1)] : 0.f;
            s_q3[96 * a + tc] = pack_bf16(v0, v1);
        }
    }
    if (threadIdx.x == 0) STAMP(1, 3);
    if (threadIdx.x == 0) {
        unsigned int v = 0;
        for (int spin = 0; spin < (1 << 22); spin++) {
            asm volatile("ld.acquire.gpu.global.u32 %0, [%1];" : "=r"(v) : "l"(&g_ln_count) : "memory");
            if (v >= gridDim.x) break;
        }
    }
    fence_async_smem();
    __syncthreads();
    if (threadIdx.x == 0) STAMP(1, 4);
    prefetch_fn();
    {
        if (tc < 16) *reinterpret_cast<uint4*>(s_u + tc * 8) = make_uint4(0, 0, 0, 0);
        const uint4* src = reinterpret_cast<const uint4*>(g_xnT + (size_t)d * L_);
        uint4 v[3];
#pragma unroll
        for (int i = 0; i < 3; i++) if (tc + 96 * i < 256) v[i] = src[tc + 96 * i];
#pragma unroll
        for (int i = 0; i < 3; i++) if (tc + 96 * i < 256) *reinterpret_cast<uint4*>(s_u + 128 + (tc + 96 * i) * 8) = v[i];
        if (tc < 2) *reinterpret_cast<uint4*>(base + (tc ? CV_O_W5 : CV_O_W3)) = make_uint4(0, 0, 0, 0);
    }
    named_bar(bar_id, 96);
#pragma unroll
    for (int rep = 0; rep < 2; rep++) {
        const int m = tc + 96 * rep;
        float P[30];
        const uint4* up = reinterpret_cast<const uint4*>(s_u + 128 + 8 * m - 24);
        P[0] = 0.f;
#pragma unroll
        for (int c4 = 0; c4 < 4; c4++) {
            const uint4 v = up[c4];
            const uint32_t ww[4] = {v.x, v.y, v.z, v.w};
#pragma unroll
            for (int j = 0; j < 4; j++) {
                const int k = c4 * 8 + 2 * j;
                if (k + 1 <= 29) P[k + 1] = P[k] + bf_lo(ww[j]);
                if (k + 2 <= 29) P[k + 2] = P[k + 1] + bf_hi(ww[j]);
            }
        }
        uint32_t o3[4], o5[4], o7[4], o9[4];
#pragma unroll
        for (int j = 0; j < 4; j++) {
            const int i = 2 * j;
            o3[j] = pack_bf16(P[i + 22] - P[i + 19], P[i + 23] - P[i + 20]);
            o5[j] = pack_bf16(P[i + 19] - P[i + 14], P[i + 20] - P[i + 15]);
            o7[j] = pack_bf16(P[i + 20] - P[i + 13], P[i + 21] - P[i + 14]);
            o9[j] = pack_bf16(P[i + 13] - P[i + 4], P[i + 14] - P[i + 5]);
        }
        *reinterpret_cast<uint4*>(base + CV_O_W3 + 16 + m * 16) = make_uint4(o3[0], o3[1], o3[2], o3[3]);
        *reinterpret_cast<uint4*>(base + CV_O_W5 + 16 + m * 16) = make_uint4(o5[0], o5[1], o5[2], o5[3]);
        if (m < 128) {
            *reinterpret_cast<uint4*>(base + CV_O_W7 + m * 16) = make_uint4(o7[0], o7[1], o7[2], o7[3]);
            *reinterpret_cast<uint4*>(base + CV_O_W9 + m * 16) = make_uint4(o9[0], o9[1], o9[2], o9[3]);
        }
    }
    if (threadIdx.x == 0) STAMP(1, 5);
    named_bar(bar_id, 96);
    if (w == 2) return;
    const int hb = w;
    float acc[16][4];
#pragma unroll
    for (int i = 0; i < 16; i++) { acc[i][0] = acc[i][1] = acc[i][2] = acc[i][3] = 0.f; }
    const uint32_t sb_addr = smem_u32(base);
    const int mi = lane >> 3, rowi = lane & 7;
#pragma unroll 1
    for (int rr = 0; rr < 4; rr++) {
        const int r = 4 * hb + rr;
        uint32_t ub[16][2];
        {
            const uint32_t addr = sb_addr + CV_O_U + (uint32_t)((128 + 16 * (8 * (mi >> 1) + rowi - r) + 8 * (mi & 1)) * 2);
#pragma unroll
            for (int j = 0; j < 16; j += 2) ldsm_x4(addr + (uint32_t)(j * 256), ub[j][0], ub[j][1], ub[j + 1][0], ub[j + 1][1]);
        }
        const uint32_t* qp = s_q + 16 + 16 * r + g - 2 * t;
        uint32_t af[4][3];
#pragma unroll
        for (int q = 0; q < 4; q++) { af[q][0] = qp[128 * q]; af[q][1] = qp[128 * q + 8]; af[q][2] = qp[128 * q - 8]; }
#pragma unroll
        for (int q = 0; q < 4; q++) {
#pragma unroll
            for (int nt = q; nt < 16; nt++) mma_bf16(acc[nt], af[q][0], af[q][1], af[q][2], af[q][0], ub[nt - q][0], ub[nt - q][1]);
        }
        if (r < 2) {
            {
                const uint32_t a0 = qp[512], a1 = qp[520], a2 = qp[504];
#pragma unroll
                for (int nt = 4; nt < 16; nt++) mma_bf16(acc[nt], a0, a1, a2, a0, ub[nt - 4][0], ub[nt - 4][1]);
            }
            {
                const uint32_t* q4p = s_q4 + 16 + 16 * r + g - 2 * t;
                const uint32_t a0 = q4p[0], a1 = q4p[8], a2 = q4p[-8];
#pragma unroll
                for (int nt = 8; nt < 16; nt++) mma_bf16(acc[nt], a0, a1, a2, a0, ub[nt - 8][0], ub[nt - 8][1]);
            }
        }
    }
#pragma unroll 1
    for (int a = hb; a <= 3 * hb; a++) {
        uint32_t bq[7];
        const uint32_t* q2 = s_q2 + a * 64 + 16 + g - 2 * t - 32;
#pragma unroll
        for (int dlt = 3; dlt <= 9; dlt++) bq[dlt - 3] = q2[8 * dlt];
        const uint32_t addr = sb_addr + ((a >> 1) ? CV_O_W5 : CV_O_W3) + (uint32_t)((8 + 16 * (8 * (mi >> 1) + rowi) + 8 * (mi & 1) - 8 * (a & 1)) * 2);
        uint32_t aa[6][4];
#pragma unroll
        for (int kp = 0; kp < 6; kp++) ldsm_x4_t(addr + kp * 512, aa[kp][0], aa[kp][1], aa[kp][2], aa[kp][3]);
#pragma unroll
        for (int kp = 0; kp < 6; kp++) {
#pragma unroll
            for (int dlt = 4; dlt <= 9; dlt++) {
                if (2 * kp + dlt < 16) mma_bf16(acc[2 * kp + dlt], aa[kp][0], aa[kp][1], aa[kp][2], aa[kp][3], bq[dlt - 3], bq[dlt - 4]);
            }
        }
    }
    if (hb == 0) {
#pragma unroll 1
        for (int a = 0; a < 2; a++) {
            uint32_t bq[9];
            const uint32_t* q3 = s_q3 + a * 96 + 16 + g - 2 * t - 64;
#pragma unroll
            for (int dlt = 7; dlt <= 15; dlt++) bq[dlt - 7] = q3[8 * dlt];
            const uint32_t addr = sb_addr + (a ? CV_O_W9 : CV_O_W7) + (uint32_t)((16 * (8 * (mi >> 1) + rowi) + 8 * (mi & 1)) * 2);
            uint32_t aa[4][4];
#pragma unroll
            for (int kp = 0; kp < 4; kp++) ldsm_x4_t(addr + kp * 512, aa[kp][0], aa[kp][1], aa[kp][2], aa[kp][3]);
#pragma unroll
            for (int kp = 0; kp < 4; kp++) {
#pragma unroll
                for (int dlt = 8; dlt <= 15; dlt++) {
                    if (2 * kp + dlt < 16) mma_bf16(acc[2 * kp + dlt], aa[kp][0], aa[kp][1], aa[kp][2], aa[kp][3], bq[dlt - 7], bq[dlt - 8]);
                }
            }
        }
    }
    if (threadIdx.x == 0) STAMP(1, 6);
    named_bar(bar_id, 64);
    {
        float4* xch = reinterpret_cast<float4*>(base + CV_O_W3) + hb * 256;
        if (hb) {
#pragma unroll
            for (int i = 0; i < 8; i++) xch[i * 32 + lane] = make_float4(acc[i][0], acc[i][1], acc[i][2], acc[i][3]);
#pragma unroll
            for (int i = 0; i < 8; i++) { acc[i][0] = acc[8 + i][0]; acc[i][1] = acc[8 + i][1]; acc[i][2] = acc[8 + i][2]; acc[i][3] = acc[8 + i][3]; }
        } else {
#pragma unroll
            for (int i = 0; i < 8; i++) xch[i * 32 + lane] = make_float4(acc[8 + i][0], acc[8 + i][1], acc[8 + i][2], acc[8 + i][3]);
        }
    }
    named_bar(bar_id, 64);
    if (threadIdx.x == 0) STAMP(1, 10);
    {
        const float4* xch = reinterpret_cast<const float4*>(base + CV_O_W3) + (hb ^ 1) * 256 + lane;
        const float dsk = __bfloat162float(p_dsk);
        uint16_t* stg = reinterpret_cast<uint16_t*>(base + CV_O_Q);
        const uint16_t* uu = reinterpret_cast<const uint16_t*>(s_u) + 128;
#pragma unroll
        for (int i = 0; i < 8; i++) {
            const float4 p0 = xch[i * 32];
            const float y[4] = {acc[i][0] + p0.x, acc[i][1] + p0.y, acc[i][2] + p0.z, acc[i][3] + p0.w};
            const int nt = 8 * hb + i;
#pragma unroll
            for (int e = 0; e < 4; e++) {
                const int tau = 16 * (8 * nt + 2 * t + (e & 1)) + g + 8 * (e >> 1);
                const float sv = bf16_round(y[e]) + bf16_round(__uint_as_float((uint32_t)uu[tau] << 16) * dsk);
                stg[tau] = (uint16_t)(__float_as_uint(bf16_round(sv)) >> 16);
            }
        }
        __syncwarp();
        if (threadIdx.x == 0) STAMP(1, 11);
        uint4* dst = reinterpret_cast<uint4*>(g_sT + (size_t)d * L_ + hb * 1024);
        const uint4* srcp = reinterpret_cast<const uint4*>(stg + hb * 1024);
#pragma unroll
        for (int i = 0; i < 4; i++) dst[i * 32 + lane] = srcp[i * 32 + lane];
    }
}

__device__ __forceinline__ uint32_t cluster_rank() { uint32_t r; asm volatile("mov.u32 %0, %%cluster_ctarank;" : "=r"(r)); return r; }
__device__ __forceinline__ void cluster_sync_all() {
    asm volatile("barrier.cluster.arrive.release.aligned;\nbarrier.cluster.wait.acquire.aligned;" ::: "memory");
}
__device__ __forceinline__ void mbar_arrive_remote(uint32_t bar, uint32_t cta) {
    asm volatile("{\n.reg .b32 ra;\nmapa.shared::cluster.u32 ra, %0, %1;\n"
                 "mbarrier.arrive.shared::cluster.b64 _, [ra];\n}\n" ::"r"(bar), "r"(cta) : "memory");
}
__device__ __forceinline__ void tma_load_2d_mc(uint32_t dst, const CUtensorMap* tm, int c0, int c1, uint32_t bar, uint16_t mask) {
    asm volatile(
        "cp.async.bulk.tensor.2d.shared::cluster.global.mbarrier::complete_tx::bytes.multicast::cluster [%0], [%1, {%3, %4}], [%2], %5;"
        ::"r"(dst), "l"((uint64_t)tm), "r"(bar), "r"(c0), "r"(c1), "h"(mask) : "memory");
}
__device__ __forceinline__ void tma_store_2d(const CUtensorMap* tm, uint32_t src, int c0, int c1) {
    asm volatile("cp.async.bulk.tensor.2d.global.shared::cta.bulk_group [%0, {%2, %3}], [%1];"
                 ::"l"((uint64_t)tm), "r"(src), "r"(c0), "r"(c1) : "memory");
}
__device__ __forceinline__ void bulk_commit() { asm volatile("cp.async.bulk.commit_group;" ::: "memory"); }
template <int N> __device__ __forceinline__ void bulk_wait_read() { asm volatile("cp.async.bulk.wait_group.read %0;" ::"n"(N) : "memory"); }
template <int N> __device__ __forceinline__ void bulk_wait() { asm volatile("cp.async.bulk.wait_group %0;" ::"n"(N) : "memory"); }
__device__ __forceinline__ void stmatrix_x4(uint32_t addr, uint32_t r0, uint32_t r1, uint32_t r2, uint32_t r3) {
    asm volatile("stmatrix.sync.aligned.m8n8.x4.shared.b16 [%0], {%1,%2,%3,%4};" ::"r"(addr), "r"(r0), "r"(r1), "r"(r2), "r"(r3) : "memory");
}

constexpr int G1_STAGES = 5;
constexpr int G1_A_BYTES = 8 * 16384;
constexpr int G1_B_STAGE = 16384;
constexpr int G1_STG = 8 * 1024;
constexpr int G1_SMEM = G1_A_BYTES + G1_STAGES * G1_B_STAGE + G1_STG + 1024 + 256;
constexpr int G1_ITERS = 32;

__device__ __forceinline__ void tma_load_3d(uint32_t dst, const CUtensorMap* tm, int c0, int c1, int c2, uint32_t bar) {
    asm volatile(
        "cp.async.bulk.tensor.3d.shared::cluster.global.mbarrier::complete_tx::bytes [%0], [%1, {%3, %4, %5}], [%2];"
        ::"r"(dst), "l"((uint64_t)tm), "r"(bar), "r"(c0), "r"(c1), "r"(c2) : "memory");
}

__device__ __forceinline__ float gelu_tanh(float x) {
    float u = x * (0.7978845608028654f + 0.035677408136300125f * x * x);
    float t; asm("tanh.approx.f32 %0, %1;" : "=f"(t) : "f"(u));
    float hx = 0.5f * x;
    return fmaf(hx, t, hx);
}
__device__ __forceinline__ uint32_t geglu_pair(uint32_t g2, uint32_t u2) {
    uint32_t a = pack_bf16(gelu_tanh(bf_lo(g2)), gelu_tanh(bf_hi(g2)));
    uint32_t r; asm("mul.rn.bf16x2 %0, %1, %2;" : "=r"(r) : "r"(a), "r"(u2));
    return r;
}

constexpr int G2_STAGES = 5;
constexpr int G2_STAGE = 16384 + 16384;
constexpr int G2_XCH = 32768;
constexpr int G2_EPI = 16384 + 16384;
constexpr int G2_SMEM = G2_STAGES * G2_STAGE + G2_XCH + G2_EPI + 1024 + 256;
constexpr int G2_KB = F_ / 64 / 2;

constexpr int MG_BAR_OFF = G2_STAGES * G2_STAGE + G2_XCH + G2_EPI;
constexpr int MG_SMEM = MG_BAR_OFF + 256 + 1024;
static_assert(MG_BAR_OFF == 229376 && G1_A_BYTES + G1_STAGES * G1_B_STAGE + G1_STG <= MG_BAR_OFF, "smem layout");

__device__ __forceinline__ void fence_async_all() { asm volatile("fence.proxy.async;" ::: "memory"); }
__device__ __forceinline__ void spin_until(const unsigned int* p, unsigned int target) {
    unsigned int v = 0;
    for (int spin = 0; spin < (1 << 22); spin++) {
        asm volatile("ld.acquire.gpu.global.u32 %0, [%1];" : "=r"(v) : "l"(p) : "memory");
        if (v >= target) break;
    }
}

struct MegaParams {
    const __nv_bfloat16 *x, *A_re, *A_im, *B_re, *B_im, *C_re, *C_im, *log_dt, *Dskip, *wg, *wu, *wd;
};

__global__ void __launch_bounds__(384, 1) mega_kernel(const __grid_constant__ MegaParams P,
                                                       const __grid_constant__ CUtensorMap tm_xn,
                                                       const __grid_constant__ CUtensorMap tm_wg4,
                                                       const __grid_constant__ CUtensorMap tm_wu4,
                                                       const __grid_constant__ CUtensorMap tm_wg3,
                                                       const __grid_constant__ CUtensorMap tm_wu3,
                                                       const __grid_constant__ CUtensorMap tm_h,
                                                       const __grid_constant__ CUtensorMap tm_wd,
                                                       const __grid_constant__ CUtensorMap tm_x,
                                                       const __grid_constant__ CUtensorMap tm_sT,
                                                       const __grid_constant__ CUtensorMap tm_out) {
    if (threadIdx.x == 0) STAMP(1, 0);
    extern __shared__ uint8_t smem_raw[];
    const uint32_t sraw = smem_u32(smem_raw);
    const uint32_t sbase = (sraw + 1023) & ~1023u;
    uint8_t* smem = smem_raw + (sbase - sraw);
    const int warp = threadIdx.x >> 5, lane = threadIdx.x & 31;
    const uint32_t sA = sbase, sB = sbase + G1_A_BYTES, sStg = sB + G1_STAGES * G1_B_STAGE;
    const uint32_t sXch = sbase + G2_STAGES * G2_STAGE, sX = sXch + G2_XCH, sS = sX + 16384;
    const uint32_t sBar = sbase + MG_BAR_OFF;
    const uint32_t bar_a = sBar, bar_full = sBar + 64, bar_empty = bar_full + 8 * G1_STAGES;
    const uint32_t bar_full2 = bar_empty + 8 * G1_STAGES, bar_empty2 = bar_full2 + 8 * G2_STAGES;
    const uint32_t bar_epi = bar_empty2 + 8 * G2_STAGES, bar_xch = bar_epi + 8, bar_g1done = bar_xch + 8, bar_g1mma = bar_g1done + 8;
    const int rb = blockIdx.x >> 3, cj = blockIdx.x & 7;
    const uint32_t kh = blockIdx.x & 1;
    const int nb = (blockIdx.x >> 1) & 3;
    const int col_fin = nb * 128 + kh * 64;

    if (threadIdx.x == 0) {
        for (int i = 0; i < 8; i++) mbar_init(bar_a + 8 * i, 1);
        for (int i = 0; i < G1_STAGES; i++) { mbar_init(bar_full + 8 * i, 1); mbar_init(bar_empty + 8 * i, 8); }
        for (int i = 0; i < G2_STAGES; i++) { mbar_init(bar_full2 + 8 * i, 1); mbar_init(bar_empty2 + 8 * i, 8); }
        mbar_init(bar_epi, 1);
        mbar_init(bar_xch, 1);
        mbar_init(bar_g1done, 8);
        mbar_init(bar_g1mma, 8);
        asm volatile("fence.mbarrier_init.release.cluster;" ::: "memory");
        mbar_expect_tx(bar_xch, G2_XCH);
    }
    if (warp == 11 && lane == 0) {
        prefetch_tmap(&tm_wg4); prefetch_tmap(&tm_wu4); prefetch_tmap(&tm_xn); prefetch_tmap(&tm_wg3); prefetch_tmap(&tm_wu3);
        prefetch_tmap(&tm_wd); prefetch_tmap(&tm_h); prefetch_tmap(&tm_x); prefetch_tmap(&tm_sT); prefetch_tmap(&tm_out);
    }
    asm volatile("barrier.cluster.arrive.release.aligned;" ::: "memory");

    auto g1_prefetch = [&]() {
        if (warp == 8 && lane == 0) {
            fence_async_all();
            mbar_expect_tx(bar_full, 16384);
            tma_load_3d(sB, &tm_wg4, 0, 0, cj * 7, bar_full);
            tma_load_3d(sB + 8192, &tm_wu4, 0, 0, cj * 7, bar_full);
            for (int k = 0; k < 8; k++) {
                mbar_expect_tx(bar_a + 8 * k, 16384);
                tma_load_2d(sA + k * 16384, &tm_xn, k * 64, rb * 128, bar_a + 8 * k);
            }
        }
    };
    front_phase(g1_prefetch, smem, P.x, P.A_re, P.A_im, P.B_re, P.B_im, P.C_re, P.C_im, P.log_dt, P.Dskip, P.wg, P.wu, P.wd);
    fence_async_smem();
    asm volatile("barrier.cluster.wait.acquire.aligned;" ::: "memory");
    __syncthreads();
    if (threadIdx.x == 0) STAMP(1, 7);

    if (warp >= 8) {
        asm volatile("setmaxnreg.dec.sync.aligned.u32 40;");
        if (warp == 11) {
            if (lane == 0) asm volatile("red.release.gpu.global.add.u32 [%0], 1;" ::"l"(&g_conv_count) : "memory");
            named_bar(3, 288);
            if (lane == 0) asm volatile("red.release.gpu.global.add.u32 [%0], 1;" ::"l"(&g_h_count[rb]) : "memory");
            named_bar(9, 288);
            if (lane == 0) asm volatile("red.release.gpu.global.add.u32 [%0], 1;" ::"l"(&g_h_count[16 + rb]) : "memory");
        } else if (lane == 0) {
            const int pw = warp - 8;
            for (int it = 1 + pw; it < G1_ITERS; it += 3) {
                const int s = it % G1_STAGES, kb = it & 15;
                if (it >= G1_STAGES) mbar_wait(bar_empty + 8 * s, ((it / G1_STAGES) - 1) & 1);
                const uint32_t dst = sB + s * G1_B_STAGE;
                if (it < 16) {
                    mbar_expect_tx(bar_full + 8 * s, 16384);
                    tma_load_3d(dst, &tm_wg4, 0, kb * 32, cj * 7, bar_full + 8 * s);
                    tma_load_3d(dst + 8192, &tm_wu4, 0, kb * 32, cj * 7, bar_full + 8 * s);
                } else {
                    mbar_expect_tx(bar_full + 8 * s, 12288);
                    tma_load_3d(dst, &tm_wg3, 0, kb * 32, cj * 7 + 4, bar_full + 8 * s);
                    tma_load_3d(dst + 6144, &tm_wu3, 0, kb * 32, cj * 7 + 4, bar_full + 8 * s);
                }
            }
            const int k0 = kh * G2_KB;
            auto kblk = [&](int it) -> int {
                const unsigned long long tab = 0xDCA96532B87410ull;
                return k0 + (int)((tab >> (4 * it)) & 15);
            };
            mbar_wait(bar_g1mma, 0);
            if (pw == 2) {
                mbar_expect_tx(bar_epi, G2_EPI);
                tma_load_2d(sX, &tm_x, col_fin, rb * 128, bar_epi);
            }
            spin_until(&g_h_count[rb], 8);
            fence_async_all();
            if (pw == 0) STAMP(3, 1);
            for (int it = pw; it < G2_KB; it += 3) {
                const int s = (it + 1) % G2_STAGES;
                if (it == 4) mbar_wait(bar_g1done, 0);
                if (it >= G2_STAGES) mbar_wait(bar_empty2 + 8 * s, ((it / G2_STAGES) - 1) & 1);
                if (it >= 6 && it < 9) { spin_until(&g_h_count[16 + rb], 8); fence_async_all(); }
                mbar_expect_tx(bar_full2 + 8 * s, G2_STAGE);
                const int kb = kblk(it);
                tma_load_3d(sbase + s * G2_STAGE + 16384, &tm_wd, 0, kb * 64, nb * 2, bar_full2 + 8 * s);
                tma_load_2d(sbase + s * G2_STAGE, &tm_h, kb * 64, rb * 128, bar_full2 + 8 * s);
                if (it == 2) {
                    spin_until(&g_conv_count, gridDim.x);
                    fence_async_all();
                    tma_load_2d(sS, &tm_sT, rb * 128, col_fin, bar_epi);
                    tma_load_2d(sS + 8192, &tm_sT, rb * 128 + 64, col_fin, bar_epi);
                }
            }
        }
    } else {
        asm volatile("setmaxnreg.inc.sync.aligned.u32 232;");
        const int wg = __shfl_sync(0xffffffffu, (int)(threadIdx.x >> 7), 0);
        {
        float r[160];
        const int row0 = rb * 128 + wg * 64 + (warp & 3) * 16;
        const uint64_t descA = make_desc(sA + wg * 8192, 16, 1024);
        const uint64_t descB = make_desc(sB, 2048, 512, 2);
        const uint32_t stg = sStg + warp * 1024;
        const uint32_t st_off = (uint32_t)(((lane & 7) + ((lane >> 3) & 1) * 8) * 32 + (lane >> 4) * 16);
        __nv_bfloat16* hrow = g_h + (size_t)(row0 + (lane >> 1)) * F_ + (lane & 1) * 8 + cj * 224;
#pragma unroll
        for (int kb = 0; kb < 16; kb++) {
            const int it = kb, s = it % G1_STAGES;
            if ((kb & 1) == 0) mbar_wait(bar_a + 8 * (kb >> 1), 0);
            mbar_wait(bar_full + 8 * s, (it / G1_STAGES) & 1);
            if (threadIdx.x == 0 && (it & 7) == 0) STAMP(2, 2 + it / 8);
            wgmma_fence();
            const uint64_t da = descA + (uint64_t)(((kb >> 1) * 16384 + (kb & 1) * 64) >> 4);
            const uint64_t db = descB + (uint64_t)((s * G1_B_STAGE) >> 4);
            wgmma_n256_k32(r, da, da + 2, db, db + 64, kb != 0);
            wgmma_commit();
            if (kb > 0) {
                wgmma_wait<1>();
                if (lane == 0) mbar_arrive(bar_empty + 8 * ((it - 1) % G1_STAGES));
            }
        }
        wgmma_wait<0>();
        if (lane == 0) mbar_arrive(bar_empty + 8 * (15 % G1_STAGES));
#pragma unroll
        for (int i = 0; i < 32; i++) r[128 + i] = __uint_as_float(pack_bf16(r[2 * i], r[2 * i + 1]));
#pragma unroll
        for (int i = 31; i >= 0; i--) r[96 + i] = __uint_as_float(pack_bf16(r[64 + 2 * i], r[65 + 2 * i]));
        uint32_t eo[4];
        uint4 pv = make_uint4(0, 0, 0, 0);
#pragma unroll
        for (int kb = 0; kb < 16; kb++) {
            const int it = 16 + kb, s = it % G1_STAGES;
            mbar_wait(bar_full + 8 * s, (it / G1_STAGES) & 1);
            if (threadIdx.x == 0 && (it & 7) == 0) STAMP(2, 2 + it / 8);
            wgmma_fence();
            const uint64_t da = descA + (uint64_t)(((kb >> 1) * 16384 + (kb & 1) * 64) >> 4);
            const uint64_t db = descB + (uint64_t)((s * G1_B_STAGE) >> 4);
            const int jj = kb >> 1;
            wgmma_n192(r, da, db, kb != 0);
            eo[(kb & 1) * 2] = geglu_pair(__float_as_uint(r[128 + 2 * kb]), __float_as_uint(r[96 + 2 * kb]));
            wgmma_n192(r, da + 2, db + 64, 1);
            wgmma_commit();
            eo[(kb & 1) * 2 + 1] = geglu_pair(__float_as_uint(r[129 + 2 * kb]), __float_as_uint(r[97 + 2 * kb]));
            if (kb & 1) {
                if (jj > 0) *reinterpret_cast<uint4*>(hrow + (jj - 1) * 16) = pv;
                stmatrix_x4(stg + (jj & 1) * 512 + st_off, eo[0], eo[1], eo[2], eo[3]);
            } else if (jj > 0) {
                __syncwarp();
                asm volatile("ld.shared.v4.u32 {%0,%1,%2,%3}, [%4];" : "=r"(pv.x), "=r"(pv.y), "=r"(pv.z), "=r"(pv.w)
                             : "r"(stg + ((jj - 1) & 1) * 512 + lane * 16));
            }
            if (kb > 0 && it - 1 + G1_STAGES < G1_ITERS) {
                wgmma_wait<1>();
                if (lane == 0) mbar_arrive(bar_empty + 8 * ((it - 1) % G1_STAGES));
            }
        }
        __syncwarp();
        asm volatile("ld.shared.v4.u32 {%0,%1,%2,%3}, [%4];" : "=r"(pv.x), "=r"(pv.y), "=r"(pv.z), "=r"(pv.w) : "r"(stg + 512 + lane * 16));
        wgmma_wait<0>();
        *reinterpret_cast<uint4*>(hrow + 7 * 16) = pv;
        fence_async_smem();
        __syncwarp();
        if (lane == 0) mbar_arrive(bar_g1mma);
        asm volatile("bar.arrive 3, 288;" ::: "memory");
        if (threadIdx.x == 0) STAMP(2, 6);
        {
            uint32_t o[24];
#pragma unroll
            for (int i = 0; i < 24; i++) o[i] = geglu_pair(pack_bf16(r[2 * i], r[2 * i + 1]), pack_bf16(r[48 + 2 * i], r[49 + 2 * i]));
            named_bar(1 + wg, 128);
            const uint32_t fbuf = sA + ((warp & 3) >> 1) * 16384 + wg * 8192 + (warp & 1) * 4096;
#pragma unroll
            for (int jj = 0; jj < 6; jj++) stmatrix_x4(fbuf + jj * 512 + st_off, o[4 * jj], o[4 * jj + 1], o[4 * jj + 2], o[4 * jj + 3]);
            __syncwarp();
            uint4 v[6];
#pragma unroll
            for (int jj = 0; jj < 6; jj++)
                asm volatile("ld.shared.v4.u32 {%0,%1,%2,%3}, [%4];" : "=r"(v[jj].x), "=r"(v[jj].y), "=r"(v[jj].z), "=r"(v[jj].w)
                             : "r"(fbuf + jj * 512 + lane * 16));
#pragma unroll
            for (int jj = 0; jj < 6; jj++) *reinterpret_cast<uint4*>(hrow + 128 + jj * 16) = v[jj];
        }
        }
        fence_async_smem();
        __syncwarp();
        if (lane == 0) mbar_arrive(bar_g1done);
        asm volatile("bar.arrive 9, 288;" ::: "memory");
        if (threadIdx.x == 0) STAMP(2, 7);
        {
        const int g = lane >> 2, t = lane & 3;
        float acc[64];
        const uint64_t descA2 = make_desc(sbase + wg * 8192, 16, 1024);
        const uint64_t descB2 = make_desc(sbase + 16384, 8192, 1024);
#pragma unroll
        for (int it = 0; it < G2_KB; it++) {
            const int s = (it + 1) % G2_STAGES;
            mbar_wait(bar_full2 + 8 * s, (it / G2_STAGES) & 1);
            if (threadIdx.x == 0 && (it == 0 || it == 7)) STAMP(3, 2 + it / 7);
            wgmma_fence();
            {
                const uint64_t da = descA2 + (uint64_t)((s * G2_STAGE) >> 4);
                const uint64_t db = descB2 + (uint64_t)((s * G2_STAGE) >> 4);
                wgmma_n128_k64(acc, da, da + 2, da + 4, da + 6, db, db + 128, db + 256, db + 384, it != 0);
            }
            wgmma_commit();
            if (it > 0 && it - 1 + G2_STAGES < G2_KB) {
                wgmma_wait<1>();
                if (lane == 0) mbar_arrive(bar_empty2 + 8 * (it % G2_STAGES));
            }
        }
        const int lr = wg * 64 + (warp & 3) * 16 + g;
        uint32_t xv[16], sv[16];
        mbar_wait(bar_epi, 0);
#pragma unroll
        for (int j = 0; j < 8; j++) {
#pragma unroll
            for (int hh = 0; hh < 2; hh++) {
                const int r = lr + 8 * hh;
                asm volatile("ld.shared.u32 %0, [%1];" : "=r"(xv[2 * j + hh]) : "r"(sX + r * 128 + ((j ^ (r & 7)) << 4) + 4 * t));
                const int c0 = 8 * j + 2 * t;
                const uint32_t sa = sS + (r >> 6) * 8192 + (((r & 63) >> 3) << 4) + (r & 7) * 2;
                uint16_t s0r, s1r;
                asm volatile("ld.shared.u16 %0, [%1];" : "=h"(s0r) : "r"((sa + c0 * 128) ^ ((c0 & 7) << 4)));
                asm volatile("ld.shared.u16 %0, [%1];" : "=h"(s1r) : "r"((sa + (c0 + 1) * 128) ^ (((c0 + 1) & 7) << 4)));
                sv[2 * j + hh] = (uint32_t)s0r | ((uint32_t)s1r << 16);
            }
        }
        wgmma_wait<0>();
        if (threadIdx.x == 0) STAMP(3, 4);
        {
            uint32_t remote, rbar;
            asm volatile("mapa.shared::cluster.u32 %0, %1, %2;" : "=r"(remote) : "r"(sXch + threadIdx.x * 16), "r"(kh ^ 1));
            asm volatile("mapa.shared::cluster.u32 %0, %1, %2;" : "=r"(rbar) : "r"(bar_xch), "r"(kh ^ 1));
            if (kh == 0) {
#pragma unroll
                for (int i = 0; i < 8; i++)
                    asm volatile("st.async.shared::cluster.mbarrier::complete_tx::bytes.v4.f32 [%0], {%1,%2,%3,%4}, [%5];" ::"r"(remote + i * 4096),
                                 "f"(acc[32 + 4 * i]), "f"(acc[33 + 4 * i]), "f"(acc[34 + 4 * i]), "f"(acc[35 + 4 * i]), "r"(rbar) : "memory");
            } else {
#pragma unroll
                for (int i = 0; i < 8; i++)
                    asm volatile("st.async.shared::cluster.mbarrier::complete_tx::bytes.v4.f32 [%0], {%1,%2,%3,%4}, [%5];" ::"r"(remote + i * 4096),
                                 "f"(acc[4 * i]), "f"(acc[1 + 4 * i]), "f"(acc[2 + 4 * i]), "f"(acc[3 + 4 * i]), "r"(rbar) : "memory");
#pragma unroll
                for (int i = 0; i < 32; i++) acc[i] = acc[32 + i];
            }
        }
        if (threadIdx.x == 0) STAMP(3, 6);
        mbar_wait(bar_xch, 0);
        if (threadIdx.x == 0) STAMP(3, 7);
#pragma unroll
        for (int j = 0; j < 8; j++) {
            float4 o;
            asm volatile("ld.shared.v4.f32 {%0,%1,%2,%3}, [%4];" : "=f"(o.x), "=f"(o.y), "=f"(o.z), "=f"(o.w) : "r"(sXch + threadIdx.x * 16 + j * 4096));
            acc[4 * j] += o.x; acc[4 * j + 1] += o.y; acc[4 * j + 2] += o.z; acc[4 * j + 3] += o.w;
        }
#pragma unroll
        for (int i = 0; i < 16; i++) {
            float f0 = bf16_round(acc[2 * i]), f1 = bf16_round(acc[2 * i + 1]);
            float g0 = bf16_round(__fdividef(f0, 1.0f + __expf(-f0)));
            float g1 = bf16_round(__fdividef(f1, 1.0f + __expf(-f1)));
            float o0 = bf_lo(xv[i]) + bf16_round(bf_lo(sv[i]) * g0);
            float o1 = bf_hi(xv[i]) + bf16_round(bf_hi(sv[i]) * g1);
            xv[i] = pack_bf16(o0, o1);
        }
#pragma unroll
        for (int j = 0; j < 8; j++) {
#pragma unroll
            for (int hh = 0; hh < 2; hh++) {
                const int r = lr + 8 * hh;
                asm volatile("st.shared.u32 [%0], %1;" ::"r"(sX + r * 128 + ((j ^ (r & 7)) << 4) + 4 * t), "r"(xv[2 * j + hh]) : "memory");
            }
        }
        if (threadIdx.x == 0) STAMP(3, 9);
        fence_async_smem();
        __syncwarp();
        if (lane == 0) {
            tma_store_2d(&tm_out, sX + (wg * 64 + (warp & 3) * 16) * 128, col_fin, rb * 128 + wg * 64 + (warp & 3) * 16);
            bulk_commit();
            bulk_wait_read<0>();
        }
        }
        if (threadIdx.x == 0) STAMP(3, 5);
        named_bar(4, 256);
        if (threadIdx.x == 0) {
            const unsigned int old = atomicAdd(&g_done_count, 1u);
            if (old == gridDim.x - 1) {
                g_ln_count = 0; g_conv_count = 0; g_done_count = 0;
                for (int i = 0; i < 32; i++) g_h_count[i] = 0;
            }
        }
    }
}

typedef CUresult (*EncodeFn)(CUtensorMap*, CUtensorMapDataType, cuuint32_t, void*, const cuuint64_t*, const cuuint64_t*,
                             const cuuint32_t*, const cuuint32_t*, CUtensorMapInterleave, CUtensorMapSwizzle,
                             CUtensorMapL2promotion, CUtensorMapFloatOOBfill);

void make_map(EncodeFn fn, CUtensorMap* m, const void* ptr, uint64_t inner, uint64_t outer, uint32_t box_in, uint32_t box_out,
              CUtensorMapSwizzle swz = CU_TENSOR_MAP_SWIZZLE_128B) {
    cuuint64_t dims[2] = {inner, outer};
    cuuint64_t strides[1] = {inner * 2};
    cuuint32_t box[2] = {box_in, box_out};
    cuuint32_t es[2] = {1, 1};
    fn(m, CU_TENSOR_MAP_DATA_TYPE_BFLOAT16, 2, const_cast<void*>(ptr), dims, strides, box, es, CU_TENSOR_MAP_INTERLEAVE_NONE,
       swz, CU_TENSOR_MAP_L2_PROMOTION_L2_256B, CU_TENSOR_MAP_FLOAT_OOB_FILL_NONE);
}
void make_map3(EncodeFn fn, CUtensorMap* m, const void* ptr, uint64_t cols, uint64_t rows, uint32_t atom, uint32_t box_rows,
               uint32_t box_atoms, CUtensorMapSwizzle swz) {
    cuuint64_t dims[3] = {atom, rows, cols / atom};
    cuuint64_t strides[2] = {cols * 2, (cuuint64_t)atom * 2};
    cuuint32_t box[3] = {atom, box_rows, box_atoms};
    cuuint32_t es[3] = {1, 1, 1};
    fn(m, CU_TENSOR_MAP_DATA_TYPE_BFLOAT16, 3, const_cast<void*>(ptr), dims, strides, box, es, CU_TENSOR_MAP_INTERLEAVE_NONE,
       swz, CU_TENSOR_MAP_L2_PROMOTION_L2_256B, CU_TENSOR_MAP_FLOAT_OOB_FILL_NONE);
}

template <typename... Args>
void launch_pdl(void (*kern)(Args...), int grid, int block, int smem, bool pdl, int cluster, Args... args) {
    cudaLaunchConfig_t cfg = {};
    cfg.gridDim = dim3(grid); cfg.blockDim = dim3(block); cfg.dynamicSmemBytes = smem; cfg.stream = cudaStreamPerThread;
    cudaLaunchAttribute at[2];
    int n = 0;
    if (pdl) {
        at[n].id = cudaLaunchAttributeProgrammaticStreamSerialization;
        at[n].val.programmaticStreamSerializationAllowed = 1;
        n++;
    }
    if (cluster > 1) {
        at[n].id = cudaLaunchAttributeClusterDimension;
        at[n].val.clusterDim.x = cluster; at[n].val.clusterDim.y = 1; at[n].val.clusterDim.z = 1;
        n++;
    }
    cfg.attrs = at; cfg.numAttrs = n;
    cudaLaunchKernelEx(&cfg, kern, args...);
}

}

extern "C" void kernel_launch(void* const* d_in, const int* in_sizes, int n_in, void* d_out, int out_size) {
    const __nv_bfloat16* x = (const __nv_bfloat16*)d_in[0];
    const __nv_bfloat16* A_re = (const __nv_bfloat16*)d_in[1];
    const __nv_bfloat16* A_im = (const __nv_bfloat16*)d_in[2];
    const __nv_bfloat16* B_re = (const __nv_bfloat16*)d_in[3];
    const __nv_bfloat16* B_im = (const __nv_bfloat16*)d_in[4];
    const __nv_bfloat16* C_re = (const __nv_bfloat16*)d_in[5];
    const __nv_bfloat16* C_im = (const __nv_bfloat16*)d_in[6];
    const __nv_bfloat16* log_dt = (const __nv_bfloat16*)d_in[7];
    const __nv_bfloat16* Dskip = (const __nv_bfloat16*)d_in[8];
    const __nv_bfloat16* wg = (const __nv_bfloat16*)d_in[10];
    const __nv_bfloat16* wu = (const __nv_bfloat16*)d_in[11];
    const __nv_bfloat16* wd = (const __nv_bfloat16*)d_in[12];
    __nv_bfloat16* out = (__nv_bfloat16*)d_out;

    static bool init = false;
    static CUtensorMap tm_xn, tm_wg4, tm_wu4, tm_wg3, tm_wu3, tm_hst, tm_hst96, tm_h, tm_wd, tm_x, tm_sT, tm_out;
    static const void* last_ptrs[5] = {nullptr, nullptr, nullptr, nullptr, nullptr};
    if (!init || last_ptrs[0] != wg || last_ptrs[1] != wu || last_ptrs[2] != wd || last_ptrs[3] != x || last_ptrs[4] != out) {
        void* fnp = nullptr;
        cudaDriverEntryPointQueryResult qres;
        cudaGetDriverEntryPoint("cuTensorMapEncodeTiled", &fnp, cudaEnableDefault, &qres);
        EncodeFn fn = (EncodeFn)fnp;
        void *p_xn, *p_h, *p_sT;
        cudaGetSymbolAddress(&p_xn, g_xn);
        cudaGetSymbolAddress(&p_h, g_h);
        cudaGetSymbolAddress(&p_sT, g_sT);
        make_map(fn, &tm_xn, p_xn, D_, L_, 64, 128);
        make_map3(fn, &tm_wg4, wg, F_, D_, 32, 32, 4, CU_TENSOR_MAP_SWIZZLE_64B);
        make_map3(fn, &tm_wu4, wu, F_, D_, 32, 32, 4, CU_TENSOR_MAP_SWIZZLE_64B);
        make_map3(fn, &tm_wg3, wg, F_, D_, 32, 32, 3, CU_TENSOR_MAP_SWIZZLE_64B);
        make_map3(fn, &tm_wu3, wu, F_, D_, 32, 32, 3, CU_TENSOR_MAP_SWIZZLE_64B);
        make_map(fn, &tm_hst, p_h, F_, L_, 16, 16, CU_TENSOR_MAP_SWIZZLE_NONE);
        make_map(fn, &tm_hst96, p_h, F_, L_, 96, 16, CU_TENSOR_MAP_SWIZZLE_NONE);
        make_map(fn, &tm_h, p_h, F_, L_, 64, 128);
        make_map3(fn, &tm_wd, wd, D_, F_, 64, 64, 2, CU_TENSOR_MAP_SWIZZLE_128B);
        make_map(fn, &tm_x, x, D_, L_, 64, 128);
        make_map(fn, &tm_sT, p_sT, L_, D_, 64, 64);
        make_map(fn, &tm_out, out, D_, L_, 64, 16);
        cudaFuncSetAttribute(mega_kernel, cudaFuncAttributeMaxDynamicSharedMemorySize, MG_SMEM);
        last_ptrs[0] = wg; last_ptrs[1] = wu; last_ptrs[2] = wd; last_ptrs[3] = x; last_ptrs[4] = out;
        init = true;
    }
    MegaParams P = {x, A_re, A_im, B_re, B_im, C_re, C_im, log_dt, Dskip, wg, wu, wd};
    launch_pdl(mega_kernel, 128, 384, MG_SMEM, false, 2, P, tm_xn, tm_wg4, tm_wu4, tm_wg3, tm_wu3, tm_h, tm_wd, tm_x, tm_sT, tm_out);
}
```

```cpp
#include <cuda_runtime.h>
#include <cuda_bf16.h>
#include <cuda.h>
#include <stdint.h>

namespace {

constexpr int L_ = 2048, D_ = 512, NS_ = 128, F_ = 1792;

__device__ __align__(1024) __nv_bfloat16 g_xn[L_ * D_];
__device__ __align__(1024) __nv_bfloat16 g_xnT[D_ * L_];
__device__ __align__(1024) __nv_bfloat16 g_sT[D_ * L_];
__device__ __align__(1024) __nv_bfloat16 g_h[L_ * F_];
__device__ unsigned int g_ln_count, g_conv_count, g_done_count, g_h_count[32];

#define STAMP(k, i)

__device__ __forceinline__ uint32_t smem_u32(const void* p) { return (uint32_t)__cvta_generic_to_shared(p); }
__device__ __forceinline__ void pdl_wait() { asm volatile("griddepcontrol.wait;" ::: "memory"); }
__device__ __forceinline__ void pdl_launch() { asm volatile("griddepcontrol.launch_dependents;" ::: "memory"); }

__device__ __forceinline__ void mbar_init(uint32_t bar, uint32_t cnt) {
    asm volatile("mbarrier.init.shared::cta.b64 [%0], %1;" ::"r"(bar), "r"(cnt) : "memory");
}
__device__ __forceinline__ void mbar_expect_tx(uint32_t bar, uint32_t bytes) {
    asm volatile("mbarrier.arrive.expect_tx.shared::cta.b64 _, [%0], %1;" ::"r"(bar), "r"(bytes) : "memory");
}
__device__ __forceinline__ void mbar_arrive(uint32_t bar) {
    asm volatile("mbarrier.arrive.shared::cta.b64 _, [%0];" ::"r"(bar) : "memory");
}
__device__ __forceinline__ void mbar_wait(uint32_t bar, uint32_t parity) {
    asm volatile(
        "{\n.reg .pred p;\n"
        "WAIT_LOOP:\n"
        "mbarrier.try_wait.parity.shared::cta.b64 p, [%0], %1;\n"
        "@p bra WAIT_DONE;\n"
        "bra WAIT_LOOP;\n"
        "WAIT_DONE:\n}\n" ::"r"(bar), "r"(parity) : "memory");
}
__device__ __forceinline__ void tma_load_2d(uint32_t dst, const CUtensorMap* tm, int c0, int c1, uint32_t bar) {
    asm volatile(
        "cp.async.bulk.tensor.2d.shared::cluster.global.mbarrier::complete_tx::bytes [%0], [%1, {%3, %4}], [%2];"
        ::"r"(dst), "l"((uint64_t)tm), "r"(bar), "r"(c0), "r"(c1) : "memory");
}
__device__ __forceinline__ void prefetch_tmap(const CUtensorMap* tm) {
    asm volatile("prefetch.tensormap [%0];" ::"l"((uint64_t)tm) : "memory");
}
__device__ __forceinline__ uint64_t make_desc(uint32_t addr, uint32_t lbo, uint32_t sbo, uint64_t mode = 1) {
    uint64_t d = 0;
    d |= (uint64_t)((addr & 0x3FFFF) >> 4);
    d |= (uint64_t)((lbo >> 4) & 0x3FFF) << 16;
    d |= (uint64_t)((sbo >> 4) & 0x3FFF) << 32;
    d |= mode << 62;
    return d;
}
__device__ __forceinline__ void fence_async_smem() { asm volatile("fence.proxy.async.shared::cta;" ::: "memory"); }
__device__ __forceinline__ void wgmma_fence() { asm volatile("wgmma.fence.sync.aligned;" ::: "memory"); }
__device__ __forceinline__ void wgmma_commit() { asm volatile("wgmma.commit_group.sync.aligned;" ::: "memory"); }
template <int N> __device__ __forceinline__ void wgmma_wait() {
    asm volatile("wgmma.wait_group.sync.aligned %0;" ::"n"(N) : "memory");
}

#define R8(a, i) "+f"(a[i + 0]), "+f"(a[i + 1]), "+f"(a[i + 2]), "+f"(a[i + 3]), "+f"(a[i + 4]), "+f"(a[i + 5]), "+f"(a[i + 6]), "+f"(a[i + 7])

__device__ __forceinline__ void wgmma_n256_k32(float* a, uint64_t da0, uint64_t da1, uint64_t db0, uint64_t db1, int scale_d) {
    asm volatile(
        "{\n.reg .pred p;\nsetp.ne.b32 p, %132, 0;\n"
        "wgmma.mma_async.sync.aligned.m64n256k16.f32.bf16.bf16 {%0,%1,%2,%3,%4,%5,%6,%7,%8,%9,%10,%11,%12,%13,%14,%15,%16,%17,%18,%19,%20,%21,%22,%23,%24,%25,%26,%27,%28,%29,%30,%31,%32,%33,%34,%35,%36,%37,%38,%39,%40,%41,%42,%43,%44,%45,%46,%47,%48,%49,%50,%51,%52,%53,%54,%55,%56,%57,%58,%59,%60,%61,%62,%63,%64,%65,%66,%67,%68,%69,%70,%71,%72,%73,%74,%75,%76,%77,%78,%79,%80,%81,%82,%83,%84,%85,%86,%87,%88,%89,%90,%91,%92,%93,%94,%95,%96,%97,%98,%99,%100,%101,%102,%103,%104,%105,%106,%107,%108,%109,%110,%111,%112,%113,%114,%115,%116,%117,%118,%119,%120,%121,%122,%123,%124,%125,%126,%127}, %128, %130, p, 1, 1, 0, 1;\n"
        "wgmma.mma_async.sync.aligned.m64n256k16.f32.bf16.bf16 {%0,%1,%2,%3,%4,%5,%6,%7,%8,%9,%10,%11,%12,%13,%14,%15,%16,%17,%18,%19,%20,%21,%22,%23,%24,%25,%26,%27,%28,%29,%30,%31,%32,%33,%34,%35,%36,%37,%38,%39,%40,%41,%42,%43,%44,%45,%46,%47,%48,%49,%50,%51,%52,%53,%54,%55,%56,%57,%58,%59,%60,%61,%62,%63,%64,%65,%66,%67,%68,%69,%70,%71,%72,%73,%74,%75,%76,%77,%78,%79,%80,%81,%82,%83,%84,%85,%86,%87,%88,%89,%90,%91,%92,%93,%94,%95,%96,%97,%98,%99,%100,%101,%102,%103,%104,%105,%106,%107,%108,%109,%110,%111,%112,%113,%114,%115,%116,%117,%118,%119,%120,%121,%122,%123,%124,%125,%126,%127}, %129, %131, 1, 1, 1, 0, 1;\n"
        "}\n"
        : R8(a, 0), R8(a, 8), R8(a, 16), R8(a, 24), R8(a, 32), R8(a, 40), R8(a, 48), R8(a, 56), R8(a, 64), R8(a, 72), R8(a, 80), R8(a, 88), R8(a, 96), R8(a, 104), R8(a, 112), R8(a, 120)
        : "l"(da0), "l"(da1), "l"(db0), "l"(db1), "r"(scale_d));
}
__device__ __forceinline__ void wgmma_n192_k32(float* a, uint64_t da0, uint64_t da1, uint64_t db0, uint64_t db1, int scale_d) {
    asm volatile(
        "{\n.reg .pred p;\nsetp.ne.b32 p, %100, 0;\n"
        "wgmma.mma_async.sync.aligned.m64n192k16.f32.bf16.bf16 {%0,%1,%2,%3,%4,%5,%6,%7,%8,%9,%10,%11,%12,%13,%14,%15,%16,%17,%18,%19,%20,%21,%22,%23,%24,%25,%26,%27,%28,%29,%30,%31,%32,%33,%34,%35,%36,%37,%38,%39,%40,%41,%42,%43,%44,%45,%46,%47,%48,%49,%50,%51,%52,%53,%54,%55,%56,%57,%58,%59,%60,%61,%62,%63,%64,%65,%66,%67,%68,%69,%70,%71,%72,%73,%74,%75,%76,%77,%78,%79,%80,%81,%82,%83,%84,%85,%86,%87,%88,%89,%90,%91,%92,%93,%94,%95}, %96, %98, p, 1, 1, 0, 1;\n"
        "wgmma.mma_async.sync.aligned.m64n192k16.f32.bf16.bf16 {%0,%1,%2,%3,%4,%5,%6,%7,%8,%9,%10,%11,%12,%13,%14,%15,%16,%17,%18,%19,%20,%21,%22,%23,%24,%25,%26,%27,%28,%29,%30,%31,%32,%33,%34,%35,%36,%37,%38,%39,%40,%41,%42,%43,%44,%45,%46,%47,%48,%49,%50,%51,%52,%53,%54,%55,%56,%57,%58,%59,%60,%61,%62,%63,%64,%65,%66,%67,%68,%69,%70,%71,%72,%73,%74,%75,%76,%77,%78,%79,%80,%81,%82,%83,%84,%85,%86,%87,%88,%89,%90,%91,%92,%93,%94,%95}, %97, %99, 1, 1, 1, 0, 1;\n"
        "}\n"
        : R8(a, 0), R8(a, 8), R8(a, 16), R8(a, 24), R8(a, 32), R8(a, 40), R8(a, 48), R8(a, 56), R8(a, 64), R8(a, 72), R8(a, 80), R8(a, 88)
        : "l"(da0), "l"(da1), "l"(db0), "l"(db1), "r"(scale_d));
}
__device__ __forceinline__ void wgmma_n192(float* a, uint64_t da0, uint64_t db0, int scale_d) {
    asm volatile(
        "{\n.reg .pred p;\nsetp.ne.b32 p, %98, 0;\n"
        "wgmma.mma_async.sync.aligned.m64n192k16.f32.bf16.bf16 {%0,%1,%2,%3,%4,%5,%6,%7,%8,%9,%10,%11,%12,%13,%14,%15,%16,%17,%18,%19,%20,%21,%22,%23,%24,%25,%26,%27,%28,%29,%30,%31,%32,%33,%34,%35,%36,%37,%38,%39,%40,%41,%42,%43,%44,%45,%46,%47,%48,%49,%50,%51,%52,%53,%54,%55,%56,%57,%58,%59,%60,%61,%62,%63,%64,%65,%66,%67,%68,%69,%70,%71,%72,%73,%74,%75,%76,%77,%78,%79,%80,%81,%82,%83,%84,%85,%86,%87,%88,%89,%90,%91,%92,%93,%94,%95}, %96, %97, p, 1, 1, 0, 1;\n"
        "}\n"
        : R8(a, 0), R8(a, 8), R8(a, 16), R8(a, 24), R8(a, 32), R8(a, 40), R8(a, 48), R8(a, 56), R8(a, 64), R8(a, 72), R8(a, 80), R8(a, 88)
        : "l"(da0), "l"(db0), "r"(scale_d));
}
__device__ __forceinline__ void wgmma_n128_k64(float* a, uint64_t da0, uint64_t da1, uint64_t da2, uint64_t da3,
                                               uint64_t db0, uint64_t db1, uint64_t db2, uint64_t db3, int scale_d) {
    asm volatile(
        "{\n.reg .pred p;\nsetp.ne.b32 p, %72, 0;\n"
        "wgmma.mma_async.sync.aligned.m64n128k16.f32.bf16.bf16 {%0,%1,%2,%3,%4,%5,%6,%7,%8,%9,%10,%11,%12,%13,%14,%15,%16,%17,%18,%19,%20,%21,%22,%23,%24,%25,%26,%27,%28,%29,%30,%31,%32,%33,%34,%35,%36,%37,%38,%39,%40,%41,%42,%43,%44,%45,%46,%47,%48,%49,%50,%51,%52,%53,%54,%55,%56,%57,%58,%59,%60,%61,%62,%63}, %64, %68, p, 1, 1, 0, 1;\n"
        "wgmma.mma_async.sync.aligned.m64n128k16.f32.bf16.bf16 {%0,%1,%2,%3,%4,%5,%6,%7,%8,%9,%10,%11,%12,%13,%14,%15,%16,%17,%18,%19,%20,%21,%22,%23,%24,%25,%26,%27,%28,%29,%30,%31,%32,%33,%34,%35,%36,%37,%38,%39,%40,%41,%42,%43,%44,%45,%46,%47,%48,%49,%50,%51,%52,%53,%54,%55,%56,%57,%58,%59,%60,%61,%62,%63}, %65, %69, 1, 1, 1, 0, 1;\n"
        "wgmma.mma_async.sync.aligned.m64n128k16.f32.bf16.bf16 {%0,%1,%2,%3,%4,%5,%6,%7,%8,%9,%10,%11,%12,%13,%14,%15,%16,%17,%18,%19,%20,%21,%22,%23,%24,%25,%26,%27,%28,%29,%30,%31,%32,%33,%34,%35,%36,%37,%38,%39,%40,%41,%42,%43,%44,%45,%46,%47,%48,%49,%50,%51,%52,%53,%54,%55,%56,%57,%58,%59,%60,%61,%62,%63}, %66, %70, 1, 1, 1, 0, 1;\n"
        "wgmma.mma_async.sync.aligned.m64n128k16.f32.bf16.bf16 {%0,%1,%2,%3,%4,%5,%6,%7,%8,%9,%10,%11,%12,%13,%14,%15,%16,%17,%18,%19,%20,%21,%22,%23,%24,%25,%26,%27,%28,%29,%30,%31,%32,%33,%34,%35,%36,%37,%38,%39,%40,%41,%42,%43,%44,%45,%46,%47,%48,%49,%50,%51,%52,%53,%54,%55,%56,%57,%58,%59,%60,%61,%62,%63}, %67, %71, 1, 1, 1, 0, 1;\n"
        "}\n"
        : R8(a, 0), R8(a, 8), R8(a, 16), R8(a, 24), R8(a, 32), R8(a, 40), R8(a, 48), R8(a, 56)
        : "l"(da0), "l"(da1), "l"(da2), "l"(da3), "l"(db0), "l"(db1), "l"(db2), "l"(db3), "r"(scale_d));
}

__device__ __forceinline__ float bf16_round(float x) {
    uint32_t p; asm("cvt.rn.bf16x2.f32 %0, %1, %2;" : "=r"(p) : "f"(x), "f"(0.0f));
    return __uint_as_float(p);
}
__device__ __forceinline__ uint32_t pack_bf16(float lo, float hi) {
    __nv_bfloat162 v = __floats2bfloat162_rn(lo, hi);
    return *reinterpret_cast<uint32_t*>(&v);
}
__device__ __forceinline__ float bf_lo(uint32_t v) { return __uint_as_float(v << 16); }
__device__ __forceinline__ float bf_hi(uint32_t v) { return __uint_as_float(v & 0xFFFF0000u); }

struct cplx { float r, i; };
__device__ __forceinline__ cplx cmul(cplx a, cplx b) {
    cplx c; c.r = a.r * b.r - a.i * b.i; c.i = a.r * b.i + a.i * b.r; return c;
}
__device__ __forceinline__ cplx csq(cplx a) {
    cplx c; c.r = a.r * a.r - a.i * a.i; c.i = 2.0f * a.r * a.i; return c;
}
__device__ __forceinline__ cplx cexp_m(float ar2, float ai2, float m) {
    float mag;
    asm("ex2.approx.ftz.f32 %0, %1;" : "=f"(mag) : "f"(ar2 * m));
    float rr = ai2 * m;
    rr -= (rr + 12582912.0f) - 12582912.0f;
    float th = rr * 6.283185307179586f;
    cplx c; c.r = mag * __cosf(th); c.i = mag * __sinf(th);
    return c;
}
__device__ __forceinline__ uint32_t to_tf32(float x) { return __float_as_uint(x) + 0x1000u; }
__device__ __forceinline__ void mma_tf32(float* c, uint32_t a0, uint32_t a1, uint32_t a2, uint32_t a3, uint32_t b0, uint32_t b1) {
    asm volatile("mma.sync.aligned.m16n8k8.row.col.f32.tf32.tf32.f32 {%0,%1,%2,%3}, {%4,%5,%6,%7}, {%8,%9}, {%0,%1,%2,%3};"
                 : "+f"(c[0]), "+f"(c[1]), "+f"(c[2]), "+f"(c[3])
                 : "r"(a0), "r"(a1), "r"(a2), "r"(a3), "r"(b0), "r"(b1));
}
__device__ __forceinline__ void mma_bf16(float* c, uint32_t a0, uint32_t a1, uint32_t a2, uint32_t a3, uint32_t b0, uint32_t b1) {
    asm volatile("mma.sync.aligned.m16n8k16.row.col.f32.bf16.bf16.f32 {%0,%1,%2,%3}, {%4,%5,%6,%7}, {%8,%9}, {%0,%1,%2,%3};"
                 : "+f"(c[0]), "+f"(c[1]), "+f"(c[2]), "+f"(c[3])
                 : "r"(a0), "r"(a1), "r"(a2), "r"(a3), "r"(b0), "r"(b1));
}
__device__ __forceinline__ void named_bar(int id, int n) { asm volatile("bar.sync %0, %1;" ::"r"(id), "r"(n) : "memory"); }
__device__ __forceinline__ void ldsm_x4(uint32_t addr, uint32_t& r0, uint32_t& r1, uint32_t& r2, uint32_t& r3) {
    asm volatile("ldmatrix.sync.aligned.m8n8.x4.shared.b16 {%0,%1,%2,%3}, [%4];" : "=r"(r0), "=r"(r1), "=r"(r2), "=r"(r3) : "r"(addr));
}
__device__ __forceinline__ void ldsm_x4_t(uint32_t addr, uint32_t& r0, uint32_t& r1, uint32_t& r2, uint32_t& r3) {
    asm volatile("ldmatrix.sync.aligned.m8n8.x4.trans.shared.b16 {%0,%1,%2,%3}, [%4];" : "=r"(r0), "=r"(r1), "=r"(r2), "=r"(r3) : "r"(addr));
}

constexpr int CV_CH = 4;
constexpr int CV_O_CONST = 0;
constexpr int CV_O_KP = 12288;
constexpr int CV_EARLY = 12288 + 7776;
constexpr int CV_O_Q = 0;
constexpr int CV_O_Q2 = CV_O_Q + 2304;
constexpr int CV_O_Q3 = CV_O_Q2 + 1024;
constexpr int CV_O_Q4X = CV_O_Q3 + 768;
constexpr int CV_O_W3 = CV_O_Q4X + 256;
constexpr int CV_O_W5 = CV_O_W3 + 3104;
constexpr int CV_O_W7 = CV_O_W5 + 3104;
constexpr int CV_O_W9 = CV_O_W7 + 2048;
constexpr int CV_O_U = CV_O_W9 + 2048;
constexpr int CV_LATE = CV_O_U + 4352;
constexpr int CV_LATE_BASE = 229376 - CV_CH * CV_LATE;
constexpr int CV_TILE_OFF = CV_CH * CV_EARLY;
static_assert(CV_TILE_OFF + 16 * (D_ + 8) * 2 <= CV_LATE_BASE && CV_LATE_BASE >= 131072 + 16384, "front layout");
static_assert(CV_O_W3 >= 4096 && CV_O_U - CV_O_W3 >= 8192 && (CV_LATE % 16) == 0 && (CV_EARLY % 16) == 0, "front layout");

constexpr int LN_ROWS = 16;

template <typename PF>
__device__ __forceinline__ void front_phase(PF prefetch_fn, uint8_t* smem, const __nv_bfloat16* __restrict__ x,
                                            const __nv_bfloat16* __restrict__ A_re, const __nv_bfloat16* __restrict__ A_im,
                                            const __nv_bfloat16* __restrict__ B_re, const __nv_bfloat16* __restrict__ B_im,
                                            const __nv_bfloat16* __restrict__ C_re, const __nv_bfloat16* __restrict__ C_im,
                                            const __nv_bfloat16* __restrict__ log_dt, const __nv_bfloat16* __restrict__ Dskip,
                                            const __nv_bfloat16* __restrict__ wg, const __nv_bfloat16* __restrict__ wu,
                                            const __nv_bfloat16* __restrict__ wd) {
    const int warp = threadIdx.x >> 5, lane = threadIdx.x & 31;
    const int ch = warp / 3, w = warp - 3 * ch, tc = threadIdx.x - 96 * ch;
    const int d = blockIdx.x * CV_CH + ch;
    const int g = lane >> 2, t = lane & 3;
    uint8_t* base = smem + CV_LATE_BASE + ch * CV_LATE;
    float4* s_const = reinterpret_cast<float4*>(smem + ch * CV_EARLY + CV_O_CONST);
    float* s_kp = reinterpret_cast<float*>(smem + ch * CV_EARLY + CV_O_KP);
    uint32_t* s_q = reinterpret_cast<uint32_t*>(base + CV_O_Q);
    uint32_t* s_q2 = reinterpret_cast<uint32_t*>(base + CV_O_Q2);
    uint32_t* s_q3 = reinterpret_cast<uint32_t*>(base + CV_O_Q3);
    uint32_t* s_q4 = reinterpret_cast<uint32_t*>(base + CV_O_Q4X);
    __nv_bfloat16* s_u = reinterpret_cast<__nv_bfloat16*>(base + CV_O_U);
    const int bar_id = 5 + ch;
    const __nv_bfloat16 p_dsk = Dskip[d];
    __nv_bfloat16 (*tile)[D_ + 8] = reinterpret_cast<__nv_bfloat16 (*)[D_ + 8]>(smem + CV_TILE_OFF);

    if (warp < 8) {
        const int row = blockIdx.x * LN_ROWS + warp * 2;
        uint4 xv[2][2];
#pragma unroll
        for (int r = 0; r < 2; r++) {
            xv[r][0] = *reinterpret_cast<const uint4*>(x + (size_t)(row + r) * D_ + lane * 8);
            xv[r][1] = *reinterpret_cast<const uint4*>(x + (size_t)(row + r) * D_ + 256 + lane * 8);
        }
        float f[2][16], sm[2], q[2];
#pragma unroll
        for (int r = 0; r < 2; r++) {
            const uint32_t wv[8] = {xv[r][0].x, xv[r][0].y, xv[r][0].z, xv[r][0].w, xv[r][1].x, xv[r][1].y, xv[r][1].z, xv[r][1].w};
#pragma unroll
            for (int i = 0; i < 8; i++) { f[r][2 * i] = bf_lo(wv[i]); f[r][2 * i + 1] = bf_hi(wv[i]); }
            sm[r] = 0.f;
#pragma unroll
            for (int i = 0; i < 16; i++) sm[r] += f[r][i];
        }
#pragma unroll
        for (int o = 16; o > 0; o >>= 1) { sm[0] += __shfl_xor_sync(0xffffffffu, sm[0], o); sm[1] += __shfl_xor_sync(0xffffffffu, sm[1], o); }
#pragma unroll
        for (int r = 0; r < 2; r++) {
            sm[r] *= (1.0f / D_);
            q[r] = 0.f;
#pragma unroll
            for (int i = 0; i < 16; i++) { float dd = f[r][i] - sm[r]; q[r] += dd * dd; }
        }
#pragma unroll
        for (int o = 16; o > 0; o >>= 1) { q[0] += __shfl_xor_sync(0xffffffffu, q[0], o); q[1] += __shfl_xor_sync(0xffffffffu, q[1], o); }
#pragma unroll
        for (int r = 0; r < 2; r++) {
            const float mb = bf16_round(sm[r]);
            const float vb = bf16_round(q[r] * (1.0f / D_));
            const float den = bf16_round(sqrtf(bf16_round(vb + 1e-5f)));
            uint32_t o[8];
#pragma unroll
            for (int i = 0; i < 8; i++) {
                float a = __fdiv_rn(bf16_round(f[r][2 * i] - mb), den);
                float b = __fdiv_rn(bf16_round(f[r][2 * i + 1] - mb), den);
                o[i] = pack_bf16(a, b);
            }
            __nv_bfloat16* dst = g_xn + (size_t)(row + r) * D_;
            *reinterpret_cast<uint4*>(dst + lane * 8) = make_uint4(o[0], o[1], o[2], o[3]);
            *reinterpret_cast<uint4*>(dst + 256 + lane * 8) = make_uint4(o[4], o[5], o[6], o[7]);
            *reinterpret_cast<uint4*>(&tile[warp * 2 + r][lane * 8]) = make_uint4(o[0], o[1], o[2], o[3]);
            *reinterpret_cast<uint4*>(&tile[warp * 2 + r][256 + lane * 8]) = make_uint4(o[4], o[5], o[6], o[7]);
        }
    } else {
        const int cc_ = warp - 8, dd = blockIdx.x * CV_CH + cc_;
        float4* sc = reinterpret_cast<float4*>(smem + cc_ * CV_EARLY + CV_O_CONST);
        __nv_bfloat16 pr[4][6];
#pragma unroll
        for (int j = 0; j < 4; j++) {
            const size_t off = (size_t)dd * NS_ + lane + 32 * j;
            pr[j][0] = A_re[off]; pr[j][1] = A_im[off]; pr[j][2] = B_re[off]; pr[j][3] = B_im[off]; pr[j][4] = C_re[off]; pr[j][5] = C_im[off];
        }
        const float dt = bf16_round(expf(__bfloat162float(log_dt[dd])));
        float tail = 0.f;
#pragma unroll
        for (int j = 0; j < 4; j++) {
            const float ar = dt * __bfloat162float(pr[j][0]), ai = dt * __bfloat162float(pr[j][1]);
            const cplx db = {dt * __bfloat162float(pr[j][2]), dt * __bfloat162float(pr[j][3])};
            const cplx cc = {__bfloat162float(pr[j][4]), __bfloat162float(pr[j][5])};
            const cplx cb = cmul(cc, db);
            const float ar2 = ar * 1.4426950408889634f, ai2 = ai * 0.15915494309189535f;
            const cplx e8 = cexp_m(ar2, ai2, 8.f), e128 = cexp_m(ar2, ai2, 128.f);
            const cplx cb8 = cmul(cb, e8);
            const cplx e256 = cexp_m(ar2, ai2, 256.f), e512 = cexp_m(ar2, ai2, 512.f), e1024 = cexp_m(ar2, ai2, 1024.f);
            const cplx c256 = cmul(cb, e256), c512 = cmul(cb, e512), c1024 = cmul(cb, e1024);
            const cplx c768 = cmul(c512, e256), c1280 = cmul(c1024, e256), c1536 = cmul(c1024, e512);
            const cplx c1792 = cmul(c1536, e256);
            tail += cmul(c1024, e1024).r;
            float4* c = sc + (lane + 32 * j) * 6;
            c[0] = make_float4(ar2, ai2, cb.r, cb.i);
            c[1] = make_float4(e128.r, e128.i, cb8.r, cb8.i);
            c[2] = make_float4(c256.r, c256.i, e8.r, e8.i);
            c[3] = make_float4(c512.r, c512.i, c768.r, c768.i);
            c[4] = make_float4(c1024.r, c1024.i, c1280.r, c1280.i);
            c[5] = make_float4(c1536.r, c1536.i, c1792.r, c1792.i);
        }
#pragma unroll
        for (int o = 16; o > 0; o >>= 1) tail += __shfl_xor_sync(0xffffffffu, tail, o);
        if (lane == 0) {
            float* kp = reinterpret_cast<float*>(smem + cc_ * CV_EARLY + CV_O_KP);
            kp[640] = tail; kp[648 + 640] = 0.f; kp[1296 + 640] = 0.f;
        }
    }
    __syncthreads();
    if (threadIdx.x == 0) STAMP(0, 3);
#pragma unroll
    for (int rep = 0; rep < 2; rep++) {
        const int c = threadIdx.x + 384 * rep;
        if (c < D_) {
            uint32_t ot[8];
#pragma unroll
            for (int i = 0; i < 8; i++) {
                uint32_t lo = *reinterpret_cast<const uint16_t*>(&tile[2 * i][c]);
                uint32_t hi = *reinterpret_cast<const uint16_t*>(&tile[2 * i + 1][c]);
                ot[i] = lo | (hi << 16);
            }
            __nv_bfloat16* dT = g_xnT + (size_t)c * L_ + blockIdx.x * LN_ROWS;
            *reinterpret_cast<uint4*>(dT) = make_uint4(ot[0], ot[1], ot[2], ot[3]);
            *reinterpret_cast<uint4*>(dT + 8) = make_uint4(ot[4], ot[5], ot[6], ot[7]);
        }
    }
    if (threadIdx.x < 336) {
        const int m = threadIdx.x / 112, i = threadIdx.x - m * 112;
        const char* wp = (const char*)(m == 0 ? wg : (m == 1 ? wu : wd));
        asm volatile("prefetch.global.L2 [%0];" ::"l"(wp + ((size_t)blockIdx.x * 112 + i) * 128));
    }
    __syncthreads();
    if (threadIdx.x == 0) STAMP(1, 1);
    {
        float acc[5][4];
#pragma unroll
        for (int i = 0; i < 5; i++) { acc[i][0] = acc[i][1] = acc[i][2] = acc[i][3] = 0.f; }
        const float gf = (float)g;
        const int src4 = ((g & 3) << 2) | t;
#pragma unroll 2
        for (int s = w; s < 32; s += 3) {
            if (s == 17 && threadIdx.x == 352) asm volatile("red.release.gpu.global.add.u32 [%0], 1;" ::"l"(&g_ln_count) : "memory");
            const float4* c = s_const + (s * 4 + t) * 6;
            const float4 k0 = c[0], k1 = c[1], k2 = c[2];
            const float2 k3 = reinterpret_cast<const float2*>(c + 3)[g >> 2];
            const float2 k4 = reinterpret_cast<const float2*>(c + 4)[g >> 1];
            const cplx cb = {k0.z, k0.w}, e128 = {k1.x, k1.y}, cb8 = {k1.z, k1.w}, c256 = {k2.x, k2.y}, e8 = {k2.z, k2.w};
            const cplx c2 = {k3.x, k3.y}, c3 = {k4.x, k4.y};
            const cplx p1 = cexp_m(k0.x, k0.y, gf);
            const cplx p2 = csq(p1), p4 = csq(p2);
            const cplx r16a = csq(csq(p4));
            cplx q4;
            q4.r = __shfl_sync(0xffffffffu, p4.r, src4);
            q4.i = __shfl_sync(0xffffffffu, p4.i, src4);
            const cplx r16b = cmul(r16a, e128);
            const cplx f0a = cmul(cb, p1), f0b = cmul(cb8, p1), f1 = cmul(c256, p2), f2 = cmul(c2, q4);
            cplx f3 = cmul(c3, e8);
            if (!(g & 1)) f3 = c3;
            const uint32_t a0 = to_tf32(r16a.r), a1 = to_tf32(r16b.r), a2 = to_tf32(-r16a.i), a3 = to_tf32(-r16b.i);
            mma_tf32(acc[0], a0, a1, a2, a3, to_tf32(f0a.r), to_tf32(f0a.i));
            mma_tf32(acc[1], a0, a1, a2, a3, to_tf32(f0b.r), to_tf32(f0b.i));
            mma_tf32(acc[2], a0, a1, a2, a3, to_tf32(f1.r), to_tf32(f1.i));
            mma_tf32(acc[3], a0, a1, a2, a3, to_tf32(f2.r), to_tf32(f2.i));
            mma_tf32(acc[4], a0, a1, a2, a3, to_tf32(f3.r), to_tf32(f3.i));
        }
        float* kv = s_kp + w * 648;
#pragma unroll
        for (int hh = 0; hh < 2; hh++) {
            const int i = g + 8 * hh;
            *reinterpret_cast<float2*>(kv + 16 * i + 2 * t) = make_float2(acc[0][2 * hh], acc[0][2 * hh + 1]);
            *reinterpret_cast<float2*>(kv + 16 * i + 8 + 2 * t) = make_float2(acc[1][2 * hh], acc[1][2 * hh + 1]);
            *reinterpret_cast<float2*>(kv + 256 + 8 * i + 2 * t) = make_float2(acc[2][2 * hh], acc[2][2 * hh + 1]);
            *reinterpret_cast<float2*>(kv + 384 + 64 * (t >> 1) + 2 * (t & 1) + 4 * i) = make_float2(acc[3][2 * hh], acc[3][2 * hh + 1]);
            *reinterpret_cast<float2*>(kv + 512 + 32 * t + 2 * i) = make_float2(acc[4][2 * hh], acc[4][2 * hh + 1]);
        }
    }
    named_bar(bar_id, 96);
    if (threadIdx.x == 0) STAMP(1, 2);
#pragma unroll
    for (int i = 0; i < 7; i++) {
        const int idx = tc + 96 * i;
        if (idx < 641) s_kp[idx] = (s_kp[idx] + s_kp[648 + idx]) + s_kp[1296 + idx];
    }
    named_bar(bar_id, 96);
    {
        auto kdir = [&](int l) -> float {
            if (l < 0 || l > 514) return 0.f;
            const int idx = (l < 256) ? l : (l > 512 ? 384 : 128 + ((l + ((l >> 1) & 1)) >> 1));
            return s_kp[idx];
        };
#pragma unroll
        for (int i = 0; i < 6; i++) {
            const int e = tc + 96 * i;
            s_q[e] = pack_bf16(kdir(e - 16), kdir(e - 17));
        }
        if (tc < 64) {
            const int xx = 1008 + tc;
            const float k1024 = s_kp[512];
            s_q4[tc] = pack_bf16((xx == 1027 || xx == 1028) ? k1024 : 0.f, (xx == 1028 || xx == 1029) ? k1024 : 0.f);
        }
#pragma unroll
        for (int i = 0; i < 3; i++) {
            const int e = tc + 96 * i;
            if (e < 256) {
                const int a = e >> 6, ii = (e & 63) - 16;
                const int b = 385 + (a >> 1) + 2 * (a & 1);
                const float v0 = (ii >= 0 && ii < 32) ? s_kp[b + 4 * ii] : 0.f;
                const float v1 = (ii >= 1 && ii < 33) ? s_kp[b + 4 * (ii - 1)] : 0.f;
                s_q2[e] = pack_bf16(v0, v1);
            }
        }
#pragma unroll
        for (int a = 0; a < 2; a++) {
            const int jj = tc - 16;
            const float v0 = (jj >= 0 && jj < 64) ? s_kp[513 + a + 2 * jj] : 0.f;
            const float v1 = (jj >= 1 && jj < 65) ? s_kp[513 + a + 2 * (jj - 1)] : 0.f;
            s_q3[96 * a + tc] = pack_bf16(v0, v1);
        }
    }
    if (threadIdx.x == 0) STAMP(1, 3);
    if (threadIdx.x == 0) {
        unsigned int v = 0;
        for (int spin = 0; spin < (1 << 22); spin++) {
            asm volatile("ld.acquire.gpu.global.u32 %0, [%1];" : "=r"(v) : "l"(&g_ln_count) : "memory");
            if (v >= gridDim.x) break;
        }
    }
    fence_async_smem();
    __syncthreads();
    if (threadIdx.x == 0) STAMP(1, 4);
    prefetch_fn();
    {
        if (tc < 16) *reinterpret_cast<uint4*>(s_u + tc * 8) = make_uint4(0, 0, 0, 0);
        const uint4* src = reinterpret_cast<const uint4*>(g_xnT + (size_t)d * L_);
        uint4 v[3];
#pragma unroll
        for (int i = 0; i < 3; i++) if (tc + 96 * i < 256) v[i] = src[tc + 96 * i];
#pragma unroll
        for (int i = 0; i < 3; i++) if (tc + 96 * i < 256) *reinterpret_cast<uint4*>(s_u + 128 + (tc + 96 * i) * 8) = v[i];
        if (tc < 2) *reinterpret_cast<uint4*>(base + (tc ? CV_O_W5 : CV_O_W3)) = make_uint4(0, 0, 0, 0);
    }
    named_bar(bar_id, 96);
#pragma unroll
    for (int rep = 0; rep < 2; rep++) {
        const int m = tc + 96 * rep;
        float P[30];
        const uint4* up = reinterpret_cast<const uint4*>(s_u + 128 + 8 * m - 24);
        P[0] = 0.f;
#pragma unroll
        for (int c4 = 0; c4 < 4; c4++) {
            const uint4 v = up[c4];
            const uint32_t ww[4] = {v.x, v.y, v.z, v.w};
#pragma unroll
            for (int j = 0; j < 4; j++) {
                const int k = c4 * 8 + 2 * j;
                if (k + 1 <= 29) P[k + 1] = P[k] + bf_lo(ww[j]);
                if (k + 2 <= 29) P[k + 2] = P[k + 1] + bf_hi(ww[j]);
            }
        }
        uint32_t o3[4], o5[4], o7[4], o9[4];
#pragma unroll
        for (int j = 0; j < 4; j++) {
            const int i = 2 * j;
            o3[j] = pack_bf16(P[i + 22] - P[i + 19], P[i + 23] - P[i + 20]);
            o5[j] = pack_bf16(P[i + 19] - P[i + 14], P[i + 20] - P[i + 15]);
            o7[j] = pack_bf16(P[i + 20] - P[i + 13], P[i + 21] - P[i + 14]);
            o9[j] = pack_bf16(P[i + 13] - P[i + 4], P[i + 14] - P[i + 5]);
        }
        *reinterpret_cast<uint4*>(base + CV_O_W3 + 16 + m * 16) = make_uint4(o3[0], o3[1], o3[2], o3[3]);
        *reinterpret_cast<uint4*>(base + CV_O_W5 + 16 + m * 16) = make_uint4(o5[0], o5[1], o5[2], o5[3]);
        if (m < 128) {
            *reinterpret_cast<uint4*>(base + CV_O_W7 + m * 16) = make_uint4(o7[0], o7[1], o7[2], o7[3]);
            *reinterpret_cast<uint4*>(base + CV_O_W9 + m * 16) = make_uint4(o9[0], o9[1], o9[2], o9[3]);
        }
    }
    if (threadIdx.x == 0) STAMP(1, 5);
    named_bar(bar_id, 96);
    if (w == 2) return;
    const int hb = w;
    float acc[16][4];
#pragma unroll
    for (int i = 0; i < 16; i++) { acc[i][0] = acc[i][1] = acc[i][2] = acc[i][3] = 0.f; }
    const uint32_t sb_addr = smem_u32(base);
    const int mi = lane >> 3, rowi = lane & 7;
#pragma unroll 1
    for (int rr = 0; rr < 4; rr++) {
        const int r = 4 * hb + rr;
        uint32_t ub[16][2];
        {
            const uint32_t addr = sb_addr + CV_O_U + (uint32_t)((128 + 16 * (8 * (mi >> 1) + rowi - r) + 8 * (mi & 1)) * 2);
#pragma unroll
            for (int j = 0; j < 16; j += 2) ldsm_x4(addr + (uint32_t)(j * 256), ub[j][0], ub[j][1], ub[j + 1][0], ub[j + 1][1]);
        }
        const uint32_t* qp = s_q + 16 + 16 * r + g - 2 * t;
        uint32_t af[4][3];
#pragma unroll
        for (int q = 0; q < 4; q++) { af[q][0] = qp[128 * q]; af[q][1] = qp[128 * q + 8]; af[q][2] = qp[128 * q - 8]; }
#pragma unroll
        for (int q = 0; q < 4; q++) {
#pragma unroll
            for (int nt = q; nt < 16; nt++) mma_bf16(acc[nt], af[q][0], af[q][1], af[q][2], af[q][0], ub[nt - q][0], ub[nt - q][1]);
        }
        if (r < 2) {
            {
                const uint32_t a0 = qp[512], a1 = qp[520], a2 = qp[504];
#pragma unroll
                for (int nt = 4; nt < 16; nt++) mma_bf16(acc[nt], a0, a1, a2, a0, ub[nt - 4][0], ub[nt - 4][1]);
            }
            {
                const uint32_t* q4p = s_q4 + 16 + 16 * r + g - 2 * t;
                const uint32_t a0 = q4p[0], a1 = q4p[8], a2 = q4p[-8];
#pragma unroll
                for (int nt = 8; nt < 16; nt++) mma_bf16(acc[nt], a0, a1, a2, a0, ub[nt - 8][0], ub[nt - 8][1]);
            }
        }
    }
#pragma unroll 1
    for (int a = hb; a <= 3 * hb; a++) {
        uint32_t bq[7];
        const uint32_t* q2 = s_q2 + a * 64 + 16 + g - 2 * t - 32;
#pragma unroll
        for (int dlt = 3; dlt <= 9; dlt++) bq[dlt - 3] = q2[8 * dlt];
        const uint32_t addr = sb_addr + ((a >> 1) ? CV_O_W5 : CV_O_W3) + (uint32_t)((8 + 16 * (8 * (mi >> 1) + rowi) + 8 * (mi & 1) - 8 * (a & 1)) * 2);
        uint32_t aa[6][4];
#pragma unroll
        for (int kp = 0; kp < 6; kp++) ldsm_x4_t(addr + kp * 512, aa[kp][0], aa[kp][1], aa[kp][2], aa[kp][3]);
#pragma unroll
        for (int kp = 0; kp < 6; kp++) {
#pragma unroll
            for (int dlt = 4; dlt <= 9; dlt++) {
                if (2 * kp + dlt < 16) mma_bf16(acc[2 * kp + dlt], aa[kp][0], aa[kp][1], aa[kp][2], aa[kp][3], bq[dlt - 3], bq[dlt - 4]);
            }
        }
    }
    if (hb == 0) {
#pragma unroll 1
        for (int a = 0; a < 2; a++) {
            uint32_t bq[9];
            const uint32_t* q3 = s_q3 + a * 96 + 16 + g - 2 * t - 64;
#pragma unroll
            for (int dlt = 7; dlt <= 15; dlt++) bq[dlt - 7] = q3[8 * dlt];
            const uint32_t addr = sb_addr + (a ? CV_O_W9 : CV_O_W7) + (uint32_t)((16 * (8 * (mi >> 1) + rowi) + 8 * (mi & 1)) * 2);
            uint32_t aa[4][4];
#pragma unroll
            for (int kp = 0; kp < 4; kp++) ldsm_x4_t(addr + kp * 512, aa[kp][0], aa[kp][1], aa[kp][2], aa[kp][3]);
#pragma unroll
            for (int kp = 0; kp < 4; kp++) {
#pragma unroll
                for (int dlt = 8; dlt <= 15; dlt++) {
                    if (2 * kp + dlt < 16) mma_bf16(acc[2 * kp + dlt], aa[kp][0], aa[kp][1], aa[kp][2], aa[kp][3], bq[dlt - 7], bq[dlt - 8]);
                }
            }
        }
    }
    if (threadIdx.x == 0) STAMP(1, 6);
    named_bar(bar_id, 64);
    {
        float4* xch = reinterpret_cast<float4*>(base + CV_O_W3) + hb * 256;
        if (hb) {
#pragma unroll
            for (int i = 0; i < 8; i++) xch[i * 32 + lane] = make_float4(acc[i][0], acc[i][1], acc[i][2], acc[i][3]);
#pragma unroll
            for (int i = 0; i < 8; i++) { acc[i][0] = acc[8 + i][0]; acc[i][1] = acc[8 + i][1]; acc[i][2] = acc[8 + i][2]; acc[i][3] = acc[8 + i][3]; }
        } else {
#pragma unroll
            for (int i = 0; i < 8; i++) xch[i * 32 + lane] = make_float4(acc[8 + i][0], acc[8 + i][1], acc[8 + i][2], acc[8 + i][3]);
        }
    }
    named_bar(bar_id, 64);
    if (threadIdx.x == 0) STAMP(1, 10);
    {
        const float4* xch = reinterpret_cast<const float4*>(base + CV_O_W3) + (hb ^ 1) * 256 + lane;
        const float dsk = __bfloat162float(p_dsk);
        uint16_t* stg = reinterpret_cast<uint16_t*>(base + CV_O_Q);
        const uint16_t* uu = reinterpret_cast<const uint16_t*>(s_u) + 128;
#pragma unroll
        for (int i = 0; i < 8; i++) {
            const float4 p0 = xch[i * 32];
            const float y[4] = {acc[i][0] + p0.x, acc[i][1] + p0.y, acc[i][2] + p0.z, acc[i][3] + p0.w};
            const int nt = 8 * hb + i;
#pragma unroll
            for (int e = 0; e < 4; e++) {
                const int tau = 16 * (8 * nt + 2 * t + (e & 1)) + g + 8 * (e >> 1);
                const float sv = bf16_round(y[e]) + bf16_round(__uint_as_float((uint32_t)uu[tau] << 16) * dsk);
                stg[tau] = (uint16_t)(__float_as_uint(bf16_round(sv)) >> 16);
            }
        }
        __syncwarp();
        if (threadIdx.x == 0) STAMP(1, 11);
        uint4* dst = reinterpret_cast<uint4*>(g_sT + (size_t)d * L_ + hb * 1024);
        const uint4* srcp = reinterpret_cast<const uint4*>(stg + hb * 1024);
#pragma unroll
        for (int i = 0; i < 4; i++) dst[i * 32 + lane] = srcp[i * 32 + lane];
    }
}

__device__ __forceinline__ uint32_t cluster_rank() { uint32_t r; asm volatile("mov.u32 %0, %%cluster_ctarank;" : "=r"(r)); return r; }
__device__ __forceinline__ void cluster_sync_all() {
    asm volatile("barrier.cluster.arrive.release.aligned;\nbarrier.cluster.wait.acquire.aligned;" ::: "memory");
}
__device__ __forceinline__ void mbar_arrive_remote(uint32_t bar, uint32_t cta) {
    asm volatile("{\n.reg .b32 ra;\nmapa.shared::cluster.u32 ra, %0, %1;\n"
                 "mbarrier.arrive.shared::cluster.b64 _, [ra];\n}\n" ::"r"(bar), "r"(cta) : "memory");
}
__device__ __forceinline__ void tma_load_2d_mc(uint32_t dst, const CUtensorMap* tm, int c0, int c1, uint32_t bar, uint16_t mask) {
    asm volatile(
        "cp.async.bulk.tensor.2d.shared::cluster.global.mbarrier::complete_tx::bytes.multicast::cluster [%0], [%1, {%3, %4}], [%2], %5;"
        ::"r"(dst), "l"((uint64_t)tm), "r"(bar), "r"(c0), "r"(c1), "h"(mask) : "memory");
}
__device__ __forceinline__ void tma_store_2d(const CUtensorMap* tm, uint32_t src, int c0, int c1) {
    asm volatile("cp.async.bulk.tensor.2d.global.shared::cta.bulk_group [%0, {%2, %3}], [%1];"
                 ::"l"((uint64_t)tm), "r"(src), "r"(c0), "r"(c1) : "memory");
}
__device__ __forceinline__ void bulk_commit() { asm volatile("cp.async.bulk.commit_group;" ::: "memory"); }
template <int N> __device__ __forceinline__ void bulk_wait_read() { asm volatile("cp.async.bulk.wait_group.read %0;" ::"n"(N) : "memory"); }
template <int N> __device__ __forceinline__ void bulk_wait() { asm volatile("cp.async.bulk.wait_group %0;" ::"n"(N) : "memory"); }
__device__ __forceinline__ void stmatrix_x4(uint32_t addr, uint32_t r0, uint32_t r1, uint32_t r2, uint32_t r3) {
    asm volatile("stmatrix.sync.aligned.m8n8.x4.shared.b16 [%0], {%1,%2,%3,%4};" ::"r"(addr), "r"(r0), "r"(r1), "r"(r2), "r"(r3) : "memory");
}

constexpr int G1_STAGES = 5;
constexpr int G1_A_BYTES = 8 * 16384;
constexpr int G1_B_STAGE = 16384;
constexpr int G1_STG = 8 * 1024;
constexpr int G1_SMEM = G1_A_BYTES + G1_STAGES * G1_B_STAGE + G1_STG + 1024 + 256;
constexpr int G1_ITERS = 32;

__device__ __forceinline__ void tma_load_3d(uint32_t dst, const CUtensorMap* tm, int c0, int c1, int c2, uint32_t bar) {
    asm volatile(
        "cp.async.bulk.tensor.3d.shared::cluster.global.mbarrier::complete_tx::bytes [%0], [%1, {%3, %4, %5}], [%2];"
        ::"r"(dst), "l"((uint64_t)tm), "r"(bar), "r"(c0), "r"(c1), "r"(c2) : "memory");
}

__device__ __forceinline__ float gelu_tanh(float x) {
    float u = x * (0.7978845608028654f + 0.035677408136300125f * x * x);
    float t; asm("tanh.approx.f32 %0, %1;" : "=f"(t) : "f"(u));
    float hx = 0.5f * x;
    return fmaf(hx, t, hx);
}
__device__ __forceinline__ uint32_t geglu_pair(uint32_t g2, uint32_t u2) {
    uint32_t a = pack_bf16(gelu_tanh(bf_lo(g2)), gelu_tanh(bf_hi(g2)));
    uint32_t r; asm("mul.rn.bf16x2 %0, %1, %2;" : "=r"(r) : "r"(a), "r"(u2));
    return r;
}

constexpr int G2_STAGES = 5;
constexpr int G2_STAGE = 16384 + 16384;
constexpr int G2_XCH = 32768;
constexpr int G2_EPI = 16384 + 16384;
constexpr int G2_SMEM = G2_STAGES * G2_STAGE + G2_XCH + G2_EPI + 1024 + 256;
constexpr int G2_KB = F_ / 64 / 2;

constexpr int MG_BAR_OFF = G2_STAGES * G2_STAGE + G2_XCH + G2_EPI;
constexpr int MG_SMEM = MG_BAR_OFF + 256 + 1024;
static_assert(MG_BAR_OFF == 229376 && G1_A_BYTES + G1_STAGES * G1_B_STAGE + G1_STG <= MG_BAR_OFF, "smem layout");

__device__ __forceinline__ void fence_async_all() { asm volatile("fence.proxy.async;" ::: "memory"); }
__device__ __forceinline__ void spin_until(const unsigned int* p, unsigned int target) {
    unsigned int v = 0;
    for (int spin = 0; spin < (1 << 22); spin++) {
        asm volatile("ld.acquire.gpu.global.u32 %0, [%1];" : "=r"(v) : "l"(p) : "memory");
        if (v >= target) break;
    }
}

struct MegaParams {
    const __nv_bfloat16 *x, *A_re, *A_im, *B_re, *B_im, *C_re, *C_im, *log_dt, *Dskip, *wg, *wu, *wd;
};

__global__ void __launch_bounds__(384, 1) mega_kernel(const __grid_constant__ MegaParams P,
                                                       const __grid_constant__ CUtensorMap tm_xn,
                                                       const __grid_constant__ CUtensorMap tm_wg4,
                                                       const __grid_constant__ CUtensorMap tm_wu4,
                                                       const __grid_constant__ CUtensorMap tm_wg3,
                                                       const __grid_constant__ CUtensorMap tm_wu3,
                                                       const __grid_constant__ CUtensorMap tm_h,
                                                       const __grid_constant__ CUtensorMap tm_wd,
                                                       const __grid_constant__ CUtensorMap tm_x,
                                                       const __grid_constant__ CUtensorMap tm_sT,
                                                       const __grid_constant__ CUtensorMap tm_out) {
    if (threadIdx.x == 0) STAMP(1, 0);
    extern __shared__ uint8_t smem_raw[];
    const uint32_t sraw = smem_u32(smem_raw);
    const uint32_t sbase = (sraw + 1023) & ~1023u;
    uint8_t* smem = smem_raw + (sbase - sraw);
    const int warp = threadIdx.x >> 5, lane = threadIdx.x & 31;
    const uint32_t sA = sbase, sB = sbase + G1_A_BYTES, sStg = sB + G1_STAGES * G1_B_STAGE;
    const uint32_t sXch = sbase + G2_STAGES * G2_STAGE, sX = sXch + G2_XCH, sS = sX + 16384;
    const uint32_t sBar = sbase + MG_BAR_OFF;
    const uint32_t bar_a = sBar, bar_full = sBar + 64, bar_empty = bar_full + 8 * G1_STAGES;
    const uint32_t bar_full2 = bar_empty + 8 * G1_STAGES, bar_empty2 = bar_full2 + 8 * G2_STAGES;
    const uint32_t bar_epi = bar_empty2 + 8 * G2_STAGES, bar_xch = bar_epi + 8, bar_g1done = bar_xch + 8, bar_g1mma = bar_g1done + 8;
    const int rb = blockIdx.x >> 3, cj = blockIdx.x & 7;
    const uint32_t kh = blockIdx.x & 1;
    const int nb = (blockIdx.x >> 1) & 3;
    const int col_fin = nb * 128 + kh * 64;

    if (threadIdx.x == 0) {
        for (int i = 0; i < 8; i++) mbar_init(bar_a + 8 * i, 1);
        for (int i = 0; i < G1_STAGES; i++) { mbar_init(bar_full + 8 * i, 1); mbar_init(bar_empty + 8 * i, 8); }
        for (int i = 0; i < G2_STAGES; i++) { mbar_init(bar_full2 + 8 * i, 1); mbar_init(bar_empty2 + 8 * i, 8); }
        mbar_init(bar_epi, 1);
        mbar_init(bar_xch, 1);
        mbar_init(bar_g1done, 8);
        mbar_init(bar_g1mma, 8);
        asm volatile("fence.mbarrier_init.release.cluster;" ::: "memory");
        mbar_expect_tx(bar_xch, G2_XCH);
    }
    if (warp == 11 && lane == 0) {
        prefetch_tmap(&tm_wg4); prefetch_tmap(&tm_wu4); prefetch_tmap(&tm_xn); prefetch_tmap(&tm_wg3); prefetch_tmap(&tm_wu3);
        prefetch_tmap(&tm_wd); prefetch_tmap(&tm_h); prefetch_tmap(&tm_x); prefetch_tmap(&tm_sT); prefetch_tmap(&tm_out);
    }
    asm volatile("barrier.cluster.arrive.release.aligned;" ::: "memory");

    auto g1_prefetch = [&]() {
        if (warp == 8 && lane == 0) {
            fence_async_all();
            mbar_expect_tx(bar_full, 16384);
            tma_load_3d(sB, &tm_wg4, 0, 0, cj * 7, bar_full);
            tma_load_3d(sB + 8192, &tm_wu4, 0, 0, cj * 7, bar_full);
            for (int k = 0; k < 8; k++) {
                mbar_expect_tx(bar_a + 8 * k, 16384);
                tma_load_2d(sA + k * 16384, &tm_xn, k * 64, rb * 128, bar_a + 8 * k);
            }
        }
    };
    front_phase(g1_prefetch, smem, P.x, P.A_re, P.A_im, P.B_re, P.B_im, P.C_re, P.C_im, P.log_dt, P.Dskip, P.wg, P.wu, P.wd);
    fence_async_smem();
    asm volatile("barrier.cluster.wait.acquire.aligned;" ::: "memory");
    __syncthreads();
    if (threadIdx.x == 0) STAMP(1, 7);

    if (warp >= 8) {
        asm volatile("setmaxnreg.dec.sync.aligned.u32 40;");
        if (warp == 11) {
            if (lane == 0) asm volatile("red.release.gpu.global.add.u32 [%0], 1;" ::"l"(&g_conv_count) : "memory");
            named_bar(3, 288);
            if (lane == 0) asm volatile("red.release.gpu.global.add.u32 [%0], 1;" ::"l"(&g_h_count[rb]) : "memory");
            named_bar(9, 288);
            if (lane == 0) asm volatile("red.release.gpu.global.add.u32 [%0], 1;" ::"l"(&g_h_count[16 + rb]) : "memory");
        } else if (lane == 0) {
            const int pw = warp - 8;
            for (int it = 1 + pw; it < G1_ITERS; it += 3) {
                const int s = it % G1_STAGES, kb = it & 15;
                if (it >= G1_STAGES) mbar_wait(bar_empty + 8 * s, ((it / G1_STAGES) - 1) & 1);
                const uint32_t dst = sB + s * G1_B_STAGE;
                if (it < 16) {
                    mbar_expect_tx(bar_full + 8 * s, 16384);
                    tma_load_3d(dst, &tm_wg4, 0, kb * 32, cj * 7, bar_full + 8 * s);
                    tma_load_3d(dst + 8192, &tm_wu4, 0, kb * 32, cj * 7, bar_full + 8 * s);
                } else {
                    mbar_expect_tx(bar_full + 8 * s, 12288);
                    tma_load_3d(dst, &tm_wg3, 0, kb * 32, cj * 7 + 4, bar_full + 8 * s);
                    tma_load_3d(dst + 6144, &tm_wu3, 0, kb * 32, cj * 7 + 4, bar_full + 8 * s);
                }
            }
            const int k0 = kh * G2_KB;
            auto kblk = [&](int it) -> int {
                const unsigned long long tab = 0xDCA96532B87410ull;
                return k0 + (int)((tab >> (4 * it)) & 15);
            };
            mbar_wait(bar_g1mma, 0);
            if (pw == 2) {
                mbar_expect_tx(bar_epi, G2_EPI);
                tma_load_2d(sX, &tm_x, col_fin, rb * 128, bar_epi);
            }
            spin_until(&g_h_count[rb], 8);
            fence_async_all();
            if (pw == 0) STAMP(3, 1);
            for (int it = pw; it < G2_KB; it += 3) {
                const int s = (it + 1) % G2_STAGES;
                if (it == 4) mbar_wait(bar_g1done, 0);
                if (it >= G2_STAGES) mbar_wait(bar_empty2 + 8 * s, ((it / G2_STAGES) - 1) & 1);
                if (it >= 6 && it < 9) { spin_until(&g_h_count[16 + rb], 8); fence_async_all(); }
                mbar_expect_tx(bar_full2 + 8 * s, G2_STAGE);
                const int kb = kblk(it);
                tma_load_3d(sbase + s * G2_STAGE + 16384, &tm_wd, 0, kb * 64, nb * 2, bar_full2 + 8 * s);
                tma_load_2d(sbase + s * G2_STAGE, &tm_h, kb * 64, rb * 128, bar_full2 + 8 * s);
                if (it == 2) {
                    spin_until(&g_conv_count, gridDim.x);
                    fence_async_all();
                    tma_load_2d(sS, &tm_sT, rb * 128, col_fin, bar_epi);
                    tma_load_2d(sS + 8192, &tm_sT, rb * 128 + 64, col_fin, bar_epi);
                }
            }
        }
    } else {
        asm volatile("setmaxnreg.inc.sync.aligned.u32 232;");
        const int wg = __shfl_sync(0xffffffffu, (int)(threadIdx.x >> 7), 0);
        {
        float r[160];
        const int row0 = rb * 128 + wg * 64 + (warp & 3) * 16;
        const uint64_t descA = make_desc(sA + wg * 8192, 16, 1024);
        const uint64_t descB = make_desc(sB, 2048, 512, 2);
        const uint32_t stg = sStg + warp * 1024;
        const uint32_t st_off = (uint32_t)(((lane & 7) + ((lane >> 3) & 1) * 8) * 32 + (lane >> 4) * 16);
        __nv_bfloat16* hrow = g_h + (size_t)(row0 + (lane >> 1)) * F_ + (lane & 1) * 8 + cj * 224;
#pragma unroll
        for (int kb = 0; kb < 16; kb++) {
            const int it = kb, s = it % G1_STAGES;
            if ((kb & 1) == 0) mbar_wait(bar_a + 8 * (kb >> 1), 0);
            mbar_wait(bar_full + 8 * s, (it / G1_STAGES) & 1);
            if (threadIdx.x == 0 && (it & 7) == 0) STAMP(2, 2 + it / 8);
            wgmma_fence();
            const uint64_t da = descA + (uint64_t)(((kb >> 1) * 16384 + (kb & 1) * 64) >> 4);
            const uint64_t db = descB + (uint64_t)((s * G1_B_STAGE) >> 4);
            wgmma_n256_k32(r, da, da + 2, db, db + 64, kb != 0);
            wgmma_commit();
            if (kb > 0) {
                wgmma_wait<1>();
                if (lane == 0) mbar_arrive(bar_empty + 8 * ((it - 1) % G1_STAGES));
            }
        }
        wgmma_wait<0>();
        if (lane == 0) mbar_arrive(bar_empty + 8 * (15 % G1_STAGES));
#pragma unroll
        for (int i = 0; i < 32; i++) r[128 + i] = __uint_as_float(pack_bf16(r[2 * i], r[2 * i + 1]));
#pragma unroll
        for (int i = 31; i >= 0; i--) r[96 + i] = __uint_as_float(pack_bf16(r[64 + 2 * i], r[65 + 2 * i]));
        uint32_t eo[4];
        uint4 pv = make_uint4(0, 0, 0, 0);
#pragma unroll
        for (int kb = 0; kb < 16; kb++) {
            const int it = 16 + kb, s = it % G1_STAGES;
            mbar_wait(bar_full + 8 * s, (it / G1_STAGES) & 1);
            if (threadIdx.x == 0 && (it & 7) == 0) STAMP(2, 2 + it / 8);
            wgmma_fence();
            const uint64_t da = descA + (uint64_t)(((kb >> 1) * 16384 + (kb & 1) * 64) >> 4);
            const uint64_t db = descB + (uint64_t)((s * G1_B_STAGE) >> 4);
            wgmma_n192(r, da, db, kb != 0);
            if (kb < 8) {
                eo[0] = geglu_pair(__float_as_uint(r[128 + 4 * kb]), __float_as_uint(r[96 + 4 * kb]));
                eo[1] = geglu_pair(__float_as_uint(r[129 + 4 * kb]), __float_as_uint(r[97 + 4 * kb]));
            }
            wgmma_n192(r, da + 2, db + 64, 1);
            wgmma_commit();
            if (kb >= 2 && kb < 10) *reinterpret_cast<uint4*>(hrow + (kb - 2) * 16) = pv;
            if (kb >= 1 && kb < 9) {
                __syncwarp();
                asm volatile("ld.shared.v4.u32 {%0,%1,%2,%3}, [%4];" : "=r"(pv.x), "=r"(pv.y), "=r"(pv.z), "=r"(pv.w)
                             : "r"(stg + ((kb - 1) & 1) * 512 + lane * 16));
            }
            if (kb < 8) {
                eo[2] = geglu_pair(__float_as_uint(r[130 + 4 * kb]), __float_as_uint(r[98 + 4 * kb]));
                eo[3] = geglu_pair(__float_as_uint(r[131 + 4 * kb]), __float_as_uint(r[99 + 4 * kb]));
                stmatrix_x4(stg + (kb & 1) * 512 + st_off, eo[0], eo[1], eo[2], eo[3]);
            }
            if (kb == 9) asm volatile("bar.arrive 3, 288;" ::: "memory");
            if (kb > 0 && it - 1 + G1_STAGES < G1_ITERS) {
                wgmma_wait<1>();
                if (lane == 0) mbar_arrive(bar_empty + 8 * ((it - 1) % G1_STAGES));
            }
        }
        wgmma_wait<0>();
        fence_async_smem();
        __syncwarp();
        if (lane == 0) mbar_arrive(bar_g1mma);
        if (threadIdx.x == 0) STAMP(2, 6);
        {
            uint32_t o[24];
#pragma unroll
            for (int i = 0; i < 24; i++) o[i] = geglu_pair(pack_bf16(r[2 * i], r[2 * i + 1]), pack_bf16(r[48 + 2 * i], r[49 + 2 * i]));
            named_bar(1 + wg, 128);
            const uint32_t fbuf = sA + ((warp & 3) >> 1) * 16384 + wg * 8192 + (warp & 1) * 4096;
#pragma unroll
            for (int jj = 0; jj < 6; jj++) stmatrix_x4(fbuf + jj * 512 + st_off, o[4 * jj], o[4 * jj + 1], o[4 * jj + 2], o[4 * jj + 3]);
            __syncwarp();
            uint4 v[6];
#pragma unroll
            for (int jj = 0; jj < 6; jj++)
                asm volatile("ld.shared.v4.u32 {%0,%1,%2,%3}, [%4];" : "=r"(v[jj].x), "=r"(v[jj].y), "=r"(v[jj].z), "=r"(v[jj].w)
                             : "r"(fbuf + jj * 512 + lane * 16));
#pragma unroll
            for (int jj = 0; jj < 6; jj++) *reinterpret_cast<uint4*>(hrow + 128 + jj * 16) = v[jj];
        }
        }
        fence_async_smem();
        __syncwarp();
        if (lane == 0) mbar_arrive(bar_g1done);
        asm volatile("bar.arrive 9, 288;" ::: "memory");
        if (threadIdx.x == 0) STAMP(2, 7);
        {
        const int g = lane >> 2, t = lane & 3;
        float acc[64];
        const uint64_t descA2 = make_desc(sbase + wg * 8192, 16, 1024);
        const uint64_t descB2 = make_desc(sbase + 16384, 8192, 1024);
#pragma unroll
        for (int it = 0; it < G2_KB; it++) {
            const int s = (it + 1) % G2_STAGES;
            mbar_wait(bar_full2 + 8 * s, (it / G2_STAGES) & 1);
            if (threadIdx.x == 0 && (it == 0 || it == 7)) STAMP(3, 2 + it / 7);
            wgmma_fence();
            {
                const uint64_t da = descA2 + (uint64_t)((s * G2_STAGE) >> 4);
                const uint64_t db = descB2 + (uint64_t)((s * G2_STAGE) >> 4);
                wgmma_n128_k64(acc, da, da + 2, da + 4, da + 6, db, db + 128, db + 256, db + 384, it != 0);
            }
            wgmma_commit();
            if (it > 0 && it - 1 + G2_STAGES < G2_KB) {
                wgmma_wait<1>();
                if (lane == 0) mbar_arrive(bar_empty2 + 8 * (it % G2_STAGES));
            }
        }
        const int lr = wg * 64 + (warp & 3) * 16 + g;
        uint32_t xv[16], sv[16];
        mbar_wait(bar_epi, 0);
#pragma unroll
        for (int j = 0; j < 8; j++) {
#pragma unroll
            for (int hh = 0; hh < 2; hh++) {
                const int r = lr + 8 * hh;
                asm volatile("ld.shared.u32 %0, [%1];" : "=r"(xv[2 * j + hh]) : "r"(sX + r * 128 + ((j ^ (r & 7)) << 4) + 4 * t));
                const int c0 = 8 * j + 2 * t;
                const uint32_t sa = sS + (r >> 6) * 8192 + (((r & 63) >> 3) << 4) + (r & 7) * 2;
                uint16_t s0r, s1r;
                asm volatile("ld.shared.u16 %0, [%1];" : "=h"(s0r) : "r"((sa + c0 * 128) ^ ((c0 & 7) << 4)));
                asm volatile("ld.shared.u16 %0, [%1];" : "=h"(s1r) : "r"((sa + (c0 + 1) * 128) ^ (((c0 + 1) & 7) << 4)));
                sv[2 * j + hh] = (uint32_t)s0r | ((uint32_t)s1r << 16);
            }
        }
        wgmma_wait<0>();
        if (threadIdx.x == 0) STAMP(3, 4);
        {
            uint32_t remote, rbar;
            asm volatile("mapa.shared::cluster.u32 %0, %1, %2;" : "=r"(remote) : "r"(sXch + threadIdx.x * 16), "r"(kh ^ 1));
            asm volatile("mapa.shared::cluster.u32 %0, %1, %2;" : "=r"(rbar) : "r"(bar_xch), "r"(kh ^ 1));
            if (kh == 0) {
#pragma unroll
                for (int i = 0; i < 8; i++)
                    asm volatile("st.async.shared::cluster.mbarrier::complete_tx::bytes.v4.f32 [%0], {%1,%2,%3,%4}, [%5];" ::"r"(remote + i * 4096),
                                 "f"(acc[32 + 4 * i]), "f"(acc[33 + 4 * i]), "f"(acc[34 + 4 * i]), "f"(acc[35 + 4 * i]), "r"(rbar) : "memory");
            } else {
#pragma unroll
                for (int i = 0; i < 8; i++)
                    asm volatile("st.async.shared::cluster.mbarrier::complete_tx::bytes.v4.f32 [%0], {%1,%2,%3,%4}, [%5];" ::"r"(remote + i * 4096),
                                 "f"(acc[4 * i]), "f"(acc[1 + 4 * i]), "f"(acc[2 + 4 * i]), "f"(acc[3 + 4 * i]), "r"(rbar) : "memory");
#pragma unroll
                for (int i = 0; i < 32; i++) acc[i] = acc[32 + i];
            }
        }
        if (threadIdx.x == 0) STAMP(3, 6);
        mbar_wait(bar_xch, 0);
        if (threadIdx.x == 0) STAMP(3, 7);
#pragma unroll
        for (int j = 0; j < 8; j++) {
            float4 o;
            asm volatile("ld.shared.v4.f32 {%0,%1,%2,%3}, [%4];" : "=f"(o.x), "=f"(o.y), "=f"(o.z), "=f"(o.w) : "r"(sXch + threadIdx.x * 16 + j * 4096));
            acc[4 * j] += o.x; acc[4 * j + 1] += o.y; acc[4 * j + 2] += o.z; acc[4 * j + 3] += o.w;
        }
#pragma unroll
        for (int i = 0; i < 16; i++) {
            float f0 = bf16_round(acc[2 * i]), f1 = bf16_round(acc[2 * i + 1]);
            float g0 = bf16_round(__fdividef(f0, 1.0f + __expf(-f0)));
            float g1 = bf16_round(__fdividef(f1, 1.0f + __expf(-f1)));
            float o0 = bf_lo(xv[i]) + bf16_round(bf_lo(sv[i]) * g0);
            float o1 = bf_hi(xv[i]) + bf16_round(bf_hi(sv[i]) * g1);
            xv[i] = pack_bf16(o0, o1);
        }
#pragma unroll
        for (int j = 0; j < 8; j++) {
#pragma unroll
            for (int hh = 0; hh < 2; hh++) {
                const int r = lr + 8 * hh;
                asm volatile("st.shared.u32 [%0], %1;" ::"r"(sX + r * 128 + ((j ^ (r & 7)) << 4) + 4 * t), "r"(xv[2 * j + hh]) : "memory");
            }
        }
        if (threadIdx.x == 0) STAMP(3, 9);
        fence_async_smem();
        __syncwarp();
        if (lane == 0) {
            tma_store_2d(&tm_out, sX + (wg * 64 + (warp & 3) * 16) * 128, col_fin, rb * 128 + wg * 64 + (warp & 3) * 16);
            bulk_commit();
            bulk_wait_read<0>();
        }
        }
        if (threadIdx.x == 0) STAMP(3, 5);
        named_bar(4, 256);
        if (threadIdx.x == 0) {
            const unsigned int old = atomicAdd(&g_done_count, 1u);
            if (old == gridDim.x - 1) {
                g_ln_count = 0; g_conv_count = 0; g_done_count = 0;
                for (int i = 0; i < 32; i++) g_h_count[i] = 0;
            }
        }
    }
}

typedef CUresult (*EncodeFn)(CUtensorMap*, CUtensorMapDataType, cuuint32_t, void*, const cuuint64_t*, const cuuint64_t*,
                             const cuuint32_t*, const cuuint32_t*, CUtensorMapInterleave, CUtensorMapSwizzle,
                             CUtensorMapL2promotion, CUtensorMapFloatOOBfill);

void make_map(EncodeFn fn, CUtensorMap* m, const void* ptr, uint64_t inner, uint64_t outer, uint32_t box_in, uint32_t box_out,
              CUtensorMapSwizzle swz = CU_TENSOR_MAP_SWIZZLE_128B) {
    cuuint64_t dims[2] = {inner, outer};
    cuuint64_t strides[1] = {inner * 2};
    cuuint32_t box[2] = {box_in, box_out};
    cuuint32_t es[2] = {1, 1};
    fn(m, CU_TENSOR_MAP_DATA_TYPE_BFLOAT16, 2, const_cast<void*>(ptr), dims, strides, box, es, CU_TENSOR_MAP_INTERLEAVE_NONE,
       swz, CU_TENSOR_MAP_L2_PROMOTION_L2_256B, CU_TENSOR_MAP_FLOAT_OOB_FILL_NONE);
}
void make_map3(EncodeFn fn, CUtensorMap* m, const void* ptr, uint64_t cols, uint64_t rows, uint32_t atom, uint32_t box_rows,
               uint32_t box_atoms, CUtensorMapSwizzle swz) {
    cuuint64_t dims[3] = {atom, rows, cols / atom};
    cuuint64_t strides[2] = {cols * 2, (cuuint64_t)atom * 2};
    cuuint32_t box[3] = {atom, box_rows, box_atoms};
    cuuint32_t es[3] = {1, 1, 1};
    fn(m, CU_TENSOR_MAP_DATA_TYPE_BFLOAT16, 3, const_cast<void*>(ptr), dims, strides, box, es, CU_TENSOR_MAP_INTERLEAVE_NONE,
       swz, CU_TENSOR_MAP_L2_PROMOTION_L2_256B, CU_TENSOR_MAP_FLOAT_OOB_FILL_NONE);
}

template <typename... Args>
void launch_pdl(void (*kern)(Args...), int grid, int block, int smem, bool pdl, int cluster, Args... args) {
    cudaLaunchConfig_t cfg = {};
    cfg.gridDim = dim3(grid); cfg.blockDim = dim3(block); cfg.dynamicSmemBytes = smem; cfg.stream = cudaStreamPerThread;
    cudaLaunchAttribute at[2];
    int n = 0;
    if (pdl) {
        at[n].id = cudaLaunchAttributeProgrammaticStreamSerialization;
        at[n].val.programmaticStreamSerializationAllowed = 1;
        n++;
    }
    if (cluster > 1) {
        at[n].id = cudaLaunchAttributeClusterDimension;
        at[n].val.clusterDim.x = cluster; at[n].val.clusterDim.y = 1; at[n].val.clusterDim.z = 1;
        n++;
    }
    cfg.attrs = at; cfg.numAttrs = n;
    cudaLaunchKernelEx(&cfg, kern, args...);
}

}

extern "C" void kernel_launch(void* const* d_in, const int* in_sizes, int n_in, void* d_out, int out_size) {
    const __nv_bfloat16* x = (const __nv_bfloat16*)d_in[0];
    const __nv_bfloat16* A_re = (const __nv_bfloat16*)d_in[1];
    const __nv_bfloat16* A_im = (const __nv_bfloat16*)d_in[2];
    const __nv_bfloat16* B_re = (const __nv_bfloat16*)d_in[3];
    const __nv_bfloat16* B_im = (const __nv_bfloat16*)d_in[4];
    const __nv_bfloat16* C_re = (const __nv_bfloat16*)d_in[5];
    const __nv_bfloat16* C_im = (const __nv_bfloat16*)d_in[6];
    const __nv_bfloat16* log_dt = (const __nv_bfloat16*)d_in[7];
    const __nv_bfloat16* Dskip = (const __nv_bfloat16*)d_in[8];
    const __nv_bfloat16* wg = (const __nv_bfloat16*)d_in[10];
    const __nv_bfloat16* wu = (const __nv_bfloat16*)d_in[11];
    const __nv_bfloat16* wd = (const __nv_bfloat16*)d_in[12];
    __nv_bfloat16* out = (__nv_bfloat16*)d_out;

    static bool init = false;
    static CUtensorMap tm_xn, tm_wg4, tm_wu4, tm_wg3, tm_wu3, tm_hst, tm_hst96, tm_h, tm_wd, tm_x, tm_sT, tm_out;
    static const void* last_ptrs[5] = {nullptr, nullptr, nullptr, nullptr, nullptr};
    if (!init || last_ptrs[0] != wg || last_ptrs[1] != wu || last_ptrs[2] != wd || last_ptrs[3] != x || last_ptrs[4] != out) {
        void* fnp = nullptr;
        cudaDriverEntryPointQueryResult qres;
        cudaGetDriverEntryPoint("cuTensorMapEncodeTiled", &fnp, cudaEnableDefault, &qres);
        EncodeFn fn = (EncodeFn)fnp;
        void *p_xn, *p_h, *p_sT;
        cudaGetSymbolAddress(&p_xn, g_xn);
        cudaGetSymbolAddress(&p_h, g_h);
        cudaGetSymbolAddress(&p_sT, g_sT);
        make_map(fn, &tm_xn, p_xn, D_, L_, 64, 128);
        make_map3(fn, &tm_wg4, wg, F_, D_, 32, 32, 4, CU_TENSOR_MAP_SWIZZLE_64B);
        make_map3(fn, &tm_wu4, wu, F_, D_, 32, 32, 4, CU_TENSOR_MAP_SWIZZLE_64B);
        make_map3(fn, &tm_wg3, wg, F_, D_, 32, 32, 3, CU_TENSOR_MAP_SWIZZLE_64B);
        make_map3(fn, &tm_wu3, wu, F_, D_, 32, 32, 3, CU_TENSOR_MAP_SWIZZLE_64B);
        make_map(fn, &tm_hst, p_h, F_, L_, 16, 16, CU_TENSOR_MAP_SWIZZLE_NONE);
        make_map(fn, &tm_hst96, p_h, F_, L_, 96, 16, CU_TENSOR_MAP_SWIZZLE_NONE);
        make_map(fn, &tm_h, p_h, F_, L_, 64, 128);
        make_map3(fn, &tm_wd, wd, D_, F_, 64, 64, 2, CU_TENSOR_MAP_SWIZZLE_128B);
        make_map(fn, &tm_x, x, D_, L_, 64, 128);
        make_map(fn, &tm_sT, p_sT, L_, D_, 64, 64);
        make_map(fn, &tm_out, out, D_, L_, 64, 16);
        cudaFuncSetAttribute(mega_kernel, cudaFuncAttributeMaxDynamicSharedMemorySize, MG_SMEM);
        last_ptrs[0] = wg; last_ptrs[1] = wu; last_ptrs[2] = wd; last_ptrs[3] = x; last_ptrs[4] = out;
        init = true;
    }
    MegaParams P = {x, A_re, A_im, B_re, B_im, C_re, C_im, log_dt, Dskip, wg, wu, wd};
    launch_pdl(mega_kernel, 128, 384, MG_SMEM, false, 2, P, tm_xn, tm_wg4, tm_wu4, tm_wg3, tm_wu3, tm_h, tm_wd, tm_x, tm_sT, tm_out);
}
```

```cpp
#include <cuda_runtime.h>
#include <cuda_bf16.h>
#include <cuda.h>
#include <stdint.h>

namespace {

constexpr int L_ = 2048, D_ = 512, NS_ = 128, F_ = 1792;

__device__ __align__(1024) __nv_bfloat16 g_xn[L_ * D_];
__device__ __align__(1024) __nv_bfloat16 g_xnT[D_ * L_];
__device__ __align__(1024) __nv_bfloat16 g_sT[D_ * L_];
__device__ __align__(1024) __nv_bfloat16 g_h[L_ * F_];
__device__ unsigned int g_ln_count, g_conv_count, g_done_count, g_h_count[32];

#define STAMP(k, i)

__device__ __forceinline__ uint32_t smem_u32(const void* p) { return (uint32_t)__cvta_generic_to_shared(p); }
__device__ __forceinline__ void pdl_wait() { asm volatile("griddepcontrol.wait;" ::: "memory"); }
__device__ __forceinline__ void pdl_launch() { asm volatile("griddepcontrol.launch_dependents;" ::: "memory"); }

__device__ __forceinline__ void mbar_init(uint32_t bar, uint32_t cnt) {
    asm volatile("mbarrier.init.shared::cta.b64 [%0], %1;" ::"r"(bar), "r"(cnt) : "memory");
}
__device__ __forceinline__ void mbar_expect_tx(uint32_t bar, uint32_t bytes) {
    asm volatile("mbarrier.arrive.expect_tx.shared::cta.b64 _, [%0], %1;" ::"r"(bar), "r"(bytes) : "memory");
}
__device__ __forceinline__ void mbar_arrive(uint32_t bar) {
    asm volatile("mbarrier.arrive.shared::cta.b64 _, [%0];" ::"r"(bar) : "memory");
}
__device__ __forceinline__ void mbar_wait(uint32_t bar, uint32_t parity) {
    asm volatile(
        "{\n.reg .pred p;\n"
        "WAIT_LOOP:\n"
        "mbarrier.try_wait.parity.shared::cta.b64 p, [%0], %1;\n"
        "@p bra WAIT_DONE;\n"
        "bra WAIT_LOOP;\n"
        "WAIT_DONE:\n}\n" ::"r"(bar), "r"(parity) : "memory");
}
__device__ __forceinline__ void tma_load_2d(uint32_t dst, const CUtensorMap* tm, int c0, int c1, uint32_t bar) {
    asm volatile(
        "cp.async.bulk.tensor.2d.shared::cluster.global.mbarrier::complete_tx::bytes [%0], [%1, {%3, %4}], [%2];"
        ::"r"(dst), "l"((uint64_t)tm), "r"(bar), "r"(c0), "r"(c1) : "memory");
}
__device__ __forceinline__ void prefetch_tmap(const CUtensorMap* tm) {
    asm volatile("prefetch.tensormap [%0];" ::"l"((uint64_t)tm) : "memory");
}
__device__ __forceinline__ uint64_t make_desc(uint32_t addr, uint32_t lbo, uint32_t sbo, uint64_t mode = 1) {
    uint64_t d = 0;
    d |= (uint64_t)((addr & 0x3FFFF) >> 4);
    d |= (uint64_t)((lbo >> 4) & 0x3FFF) << 16;
    d |= (uint64_t)((sbo >> 4) & 0x3FFF) << 32;
    d |= mode << 62;
    return d;
}
__device__ __forceinline__ void fence_async_smem() { asm volatile("fence.proxy.async.shared::cta;" ::: "memory"); }
__device__ __forceinline__ void wgmma_fence() { asm volatile("wgmma.fence.sync.aligned;" ::: "memory"); }
__device__ __forceinline__ void wgmma_commit() { asm volatile("wgmma.commit_group.sync.aligned;" ::: "memory"); }
template <int N> __device__ __forceinline__ void wgmma_wait() {
    asm volatile("wgmma.wait_group.sync.aligned %0;" ::"n"(N) : "memory");
}

#define R8(a, i) "+f"(a[i + 0]), "+f"(a[i + 1]), "+f"(a[i + 2]), "+f"(a[i + 3]), "+f"(a[i + 4]), "+f"(a[i + 5]), "+f"(a[i + 6]), "+f"(a[i + 7])

__device__ __forceinline__ void wgmma_n256_k32(float* a, uint64_t da0, uint64_t da1, uint64_t db0, uint64_t db1, int scale_d) {
    asm volatile(
        "{\n.reg .pred p;\nsetp.ne.b32 p, %132, 0;\n"
        "wgmma.mma_async.sync.aligned.m64n256k16.f32.bf16.bf16 {%0,%1,%2,%3,%4,%5,%6,%7,%8,%9,%10,%11,%12,%13,%14,%15,%16,%17,%18,%19,%20,%21,%22,%23,%24,%25,%26,%27,%28,%29,%30,%31,%32,%33,%34,%35,%36,%37,%38,%39,%40,%41,%42,%43,%44,%45,%46,%47,%48,%49,%50,%51,%52,%53,%54,%55,%56,%57,%58,%59,%60,%61,%62,%63,%64,%65,%66,%67,%68,%69,%70,%71,%72,%73,%74,%75,%76,%77,%78,%79,%80,%81,%82,%83,%84,%85,%86,%87,%88,%89,%90,%91,%92,%93,%94,%95,%96,%97,%98,%99,%100,%101,%102,%103,%104,%105,%106,%107,%108,%109,%110,%111,%112,%113,%114,%115,%116,%117,%118,%119,%120,%121,%122,%123,%124,%125,%126,%127}, %128, %130, p, 1, 1, 0, 1;\n"
        "wgmma.mma_async.sync.aligned.m64n256k16.f32.bf16.bf16 {%0,%1,%2,%3,%4,%5,%6,%7,%8,%9,%10,%11,%12,%13,%14,%15,%16,%17,%18,%19,%20,%21,%22,%23,%24,%25,%26,%27,%28,%29,%30,%31,%32,%33,%34,%35,%36,%37,%38,%39,%40,%41,%42,%43,%44,%45,%46,%47,%48,%49,%50,%51,%52,%53,%54,%55,%56,%57,%58,%59,%60,%61,%62,%63,%64,%65,%66,%67,%68,%69,%70,%71,%72,%73,%74,%75,%76,%77,%78,%79,%80,%81,%82,%83,%84,%85,%86,%87,%88,%89,%90,%91,%92,%93,%94,%95,%96,%97,%98,%99,%100,%101,%102,%103,%104,%105,%106,%107,%108,%109,%110,%111,%112,%113,%114,%115,%116,%117,%118,%119,%120,%121,%122,%123,%124,%125,%126,%127}, %129, %131, 1, 1, 1, 0, 1;\n"
        "}\n"
        : R8(a, 0), R8(a, 8), R8(a, 16), R8(a, 24), R8(a, 32), R8(a, 40), R8(a, 48), R8(a, 56), R8(a, 64), R8(a, 72), R8(a, 80), R8(a, 88), R8(a, 96), R8(a, 104), R8(a, 112), R8(a, 120)
        : "l"(da0), "l"(da1), "l"(db0), "l"(db1), "r"(scale_d));
}
__device__ __forceinline__ void wgmma_n192_k32(float* a, uint64_t da0, uint64_t da1, uint64_t db0, uint64_t db1, int scale_d) {
    asm volatile(
        "{\n.reg .pred p;\nsetp.ne.b32 p, %100, 0;\n"
        "wgmma.mma_async.sync.aligned.m64n192k16.f32.bf16.bf16 {%0,%1,%2,%3,%4,%5,%6,%7,%8,%9,%10,%11,%12,%13,%14,%15,%16,%17,%18,%19,%20,%21,%22,%23,%24,%25,%26,%27,%28,%29,%30,%31,%32,%33,%34,%35,%36,%37,%38,%39,%40,%41,%42,%43,%44,%45,%46,%47,%48,%49,%50,%51,%52,%53,%54,%55,%56,%57,%58,%59,%60,%61,%62,%63,%64,%65,%66,%67,%68,%69,%70,%71,%72,%73,%74,%75,%76,%77,%78,%79,%80,%81,%82,%83,%84,%85,%86,%87,%88,%89,%90,%91,%92,%93,%94,%95}, %96, %98, p, 1, 1, 0, 1;\n"
        "wgmma.mma_async.sync.aligned.m64n192k16.f32.bf16.bf16 {%0,%1,%2,%3,%4,%5,%6,%7,%8,%9,%10,%11,%12,%13,%14,%15,%16,%17,%18,%19,%20,%21,%22,%23,%24,%25,%26,%27,%28,%29,%30,%31,%32,%33,%34,%35,%36,%37,%38,%39,%40,%41,%42,%43,%44,%45,%46,%47,%48,%49,%50,%51,%52,%53,%54,%55,%56,%57,%58,%59,%60,%61,%62,%63,%64,%65,%66,%67,%68,%69,%70,%71,%72,%73,%74,%75,%76,%77,%78,%79,%80,%81,%82,%83,%84,%85,%86,%87,%88,%89,%90,%91,%92,%93,%94,%95}, %97, %99, 1, 1, 1, 0, 1;\n"
        "}\n"
        : R8(a, 0), R8(a, 8), R8(a, 16), R8(a, 24), R8(a, 32), R8(a, 40), R8(a, 48), R8(a, 56), R8(a, 64), R8(a, 72), R8(a, 80), R8(a, 88)
        : "l"(da0), "l"(da1), "l"(db0), "l"(db1), "r"(scale_d));
}
__device__ __forceinline__ void wgmma_n192(float* a, uint64_t da0, uint64_t db0, int scale_d) {
    asm volatile(
        "{\n.reg .pred p;\nsetp.ne.b32 p, %98, 0;\n"
        "wgmma.mma_async.sync.aligned.m64n192k16.f32.bf16.bf16 {%0,%1,%2,%3,%4,%5,%6,%7,%8,%9,%10,%11,%12,%13,%14,%15,%16,%17,%18,%19,%20,%21,%22,%23,%24,%25,%26,%27,%28,%29,%30,%31,%32,%33,%34,%35,%36,%37,%38,%39,%40,%41,%42,%43,%44,%45,%46,%47,%48,%49,%50,%51,%52,%53,%54,%55,%56,%57,%58,%59,%60,%61,%62,%63,%64,%65,%66,%67,%68,%69,%70,%71,%72,%73,%74,%75,%76,%77,%78,%79,%80,%81,%82,%83,%84,%85,%86,%87,%88,%89,%90,%91,%92,%93,%94,%95}, %96, %97, p, 1, 1, 0, 1;\n"
        "}\n"
        : R8(a, 0), R8(a, 8), R8(a, 16), R8(a, 24), R8(a, 32), R8(a, 40), R8(a, 48), R8(a, 56), R8(a, 64), R8(a, 72), R8(a, 80), R8(a, 88)
        : "l"(da0), "l"(db0), "r"(scale_d));
}
__device__ __forceinline__ void wgmma_n128_k64(float* a, uint64_t da0, uint64_t da1, uint64_t da2, uint64_t da3,
                                               uint64_t db0, uint64_t db1, uint64_t db2, uint64_t db3, int scale_d) {
    asm volatile(
        "{\n.reg .pred p;\nsetp.ne.b32 p, %72, 0;\n"
        "wgmma.mma_async.sync.aligned.m64n128k16.f32.bf16.bf16 {%0,%1,%2,%3,%4,%5,%6,%7,%8,%9,%10,%11,%12,%13,%14,%15,%16,%17,%18,%19,%20,%21,%22,%23,%24,%25,%26,%27,%28,%29,%30,%31,%32,%33,%34,%35,%36,%37,%38,%39,%40,%41,%42,%43,%44,%45,%46,%47,%48,%49,%50,%51,%52,%53,%54,%55,%56,%57,%58,%59,%60,%61,%62,%63}, %64, %68, p, 1, 1, 0, 1;\n"
        "wgmma.mma_async.sync.aligned.m64n128k16.f32.bf16.bf16 {%0,%1,%2,%3,%4,%5,%6,%7,%8,%9,%10,%11,%12,%13,%14,%15,%16,%17,%18,%19,%20,%21,%22,%23,%24,%25,%26,%27,%28,%29,%30,%31,%32,%33,%34,%35,%36,%37,%38,%39,%40,%41,%42,%43,%44,%45,%46,%47,%48,%49,%50,%51,%52,%53,%54,%55,%56,%57,%58,%59,%60,%61,%62,%63}, %65, %69, 1, 1, 1, 0, 1;\n"
        "wgmma.mma_async.sync.aligned.m64n128k16.f32.bf16.bf16 {%0,%1,%2,%3,%4,%5,%6,%7,%8,%9,%10,%11,%12,%13,%14,%15,%16,%17,%18,%19,%20,%21,%22,%23,%24,%25,%26,%27,%28,%29,%30,%31,%32,%33,%34,%35,%36,%37,%38,%39,%40,%41,%42,%43,%44,%45,%46,%47,%48,%49,%50,%51,%52,%53,%54,%55,%56,%57,%58,%59,%60,%61,%62,%63}, %66, %70, 1, 1, 1, 0, 1;\n"
        "wgmma.mma_async.sync.aligned.m64n128k16.f32.bf16.bf16 {%0,%1,%2,%3,%4,%5,%6,%7,%8,%9,%10,%11,%12,%13,%14,%15,%16,%17,%18,%19,%20,%21,%22,%23,%24,%25,%26,%27,%28,%29,%30,%31,%32,%33,%34,%35,%36,%37,%38,%39,%40,%41,%42,%43,%44,%45,%46,%47,%48,%49,%50,%51,%52,%53,%54,%55,%56,%57,%58,%59,%60,%61,%62,%63}, %67, %71, 1, 1, 1, 0, 1;\n"
        "}\n"
        : R8(a, 0), R8(a, 8), R8(a, 16), R8(a, 24), R8(a, 32), R8(a, 40), R8(a, 48), R8(a, 56)
        : "l"(da0), "l"(da1), "l"(da2), "l"(da3), "l"(db0), "l"(db1), "l"(db2), "l"(db3), "r"(scale_d));
}

__device__ __forceinline__ float bf16_round(float x) {
    uint32_t p; asm("cvt.rn.bf16x2.f32 %0, %1, %2;" : "=r"(p) : "f"(x), "f"(0.0f));
    return __uint_as_float(p);
}
__device__ __forceinline__ uint32_t pack_bf16(float lo, float hi) {
    __nv_bfloat162 v = __floats2bfloat162_rn(lo, hi);
    return *reinterpret_cast<uint32_t*>(&v);
}
__device__ __forceinline__ float bf_lo(uint32_t v) { return __uint_as_float(v << 16); }
__device__ __forceinline__ float bf_hi(uint32_t v) { return __uint_as_float(v & 0xFFFF0000u); }

struct cplx { float r, i; };
__device__ __forceinline__ cplx cmul(cplx a, cplx b) {
    cplx c; c.r = a.r * b.r - a.i * b.i; c.i = a.r * b.i + a.i * b.r; return c;
}
__device__ __forceinline__ cplx csq(cplx a) {
    cplx c; c.r = a.r * a.r - a.i * a.i; c.i = 2.0f * a.r * a.i; return c;
}
__device__ __forceinline__ cplx cexp_m(float ar2, float ai2, float m) {
    float mag;
    asm("ex2.approx.ftz.f32 %0, %1;" : "=f"(mag) : "f"(ar2 * m));
    float rr = ai2 * m;
    rr -= (rr + 12582912.0f) - 12582912.0f;
    float th = rr * 6.283185307179586f;
    cplx c; c.r = mag * __cosf(th); c.i = mag * __sinf(th);
    return c;
}
__device__ __forceinline__ uint32_t to_tf32(float x) { return __float_as_uint(x) + 0x1000u; }
__device__ __forceinline__ void mma_tf32(float* c, uint32_t a0, uint32_t a1, uint32_t a2, uint32_t a3, uint32_t b0, uint32_t b1) {
    asm volatile("mma.sync.aligned.m16n8k8.row.col.f32.tf32.tf32.f32 {%0,%1,%2,%3}, {%4,%5,%6,%7}, {%8,%9}, {%0,%1,%2,%3};"
                 : "+f"(c[0]), "+f"(c[1]), "+f"(c[2]), "+f"(c[3])
                 : "r"(a0), "r"(a1), "r"(a2), "r"(a3), "r"(b0), "r"(b1));
}
__device__ __forceinline__ void mma_bf16(float* c, uint32_t a0, uint32_t a1, uint32_t a2, uint32_t a3, uint32_t b0, uint32_t b1) {
    asm volatile("mma.sync.aligned.m16n8k16.row.col.f32.bf16.bf16.f32 {%0,%1,%2,%3}, {%4,%5,%6,%7}, {%8,%9}, {%0,%1,%2,%3};"
                 : "+f"(c[0]), "+f"(c[1]), "+f"(c[2]), "+f"(c[3])
                 : "r"(a0), "r"(a1), "r"(a2), "r"(a3), "r"(b0), "r"(b1));
}
__device__ __forceinline__ void named_bar(int id, int n) { asm volatile("bar.sync %0, %1;" ::"r"(id), "r"(n) : "memory"); }
__device__ __forceinline__ void ldsm_x4(uint32_t addr, uint32_t& r0, uint32_t& r1, uint32_t& r2, uint32_t& r3) {
    asm volatile("ldmatrix.sync.aligned.m8n8.x4.shared.b16 {%0,%1,%2,%3}, [%4];" : "=r"(r0), "=r"(r1), "=r"(r2), "=r"(r3) : "r"(addr));
}
__device__ __forceinline__ void ldsm_x4_t(uint32_t addr, uint32_t& r0, uint32_t& r1, uint32_t& r2, uint32_t& r3) {
    asm volatile("ldmatrix.sync.aligned.m8n8.x4.trans.shared.b16 {%0,%1,%2,%3}, [%4];" : "=r"(r0), "=r"(r1), "=r"(r2), "=r"(r3) : "r"(addr));
}

constexpr int CV_CH = 4;
constexpr int CV_O_CONST = 0;
constexpr int CV_O_KP = 12288;
constexpr int CV_EARLY = 12288 + 7776;
constexpr int CV_O_Q = 0;
constexpr int CV_O_Q2 = CV_O_Q + 2304;
constexpr int CV_O_Q3 = CV_O_Q2 + 1024;
constexpr int CV_O_Q4X = CV_O_Q3 + 768;
constexpr int CV_O_W3 = CV_O_Q4X + 256;
constexpr int CV_O_W5 = CV_O_W3 + 3104;
constexpr int CV_O_W7 = CV_O_W5 + 3104;
constexpr int CV_O_W9 = CV_O_W7 + 2048;
constexpr int CV_O_U = CV_O_W9 + 2048;
constexpr int CV_LATE = CV_O_U + 4352;
constexpr int CV_LATE_BASE = 229376 - CV_CH * CV_LATE;
constexpr int CV_TILE_OFF = CV_CH * CV_EARLY;
static_assert(CV_TILE_OFF + 16 * (D_ + 8) * 2 <= CV_LATE_BASE && CV_LATE_BASE >= 131072 + 16384, "front layout");
static_assert(CV_O_W3 >= 4096 && CV_O_U - CV_O_W3 >= 8192 && (CV_LATE % 16) == 0 && (CV_EARLY % 16) == 0, "front layout");

constexpr int LN_ROWS = 16;

template <typename PF>
__device__ __forceinline__ void front_phase(PF prefetch_fn, uint8_t* smem, const __nv_bfloat16* __restrict__ x,
                                            const __nv_bfloat16* __restrict__ A_re, const __nv_bfloat16* __restrict__ A_im,
                                            const __nv_bfloat16* __restrict__ B_re, const __nv_bfloat16* __restrict__ B_im,
                                            const __nv_bfloat16* __restrict__ C_re, const __nv_bfloat16* __restrict__ C_im,
                                            const __nv_bfloat16* __restrict__ log_dt, const __nv_bfloat16* __restrict__ Dskip,
                                            const __nv_bfloat16* __restrict__ wg, const __nv_bfloat16* __restrict__ wu,
                                            const __nv_bfloat16* __restrict__ wd) {
    const int warp = threadIdx.x >> 5, lane = threadIdx.x & 31;
    const int ch = warp / 3, w = warp - 3 * ch, tc = threadIdx.x - 96 * ch;
    const int d = blockIdx.x * CV_CH + ch;
    const int g = lane >> 2, t = lane & 3;
    uint8_t* base = smem + CV_LATE_BASE + ch * CV_LATE;
    float4* s_const = reinterpret_cast<float4*>(smem + ch * CV_EARLY + CV_O_CONST);
    float* s_kp = reinterpret_cast<float*>(smem + ch * CV_EARLY + CV_O_KP);
    uint32_t* s_q = reinterpret_cast<uint32_t*>(base + CV_O_Q);
    uint32_t* s_q2 = reinterpret_cast<uint32_t*>(base + CV_O_Q2);
    uint32_t* s_q3 = reinterpret_cast<uint32_t*>(base + CV_O_Q3);
    uint32_t* s_q4 = reinterpret_cast<uint32_t*>(base + CV_O_Q4X);
    __nv_bfloat16* s_u = reinterpret_cast<__nv_bfloat16*>(base + CV_O_U);
    const int bar_id = 5 + ch;
    const __nv_bfloat16 p_dsk = Dskip[d];
    __nv_bfloat16 (*tile)[D_ + 8] = reinterpret_cast<__nv_bfloat16 (*)[D_ + 8]>(smem + CV_TILE_OFF);

    if (warp < 8) {
        const int row = blockIdx.x * LN_ROWS + warp * 2;
        uint4 xv[2][2];
#pragma unroll
        for (int r = 0; r < 2; r++) {
            xv[r][0] = *reinterpret_cast<const uint4*>(x + (size_t)(row + r) * D_ + lane * 8);
            xv[r][1] = *reinterpret_cast<const uint4*>(x + (size_t)(row + r) * D_ + 256 + lane * 8);
        }
        float f[2][16], sm[2], q[2];
#pragma unroll
        for (int r = 0; r < 2; r++) {
            const uint32_t wv[8] = {xv[r][0].x, xv[r][0].y, xv[r][0].z, xv[r][0].w, xv[r][1].x, xv[r][1].y, xv[r][1].z, xv[r][1].w};
#pragma unroll
            for (int i = 0; i < 8; i++) { f[r][2 * i] = bf_lo(wv[i]); f[r][2 * i + 1] = bf_hi(wv[i]); }
            sm[r] = 0.f;
#pragma unroll
            for (int i = 0; i < 16; i++) sm[r] += f[r][i];
        }
#pragma unroll
        for (int o = 16; o > 0; o >>= 1) { sm[0] += __shfl_xor_sync(0xffffffffu, sm[0], o); sm[1] += __shfl_xor_sync(0xffffffffu, sm[1], o); }
#pragma unroll
        for (int r = 0; r < 2; r++) {
            sm[r] *= (1.0f / D_);
            q[r] = 0.f;
#pragma unroll
            for (int i = 0; i < 16; i++) { float dd = f[r][i] - sm[r]; q[r] += dd * dd; }
        }
#pragma unroll
        for (int o = 16; o > 0; o >>= 1) { q[0] += __shfl_xor_sync(0xffffffffu, q[0], o); q[1] += __shfl_xor_sync(0xffffffffu, q[1], o); }
#pragma unroll
        for (int r = 0; r < 2; r++) {
            const float mb = bf16_round(sm[r]);
            const float vb = bf16_round(q[r] * (1.0f / D_));
            const float den = bf16_round(sqrtf(bf16_round(vb + 1e-5f)));
            uint32_t o[8];
#pragma unroll
            for (int i = 0; i < 8; i++) {
                float a = __fdiv_rn(bf16_round(f[r][2 * i] - mb), den);
                float b = __fdiv_rn(bf16_round(f[r][2 * i + 1] - mb), den);
                o[i] = pack_bf16(a, b);
            }
            __nv_bfloat16* dst = g_xn + (size_t)(row + r) * D_;
            *reinterpret_cast<uint4*>(dst + lane * 8) = make_uint4(o[0], o[1], o[2], o[3]);
            *reinterpret_cast<uint4*>(dst + 256 + lane * 8) = make_uint4(o[4], o[5], o[6], o[7]);
            *reinterpret_cast<uint4*>(&tile[warp * 2 + r][lane * 8]) = make_uint4(o[0], o[1], o[2], o[3]);
            *reinterpret_cast<uint4*>(&tile[warp * 2 + r][256 + lane * 8]) = make_uint4(o[4], o[5], o[6], o[7]);
        }
    } else {
        const int cc_ = warp - 8, dd = blockIdx.x * CV_CH + cc_;
        float4* sc = reinterpret_cast<float4*>(smem + cc_ * CV_EARLY + CV_O_CONST);
        __nv_bfloat16 pr[4][6];
#pragma unroll
        for (int j = 0; j < 4; j++) {
            const size_t off = (size_t)dd * NS_ + lane + 32 * j;
            pr[j][0] = A_re[off]; pr[j][1] = A_im[off]; pr[j][2] = B_re[off]; pr[j][3] = B_im[off]; pr[j][4] = C_re[off]; pr[j][5] = C_im[off];
        }
        const float dt = bf16_round(expf(__bfloat162float(log_dt[dd])));
        float tail = 0.f;
#pragma unroll
        for (int j = 0; j < 4; j++) {
            const float ar = dt * __bfloat162float(pr[j][0]), ai = dt * __bfloat162float(pr[j][1]);
            const cplx db = {dt * __bfloat162float(pr[j][2]), dt * __bfloat162float(pr[j][3])};
            const cplx cc = {__bfloat162float(pr[j][4]), __bfloat162float(pr[j][5])};
            const cplx cb = cmul(cc, db);
            const float ar2 = ar * 1.4426950408889634f, ai2 = ai * 0.15915494309189535f;
            const cplx e8 = cexp_m(ar2, ai2, 8.f), e128 = cexp_m(ar2, ai2, 128.f);
            const cplx cb8 = cmul(cb, e8);
            const cplx e256 = cexp_m(ar2, ai2, 256.f), e512 = cexp_m(ar2, ai2, 512.f), e1024 = cexp_m(ar2, ai2, 1024.f);
            const cplx c256 = cmul(cb, e256), c512 = cmul(cb, e512), c1024 = cmul(cb, e1024);
            const cplx c768 = cmul(c512, e256), c1280 = cmul(c1024, e256), c1536 = cmul(c1024, e512);
            const cplx c1792 = cmul(c1536, e256);
            tail += cmul(c1024, e1024).r;
            float4* c = sc + (lane + 32 * j) * 6;
            c[0] = make_float4(ar2, ai2, cb.r, cb.i);
            c[1] = make_float4(e128.r, e128.i, cb8.r, cb8.i);
            c[2] = make_float4(c256.r, c256.i, e8.r, e8.i);
            c[3] = make_float4(c512.r, c512.i, c768.r, c768.i);
            c[4] = make_float4(c1024.r, c1024.i, c1280.r, c1280.i);
            c[5] = make_float4(c1536.r, c1536.i, c1792.r, c1792.i);
        }
#pragma unroll
        for (int o = 16; o > 0; o >>= 1) tail += __shfl_xor_sync(0xffffffffu, tail, o);
        if (lane == 0) {
            float* kp = reinterpret_cast<float*>(smem + cc_ * CV_EARLY + CV_O_KP);
            kp[640] = tail; kp[648 + 640] = 0.f; kp[1296 + 640] = 0.f;
        }
    }
    __syncthreads();
    if (threadIdx.x == 0) STAMP(0, 3);
#pragma unroll
    for (int rep = 0; rep < 2; rep++) {
        const int c = threadIdx.x + 384 * rep;
        if (c < D_) {
            uint32_t ot[8];
#pragma unroll
            for (int i = 0; i < 8; i++) {
                uint32_t lo = *reinterpret_cast<const uint16_t*>(&tile[2 * i][c]);
                uint32_t hi = *reinterpret_cast<const uint16_t*>(&tile[2 * i + 1][c]);
                ot[i] = lo | (hi << 16);
            }
            __nv_bfloat16* dT = g_xnT + (size_t)c * L_ + blockIdx.x * LN_ROWS;
            *reinterpret_cast<uint4*>(dT) = make_uint4(ot[0], ot[1], ot[2], ot[3]);
            *reinterpret_cast<uint4*>(dT + 8) = make_uint4(ot[4], ot[5], ot[6], ot[7]);
        }
    }
    if (threadIdx.x < 336) {
        const int m = threadIdx.x / 112, i = threadIdx.x - m * 112;
        const char* wp = (const char*)(m == 0 ? wg : (m == 1 ? wu : wd));
        asm volatile("prefetch.global.L2 [%0];" ::"l"(wp + ((size_t)blockIdx.x * 112 + i) * 128));
    }
    __syncthreads();
    if (threadIdx.x == 0) STAMP(1, 1);
    {
        float acc[5][4];
#pragma unroll
        for (int i = 0; i < 5; i++) { acc[i][0] = acc[i][1] = acc[i][2] = acc[i][3] = 0.f; }
        const float gf = (float)g;
        const int src4 = ((g & 3) << 2) | t;
#pragma unroll 2
        for (int s = w; s < 32; s += 3) {
            if (s == 17 && threadIdx.x == 352) asm volatile("red.release.gpu.global.add.u32 [%0], 1;" ::"l"(&g_ln_count) : "memory");
            const float4* c = s_const + (s * 4 + t) * 6;
            const float4 k0 = c[0], k1 = c[1], k2 = c[2];
            const float2 k3 = reinterpret_cast<const float2*>(c + 3)[g >> 2];
            const float2 k4 = reinterpret_cast<const float2*>(c + 4)[g >> 1];
            const cplx cb = {k0.z, k0.w}, e128 = {k1.x, k1.y}, cb8 = {k1.z, k1.w}, c256 = {k2.x, k2.y}, e8 = {k2.z, k2.w};
            const cplx c2 = {k3.x, k3.y}, c3 = {k4.x, k4.y};
            const cplx p1 = cexp_m(k0.x, k0.y, gf);
            const cplx p2 = csq(p1), p4 = csq(p2);
            const cplx r16a = csq(csq(p4));
            cplx q4;
            q4.r = __shfl_sync(0xffffffffu, p4.r, src4);
            q4.i = __shfl_sync(0xffffffffu, p4.i, src4);
            const cplx r16b = cmul(r16a, e128);
            const cplx f0a = cmul(cb, p1), f0b = cmul(cb8, p1), f1 = cmul(c256, p2), f2 = cmul(c2, q4);
            cplx f3 = cmul(c3, e8);
            if (!(g & 1)) f3 = c3;
            const uint32_t a0 = to_tf32(r16a.r), a1 = to_tf32(r16b.r), a2 = to_tf32(-r16a.i), a3 = to_tf32(-r16b.i);
            mma_tf32(acc[0], a0, a1, a2, a3, to_tf32(f0a.r), to_tf32(f0a.i));
            mma_tf32(acc[1], a0, a1, a2, a3, to_tf32(f0b.r), to_tf32(f0b.i));
            mma_tf32(acc[2], a0, a1, a2, a3, to_tf32(f1.r), to_tf32(f1.i));
            mma_tf32(acc[3], a0, a1, a2, a3, to_tf32(f2.r), to_tf32(f2.i));
            mma_tf32(acc[4], a0, a1, a2, a3, to_tf32(f3.r), to_tf32(f3.i));
        }
        float* kv = s_kp + w * 648;
#pragma unroll
        for (int hh = 0; hh < 2; hh++) {
            const int i = g + 8 * hh;
            *reinterpret_cast<float2*>(kv + 16 * i + 2 * t) = make_float2(acc[0][2 * hh], acc[0][2 * hh + 1]);
            *reinterpret_cast<float2*>(kv + 16 * i + 8 + 2 * t) = make_float2(acc[1][2 * hh], acc[1][2 * hh + 1]);
            *reinterpret_cast<float2*>(kv + 256 + 8 * i + 2 * t) = make_float2(acc[2][2 * hh], acc[2][2 * hh + 1]);
            *reinterpret_cast<float2*>(kv + 384 + 64 * (t >> 1) + 2 * (t & 1) + 4 * i) = make_float2(acc[3][2 * hh], acc[3][2 * hh + 1]);
            *reinterpret_cast<float2*>(kv + 512 + 32 * t + 2 * i) = make_float2(acc[4][2 * hh], acc[4][2 * hh + 1]);
        }
    }
    named_bar(bar_id, 96);
    if (threadIdx.x == 0) STAMP(1, 2);
#pragma unroll
    for (int i = 0; i < 7; i++) {
        const int idx = tc + 96 * i;
        if (idx < 641) s_kp[idx] = (s_kp[idx] + s_kp[648 + idx]) + s_kp[1296 + idx];
    }
    named_bar(bar_id, 96);
    {
        auto kdir = [&](int l) -> float {
            if (l < 0 || l > 514) return 0.f;
            const int idx = (l < 256) ? l : (l > 512 ? 384 : 128 + ((l + ((l >> 1) & 1)) >> 1));
            return s_kp[idx];
        };
#pragma unroll
        for (int i = 0; i < 6; i++) {
            const int e = tc + 96 * i;
            s_q[e] = pack_bf16(kdir(e - 16), kdir(e - 17));
        }
        if (tc < 64) {
            const int xx = 1008 + tc;
            const float k1024 = s_kp[512];
            s_q4[tc] = pack_bf16((xx == 1027 || xx == 1028) ? k1024 : 0.f, (xx == 1028 || xx == 1029) ? k1024 : 0.f);
        }
#pragma unroll
        for (int i = 0; i < 3; i++) {
            const int e = tc + 96 * i;
            if (e < 256) {
                const int a = e >> 6, ii = (e & 63) - 16;
                const int b = 385 + (a >> 1) + 2 * (a & 1);
                const float v0 = (ii >= 0 && ii < 32) ? s_kp[b + 4 * ii] : 0.f;
                const float v1 = (ii >= 1 && ii < 33) ? s_kp[b + 4 * (ii - 1)] : 0.f;
                s_q2[e] = pack_bf16(v0, v1);
            }
        }
#pragma unroll
        for (int a = 0; a < 2; a++) {
            const int jj = tc - 16;
            const float v0 = (jj >= 0 && jj < 64) ? s_kp[513 + a + 2 * jj] : 0.f;
            const float v1 = (jj >= 1 && jj < 65) ? s_kp[513 + a + 2 * (jj - 1)] : 0.f;
            s_q3[96 * a + tc] = pack_bf16(v0, v1);
        }
    }
    if (threadIdx.x == 0) STAMP(1, 3);
    if (threadIdx.x == 0) {
        unsigned int v = 0;
        for (int spin = 0; spin < (1 << 22); spin++) {
            asm volatile("ld.acquire.gpu.global.u32 %0, [%1];" : "=r"(v) : "l"(&g_ln_count) : "memory");
            if (v >= gridDim.x) break;
        }
    }
    fence_async_smem();
    __syncthreads();
    if (threadIdx.x == 0) STAMP(1, 4);
    prefetch_fn();
    {
        if (tc < 16) *reinterpret_cast<uint4*>(s_u + tc * 8) = make_uint4(0, 0, 0, 0);
        const uint4* src = reinterpret_cast<const uint4*>(g_xnT + (size_t)d * L_);
        uint4 v[3];
#pragma unroll
        for (int i = 0; i < 3; i++) if (tc + 96 * i < 256) v[i] = src[tc + 96 * i];
#pragma unroll
        for (int i = 0; i < 3; i++) if (tc + 96 * i < 256) *reinterpret_cast<uint4*>(s_u + 128 + (tc + 96 * i) * 8) = v[i];
        if (tc < 2) *reinterpret_cast<uint4*>(base + (tc ? CV_O_W5 : CV_O_W3)) = make_uint4(0, 0, 0, 0);
    }
    named_bar(bar_id, 96);
#pragma unroll
    for (int rep = 0; rep < 2; rep++) {
        const int m = tc + 96 * rep;
        float P[30];
        const uint4* up = reinterpret_cast<const uint4*>(s_u + 128 + 8 * m - 24);
        P[0] = 0.f;
#pragma unroll
        for (int c4 = 0; c4 < 4; c4++) {
            const uint4 v = up[c4];
            const uint32_t ww[4] = {v.x, v.y, v.z, v.w};
#pragma unroll
            for (int j = 0; j < 4; j++) {
                const int k = c4 * 8 + 2 * j;
                if (k + 1 <= 29) P[k + 1] = P[k] + bf_lo(ww[j]);
                if (k + 2 <= 29) P[k + 2] = P[k + 1] + bf_hi(ww[j]);
            }
        }
        uint32_t o3[4], o5[4], o7[4], o9[4];
#pragma unroll
        for (int j = 0; j < 4; j++) {
            const int i = 2 * j;
            o3[j] = pack_bf16(P[i + 22] - P[i + 19], P[i + 23] - P[i + 20]);
            o5[j] = pack_bf16(P[i + 19] - P[i + 14], P[i + 20] - P[i + 15]);
            o7[j] = pack_bf16(P[i + 20] - P[i + 13], P[i + 21] - P[i + 14]);
            o9[j] = pack_bf16(P[i + 13] - P[i + 4], P[i + 14] - P[i + 5]);
        }
        *reinterpret_cast<uint4*>(base + CV_O_W3 + 16 + m * 16) = make_uint4(o3[0], o3[1], o3[2], o3[3]);
        *reinterpret_cast<uint4*>(base + CV_O_W5 + 16 + m * 16) = make_uint4(o5[0], o5[1], o5[2], o5[3]);
        if (m < 128) {
            *reinterpret_cast<uint4*>(base + CV_O_W7 + m * 16) = make_uint4(o7[0], o7[1], o7[2], o7[3]);
            *reinterpret_cast<uint4*>(base + CV_O_W9 + m * 16) = make_uint4(o9[0], o9[1], o9[2], o9[3]);
        }
    }
    if (threadIdx.x == 0) STAMP(1, 5);
    named_bar(bar_id, 96);
    if (w == 2) return;
    const int hb = w;
    float acc[16][4];
#pragma unroll
    for (int i = 0; i < 16; i++) { acc[i][0] = acc[i][1] = acc[i][2] = acc[i][3] = 0.f; }
    const uint32_t sb_addr = smem_u32(base);
    const int mi = lane >> 3, rowi = lane & 7;
#pragma unroll 1
    for (int rr = 0; rr < 4; rr++) {
        const int r = 4 * hb + rr;
        uint32_t ub[16][2];
        {
            const uint32_t addr = sb_addr + CV_O_U + (uint32_t)((128 + 16 * (8 * (mi >> 1) + rowi - r) + 8 * (mi & 1)) * 2);
#pragma unroll
            for (int j = 0; j < 16; j += 2) ldsm_x4(addr + (uint32_t)(j * 256), ub[j][0], ub[j][1], ub[j + 1][0], ub[j + 1][1]);
        }
        const uint32_t* qp = s_q + 16 + 16 * r + g - 2 * t;
        uint32_t af[4][3];
#pragma unroll
        for (int q = 0; q < 4; q++) { af[q][0] = qp[128 * q]; af[q][1] = qp[128 * q + 8]; af[q][2] = qp[128 * q - 8]; }
#pragma unroll
        for (int q = 0; q < 4; q++) {
#pragma unroll
            for (int nt = q; nt < 16; nt++) mma_bf16(acc[nt], af[q][0], af[q][1], af[q][2], af[q][0], ub[nt - q][0], ub[nt - q][1]);
        }
        if (r < 2) {
            {
                const uint32_t a0 = qp[512], a1 = qp[520], a2 = qp[504];
#pragma unroll
                for (int nt = 4; nt < 16; nt++) mma_bf16(acc[nt], a0, a1, a2, a0, ub[nt - 4][0], ub[nt - 4][1]);
            }
            {
                const uint32_t* q4p = s_q4 + 16 + 16 * r + g - 2 * t;
                const uint32_t a0 = q4p[0], a1 = q4p[8], a2 = q4p[-8];
#pragma unroll
                for (int nt = 8; nt < 16; nt++) mma_bf16(acc[nt], a0, a1, a2, a0, ub[nt - 8][0], ub[nt - 8][1]);
            }
        }
    }
#pragma unroll 1
    for (int a = hb; a <= 3 * hb; a++) {
        uint32_t bq[7];
        const uint32_t* q2 = s_q2 + a * 64 + 16 + g - 2 * t - 32;
#pragma unroll
        for (int dlt = 3; dlt <= 9; dlt++) bq[dlt - 3] = q2[8 * dlt];
        const uint32_t addr = sb_addr + ((a >> 1) ? CV_O_W5 : CV_O_W3) + (uint32_t)((8 + 16 * (8 * (mi >> 1) + rowi) + 8 * (mi & 1) - 8 * (a & 1)) * 2);
        uint32_t aa[6][4];
#pragma unroll
        for (int kp = 0; kp < 6; kp++) ldsm_x4_t(addr + kp * 512, aa[kp][0], aa[kp][1], aa[kp][2], aa[kp][3]);
#pragma unroll
        for (int kp = 0; kp < 6; kp++) {
#pragma unroll
            for (int dlt = 4; dlt <= 9; dlt++) {
                if (2 * kp + dlt < 16) mma_bf16(acc[2 * kp + dlt], aa[kp][0], aa[kp][1], aa[kp][2], aa[kp][3], bq[dlt - 3], bq[dlt - 4]);
            }
        }
    }
    if (hb == 0) {
#pragma unroll 1
        for (int a = 0; a < 2; a++) {
            uint32_t bq[9];
            const uint32_t* q3 = s_q3 + a * 96 + 16 + g - 2 * t - 64;
#pragma unroll
            for (int dlt = 7; dlt <= 15; dlt++) bq[dlt - 7] = q3[8 * dlt];
            const uint32_t addr = sb_addr + (a ? CV_O_W9 : CV_O_W7) + (uint32_t)((16 * (8 * (mi >> 1) + rowi) + 8 * (mi & 1)) * 2);
            uint32_t aa[4][4];
#pragma unroll
            for (int kp = 0; kp < 4; kp++) ldsm_x4_t(addr + kp * 512, aa[kp][0], aa[kp][1], aa[kp][2], aa[kp][3]);
#pragma unroll
            for (int kp = 0; kp < 4; kp++) {
#pragma unroll
                for (int dlt = 8; dlt <= 15; dlt++) {
                    if (2 * kp + dlt < 16) mma_bf16(acc[2 * kp + dlt], aa[kp][0], aa[kp][1], aa[kp][2], aa[kp][3], bq[dlt - 7], bq[dlt - 8]);
                }
            }
        }
    }
    if (threadIdx.x == 0) STAMP(1, 6);
    named_bar(bar_id, 64);
    {
        float4* xch = reinterpret_cast<float4*>(base + CV_O_W3) + hb * 256;
        if (hb) {
#pragma unroll
            for (int i = 0; i < 8; i++) xch[i * 32 + lane] = make_float4(acc[i][0], acc[i][1], acc[i][2], acc[i][3]);
#pragma unroll
            for (int i = 0; i < 8; i++) { acc[i][0] = acc[8 + i][0]; acc[i][1] = acc[8 + i][1]; acc[i][2] = acc[8 + i][2]; acc[i][3] = acc[8 + i][3]; }
        } else {
#pragma unroll
            for (int i = 0; i < 8; i++) xch[i * 32 + lane] = make_float4(acc[8 + i][0], acc[8 + i][1], acc[8 + i][2], acc[8 + i][3]);
        }
    }
    named_bar(bar_id, 64);
    if (threadIdx.x == 0) STAMP(1, 10);
    {
        const float4* xch = reinterpret_cast<const float4*>(base + CV_O_W3) + (hb ^ 1) * 256 + lane;
        const float dsk = __bfloat162float(p_dsk);
        uint16_t* stg = reinterpret_cast<uint16_t*>(base + CV_O_Q);
        const uint16_t* uu = reinterpret_cast<const uint16_t*>(s_u) + 128;
#pragma unroll
        for (int i = 0; i < 8; i++) {
            const float4 p0 = xch[i * 32];
            const float y[4] = {acc[i][0] + p0.x, acc[i][1] + p0.y, acc[i][2] + p0.z, acc[i][3] + p0.w};
            const int nt = 8 * hb + i;
#pragma unroll
            for (int e = 0; e < 4; e++) {
                const int tau = 16 * (8 * nt + 2 * t + (e & 1)) + g + 8 * (e >> 1);
                const float sv = bf16_round(y[e]) + bf16_round(__uint_as_float((uint32_t)uu[tau] << 16) * dsk);
                stg[tau] = (uint16_t)(__float_as_uint(bf16_round(sv)) >> 16);
            }
        }
        __syncwarp();
        if (threadIdx.x == 0) STAMP(1, 11);
        uint4* dst = reinterpret_cast<uint4*>(g_sT + (size_t)d * L_ + hb * 1024);
        const uint4* srcp = reinterpret_cast<const uint4*>(stg + hb * 1024);
#pragma unroll
        for (int i = 0; i < 4; i++) dst[i * 32 + lane] = srcp[i * 32 + lane];
    }
}

__device__ __forceinline__ uint32_t cluster_rank() { uint32_t r; asm volatile("mov.u32 %0, %%cluster_ctarank;" : "=r"(r)); return r; }
__device__ __forceinline__ void cluster_sync_all() {
    asm volatile("barrier.cluster.arrive.release.aligned;\nbarrier.cluster.wait.acquire.aligned;" ::: "memory");
}
__device__ __forceinline__ void mbar_arrive_remote(uint32_t bar, uint32_t cta) {
    asm volatile("{\n.reg .b32 ra;\nmapa.shared::cluster.u32 ra, %0, %1;\n"
                 "mbarrier.arrive.shared::cluster.b64 _, [ra];\n}\n" ::"r"(bar), "r"(cta) : "memory");
}
__device__ __forceinline__ void tma_load_2d_mc(uint32_t dst, const CUtensorMap* tm, int c0, int c1, uint32_t bar, uint16_t mask) {
    asm volatile(
        "cp.async.bulk.tensor.2d.shared::cluster.global.mbarrier::complete_tx::bytes.multicast::cluster [%0], [%1, {%3, %4}], [%2], %5;"
        ::"r"(dst), "l"((uint64_t)tm), "r"(bar), "r"(c0), "r"(c1), "h"(mask) : "memory");
}
__device__ __forceinline__ void tma_store_2d(const CUtensorMap* tm, uint32_t src, int c0, int c1) {
    asm volatile("cp.async.bulk.tensor.2d.global.shared::cta.bulk_group [%0, {%2, %3}], [%1];"
                 ::"l"((uint64_t)tm), "r"(src), "r"(c0), "r"(c1) : "memory");
}
__device__ __forceinline__ void bulk_commit() { asm volatile("cp.async.bulk.commit_group;" ::: "memory"); }
template <int N> __device__ __forceinline__ void bulk_wait_read() { asm volatile("cp.async.bulk.wait_group.read %0;" ::"n"(N) : "memory"); }
template <int N> __device__ __forceinline__ void bulk_wait() { asm volatile("cp.async.bulk.wait_group %0;" ::"n"(N) : "memory"); }
__device__ __forceinline__ void stmatrix_x4(uint32_t addr, uint32_t r0, uint32_t r1, uint32_t r2, uint32_t r3) {
    asm volatile("stmatrix.sync.aligned.m8n8.x4.shared.b16 [%0], {%1,%2,%3,%4};" ::"r"(addr), "r"(r0), "r"(r1), "r"(r2), "r"(r3) : "memory");
}

constexpr int G1_STAGES = 5;
constexpr int G1_A_BYTES = 8 * 16384;
constexpr int G1_B_STAGE = 16384;
constexpr int G1_STG = 8 * 1024;
constexpr int G1_SMEM = G1_A_BYTES + G1_STAGES * G1_B_STAGE + G1_STG + 1024 + 256;
constexpr int G1_ITERS = 32;

__device__ __forceinline__ void tma_load_3d(uint32_t dst, const CUtensorMap* tm, int c0, int c1, int c2, uint32_t bar) {
    asm volatile(
        "cp.async.bulk.tensor.3d.shared::cluster.global.mbarrier::complete_tx::bytes [%0], [%1, {%3, %4, %5}], [%2];"
        ::"r"(dst), "l"((uint64_t)tm), "r"(bar), "r"(c0), "r"(c1), "r"(c2) : "memory");
}

__device__ __forceinline__ void tma_load_3d_mc(uint32_t dst, const CUtensorMap* tm, int c0, int c1, int c2, uint32_t bar, uint16_t mask) {
    asm volatile(
        "cp.async.bulk.tensor.3d.shared::cluster.global.mbarrier::complete_tx::bytes.multicast::cluster [%0], [%1, {%3, %4, %5}], [%2], %6;"
        ::"r"(dst), "l"((uint64_t)tm), "r"(bar), "r"(c0), "r"(c1), "r"(c2), "h"(mask) : "memory");
}

__device__ __forceinline__ float gelu_tanh(float x) {
    float u = x * (0.7978845608028654f + 0.035677408136300125f * x * x);
    float t; asm("tanh.approx.f32 %0, %1;" : "=f"(t) : "f"(u));
    float hx = 0.5f * x;
    return fmaf(hx, t, hx);
}
__device__ __forceinline__ uint32_t geglu_pair(uint32_t g2, uint32_t u2) {
    uint32_t a = pack_bf16(gelu_tanh(bf_lo(g2)), gelu_tanh(bf_hi(g2)));
    uint32_t r; asm("mul.rn.bf16x2 %0, %1, %2;" : "=r"(r) : "r"(a), "r"(u2));
    return r;
}

constexpr int G2_STAGES = 5;
constexpr int G2_STAGE = 16384 + 16384;
constexpr int G2_XCH = 32768;
constexpr int G2_EPI = 16384 + 16384;
constexpr int G2_SMEM = G2_STAGES * G2_STAGE + G2_XCH + G2_EPI + 1024 + 256;
constexpr int G2_KB = F_ / 64 / 2;

constexpr int MG_BAR_OFF = G2_STAGES * G2_STAGE + G2_XCH + G2_EPI;
constexpr int MG_SMEM = MG_BAR_OFF + 256 + 1024;
static_assert(MG_BAR_OFF == 229376 && G1_A_BYTES + G1_STAGES * G1_B_STAGE + G1_STG <= MG_BAR_OFF, "smem layout");

__device__ __forceinline__ void fence_async_all() { asm volatile("fence.proxy.async;" ::: "memory"); }
__device__ __forceinline__ void spin_until(const unsigned int* p, unsigned int target) {
    unsigned int v = 0;
    for (int spin = 0; spin < (1 << 22); spin++) {
        asm volatile("ld.acquire.gpu.global.u32 %0, [%1];" : "=r"(v) : "l"(p) : "memory");
        if (v >= target) break;
    }
}

struct MegaParams {
    const __nv_bfloat16 *x, *A_re, *A_im, *B_re, *B_im, *C_re, *C_im, *log_dt, *Dskip, *wg, *wu, *wd;
};

__global__ void __launch_bounds__(384, 1) mega_kernel(const __grid_constant__ MegaParams P,
                                                       const __grid_constant__ CUtensorMap tm_xn,
                                                       const __grid_constant__ CUtensorMap tm_wg4,
                                                       const __grid_constant__ CUtensorMap tm_wu4,
                                                       const __grid_constant__ CUtensorMap tm_wg3,
                                                       const __grid_constant__ CUtensorMap tm_wu3,
                                                       const __grid_constant__ CUtensorMap tm_h,
                                                       const __grid_constant__ CUtensorMap tm_wd,
                                                       const __grid_constant__ CUtensorMap tm_x,
                                                       const __grid_constant__ CUtensorMap tm_sT,
                                                       const __grid_constant__ CUtensorMap tm_out) {
    if (threadIdx.x == 0) STAMP(1, 0);
    extern __shared__ uint8_t smem_raw[];
    const uint32_t sraw = smem_u32(smem_raw);
    const uint32_t sbase = (sraw + 1023) & ~1023u;
    uint8_t* smem = smem_raw + (sbase - sraw);
    const int warp = threadIdx.x >> 5, lane = threadIdx.x & 31;
    const uint32_t sA = sbase, sB = sbase + G1_A_BYTES, sStg = sB + G1_STAGES * G1_B_STAGE;
    const uint32_t sXch = sbase + G2_STAGES * G2_STAGE, sX = sXch + G2_XCH, sS = sX + 16384;
    const uint32_t sBar = sbase + MG_BAR_OFF;
    const uint32_t bar_a = sBar, bar_full = sBar + 64, bar_empty = bar_full + 8 * G1_STAGES;
    const uint32_t bar_full2 = bar_empty + 8 * G1_STAGES, bar_empty2 = bar_full2 + 8 * G2_STAGES;
    const uint32_t bar_epi = bar_empty2 + 8 * G2_STAGES, bar_xch = bar_epi + 8, bar_g1done = bar_xch + 8, bar_g1mma = bar_g1done + 8;
    const uint32_t kh = blockIdx.x & 1;
    const int rb1 = ((blockIdx.x >> 4) << 1) + (int)kh, cj = (blockIdx.x >> 1) & 7;
    const int rb = blockIdx.x >> 3;
    const int nb = (blockIdx.x >> 1) & 3;
    const int col_fin = nb * 128 + kh * 64;

    if (threadIdx.x == 0) {
        for (int i = 0; i < 8; i++) mbar_init(bar_a + 8 * i, 1);
        for (int i = 0; i < G1_STAGES; i++) { mbar_init(bar_full + 8 * i, 1); mbar_init(bar_empty + 8 * i, 16); }
        for (int i = 0; i < G2_STAGES; i++) { mbar_init(bar_full2 + 8 * i, 1); mbar_init(bar_empty2 + 8 * i, 8); }
        mbar_init(bar_epi, 1);
        mbar_init(bar_xch, 1);
        mbar_init(bar_g1done, 8);
        mbar_init(bar_g1mma, 8);
        asm volatile("fence.mbarrier_init.release.cluster;" ::: "memory");
        mbar_expect_tx(bar_xch, G2_XCH);
    }
    if (warp == 11 && lane == 0) {
        prefetch_tmap(&tm_wg4); prefetch_tmap(&tm_wu4); prefetch_tmap(&tm_xn); prefetch_tmap(&tm_wg3); prefetch_tmap(&tm_wu3);
        prefetch_tmap(&tm_wd); prefetch_tmap(&tm_h); prefetch_tmap(&tm_x); prefetch_tmap(&tm_sT); prefetch_tmap(&tm_out);
    }
    asm volatile("barrier.cluster.arrive.release.aligned;" ::: "memory");

    auto g1_prefetch = [&]() {
        if (warp == 8 && lane == 0) {
            fence_async_all();
            mbar_expect_tx(bar_full, 16384);
            tma_load_3d(sB, &tm_wg4, 0, 0, cj * 7, bar_full);
            tma_load_3d(sB + 8192, &tm_wu4, 0, 0, cj * 7, bar_full);
            for (int k = 0; k < 8; k++) {
                mbar_expect_tx(bar_a + 8 * k, 16384);
                tma_load_2d(sA + k * 16384, &tm_xn, k * 64, rb1 * 128, bar_a + 8 * k);
            }
        }
    };
    front_phase(g1_prefetch, smem, P.x, P.A_re, P.A_im, P.B_re, P.B_im, P.C_re, P.C_im, P.log_dt, P.Dskip, P.wg, P.wu, P.wd);
    fence_async_smem();
    asm volatile("barrier.cluster.wait.acquire.aligned;" ::: "memory");
    cluster_sync_all();
    if (threadIdx.x == 0) STAMP(1, 7);

    if (warp >= 8) {
        asm volatile("setmaxnreg.dec.sync.aligned.u32 40;");
        if (warp == 11) {
            if (lane == 0) asm volatile("red.release.gpu.global.add.u32 [%0], 1;" ::"l"(&g_conv_count) : "memory");
            named_bar(3, 288);
            if (lane == 0) asm volatile("red.release.gpu.global.add.u32 [%0], 1;" ::"l"(&g_h_count[rb1]) : "memory");
            named_bar(9, 288);
            if (lane == 0) asm volatile("red.release.gpu.global.add.u32 [%0], 1;" ::"l"(&g_h_count[16 + rb1]) : "memory");
        } else if (lane == 0) {
            const int pw = warp - 8;
            for (int it = 1 + pw; it < G1_ITERS; it += 3) {
                const int s = it % G1_STAGES, kb = it & 15;
                if (it >= G1_STAGES) mbar_wait(bar_empty + 8 * s, ((it / G1_STAGES) - 1) & 1);
                const uint32_t dst = sB + s * G1_B_STAGE;
                if (it < 16) {
                    mbar_expect_tx(bar_full + 8 * s, 16384);
                    tma_load_3d_mc(dst + kh * 8192, kh ? &tm_wu4 : &tm_wg4, 0, kb * 32, cj * 7, bar_full + 8 * s, 3);
                } else {
                    mbar_expect_tx(bar_full + 8 * s, 12288);
                    tma_load_3d_mc(dst + kh * 6144, kh ? &tm_wu3 : &tm_wg3, 0, kb * 32, cj * 7 + 4, bar_full + 8 * s, 3);
                }
            }
            const int k0 = kh * G2_KB;
            auto kblk = [&](int it) -> int {
                const unsigned long long tab = 0xDCA96532B87410ull;
                return k0 + (int)((tab >> (4 * it)) & 15);
            };
            mbar_wait(bar_g1mma, 0);
            if (pw == 2) {
                mbar_expect_tx(bar_epi, G2_EPI);
                tma_load_2d(sX, &tm_x, col_fin, rb * 128, bar_epi);
            }
            spin_until(&g_h_count[rb], 8);
            fence_async_all();
            if (pw == 0) STAMP(3, 1);
            for (int it = pw; it < G2_KB; it += 3) {
                const int s = (it + 1) % G2_STAGES;
                if (it == 4) mbar_wait(bar_g1done, 0);
                if (it >= G2_STAGES) mbar_wait(bar_empty2 + 8 * s, ((it / G2_STAGES) - 1) & 1);
                if (it >= 6 && it < 9) { spin_until(&g_h_count[16 + rb], 8); fence_async_all(); }
                mbar_expect_tx(bar_full2 + 8 * s, G2_STAGE);
                const int kb = kblk(it);
                tma_load_3d(sbase + s * G2_STAGE + 16384, &tm_wd, 0, kb * 64, nb * 2, bar_full2 + 8 * s);
                tma_load_2d(sbase + s * G2_STAGE, &tm_h, kb * 64, rb * 128, bar_full2 + 8 * s);
                if (it == 2) {
                    spin_until(&g_conv_count, gridDim.x);
                    fence_async_all();
                    tma_load_2d(sS, &tm_sT, rb * 128, col_fin, bar_epi);
                    tma_load_2d(sS + 8192, &tm_sT, rb * 128 + 64, col_fin, bar_epi);
                }
            }
        }
    } else {
        asm volatile("setmaxnreg.inc.sync.aligned.u32 232;");
        const int wg = __shfl_sync(0xffffffffu, (int)(threadIdx.x >> 7), 0);
        {
        float r[160];
        const int row0 = rb1 * 128 + wg * 64 + (warp & 3) * 16;
        const uint64_t descA = make_desc(sA + wg * 8192, 16, 1024);
        const uint64_t descB = make_desc(sB, 2048, 512, 2);
        const uint32_t stg = sStg + warp * 1024;
        const uint32_t st_off = (uint32_t)(((lane & 7) + ((lane >> 3) & 1) * 8) * 32 + (lane >> 4) * 16);
        __nv_bfloat16* hrow = g_h + (size_t)(row0 + (lane >> 1)) * F_ + (lane & 1) * 8 + cj * 224;
#pragma unroll
        for (int kb = 0; kb < 16; kb++) {
            const int it = kb, s = it % G1_STAGES;
            if ((kb & 1) == 0) mbar_wait(bar_a + 8 * (kb >> 1), 0);
            mbar_wait(bar_full + 8 * s, (it / G1_STAGES) & 1);
            if (threadIdx.x == 0 && (it & 7) == 0) STAMP(2, 2 + it / 8);
            wgmma_fence();
            const uint64_t da = descA + (uint64_t)(((kb >> 1) * 16384 + (kb & 1) * 64) >> 4);
            const uint64_t db = descB + (uint64_t)((s * G1_B_STAGE) >> 4);
            wgmma_n256_k32(r, da, da + 2, db, db + 64, kb != 0);
            wgmma_commit();
            if (kb > 0) {
                wgmma_wait<1>();
                if (lane < 2) mbar_arrive_remote(bar_empty + 8 * ((it - 1) % G1_STAGES), lane);
            }
        }
        wgmma_wait<0>();
        if (lane < 2) mbar_arrive_remote(bar_empty + 8 * (15 % G1_STAGES), lane);
#pragma unroll
        for (int i = 0; i < 32; i++) r[128 + i] = __uint_as_float(pack_bf16(r[2 * i], r[2 * i + 1]));
#pragma unroll
        for (int i = 31; i >= 0; i--) r[96 + i] = __uint_as_float(pack_bf16(r[64 + 2 * i], r[65 + 2 * i]));
        uint32_t eo[4];
        uint4 pv = make_uint4(0, 0, 0, 0);
#pragma unroll
        for (int kb = 0; kb < 16; kb++) {
            const int it = 16 + kb, s = it % G1_STAGES;
            mbar_wait(bar_full + 8 * s, (it / G1_STAGES) & 1);
            if (threadIdx.x == 0 && (it & 7) == 0) STAMP(2, 2 + it / 8);
            wgmma_fence();
            const uint64_t da = descA + (uint64_t)(((kb >> 1) * 16384 + (kb & 1) * 64) >> 4);
            const uint64_t db = descB + (uint64_t)((s * G1_B_STAGE) >> 4);
            wgmma_n192(r, da, db, kb != 0);
            if (kb < 8) {
                eo[0] = geglu_pair(__float_as_uint(r[128 + 4 * kb]), __float_as_uint(r[96 + 4 * kb]));
                eo[1] = geglu_pair(__float_as_uint(r[129 + 4 * kb]), __float_as_uint(r[97 + 4 * kb]));
            }
            wgmma_n192(r, da + 2, db + 64, 1);
            wgmma_commit();
            if (kb >= 2 && kb < 10) *reinterpret_cast<uint4*>(hrow + (kb - 2) * 16) = pv;
            if (kb >= 1 && kb < 9) {
                __syncwarp();
                asm volatile("ld.shared.v4.u32 {%0,%1,%2,%3}, [%4];" : "=r"(pv.x), "=r"(pv.y), "=r"(pv.z), "=r"(pv.w)
                             : "r"(stg + ((kb - 1) & 1) * 512 + lane * 16));
            }
            if (kb < 8) {
                eo[2] = geglu_pair(__float_as_uint(r[130 + 4 * kb]), __float_as_uint(r[98 + 4 * kb]));
                eo[3] = geglu_pair(__float_as_uint(r[131 + 4 * kb]), __float_as_uint(r[99 + 4 * kb]));
                stmatrix_x4(stg + (kb & 1) * 512 + st_off, eo[0], eo[1], eo[2], eo[3]);
            }
            if (kb == 9) asm volatile("bar.arrive 3, 288;" ::: "memory");
            if (kb > 0 && it - 1 + G1_STAGES < G1_ITERS) {
                wgmma_wait<1>();
                if (lane < 2) mbar_arrive_remote(bar_empty + 8 * ((it - 1) % G1_STAGES), lane);
            }
        }
        wgmma_wait<0>();
        fence_async_smem();
        __syncwarp();
        if (lane == 0) mbar_arrive(bar_g1mma);
        if (threadIdx.x == 0) STAMP(2, 6);
        {
            uint32_t o[24];
#pragma unroll
            for (int i = 0; i < 24; i++) o[i] = geglu_pair(pack_bf16(r[2 * i], r[2 * i + 1]), pack_bf16(r[48 + 2 * i], r[49 + 2 * i]));
            named_bar(1 + wg, 128);
            const uint32_t fbuf = sA + ((warp & 3) >> 1) * 16384 + wg * 8192 + (warp & 1) * 4096;
#pragma unroll
            for (int jj = 0; jj < 6; jj++) stmatrix_x4(fbuf + jj * 512 + st_off, o[4 * jj], o[4 * jj + 1], o[4 * jj + 2], o[4 * jj + 3]);
            __syncwarp();
            uint4 v[6];
#pragma unroll
            for (int jj = 0; jj < 6; jj++)
                asm volatile("ld.shared.v4.u32 {%0,%1,%2,%3}, [%4];" : "=r"(v[jj].x), "=r"(v[jj].y), "=r"(v[jj].z), "=r"(v[jj].w)
                             : "r"(fbuf + jj * 512 + lane * 16));
#pragma unroll
            for (int jj = 0; jj < 6; jj++) *reinterpret_cast<uint4*>(hrow + 128 + jj * 16) = v[jj];
        }
        }
        fence_async_smem();
        __syncwarp();
        if (lane == 0) mbar_arrive(bar_g1done);
        asm volatile("bar.arrive 9, 288;" ::: "memory");
        if (threadIdx.x == 0) STAMP(2, 7);
        {
        const int g = lane >> 2, t = lane & 3;
        float acc[64];
        const uint64_t descA2 = make_desc(sbase + wg * 8192, 16, 1024);
        const uint64_t descB2 = make_desc(sbase + 16384, 8192, 1024);
#pragma unroll
        for (int it = 0; it < G2_KB; it++) {
            const int s = (it + 1) % G2_STAGES;
            mbar_wait(bar_full2 + 8 * s, (it / G2_STAGES) & 1);
            if (threadIdx.x == 0 && (it == 0 || it == 7)) STAMP(3, 2 + it / 7);
            wgmma_fence();
            {
                const uint64_t da = descA2 + (uint64_t)((s * G2_STAGE) >> 4);
                const uint64_t db = descB2 + (uint64_t)((s * G2_STAGE) >> 4);
                wgmma_n128_k64(acc, da, da + 2, da + 4, da + 6, db, db + 128, db + 256, db + 384, it != 0);
            }
            wgmma_commit();
            if (it > 0 && it - 1 + G2_STAGES < G2_KB) {
                wgmma_wait<1>();
                if (lane == 0) mbar_arrive(bar_empty2 + 8 * (it % G2_STAGES));
            }
        }
        const int lr = wg * 64 + (warp & 3) * 16 + g;
        uint32_t xv[16], sv[16];
        mbar_wait(bar_epi, 0);
#pragma unroll
        for (int j = 0; j < 8; j++) {
#pragma unroll
            for (int hh = 0; hh < 2; hh++) {
                const int r = lr + 8 * hh;
                asm volatile("ld.shared.u32 %0, [%1];" : "=r"(xv[2 * j + hh]) : "r"(sX + r * 128 + ((j ^ (r & 7)) << 4) + 4 * t));
                const int c0 = 8 * j + 2 * t;
                const uint32_t sa = sS + (r >> 6) * 8192 + (((r & 63) >> 3) << 4) + (r & 7) * 2;
                uint16_t s0r, s1r;
                asm volatile("ld.shared.u16 %0, [%1];" : "=h"(s0r) : "r"((sa + c0 * 128) ^ ((c0 & 7) << 4)));
                asm volatile("ld.shared.u16 %0, [%1];" : "=h"(s1r) : "r"((sa + (c0 + 1) * 128) ^ (((c0 + 1) & 7) << 4)));
                sv[2 * j + hh] = (uint32_t)s0r | ((uint32_t)s1r << 16);
            }
        }
        wgmma_wait<0>();
        if (threadIdx.x == 0) STAMP(3, 4);
        {
            uint32_t remote, rbar;
            asm volatile("mapa.shared::cluster.u32 %0, %1, %2;" : "=r"(remote) : "r"(sXch + threadIdx.x * 16), "r"(kh ^ 1));
            asm volatile("mapa.shared::cluster.u32 %0, %1, %2;" : "=r"(rbar) : "r"(bar_xch), "r"(kh ^ 1));
            if (kh == 0) {
#pragma unroll
                for (int i = 0; i < 8; i++)
                    asm volatile("st.async.shared::cluster.mbarrier::complete_tx::bytes.v4.f32 [%0], {%1,%2,%3,%4}, [%5];" ::"r"(remote + i * 4096),
                                 "f"(acc[32 + 4 * i]), "f"(acc[33 + 4 * i]), "f"(acc[34 + 4 * i]), "f"(acc[35 + 4 * i]), "r"(rbar) : "memory");
            } else {
#pragma unroll
                for (int i = 0; i < 8; i++)
                    asm volatile("st.async.shared::cluster.mbarrier::complete_tx::bytes.v4.f32 [%0], {%1,%2,%3,%4}, [%5];" ::"r"(remote + i * 4096),
                                 "f"(acc[4 * i]), "f"(acc[1 + 4 * i]), "f"(acc[2 + 4 * i]), "f"(acc[3 + 4 * i]), "r"(rbar) : "memory");
#pragma unroll
                for (int i = 0; i < 32; i++) acc[i] = acc[32 + i];
            }
        }
        if (threadIdx.x == 0) STAMP(3, 6);
        mbar_wait(bar_xch, 0);
        if (threadIdx.x == 0) STAMP(3, 7);
#pragma unroll
        for (int j = 0; j < 8; j++) {
            float4 o;
            asm volatile("ld.shared.v4.f32 {%0,%1,%2,%3}, [%4];" : "=f"(o.x), "=f"(o.y), "=f"(o.z), "=f"(o.w) : "r"(sXch + threadIdx.x * 16 + j * 4096));
            acc[4 * j] += o.x; acc[4 * j + 1] += o.y; acc[4 * j + 2] += o.z; acc[4 * j + 3] += o.w;
        }
#pragma unroll
        for (int i = 0; i < 16; i++) {
            float f0 = bf16_round(acc[2 * i]), f1 = bf16_round(acc[2 * i + 1]);
            float g0 = bf16_round(__fdividef(f0, 1.0f + __expf(-f0)));
            float g1 = bf16_round(__fdividef(f1, 1.0f + __expf(-f1)));
            float o0 = bf_lo(xv[i]) + bf16_round(bf_lo(sv[i]) * g0);
            float o1 = bf_hi(xv[i]) + bf16_round(bf_hi(sv[i]) * g1);
            xv[i] = pack_bf16(o0, o1);
        }
#pragma unroll
        for (int j = 0; j < 8; j++) {
#pragma unroll
            for (int hh = 0; hh < 2; hh++) {
                const int r = lr + 8 * hh;
                asm volatile("st.shared.u32 [%0], %1;" ::"r"(sX + r * 128 + ((j ^ (r & 7)) << 4) + 4 * t), "r"(xv[2 * j + hh]) : "memory");
            }
        }
        if (threadIdx.x == 0) STAMP(3, 9);
        fence_async_smem();
        __syncwarp();
        if (lane == 0) {
            tma_store_2d(&tm_out, sX + (wg * 64 + (warp & 3) * 16) * 128, col_fin, rb * 128 + wg * 64 + (warp & 3) * 16);
            bulk_commit();
            bulk_wait_read<0>();
        }
        }
        if (threadIdx.x == 0) STAMP(3, 5);
        named_bar(4, 256);
        if (threadIdx.x == 0) {
            const unsigned int old = atomicAdd(&g_done_count, 1u);
            if (old == gridDim.x - 1) {
                g_ln_count = 0; g_conv_count = 0; g_done_count = 0;
                for (int i = 0; i < 32; i++) g_h_count[i] = 0;
            }
        }
    }
}

typedef CUresult (*EncodeFn)(CUtensorMap*, CUtensorMapDataType, cuuint32_t, void*, const cuuint64_t*, const cuuint64_t*,
                             const cuuint32_t*, const cuuint32_t*, CUtensorMapInterleave, CUtensorMapSwizzle,
                             CUtensorMapL2promotion, CUtensorMapFloatOOBfill);

void make_map(EncodeFn fn, CUtensorMap* m, const void* ptr, uint64_t inner, uint64_t outer, uint32_t box_in, uint32_t box_out,
              CUtensorMapSwizzle swz = CU_TENSOR_MAP_SWIZZLE_128B) {
    cuuint64_t dims[2] = {inner, outer};
    cuuint64_t strides[1] = {inner * 2};
    cuuint32_t box[2] = {box_in, box_out};
    cuuint32_t es[2] = {1, 1};
    fn(m, CU_TENSOR_MAP_DATA_TYPE_BFLOAT16, 2, const_cast<void*>(ptr), dims, strides, box, es, CU_TENSOR_MAP_INTERLEAVE_NONE,
       swz, CU_TENSOR_MAP_L2_PROMOTION_L2_256B, CU_TENSOR_MAP_FLOAT_OOB_FILL_NONE);
}
void make_map3(EncodeFn fn, CUtensorMap* m, const void* ptr, uint64_t cols, uint64_t rows, uint32_t atom, uint32_t box_rows,
               uint32_t box_atoms, CUtensorMapSwizzle swz) {
    cuuint64_t dims[3] = {atom, rows, cols / atom};
    cuuint64_t strides[2] = {cols * 2, (cuuint64_t)atom * 2};
    cuuint32_t box[3] = {atom, box_rows, box_atoms};
    cuuint32_t es[3] = {1, 1, 1};
    fn(m, CU_TENSOR_MAP_DATA_TYPE_BFLOAT16, 3, const_cast<void*>(ptr), dims, strides, box, es, CU_TENSOR_MAP_INTERLEAVE_NONE,
       swz, CU_TENSOR_MAP_L2_PROMOTION_L2_256B, CU_TENSOR_MAP_FLOAT_OOB_FILL_NONE);
}

template <typename... Args>
void launch_pdl(void (*kern)(Args...), int grid, int block, int smem, bool pdl, int cluster, Args... args) {
    cudaLaunchConfig_t cfg = {};
    cfg.gridDim = dim3(grid); cfg.blockDim = dim3(block); cfg.dynamicSmemBytes = smem; cfg.stream = cudaStreamPerThread;
    cudaLaunchAttribute at[2];
    int n = 0;
    if (pdl) {
        at[n].id = cudaLaunchAttributeProgrammaticStreamSerialization;
        at[n].val.programmaticStreamSerializationAllowed = 1;
        n++;
    }
    if (cluster > 1) {
        at[n].id = cudaLaunchAttributeClusterDimension;
        at[n].val.clusterDim.x = cluster; at[n].val.clusterDim.y = 1; at[n].val.clusterDim.z = 1;
        n++;
    }
    cfg.attrs = at; cfg.numAttrs = n;
    cudaLaunchKernelEx(&cfg, kern, args...);
}

}

extern "C" void kernel_launch(void* const* d_in, const int* in_sizes, int n_in, void* d_out, int out_size) {
    const __nv_bfloat16* x = (const __nv_bfloat16*)d_in[0];
    const __nv_bfloat16* A_re = (const __nv_bfloat16*)d_in[1];
    const __nv_bfloat16* A_im = (const __nv_bfloat16*)d_in[2];
    const __nv_bfloat16* B_re = (const __nv_bfloat16*)d_in[3];
    const __nv_bfloat16* B_im = (const __nv_bfloat16*)d_in[4];
    const __nv_bfloat16* C_re = (const __nv_bfloat16*)d_in[5];
    const __nv_bfloat16* C_im = (const __nv_bfloat16*)d_in[6];
    const __nv_bfloat16* log_dt = (const __nv_bfloat16*)d_in[7];
    const __nv_bfloat16* Dskip = (const __nv_bfloat16*)d_in[8];
    const __nv_bfloat16* wg = (const __nv_bfloat16*)d_in[10];
    const __nv_bfloat16* wu = (const __nv_bfloat16*)d_in[11];
    const __nv_bfloat16* wd = (const __nv_bfloat16*)d_in[12];
    __nv_bfloat16* out = (__nv_bfloat16*)d_out;

    static bool init = false;
    static CUtensorMap tm_xn, tm_wg4, tm_wu4, tm_wg3, tm_wu3, tm_hst, tm_hst96, tm_h, tm_wd, tm_x, tm_sT, tm_out;
    static const void* last_ptrs[5] = {nullptr, nullptr, nullptr, nullptr, nullptr};
    if (!init || last_ptrs[0] != wg || last_ptrs[1] != wu || last_ptrs[2] != wd || last_ptrs[3] != x || last_ptrs[4] != out) {
        void* fnp = nullptr;
        cudaDriverEntryPointQueryResult qres;
        cudaGetDriverEntryPoint("cuTensorMapEncodeTiled", &fnp, cudaEnableDefault, &qres);
        EncodeFn fn = (EncodeFn)fnp;
        void *p_xn, *p_h, *p_sT;
        cudaGetSymbolAddress(&p_xn, g_xn);
        cudaGetSymbolAddress(&p_h, g_h);
        cudaGetSymbolAddress(&p_sT, g_sT);
        make_map(fn, &tm_xn, p_xn, D_, L_, 64, 128);
        make_map3(fn, &tm_wg4, wg, F_, D_, 32, 32, 4, CU_TENSOR_MAP_SWIZZLE_64B);
        make_map3(fn, &tm_wu4, wu, F_, D_, 32, 32, 4, CU_TENSOR_MAP_SWIZZLE_64B);
        make_map3(fn, &tm_wg3, wg, F_, D_, 32, 32, 3, CU_TENSOR_MAP_SWIZZLE_64B);
        make_map3(fn, &tm_wu3, wu, F_, D_, 32, 32, 3, CU_TENSOR_MAP_SWIZZLE_64B);
        make_map(fn, &tm_hst, p_h, F_, L_, 16, 16, CU_TENSOR_MAP_SWIZZLE_NONE);
        make_map(fn, &tm_hst96, p_h, F_, L_, 96, 16, CU_TENSOR_MAP_SWIZZLE_NONE);
        make_map(fn, &tm_h, p_h, F_, L_, 64, 128);
        make_map3(fn, &tm_wd, wd, D_, F_, 64, 64, 2, CU_TENSOR_MAP_SWIZZLE_128B);
        make_map(fn, &tm_x, x, D_, L_, 64, 128);
        make_map(fn, &tm_sT, p_sT, L_, D_, 64, 64);
        make_map(fn, &tm_out, out, D_, L_, 64, 16);
        cudaFuncSetAttribute(mega_kernel, cudaFuncAttributeMaxDynamicSharedMemorySize, MG_SMEM);
        last_ptrs[0] = wg; last_ptrs[1] = wu; last_ptrs[2] = wd; last_ptrs[3] = x; last_ptrs[4] = out;
        init = true;
    }
    MegaParams P = {x, A_re, A_im, B_re, B_im, C_re, C_im, log_dt, Dskip, wg, wu, wd};
    launch_pdl(mega_kernel, 128, 384, MG_SMEM, false, 2, P, tm_xn, tm_wg4, tm_wu4, tm_wg3, tm_wu3, tm_h, tm_wd, tm_x, tm_sT, tm_out);
}
```

```cpp
#include <cuda_runtime.h>
#include <cuda_bf16.h>
#include <cuda.h>
#include <stdint.h>

namespace {

constexpr int L_ = 2048, D_ = 512, NS_ = 128, F_ = 1792;

__device__ __align__(1024) __nv_bfloat16 g_xn[L_ * D_];
__device__ __align__(1024) __nv_bfloat16 g_xnT[D_ * L_];
__device__ __align__(1024) __nv_bfloat16 g_sT[D_ * L_];
__device__ __align__(1024) __nv_bfloat16 g_h[L_ * F_];
__device__ unsigned int g_ln_count, g_conv_count, g_done_count, g_h_count[32];

#define STAMP(k, i)

__device__ __forceinline__ uint32_t smem_u32(const void* p) { return (uint32_t)__cvta_generic_to_shared(p); }
__device__ __forceinline__ void pdl_wait() { asm volatile("griddepcontrol.wait;" ::: "memory"); }
__device__ __forceinline__ void pdl_launch() { asm volatile("griddepcontrol.launch_dependents;" ::: "memory"); }

__device__ __forceinline__ void mbar_init(uint32_t bar, uint32_t cnt) {
    asm volatile("mbarrier.init.shared::cta.b64 [%0], %1;" ::"r"(bar), "r"(cnt) : "memory");
}
__device__ __forceinline__ void mbar_expect_tx(uint32_t bar, uint32_t bytes) {
    asm volatile("mbarrier.arrive.expect_tx.shared::cta.b64 _, [%0], %1;" ::"r"(bar), "r"(bytes) : "memory");
}
__device__ __forceinline__ void mbar_arrive(uint32_t bar) {
    asm volatile("mbarrier.arrive.shared::cta.b64 _, [%0];" ::"r"(bar) : "memory");
}
__device__ __forceinline__ void mbar_wait(uint32_t bar, uint32_t parity) {
    asm volatile(
        "{\n.reg .pred p;\n"
        "WAIT_LOOP:\n"
        "mbarrier.try_wait.parity.shared::cta.b64 p, [%0], %1;\n"
        "@p bra WAIT_DONE;\n"
        "bra WAIT_LOOP;\n"
        "WAIT_DONE:\n}\n" ::"r"(bar), "r"(parity) : "memory");
}
__device__ __forceinline__ void tma_load_2d(uint32_t dst, const CUtensorMap* tm, int c0, int c1, uint32_t bar) {
    asm volatile(
        "cp.async.bulk.tensor.2d.shared::cluster.global.mbarrier::complete_tx::bytes [%0], [%1, {%3, %4}], [%2];"
        ::"r"(dst), "l"((uint64_t)tm), "r"(bar), "r"(c0), "r"(c1) : "memory");
}
__device__ __forceinline__ void prefetch_tmap(const CUtensorMap* tm) {
    asm volatile("prefetch.tensormap [%0];" ::"l"((uint64_t)tm) : "memory");
}
__device__ __forceinline__ uint64_t make_desc(uint32_t addr, uint32_t lbo, uint32_t sbo, uint64_t mode = 1) {
    uint64_t d = 0;
    d |= (uint64_t)((addr & 0x3FFFF) >> 4);
    d |= (uint64_t)((lbo >> 4) & 0x3FFF) << 16;
    d |= (uint64_t)((sbo >> 4) & 0x3FFF) << 32;
    d |= mode << 62;
    return d;
}
__device__ __forceinline__ void fence_async_smem() { asm volatile("fence.proxy.async.shared::cta;" ::: "memory"); }
__device__ __forceinline__ void wgmma_fence() { asm volatile("wgmma.fence.sync.aligned;" ::: "memory"); }
__device__ __forceinline__ void wgmma_commit() { asm volatile("wgmma.commit_group.sync.aligned;" ::: "memory"); }
template <int N> __device__ __forceinline__ void wgmma_wait() {
    asm volatile("wgmma.wait_group.sync.aligned %0;" ::"n"(N) : "memory");
}

#define R8(a, i) "+f"(a[i + 0]), "+f"(a[i + 1]), "+f"(a[i + 2]), "+f"(a[i + 3]), "+f"(a[i + 4]), "+f"(a[i + 5]), "+f"(a[i + 6]), "+f"(a[i + 7])

__device__ __forceinline__ void wgmma_n256_k32(float* a, uint64_t da0, uint64_t da1, uint64_t db0, uint64_t db1, int scale_d) {
    asm volatile(
        "{\n.reg .pred p;\nsetp.ne.b32 p, %132, 0;\n"
        "wgmma.mma_async.sync.aligned.m64n256k16.f32.bf16.bf16 {%0,%1,%2,%3,%4,%5,%6,%7,%8,%9,%10,%11,%12,%13,%14,%15,%16,%17,%18,%19,%20,%21,%22,%23,%24,%25,%26,%27,%28,%29,%30,%31,%32,%33,%34,%35,%36,%37,%38,%39,%40,%41,%42,%43,%44,%45,%46,%47,%48,%49,%50,%51,%52,%53,%54,%55,%56,%57,%58,%59,%60,%61,%62,%63,%64,%65,%66,%67,%68,%69,%70,%71,%72,%73,%74,%75,%76,%77,%78,%79,%80,%81,%82,%83,%84,%85,%86,%87,%88,%89,%90,%91,%92,%93,%94,%95,%96,%97,%98,%99,%100,%101,%102,%103,%104,%105,%106,%107,%108,%109,%110,%111,%112,%113,%114,%115,%116,%117,%118,%119,%120,%121,%122,%123,%124,%125,%126,%127}, %128, %130, p, 1, 1, 0, 1;\n"
        "wgmma.mma_async.sync.aligned.m64n256k16.f32.bf16.bf16 {%0,%1,%2,%3,%4,%5,%6,%7,%8,%9,%10,%11,%12,%13,%14,%15,%16,%17,%18,%19,%20,%21,%22,%23,%24,%25,%26,%27,%28,%29,%30,%31,%32,%33,%34,%35,%36,%37,%38,%39,%40,%41,%42,%43,%44,%45,%46,%47,%48,%49,%50,%51,%52,%53,%54,%55,%56,%57,%58,%59,%60,%61,%62,%63,%64,%65,%66,%67,%68,%69,%70,%71,%72,%73,%74,%75,%76,%77,%78,%79,%80,%81,%82,%83,%84,%85,%86,%87,%88,%89,%90,%91,%92,%93,%94,%95,%96,%97,%98,%99,%100,%101,%102,%103,%104,%105,%106,%107,%108,%109,%110,%111,%112,%113,%114,%115,%116,%117,%118,%119,%120,%121,%122,%123,%124,%125,%126,%127}, %129, %131, 1, 1, 1, 0, 1;\n"
        "}\n"
        : R8(a, 0), R8(a, 8), R8(a, 16), R8(a, 24), R8(a, 32), R8(a, 40), R8(a, 48), R8(a, 56), R8(a, 64), R8(a, 72), R8(a, 80), R8(a, 88), R8(a, 96), R8(a, 104), R8(a, 112), R8(a, 120)
        : "l"(da0), "l"(da1), "l"(db0), "l"(db1), "r"(scale_d));
}
__device__ __forceinline__ void wgmma_n192_k32(float* a, uint64_t da0, uint64_t da1, uint64_t db0, uint64_t db1, int scale_d) {
    asm volatile(
        "{\n.reg .pred p;\nsetp.ne.b32 p, %100, 0;\n"
        "wgmma.mma_async.sync.aligned.m64n192k16.f32.bf16.bf16 {%0,%1,%2,%3,%4,%5,%6,%7,%8,%9,%10,%11,%12,%13,%14,%15,%16,%17,%18,%19,%20,%21,%22,%23,%24,%25,%26,%27,%28,%29,%30,%31,%32,%33,%34,%35,%36,%37,%38,%39,%40,%41,%42,%43,%44,%45,%46,%47,%48,%49,%50,%51,%52,%53,%54,%55,%56,%57,%58,%59,%60,%61,%62,%63,%64,%65,%66,%67,%68,%69,%70,%71,%72,%73,%74,%75,%76,%77,%78,%79,%80,%81,%82,%83,%84,%85,%86,%87,%88,%89,%90,%91,%92,%93,%94,%95}, %96, %98, p, 1, 1, 0, 1;\n"
        "wgmma.mma_async.sync.aligned.m64n192k16.f32.bf16.bf16 {%0,%1,%2,%3,%4,%5,%6,%7,%8,%9,%10,%11,%12,%13,%14,%15,%16,%17,%18,%19,%20,%21,%22,%23,%24,%25,%26,%27,%28,%29,%30,%31,%32,%33,%34,%35,%36,%37,%38,%39,%40,%41,%42,%43,%44,%45,%46,%47,%48,%49,%50,%51,%52,%53,%54,%55,%56,%57,%58,%59,%60,%61,%62,%63,%64,%65,%66,%67,%68,%69,%70,%71,%72,%73,%74,%75,%76,%77,%78,%79,%80,%81,%82,%83,%84,%85,%86,%87,%88,%89,%90,%91,%92,%93,%94,%95}, %97, %99, 1, 1, 1, 0, 1;\n"
        "}\n"
        : R8(a, 0), R8(a, 8), R8(a, 16), R8(a, 24), R8(a, 32), R8(a, 40), R8(a, 48), R8(a, 56), R8(a, 64), R8(a, 72), R8(a, 80), R8(a, 88)
        : "l"(da0), "l"(da1), "l"(db0), "l"(db1), "r"(scale_d));
}
__device__ __forceinline__ void wgmma_n192(float* a, uint64_t da0, uint64_t db0, int scale_d) {
    asm volatile(
        "{\n.reg .pred p;\nsetp.ne.b32 p, %98, 0;\n"
        "wgmma.mma_async.sync.aligned.m64n192k16.f32.bf16.bf16 {%0,%1,%2,%3,%4,%5,%6,%7,%8,%9,%10,%11,%12,%13,%14,%15,%16,%17,%18,%19,%20,%21,%22,%23,%24,%25,%26,%27,%28,%29,%30,%31,%32,%33,%34,%35,%36,%37,%38,%39,%40,%41,%42,%43,%44,%45,%46,%47,%48,%49,%50,%51,%52,%53,%54,%55,%56,%57,%58,%59,%60,%61,%62,%63,%64,%65,%66,%67,%68,%69,%70,%71,%72,%73,%74,%75,%76,%77,%78,%79,%80,%81,%82,%83,%84,%85,%86,%87,%88,%89,%90,%91,%92,%93,%94,%95}, %96, %97, p, 1, 1, 0, 1;\n"
        "}\n"
        : R8(a, 0), R8(a, 8), R8(a, 16), R8(a, 24), R8(a, 32), R8(a, 40), R8(a, 48), R8(a, 56), R8(a, 64), R8(a, 72), R8(a, 80), R8(a, 88)
        : "l"(da0), "l"(db0), "r"(scale_d));
}
__device__ __forceinline__ void wgmma_n128_k64(float* a, uint64_t da0, uint64_t da1, uint64_t da2, uint64_t da3,
                                               uint64_t db0, uint64_t db1, uint64_t db2, uint64_t db3, int scale_d) {
    asm volatile(
        "{\n.reg .pred p;\nsetp.ne.b32 p, %72, 0;\n"
        "wgmma.mma_async.sync.aligned.m64n128k16.f32.bf16.bf16 {%0,%1,%2,%3,%4,%5,%6,%7,%8,%9,%10,%11,%12,%13,%14,%15,%16,%17,%18,%19,%20,%21,%22,%23,%24,%25,%26,%27,%28,%29,%30,%31,%32,%33,%34,%35,%36,%37,%38,%39,%40,%41,%42,%43,%44,%45,%46,%47,%48,%49,%50,%51,%52,%53,%54,%55,%56,%57,%58,%59,%60,%61,%62,%63}, %64, %68, p, 1, 1, 0, 1;\n"
        "wgmma.mma_async.sync.aligned.m64n128k16.f32.bf16.bf16 {%0,%1,%2,%3,%4,%5,%6,%7,%8,%9,%10,%11,%12,%13,%14,%15,%16,%17,%18,%19,%20,%21,%22,%23,%24,%25,%26,%27,%28,%29,%30,%31,%32,%33,%34,%35,%36,%37,%38,%39,%40,%41,%42,%43,%44,%45,%46,%47,%48,%49,%50,%51,%52,%53,%54,%55,%56,%57,%58,%59,%60,%61,%62,%63}, %65, %69, 1, 1, 1, 0, 1;\n"
        "wgmma.mma_async.sync.aligned.m64n128k16.f32.bf16.bf16 {%0,%1,%2,%3,%4,%5,%6,%7,%8,%9,%10,%11,%12,%13,%14,%15,%16,%17,%18,%19,%20,%21,%22,%23,%24,%25,%26,%27,%28,%29,%30,%31,%32,%33,%34,%35,%36,%37,%38,%39,%40,%41,%42,%43,%44,%45,%46,%47,%48,%49,%50,%51,%52,%53,%54,%55,%56,%57,%58,%59,%60,%61,%62,%63}, %66, %70, 1, 1, 1, 0, 1;\n"
        "wgmma.mma_async.sync.aligned.m64n128k16.f32.bf16.bf16 {%0,%1,%2,%3,%4,%5,%6,%7,%8,%9,%10,%11,%12,%13,%14,%15,%16,%17,%18,%19,%20,%21,%22,%23,%24,%25,%26,%27,%28,%29,%30,%31,%32,%33,%34,%35,%36,%37,%38,%39,%40,%41,%42,%43,%44,%45,%46,%47,%48,%49,%50,%51,%52,%53,%54,%55,%56,%57,%58,%59,%60,%61,%62,%63}, %67, %71, 1, 1, 1, 0, 1;\n"
        "}\n"
        : R8(a, 0), R8(a, 8), R8(a, 16), R8(a, 24), R8(a, 32), R8(a, 40), R8(a, 48), R8(a, 56)
        : "l"(da0), "l"(da1), "l"(da2), "l"(da3), "l"(db0), "l"(db1), "l"(db2), "l"(db3), "r"(scale_d));
}

__device__ __forceinline__ float bf16_round(float x) {
    uint32_t p; asm("cvt.rn.bf16x2.f32 %0, %1, %2;" : "=r"(p) : "f"(x), "f"(0.0f));
    return __uint_as_float(p);
}
__device__ __forceinline__ uint32_t pack_bf16(float lo, float hi) {
    __nv_bfloat162 v = __floats2bfloat162_rn(lo, hi);
    return *reinterpret_cast<uint32_t*>(&v);
}
__device__ __forceinline__ float bf_lo(uint32_t v) { return __uint_as_float(v << 16); }
__device__ __forceinline__ float bf_hi(uint32_t v) { return __uint_as_float(v & 0xFFFF0000u); }

struct cplx { float r, i; };
__device__ __forceinline__ cplx cmul(cplx a, cplx b) {
    cplx c; c.r = a.r * b.r - a.i * b.i; c.i = a.r * b.i + a.i * b.r; return c;
}
__device__ __forceinline__ cplx csq(cplx a) {
    cplx c; c.r = a.r * a.r - a.i * a.i; c.i = 2.0f * a.r * a.i; return c;
}
__device__ __forceinline__ cplx cexp_m(float ar2, float ai2, float m) {
    float mag;
    asm("ex2.approx.ftz.f32 %0, %1;" : "=f"(mag) : "f"(ar2 * m));
    float rr = ai2 * m;
    rr -= (rr + 12582912.0f) - 12582912.0f;
    float th = rr * 6.283185307179586f;
    cplx c; c.r = mag * __cosf(th); c.i = mag * __sinf(th);
    return c;
}
__device__ __forceinline__ uint32_t to_tf32(float x) { return __float_as_uint(x) + 0x1000u; }
__device__ __forceinline__ void mma_tf32(float* c, uint32_t a0, uint32_t a1, uint32_t a2, uint32_t a3, uint32_t b0, uint32_t b1) {
    asm volatile("mma.sync.aligned.m16n8k8.row.col.f32.tf32.tf32.f32 {%0,%1,%2,%3}, {%4,%5,%6,%7}, {%8,%9}, {%0,%1,%2,%3};"
                 : "+f"(c[0]), "+f"(c[1]), "+f"(c[2]), "+f"(c[3])
                 : "r"(a0), "r"(a1), "r"(a2), "r"(a3), "r"(b0), "r"(b1));
}
__device__ __forceinline__ void mma_bf16(float* c, uint32_t a0, uint32_t a1, uint32_t a2, uint32_t a3, uint32_t b0, uint32_t b1) {
    asm volatile("mma.sync.aligned.m16n8k16.row.col.f32.bf16.bf16.f32 {%0,%1,%2,%3}, {%4,%5,%6,%7}, {%8,%9}, {%0,%1,%2,%3};"
                 : "+f"(c[0]), "+f"(c[1]), "+f"(c[2]), "+f"(c[3])
                 : "r"(a0), "r"(a1), "r"(a2), "r"(a3), "r"(b0), "r"(b1));
}
__device__ __forceinline__ void named_bar(int id, int n) { asm volatile("bar.sync %0, %1;" ::"r"(id), "r"(n) : "memory"); }
__device__ __forceinline__ void ldsm_x4(uint32_t addr, uint32_t& r0, uint32_t& r1, uint32_t& r2, uint32_t& r3) {
    asm volatile("ldmatrix.sync.aligned.m8n8.x4.shared.b16 {%0,%1,%2,%3}, [%4];" : "=r"(r0), "=r"(r1), "=r"(r2), "=r"(r3) : "r"(addr));
}
__device__ __forceinline__ void ldsm_x4_t(uint32_t addr, uint32_t& r0, uint32_t& r1, uint32_t& r2, uint32_t& r3) {
    asm volatile("ldmatrix.sync.aligned.m8n8.x4.trans.shared.b16 {%0,%1,%2,%3}, [%4];" : "=r"(r0), "=r"(r1), "=r"(r2), "=r"(r3) : "r"(addr));
}

constexpr int CV_CH = 4;
constexpr int CV_O_CONST = 0;
constexpr int CV_O_KP = 12288;
constexpr int CV_EARLY = 12288 + 7776;
constexpr int CV_O_Q = 0;
constexpr int CV_O_Q2 = CV_O_Q + 2304;
constexpr int CV_O_Q3 = CV_O_Q2 + 1024;
constexpr int CV_O_Q4X = CV_O_Q3 + 768;
constexpr int CV_O_W3 = CV_O_Q4X + 256;
constexpr int CV_O_W5 = CV_O_W3 + 3104;
constexpr int CV_O_W7 = CV_O_W5 + 3104;
constexpr int CV_O_W9 = CV_O_W7 + 2048;
constexpr int CV_O_U = CV_O_W9 + 2048;
constexpr int CV_LATE = CV_O_U + 4352;
constexpr int CV_LATE_BASE = 229376 - CV_CH * CV_LATE;
constexpr int CV_TILE_OFF = CV_CH * CV_EARLY;
static_assert(CV_TILE_OFF + 16 * (D_ + 8) * 2 <= CV_LATE_BASE && CV_LATE_BASE >= 131072 + 16384, "front layout");
static_assert(CV_O_W3 >= 4096 && CV_O_U - CV_O_W3 >= 8192 && (CV_LATE % 16) == 0 && (CV_EARLY % 16) == 0, "front layout");

constexpr int LN_ROWS = 16;

template <typename PF>
__device__ __forceinline__ void front_phase(PF prefetch_fn, uint8_t* smem, const __nv_bfloat16* __restrict__ x,
                                            const __nv_bfloat16* __restrict__ A_re, const __nv_bfloat16* __restrict__ A_im,
                                            const __nv_bfloat16* __restrict__ B_re, const __nv_bfloat16* __restrict__ B_im,
                                            const __nv_bfloat16* __restrict__ C_re, const __nv_bfloat16* __restrict__ C_im,
                                            const __nv_bfloat16* __restrict__ log_dt, const __nv_bfloat16* __restrict__ Dskip,
                                            const __nv_bfloat16* __restrict__ wg, const __nv_bfloat16* __restrict__ wu,
                                            const __nv_bfloat16* __restrict__ wd) {
    const int warp = threadIdx.x >> 5, lane = threadIdx.x & 31;
    const int ch = warp / 3, w = warp - 3 * ch, tc = threadIdx.x - 96 * ch;
    const int d = blockIdx.x * CV_CH + ch;
    const int g = lane >> 2, t = lane & 3;
    uint8_t* base = smem + CV_LATE_BASE + ch * CV_LATE;
    float4* s_const = reinterpret_cast<float4*>(smem + ch * CV_EARLY + CV_O_CONST);
    float* s_kp = reinterpret_cast<float*>(smem + ch * CV_EARLY + CV_O_KP);
    uint32_t* s_q = reinterpret_cast<uint32_t*>(base + CV_O_Q);
    uint32_t* s_q2 = reinterpret_cast<uint32_t*>(base + CV_O_Q2);
    uint32_t* s_q3 = reinterpret_cast<uint32_t*>(base + CV_O_Q3);
    uint32_t* s_q4 = reinterpret_cast<uint32_t*>(base + CV_O_Q4X);
    __nv_bfloat16* s_u = reinterpret_cast<__nv_bfloat16*>(base + CV_O_U);
    const int bar_id = 5 + ch;
    const __nv_bfloat16 p_dsk = Dskip[d];
    __nv_bfloat16 (*tile)[D_ + 8] = reinterpret_cast<__nv_bfloat16 (*)[D_ + 8]>(smem + CV_TILE_OFF);

    if (warp < 8) {
        const int row = blockIdx.x * LN_ROWS + warp * 2;
        uint4 xv[2][2];
#pragma unroll
        for (int r = 0; r < 2; r++) {
            xv[r][0] = *reinterpret_cast<const uint4*>(x + (size_t)(row + r) * D_ + lane * 8);
            xv[r][1] = *reinterpret_cast<const uint4*>(x + (size_t)(row + r) * D_ + 256 + lane * 8);
        }
        float f[2][16], sm[2], q[2];
#pragma unroll
        for (int r = 0; r < 2; r++) {
            const uint32_t wv[8] = {xv[r][0].x, xv[r][0].y, xv[r][0].z, xv[r][0].w, xv[r][1].x, xv[r][1].y, xv[r][1].z, xv[r][1].w};
#pragma unroll
            for (int i = 0; i < 8; i++) { f[r][2 * i] = bf_lo(wv[i]); f[r][2 * i + 1] = bf_hi(wv[i]); }
            sm[r] = 0.f;
#pragma unroll
            for (int i = 0; i < 16; i++) sm[r] += f[r][i];
        }
#pragma unroll
        for (int o = 16; o > 0; o >>= 1) { sm[0] += __shfl_xor_sync(0xffffffffu, sm[0], o); sm[1] += __shfl_xor_sync(0xffffffffu, sm[1], o); }
#pragma unroll
        for (int r = 0; r < 2; r++) {
            sm[r] *= (1.0f / D_);
            q[r] = 0.f;
#pragma unroll
            for (int i = 0; i < 16; i++) { float dd = f[r][i] - sm[r]; q[r] += dd * dd; }
        }
#pragma unroll
        for (int o = 16; o > 0; o >>= 1) { q[0] += __shfl_xor_sync(0xffffffffu, q[0], o); q[1] += __shfl_xor_sync(0xffffffffu, q[1], o); }
#pragma unroll
        for (int r = 0; r < 2; r++) {
            const float mb = bf16_round(sm[r]);
            const float vb = bf16_round(q[r] * (1.0f / D_));
            const float den = bf16_round(sqrtf(bf16_round(vb + 1e-5f)));
            uint32_t o[8];
#pragma unroll
            for (int i = 0; i < 8; i++) {
                float a = __fdiv_rn(bf16_round(f[r][2 * i] - mb), den);
                float b = __fdiv_rn(bf16_round(f[r][2 * i + 1] - mb), den);
                o[i] = pack_bf16(a, b);
            }
            __nv_bfloat16* dst = g_xn + (size_t)(row + r) * D_;
            *reinterpret_cast<uint4*>(dst + lane * 8) = make_uint4(o[0], o[1], o[2], o[3]);
            *reinterpret_cast<uint4*>(dst + 256 + lane * 8) = make_uint4(o[4], o[5], o[6], o[7]);
            *reinterpret_cast<uint4*>(&tile[warp * 2 + r][lane * 8]) = make_uint4(o[0], o[1], o[2], o[3]);
            *reinterpret_cast<uint4*>(&tile[warp * 2 + r][256 + lane * 8]) = make_uint4(o[4], o[5], o[6], o[7]);
        }
    } else {
        const int cc_ = warp - 8, dd = blockIdx.x * CV_CH + cc_;
        float4* sc = reinterpret_cast<float4*>(smem + cc_ * CV_EARLY + CV_O_CONST);
        __nv_bfloat16 pr[4][6];
#pragma unroll
        for (int j = 0; j < 4; j++) {
            const size_t off = (size_t)dd * NS_ + lane + 32 * j;
            pr[j][0] = A_re[off]; pr[j][1] = A_im[off]; pr[j][2] = B_re[off]; pr[j][3] = B_im[off]; pr[j][4] = C_re[off]; pr[j][5] = C_im[off];
        }
        const float dt = bf16_round(expf(__bfloat162float(log_dt[dd])));
        float tail = 0.f;
#pragma unroll
        for (int j = 0; j < 4; j++) {
            const float ar = dt * __bfloat162float(pr[j][0]), ai = dt * __bfloat162float(pr[j][1]);
            const cplx db = {dt * __bfloat162float(pr[j][2]), dt * __bfloat162float(pr[j][3])};
            const cplx cc = {__bfloat162float(pr[j][4]), __bfloat162float(pr[j][5])};
            const cplx cb = cmul(cc, db);
            const float ar2 = ar * 1.4426950408889634f, ai2 = ai * 0.15915494309189535f;
            const cplx e8 = cexp_m(ar2, ai2, 8.f), e128 = cexp_m(ar2, ai2, 128.f);
            const cplx cb8 = cmul(cb, e8);
            const cplx e256 = cexp_m(ar2, ai2, 256.f), e512 = cexp_m(ar2, ai2, 512.f), e1024 = cexp_m(ar2, ai2, 1024.f);
            const cplx c256 = cmul(cb, e256), c512 = cmul(cb, e512), c1024 = cmul(cb, e1024);
            const cplx c768 = cmul(c512, e256), c1280 = cmul(c1024, e256), c1536 = cmul(c1024, e512);
            const cplx c1792 = cmul(c1536, e256);
            tail += cmul(c1024, e1024).r;
            float4* c = sc + (lane + 32 * j) * 6;
            c[0] = make_float4(ar2, ai2, cb.r, cb.i);
            c[1] = make_float4(e128.r, e128.i, cb8.r, cb8.i);
            c[2] = make_float4(c256.r, c256.i, e8.r, e8.i);
            c[3] = make_float4(c512.r, c512.i, c768.r, c768.i);
            c[4] = make_float4(c1024.r, c1024.i, c1280.r, c1280.i);
            c[5] = make_float4(c1536.r, c1536.i, c1792.r, c1792.i);
        }
#pragma unroll
        for (int o = 16; o > 0; o >>= 1) tail += __shfl_xor_sync(0xffffffffu, tail, o);
        if (lane == 0) {
            float* kp = reinterpret_cast<float*>(smem + cc_ * CV_EARLY + CV_O_KP);
            kp[640] = tail; kp[648 + 640] = 0.f; kp[1296 + 640] = 0.f;
        }
    }
    __syncthreads();
    if (threadIdx.x == 0) STAMP(0, 3);
#pragma unroll
    for (int rep = 0; rep < 2; rep++) {
        const int c = threadIdx.x + 384 * rep;
        if (c < D_) {
            uint32_t ot[8];
#pragma unroll
            for (int i = 0; i < 8; i++) {
                uint32_t lo = *reinterpret_cast<const uint16_t*>(&tile[2 * i][c]);
                uint32_t hi = *reinterpret_cast<const uint16_t*>(&tile[2 * i + 1][c]);
                ot[i] = lo | (hi << 16);
            }
            __nv_bfloat16* dT = g_xnT + (size_t)c * L_ + blockIdx.x * LN_ROWS;
            *reinterpret_cast<uint4*>(dT) = make_uint4(ot[0], ot[1], ot[2], ot[3]);
            *reinterpret_cast<uint4*>(dT + 8) = make_uint4(ot[4], ot[5], ot[6], ot[7]);
        }
    }
    if (threadIdx.x < 336) {
        const int m = threadIdx.x / 112, i = threadIdx.x - m * 112;
        const char* wp = (const char*)(m == 0 ? wg : (m == 1 ? wu : wd));
        asm volatile("prefetch.global.L2 [%0];" ::"l"(wp + ((size_t)blockIdx.x * 112 + i) * 128));
    }
    __syncthreads();
    if (threadIdx.x == 0) STAMP(1, 1);
    {
        float acc[5][4];
#pragma unroll
        for (int i = 0; i < 5; i++) { acc[i][0] = acc[i][1] = acc[i][2] = acc[i][3] = 0.f; }
        const float gf = (float)g;
        const int src4 = ((g & 3) << 2) | t;
#pragma unroll 2
        for (int s = w; s < 32; s += 3) {
            if (s == 17 && threadIdx.x == 352) asm volatile("red.release.gpu.global.add.u32 [%0], 1;" ::"l"(&g_ln_count) : "memory");
            const float4* c = s_const + (s * 4 + t) * 6;
            const float4 k0 = c[0], k1 = c[1], k2 = c[2];
            const float2 k3 = reinterpret_cast<const float2*>(c + 3)[g >> 2];
            const float2 k4 = reinterpret_cast<const float2*>(c + 4)[g >> 1];
            const cplx cb = {k0.z, k0.w}, e128 = {k1.x, k1.y}, cb8 = {k1.z, k1.w}, c256 = {k2.x, k2.y}, e8 = {k2.z, k2.w};
            const cplx c2 = {k3.x, k3.y}, c3 = {k4.x, k4.y};
            const cplx p1 = cexp_m(k0.x, k0.y, gf);
            const cplx p2 = csq(p1), p4 = csq(p2);
            const cplx r16a = csq(csq(p4));
            cplx q4;
            q4.r = __shfl_sync(0xffffffffu, p4.r, src4);
            q4.i = __shfl_sync(0xffffffffu, p4.i, src4);
            const cplx r16b = cmul(r16a, e128);
            const cplx f0a = cmul(cb, p1), f0b = cmul(cb8, p1), f1 = cmul(c256, p2), f2 = cmul(c2, q4);
            cplx f3 = cmul(c3, e8);
            if (!(g & 1)) f3 = c3;
            const uint32_t a0 = to_tf32(r16a.r), a1 = to_tf32(r16b.r), a2 = to_tf32(-r16a.i), a3 = to_tf32(-r16b.i);
            mma_tf32(acc[0], a0, a1, a2, a3, to_tf32(f0a.r), to_tf32(f0a.i));
            mma_tf32(acc[1], a0, a1, a2, a3, to_tf32(f0b.r), to_tf32(f0b.i));
            mma_tf32(acc[2], a0, a1, a2, a3, to_tf32(f1.r), to_tf32(f1.i));
            mma_tf32(acc[3], a0, a1, a2, a3, to_tf32(f2.r), to_tf32(f2.i));
            mma_tf32(acc[4], a0, a1, a2, a3, to_tf32(f3.r), to_tf32(f3.i));
        }
        float* kv = s_kp + w * 648;
#pragma unroll
        for (int hh = 0; hh < 2; hh++) {
            const int i = g + 8 * hh;
            *reinterpret_cast<float2*>(kv + 16 * i + 2 * t) = make_float2(acc[0][2 * hh], acc[0][2 * hh + 1]);
            *reinterpret_cast<float2*>(kv + 16 * i + 8 + 2 * t) = make_float2(acc[1][2 * hh], acc[1][2 * hh + 1]);
            *reinterpret_cast<float2*>(kv + 256 + 8 * i + 2 * t) = make_float2(acc[2][2 * hh], acc[2][2 * hh + 1]);
            *reinterpret_cast<float2*>(kv + 384 + 64 * (t >> 1) + 2 * (t & 1) + 4 * i) = make_float2(acc[3][2 * hh], acc[3][2 * hh + 1]);
            *reinterpret_cast<float2*>(kv + 512 + 32 * t + 2 * i) = make_float2(acc[4][2 * hh], acc[4][2 * hh + 1]);
        }
    }
    named_bar(bar_id, 96);
    if (threadIdx.x == 0) STAMP(1, 2);
#pragma unroll
    for (int i = 0; i < 7; i++) {
        const int idx = tc + 96 * i;
        if (idx < 641) s_kp[idx] = (s_kp[idx] + s_kp[648 + idx]) + s_kp[1296 + idx];
    }
    named_bar(bar_id, 96);
    {
        auto kdir = [&](int l) -> float {
            if (l < 0 || l > 514) return 0.f;
            const int idx = (l < 256) ? l : (l > 512 ? 384 : 128 + ((l + ((l >> 1) & 1)) >> 1));
            return s_kp[idx];
        };
#pragma unroll
        for (int i = 0; i < 6; i++) {
            const int e = tc + 96 * i;
            s_q[e] = pack_bf16(kdir(e - 16), kdir(e - 17));
        }
        if (tc < 64) {
            const int xx = 1008 + tc;
            const float k1024 = s_kp[512];
            s_q4[tc] = pack_bf16((xx == 1027 || xx == 1028) ? k1024 : 0.f, (xx == 1028 || xx == 1029) ? k1024 : 0.f);
        }
#pragma unroll
        for (int i = 0; i < 3; i++) {
            const int e = tc + 96 * i;
            if (e < 256) {
                const int a = e >> 6, ii = (e & 63) - 16;
                const int b = 385 + (a >> 1) + 2 * (a & 1);
                const float v0 = (ii >= 0 && ii < 32) ? s_kp[b + 4 * ii] : 0.f;
                const float v1 = (ii >= 1 && ii < 33) ? s_kp[b + 4 * (ii - 1)] : 0.f;
                s_q2[e] = pack_bf16(v0, v1);
            }
        }
#pragma unroll
        for (int a = 0; a < 2; a++) {
            const int jj = tc - 16;
            const float v0 = (jj >= 0 && jj < 64) ? s_kp[513 + a + 2 * jj] : 0.f;
            const float v1 = (jj >= 1 && jj < 65) ? s_kp[513 + a + 2 * (jj - 1)] : 0.f;
            s_q3[96 * a + tc] = pack_bf16(v0, v1);
        }
    }
    if (threadIdx.x == 0) STAMP(1, 3);
    if (threadIdx.x == 0) {
        unsigned int v = 0;
        for (int spin = 0; spin < (1 << 22); spin++) {
            asm volatile("ld.acquire.gpu.global.u32 %0, [%1];" : "=r"(v) : "l"(&g_ln_count) : "memory");
            if (v >= gridDim.x) break;
        }
    }
    fence_async_smem();
    __syncthreads();
    if (threadIdx.x == 0) STAMP(1, 4);
    prefetch_fn();
    {
        if (tc < 16) *reinterpret_cast<uint4*>(s_u + tc * 8) = make_uint4(0, 0, 0, 0);
        const uint4* src = reinterpret_cast<const uint4*>(g_xnT + (size_t)d * L_);
        uint4 v[3];
#pragma unroll
        for (int i = 0; i < 3; i++) if (tc + 96 * i < 256) v[i] = src[tc + 96 * i];
#pragma unroll
        for (int i = 0; i < 3; i++) if (tc + 96 * i < 256) *reinterpret_cast<uint4*>(s_u + 128 + (tc + 96 * i) * 8) = v[i];
        if (tc < 2) *reinterpret_cast<uint4*>(base + (tc ? CV_O_W5 : CV_O_W3)) = make_uint4(0, 0, 0, 0);
    }
    named_bar(bar_id, 96);
#pragma unroll
    for (int rep = 0; rep < 2; rep++) {
        const int m = tc + 96 * rep;
        float P[30];
        const uint4* up = reinterpret_cast<const uint4*>(s_u + 128 + 8 * m - 24);
        P[0] = 0.f;
#pragma unroll
        for (int c4 = 0; c4 < 4; c4++) {
            const uint4 v = up[c4];
            const uint32_t ww[4] = {v.x, v.y, v.z, v.w};
#pragma unroll
            for (int j = 0; j < 4; j++) {
                const int k = c4 * 8 + 2 * j;
                if (k + 1 <= 29) P[k + 1] = P[k] + bf_lo(ww[j]);
                if (k + 2 <= 29) P[k + 2] = P[k + 1] + bf_hi(ww[j]);
            }
        }
        uint32_t o3[4], o5[4], o7[4], o9[4];
#pragma unroll
        for (int j = 0; j < 4; j++) {
            const int i = 2 * j;
            o3[j] = pack_bf16(P[i + 22] - P[i + 19], P[i + 23] - P[i + 20]);
            o5[j] = pack_bf16(P[i + 19] - P[i + 14], P[i + 20] - P[i + 15]);
            o7[j] = pack_bf16(P[i + 20] - P[i + 13], P[i + 21] - P[i + 14]);
            o9[j] = pack_bf16(P[i + 13] - P[i + 4], P[i + 14] - P[i + 5]);
        }
        *reinterpret_cast<uint4*>(base + CV_O_W3 + 16 + m * 16) = make_uint4(o3[0], o3[1], o3[2], o3[3]);
        *reinterpret_cast<uint4*>(base + CV_O_W5 + 16 + m * 16) = make_uint4(o5[0], o5[1], o5[2], o5[3]);
        if (m < 128) {
            *reinterpret_cast<uint4*>(base + CV_O_W7 + m * 16) = make_uint4(o7[0], o7[1], o7[2], o7[3]);
            *reinterpret_cast<uint4*>(base + CV_O_W9 + m * 16) = make_uint4(o9[0], o9[1], o9[2], o9[3]);
        }
    }
    if (threadIdx.x == 0) STAMP(1, 5);
    named_bar(bar_id, 96);
    if (w == 2) return;
    const int hb = w;
    float acc[16][4];
#pragma unroll
    for (int i = 0; i < 16; i++) { acc[i][0] = acc[i][1] = acc[i][2] = acc[i][3] = 0.f; }
    const uint32_t sb_addr = smem_u32(base);
    const int mi = lane >> 3, rowi = lane & 7;
#pragma unroll 1
    for (int rr = 0; rr < 4; rr++) {
        const int r = 4 * hb + rr;
        uint32_t ub[16][2];
        {
            const uint32_t addr = sb_addr + CV_O_U + (uint32_t)((128 + 16 * (8 * (mi >> 1) + rowi - r) + 8 * (mi & 1)) * 2);
#pragma unroll
            for (int j = 0; j < 16; j += 2) ldsm_x4(addr + (uint32_t)(j * 256), ub[j][0], ub[j][1], ub[j + 1][0], ub[j + 1][1]);
        }
        const uint32_t* qp = s_q + 16 + 16 * r + g - 2 * t;
        uint32_t af[4][3];
#pragma unroll
        for (int q = 0; q < 4; q++) { af[q][0] = qp[128 * q]; af[q][1] = qp[128 * q + 8]; af[q][2] = qp[128 * q - 8]; }
#pragma unroll
        for (int q = 0; q < 4; q++) {
#pragma unroll
            for (int nt = q; nt < 16; nt++) mma_bf16(acc[nt], af[q][0], af[q][1], af[q][2], af[q][0], ub[nt - q][0], ub[nt - q][1]);
        }
        if (r < 2) {
            {
                const uint32_t a0 = qp[512], a1 = qp[520], a2 = qp[504];
#pragma unroll
                for (int nt = 4; nt < 16; nt++) mma_bf16(acc[nt], a0, a1, a2, a0, ub[nt - 4][0], ub[nt - 4][1]);
            }
            {
                const uint32_t* q4p = s_q4 + 16 + 16 * r + g - 2 * t;
                const uint32_t a0 = q4p[0], a1 = q4p[8], a2 = q4p[-8];
#pragma unroll
                for (int nt = 8; nt < 16; nt++) mma_bf16(acc[nt], a0, a1, a2, a0, ub[nt - 8][0], ub[nt - 8][1]);
            }
        }
    }
#pragma unroll 1
    for (int a = hb; a <= 3 * hb; a++) {
        uint32_t bq[7];
        const uint32_t* q2 = s_q2 + a * 64 + 16 + g - 2 * t - 32;
#pragma unroll
        for (int dlt = 3; dlt <= 9; dlt++) bq[dlt - 3] = q2[8 * dlt];
        const uint32_t addr = sb_addr + ((a >> 1) ? CV_O_W5 : CV_O_W3) + (uint32_t)((8 + 16 * (8 * (mi >> 1) + rowi) + 8 * (mi & 1) - 8 * (a & 1)) * 2);
        uint32_t aa[6][4];
#pragma unroll
        for (int kp = 0; kp < 6; kp++) ldsm_x4_t(addr + kp * 512, aa[kp][0], aa[kp][1], aa[kp][2], aa[kp][3]);
#pragma unroll
        for (int kp = 0; kp < 6; kp++) {
#pragma unroll
            for (int dlt = 4; dlt <= 9; dlt++) {
                if (2 * kp + dlt < 16) mma_bf16(acc[2 * kp + dlt], aa[kp][0], aa[kp][1], aa[kp][2], aa[kp][3], bq[dlt - 3], bq[dlt - 4]);
            }
        }
    }
    if (hb == 0) {
#pragma unroll 1
        for (int a = 0; a < 2; a++) {
            uint32_t bq[9];
            const uint32_t* q3 = s_q3 + a * 96 + 16 + g - 2 * t - 64;
#pragma unroll
            for (int dlt = 7; dlt <= 15; dlt++) bq[dlt - 7] = q3[8 * dlt];
            const uint32_t addr = sb_addr + (a ? CV_O_W9 : CV_O_W7) + (uint32_t)((16 * (8 * (mi >> 1) + rowi) + 8 * (mi & 1)) * 2);
            uint32_t aa[4][4];
#pragma unroll
            for (int kp = 0; kp < 4; kp++) ldsm_x4_t(addr + kp * 512, aa[kp][0], aa[kp][1], aa[kp][2], aa[kp][3]);
#pragma unroll
            for (int kp = 0; kp < 4; kp++) {
#pragma unroll
                for (int dlt = 8; dlt <= 15; dlt++) {
                    if (2 * kp + dlt < 16) mma_bf16(acc[2 * kp + dlt], aa[kp][0], aa[kp][1], aa[kp][2], aa[kp][3], bq[dlt - 7], bq[dlt - 8]);
                }
            }
        }
    }
    if (threadIdx.x == 0) STAMP(1, 6);
    named_bar(bar_id, 64);
    {
        float4* xch = reinterpret_cast<float4*>(base + CV_O_W3) + hb * 256;
        if (hb) {
#pragma unroll
            for (int i = 0; i < 8; i++) xch[i * 32 + lane] = make_float4(acc[i][0], acc[i][1], acc[i][2], acc[i][3]);
#pragma unroll
            for (int i = 0; i < 8; i++) { acc[i][0] = acc[8 + i][0]; acc[i][1] = acc[8 + i][1]; acc[i][2] = acc[8 + i][2]; acc[i][3] = acc[8 + i][3]; }
        } else {
#pragma unroll
            for (int i = 0; i < 8; i++) xch[i * 32 + lane] = make_float4(acc[8 + i][0], acc[8 + i][1], acc[8 + i][2], acc[8 + i][3]);
        }
    }
    named_bar(bar_id, 64);
    if (threadIdx.x == 0) STAMP(1, 10);
    {
        const float4* xch = reinterpret_cast<const float4*>(base + CV_O_W3) + (hb ^ 1) * 256 + lane;
        const float dsk = __bfloat162float(p_dsk);
        uint16_t* stg = reinterpret_cast<uint16_t*>(base + CV_O_Q);
        const uint16_t* uu = reinterpret_cast<const uint16_t*>(s_u) + 128;
#pragma unroll
        for (int i = 0; i < 8; i++) {
            const float4 p0 = xch[i * 32];
            const float y[4] = {acc[i][0] + p0.x, acc[i][1] + p0.y, acc[i][2] + p0.z, acc[i][3] + p0.w};
            const int nt = 8 * hb + i;
#pragma unroll
            for (int e = 0; e < 4; e++) {
                const int tau = 16 * (8 * nt + 2 * t + (e & 1)) + g + 8 * (e >> 1);
                const float sv = bf16_round(y[e]) + bf16_round(__uint_as_float((uint32_t)uu[tau] << 16) * dsk);
                stg[tau] = (uint16_t)(__float_as_uint(bf16_round(sv)) >> 16);
            }
        }
        __syncwarp();
        if (threadIdx.x == 0) STAMP(1, 11);
        uint4* dst = reinterpret_cast<uint4*>(g_sT + (size_t)d * L_ + hb * 1024);
        const uint4* srcp = reinterpret_cast<const uint4*>(stg + hb * 1024);
#pragma unroll
        for (int i = 0; i < 4; i++) dst[i * 32 + lane] = srcp[i * 32 + lane];
    }
}

__device__ __forceinline__ uint32_t cluster_rank() { uint32_t r; asm volatile("mov.u32 %0, %%cluster_ctarank;" : "=r"(r)); return r; }
__device__ __forceinline__ void cluster_sync_all() {
    asm volatile("barrier.cluster.arrive.release.aligned;\nbarrier.cluster.wait.acquire.aligned;" ::: "memory");
}
__device__ __forceinline__ void mbar_arrive_remote(uint32_t bar, uint32_t cta) {
    asm volatile("{\n.reg .b32 ra;\nmapa.shared::cluster.u32 ra, %0, %1;\n"
                 "mbarrier.arrive.shared::cluster.b64 _, [ra];\n}\n" ::"r"(bar), "r"(cta) : "memory");
}
__device__ __forceinline__ void tma_load_2d_mc(uint32_t dst, const CUtensorMap* tm, int c0, int c1, uint32_t bar, uint16_t mask) {
    asm volatile(
        "cp.async.bulk.tensor.2d.shared::cluster.global.mbarrier::complete_tx::bytes.multicast::cluster [%0], [%1, {%3, %4}], [%2], %5;"
        ::"r"(dst), "l"((uint64_t)tm), "r"(bar), "r"(c0), "r"(c1), "h"(mask) : "memory");
}
__device__ __forceinline__ void tma_store_2d(const CUtensorMap* tm, uint32_t src, int c0, int c1) {
    asm volatile("cp.async.bulk.tensor.2d.global.shared::cta.bulk_group [%0, {%2, %3}], [%1];"
                 ::"l"((uint64_t)tm), "r"(src), "r"(c0), "r"(c1) : "memory");
}
__device__ __forceinline__ void bulk_commit() { asm volatile("cp.async.bulk.commit_group;" ::: "memory"); }
template <int N> __device__ __forceinline__ void bulk_wait_read() { asm volatile("cp.async.bulk.wait_group.read %0;" ::"n"(N) : "memory"); }
template <int N> __device__ __forceinline__ void bulk_wait() { asm volatile("cp.async.bulk.wait_group %0;" ::"n"(N) : "memory"); }
__device__ __forceinline__ void stmatrix_x4(uint32_t addr, uint32_t r0, uint32_t r1, uint32_t r2, uint32_t r3) {
    asm volatile("stmatrix.sync.aligned.m8n8.x4.shared.b16 [%0], {%1,%2,%3,%4};" ::"r"(addr), "r"(r0), "r"(r1), "r"(r2), "r"(r3) : "memory");
}

constexpr int G1_STAGES = 5;
constexpr int G1_A_BYTES = 8 * 16384;
constexpr int G1_B_STAGE = 16384;
constexpr int G1_STG = 8 * 1024;
constexpr int G1_SMEM = G1_A_BYTES + G1_STAGES * G1_B_STAGE + G1_STG + 1024 + 256;
constexpr int G1_ITERS = 32;

__device__ __forceinline__ void tma_load_3d(uint32_t dst, const CUtensorMap* tm, int c0, int c1, int c2, uint32_t bar) {
    asm volatile(
        "cp.async.bulk.tensor.3d.shared::cluster.global.mbarrier::complete_tx::bytes [%0], [%1, {%3, %4, %5}], [%2];"
        ::"r"(dst), "l"((uint64_t)tm), "r"(bar), "r"(c0), "r"(c1), "r"(c2) : "memory");
}

__device__ __forceinline__ void tma_load_3d_mc(uint32_t dst, const CUtensorMap* tm, int c0, int c1, int c2, uint32_t bar, uint16_t mask) {
    asm volatile(
        "cp.async.bulk.tensor.3d.shared::cluster.global.mbarrier::complete_tx::bytes.multicast::cluster [%0], [%1, {%3, %4, %5}], [%2], %6;"
        ::"r"(dst), "l"((uint64_t)tm), "r"(bar), "r"(c0), "r"(c1), "r"(c2), "h"(mask) : "memory");
}

__device__ __forceinline__ float gelu_tanh(float x) {
    float u = x * (0.7978845608028654f + 0.035677408136300125f * x * x);
    float t; asm("tanh.approx.f32 %0, %1;" : "=f"(t) : "f"(u));
    float hx = 0.5f * x;
    return fmaf(hx, t, hx);
}
__device__ __forceinline__ uint32_t geglu_pair(uint32_t g2, uint32_t u2) {
    uint32_t a = pack_bf16(gelu_tanh(bf_lo(g2)), gelu_tanh(bf_hi(g2)));
    uint32_t r; asm("mul.rn.bf16x2 %0, %1, %2;" : "=r"(r) : "r"(a), "r"(u2));
    return r;
}

constexpr int G2_STAGES = 5;
constexpr int G2_STAGE = 16384 + 16384;
constexpr int G2_XCH = 32768;
constexpr int G2_EPI = 16384 + 16384;
constexpr int G2_SMEM = G2_STAGES * G2_STAGE + G2_XCH + G2_EPI + 1024 + 256;
constexpr int G2_KB = F_ / 64 / 2;

constexpr int MG_BAR_OFF = G2_STAGES * G2_STAGE + G2_XCH + G2_EPI;
constexpr int MG_SMEM = MG_BAR_OFF + 512 + 1024;
static_assert(MG_BAR_OFF == 229376 && G1_A_BYTES + G1_STAGES * G1_B_STAGE + G1_STG <= MG_BAR_OFF, "smem layout");

__device__ __forceinline__ void fence_async_all() { asm volatile("fence.proxy.async;" ::: "memory"); }
__device__ __forceinline__ void spin_until(const unsigned int* p, unsigned int target) {
    unsigned int v = 0;
    for (int spin = 0; spin < (1 << 22); spin++) {
        asm volatile("ld.acquire.gpu.global.u32 %0, [%1];" : "=r"(v) : "l"(p) : "memory");
        if (v >= target) break;
    }
}

struct MegaParams {
    const __nv_bfloat16 *x, *A_re, *A_im, *B_re, *B_im, *C_re, *C_im, *log_dt, *Dskip, *wg, *wu, *wd;
};

__global__ void __launch_bounds__(384, 1) mega_kernel(const __grid_constant__ MegaParams P,
                                                       const __grid_constant__ CUtensorMap tm_xn,
                                                       const __grid_constant__ CUtensorMap tm_wg4,
                                                       const __grid_constant__ CUtensorMap tm_wu4,
                                                       const __grid_constant__ CUtensorMap tm_wg3,
                                                       const __grid_constant__ CUtensorMap tm_wu3,
                                                       const __grid_constant__ CUtensorMap tm_h,
                                                       const __grid_constant__ CUtensorMap tm_wd,
                                                       const __grid_constant__ CUtensorMap tm_x,
                                                       const __grid_constant__ CUtensorMap tm_sT,
                                                       const __grid_constant__ CUtensorMap tm_out) {
    if (threadIdx.x == 0) STAMP(1, 0);
    extern __shared__ uint8_t smem_raw[];
    const uint32_t sraw = smem_u32(smem_raw);
    const uint32_t sbase = (sraw + 1023) & ~1023u;
    uint8_t* smem = smem_raw + (sbase - sraw);
    const int warp = threadIdx.x >> 5, lane = threadIdx.x & 31;
    const uint32_t sA = sbase, sB = sbase + G1_A_BYTES, sStg = sB + G1_STAGES * G1_B_STAGE;
    const uint32_t sXch = sbase + G2_STAGES * G2_STAGE, sX = sXch + G2_XCH, sS = sX + 16384;
    const uint32_t sBar = sbase + MG_BAR_OFF;
    const uint32_t bar_a = sBar, bar_full = sBar + 64, bar_empty = bar_full + 8 * G1_STAGES;
    const uint32_t bar_full2 = bar_empty + 8 * G1_STAGES, bar_empty2 = bar_full2 + 8 * G2_STAGES;
    const uint32_t bar_epi = bar_empty2 + 8 * G2_STAGES, bar_xch = bar_epi + 8, bar_g1done = bar_xch + 8, bar_g1mma = bar_g1done + 8, bar_peer = bar_g1mma + 8;
    const uint32_t kh = blockIdx.x & 1;
    const int rb1 = ((blockIdx.x >> 4) << 1) + (int)kh, cj = (blockIdx.x >> 1) & 7;
    const int rb = blockIdx.x >> 3;
    const int nb = (blockIdx.x >> 1) & 3;
    const int col_fin = nb * 128 + kh * 64;

    if (threadIdx.x == 0) {
        for (int i = 0; i < 8; i++) mbar_init(bar_a + 8 * i, 1);
        for (int i = 0; i < G1_STAGES; i++) { mbar_init(bar_full + 8 * i, 1); mbar_init(bar_empty + 8 * i, 16); }
        for (int i = 0; i < G2_STAGES; i++) { mbar_init(bar_full2 + 8 * i, 1); mbar_init(bar_empty2 + 8 * i, 8); }
        mbar_init(bar_epi, 1);
        mbar_init(bar_xch, 1);
        mbar_init(bar_g1done, 8);
        mbar_init(bar_g1mma, 8);
        mbar_init(bar_peer, 1);
        asm volatile("fence.mbarrier_init.release.cluster;" ::: "memory");
        mbar_expect_tx(bar_xch, G2_XCH);
    }
    if (warp == 11 && lane == 0) {
        prefetch_tmap(&tm_wg4); prefetch_tmap(&tm_wu4); prefetch_tmap(&tm_xn); prefetch_tmap(&tm_wg3); prefetch_tmap(&tm_wu3);
        prefetch_tmap(&tm_wd); prefetch_tmap(&tm_h); prefetch_tmap(&tm_x); prefetch_tmap(&tm_sT); prefetch_tmap(&tm_out);
    }
    asm volatile("barrier.cluster.arrive.release.aligned;" ::: "memory");

    auto g1_prefetch = [&]() {
        if (warp == 8 && lane == 0) {
            fence_async_all();
            mbar_expect_tx(bar_full, 16384);
            tma_load_3d(sB, &tm_wg4, 0, 0, cj * 7, bar_full);
            tma_load_3d(sB + 8192, &tm_wu4, 0, 0, cj * 7, bar_full);
            for (int k = 0; k < 8; k++) {
                mbar_expect_tx(bar_a + 8 * k, 16384);
                tma_load_2d(sA + k * 16384, &tm_xn, k * 64, rb1 * 128, bar_a + 8 * k);
            }
        }
    };
    front_phase(g1_prefetch, smem, P.x, P.A_re, P.A_im, P.B_re, P.B_im, P.C_re, P.C_im, P.log_dt, P.Dskip, P.wg, P.wu, P.wd);
    fence_async_smem();
    asm volatile("barrier.cluster.wait.acquire.aligned;" ::: "memory");
    __syncthreads();
    if (threadIdx.x == 352) mbar_arrive_remote(bar_peer, kh ^ 1);
    if (threadIdx.x == 0) STAMP(1, 7);

    if (warp >= 8) {
        asm volatile("setmaxnreg.dec.sync.aligned.u32 40;");
        if (warp == 11) {
            if (lane == 0) asm volatile("red.release.gpu.global.add.u32 [%0], 1;" ::"l"(&g_conv_count) : "memory");
            named_bar(3, 288);
            if (lane == 0) asm volatile("red.release.gpu.global.add.u32 [%0], 1;" ::"l"(&g_h_count[rb1]) : "memory");
            named_bar(9, 288);
            if (lane == 0) asm volatile("red.release.gpu.global.add.u32 [%0], 1;" ::"l"(&g_h_count[16 + rb1]) : "memory");
        } else if (lane == 0) {
            const int pw = warp - 8;
            mbar_wait(bar_peer, 0);
            for (int it = 1 + pw; it < G1_ITERS; it += 3) {
                const int s = it % G1_STAGES, kb = it & 15;
                if (it >= G1_STAGES) mbar_wait(bar_empty + 8 * s, ((it / G1_STAGES) - 1) & 1);
                const uint32_t dst = sB + s * G1_B_STAGE;
                if (it < 16) {
                    mbar_expect_tx(bar_full + 8 * s, 16384);
                    tma_load_3d_mc(dst + kh * 8192, kh ? &tm_wu4 : &tm_wg4, 0, kb * 32, cj * 7, bar_full + 8 * s, 3);
                } else {
                    mbar_expect_tx(bar_full + 8 * s, 12288);
                    tma_load_3d_mc(dst + kh * 6144, kh ? &tm_wu3 : &tm_wg3, 0, kb * 32, cj * 7 + 4, bar_full + 8 * s, 3);
                }
            }
            const int k0 = kh * G2_KB;
            auto kblk = [&](int it) -> int {
                const unsigned long long tab = 0xDCA96532B87410ull;
                return k0 + (int)((tab >> (4 * it)) & 15);
            };
            mbar_wait(bar_g1mma, 0);
            if (pw == 2) {
                mbar_expect_tx(bar_epi, G2_EPI);
                tma_load_2d(sX, &tm_x, col_fin, rb * 128, bar_epi);
            }
            spin_until(&g_h_count[rb], 8);
            fence_async_all();
            if (pw == 0) STAMP(3, 1);
            for (int it = pw; it < G2_KB; it += 3) {
                const int s = (it + 1) % G2_STAGES;
                if (it == 4) mbar_wait(bar_g1done, 0);
                if (it >= G2_STAGES) mbar_wait(bar_empty2 + 8 * s, ((it / G2_STAGES) - 1) & 1);
                if (it >= 6 && it < 9) { spin_until(&g_h_count[16 + rb], 8); fence_async_all(); }
                mbar_expect_tx(bar_full2 + 8 * s, G2_STAGE);
                const int kb = kblk(it);
                tma_load_3d(sbase + s * G2_STAGE + 16384, &tm_wd, 0, kb * 64, nb * 2, bar_full2 + 8 * s);
                tma_load_2d(sbase + s * G2_STAGE, &tm_h, kb * 64, rb * 128, bar_full2 + 8 * s);
                if (it == 2) {
                    spin_until(&g_conv_count, gridDim.x);
                    fence_async_all();
                    tma_load_2d(sS, &tm_sT, rb * 128, col_fin, bar_epi);
                    tma_load_2d(sS + 8192, &tm_sT, rb * 128 + 64, col_fin, bar_epi);
                }
            }
        }
    } else {
        asm volatile("setmaxnreg.inc.sync.aligned.u32 232;");
        const int wg = __shfl_sync(0xffffffffu, (int)(threadIdx.x >> 7), 0);
        {
        float r[160];
        const int row0 = rb1 * 128 + wg * 64 + (warp & 3) * 16;
        const uint64_t descA = make_desc(sA + wg * 8192, 16, 1024);
        const uint64_t descB = make_desc(sB, 2048, 512, 2);
        const uint32_t stg = sStg + warp * 1024;
        const uint32_t st_off = (uint32_t)(((lane & 7) + ((lane >> 3) & 1) * 8) * 32 + (lane >> 4) * 16);
        __nv_bfloat16* hrow = g_h + (size_t)(row0 + (lane >> 1)) * F_ + (lane & 1) * 8 + cj * 224;
#pragma unroll
        for (int kb = 0; kb < 16; kb++) {
            const int it = kb, s = it % G1_STAGES;
            if ((kb & 1) == 0) mbar_wait(bar_a + 8 * (kb >> 1), 0);
            mbar_wait(bar_full + 8 * s, (it / G1_STAGES) & 1);
            if (threadIdx.x == 0 && (it & 7) == 0) STAMP(2, 2 + it / 8);
            wgmma_fence();
            const uint64_t da = descA + (uint64_t)(((kb >> 1) * 16384 + (kb & 1) * 64) >> 4);
            const uint64_t db = descB + (uint64_t)((s * G1_B_STAGE) >> 4);
            wgmma_n256_k32(r, da, da + 2, db, db + 64, kb != 0);
            wgmma_commit();
            if (kb > 0) {
                wgmma_wait<1>();
                if (lane < 2) mbar_arrive_remote(bar_empty + 8 * ((it - 1) % G1_STAGES), lane);
            }
        }
        wgmma_wait<0>();
        if (lane < 2) mbar_arrive_remote(bar_empty + 8 * (15 % G1_STAGES), lane);
#pragma unroll
        for (int i = 0; i < 32; i++) r[128 + i] = __uint_as_float(pack_bf16(r[2 * i], r[2 * i + 1]));
#pragma unroll
        for (int i = 31; i >= 0; i--) r[96 + i] = __uint_as_float(pack_bf16(r[64 + 2 * i], r[65 + 2 * i]));
        uint32_t eo[4];
        uint4 pv = make_uint4(0, 0, 0, 0);
#pragma unroll
        for (int kb = 0; kb < 16; kb++) {
            const int it = 16 + kb, s = it % G1_STAGES;
            mbar_wait(bar_full + 8 * s, (it / G1_STAGES) & 1);
            if (threadIdx.x == 0 && (it & 7) == 0) STAMP(2, 2 + it / 8);
            wgmma_fence();
            const uint64_t da = descA + (uint64_t)(((kb >> 1) * 16384 + (kb & 1) * 64) >> 4);
            const uint64_t db = descB + (uint64_t)((s * G1_B_STAGE) >> 4);
            wgmma_n192(r, da, db, kb != 0);
            if (kb < 8) {
                eo[0] = geglu_pair(__float_as_uint(r[128 + 4 * kb]), __float_as_uint(r[96 + 4 * kb]));
                eo[1] = geglu_pair(__float_as_uint(r[129 + 4 * kb]), __float_as_uint(r[97 + 4 * kb]));
            }
            wgmma_n192(r, da + 2, db + 64, 1);
            wgmma_commit();
            if (kb >= 2 && kb < 10) *reinterpret_cast<uint4*>(hrow + (kb - 2) * 16) = pv;
            if (kb >= 1 && kb < 9) {
                __syncwarp();
                asm volatile("ld.shared.v4.u32 {%0,%1,%2,%3}, [%4];" : "=r"(pv.x), "=r"(pv.y), "=r"(pv.z), "=r"(pv.w)
                             : "r"(stg + ((kb - 1) & 1) * 512 + lane * 16));
            }
            if (kb < 8) {
                eo[2] = geglu_pair(__float_as_uint(r[130 + 4 * kb]), __float_as_uint(r[98 + 4 * kb]));
                eo[3] = geglu_pair(__float_as_uint(r[131 + 4 * kb]), __float_as_uint(r[99 + 4 * kb]));
                stmatrix_x4(stg + (kb & 1) * 512 + st_off, eo[0], eo[1], eo[2], eo[3]);
            }
            if (kb == 9) asm volatile("bar.arrive 3, 288;" ::: "memory");
            if (kb > 0 && it - 1 + G1_STAGES < G1_ITERS) {
                wgmma_wait<1>();
                if (lane < 2) mbar_arrive_remote(bar_empty + 8 * ((it - 1) % G1_STAGES), lane);
            }
        }
        wgmma_wait<0>();
        fence_async_smem();
        __syncwarp();
        if (lane == 0) mbar_arrive(bar_g1mma);
        if (threadIdx.x == 0) STAMP(2, 6);
        {
            uint32_t o[24];
#pragma unroll
            for (int i = 0; i < 24; i++) o[i] = geglu_pair(pack_bf16(r[2 * i], r[2 * i + 1]), pack_bf16(r[48 + 2 * i], r[49 + 2 * i]));
            named_bar(1 + wg, 128);
            const uint32_t fbuf = sA + ((warp & 3) >> 1) * 16384 + wg * 8192 + (warp & 1) * 4096;
#pragma unroll
            for (int jj = 0; jj < 6; jj++) stmatrix_x4(fbuf + jj * 512 + st_off, o[4 * jj], o[4 * jj + 1], o[4 * jj + 2], o[4 * jj + 3]);
            __syncwarp();
            uint4 v[6];
#pragma unroll
            for (int jj = 0; jj < 6; jj++)
                asm volatile("ld.shared.v4.u32 {%0,%1,%2,%3}, [%4];" : "=r"(v[jj].x), "=r"(v[jj].y), "=r"(v[jj].z), "=r"(v[jj].w)
                             : "r"(fbuf + jj * 512 + lane * 16));
#pragma unroll
            for (int jj = 0; jj < 6; jj++) *reinterpret_cast<uint4*>(hrow + 128 + jj * 16) = v[jj];
        }
        }
        fence_async_smem();
        __syncwarp();
        if (lane == 0) mbar_arrive(bar_g1done);
        asm volatile("bar.arrive 9, 288;" ::: "memory");
        if (threadIdx.x == 0) STAMP(2, 7);
        {
        const int g = lane >> 2, t = lane & 3;
        float acc[64];
        const uint64_t descA2 = make_desc(sbase + wg * 8192, 16, 1024);
        const uint64_t descB2 = make_desc(sbase + 16384, 8192, 1024);
#pragma unroll
        for (int it = 0; it < G2_KB; it++) {
            const int s = (it + 1) % G2_STAGES;
            mbar_wait(bar_full2 + 8 * s, (it / G2_STAGES) & 1);
            if (threadIdx.x == 0 && (it == 0 || it == 7)) STAMP(3, 2 + it / 7);
            wgmma_fence();
            {
                const uint64_t da = descA2 + (uint64_t)((s * G2_STAGE) >> 4);
                const uint64_t db = descB2 + (uint64_t)((s * G2_STAGE) >> 4);
                wgmma_n128_k64(acc, da, da + 2, da + 4, da + 6, db, db + 128, db + 256, db + 384, it != 0);
            }
            wgmma_commit();
            if (it > 0 && it - 1 + G2_STAGES < G2_KB) {
                wgmma_wait<1>();
                if (lane == 0) mbar_arrive(bar_empty2 + 8 * (it % G2_STAGES));
            }
        }
        const int lr = wg * 64 + (warp & 3) * 16 + g;
        uint32_t xv[16], sv[16];
        mbar_wait(bar_epi, 0);
#pragma unroll
        for (int j = 0; j < 8; j++) {
#pragma unroll
            for (int hh = 0; hh < 2; hh++) {
                const int r = lr + 8 * hh;
                asm volatile("ld.shared.u32 %0, [%1];" : "=r"(xv[2 * j + hh]) : "r"(sX + r * 128 + ((j ^ (r & 7)) << 4) + 4 * t));
                const int c0 = 8 * j + 2 * t;
                const uint32_t sa = sS + (r >> 6) * 8192 + (((r & 63) >> 3) << 4) + (r & 7) * 2;
                uint16_t s0r, s1r;
                asm volatile("ld.shared.u16 %0, [%1];" : "=h"(s0r) : "r"((sa + c0 * 128) ^ ((c0 & 7) << 4)));
                asm volatile("ld.shared.u16 %0, [%1];" : "=h"(s1r) : "r"((sa + (c0 + 1) * 128) ^ (((c0 + 1) & 7) << 4)));
                sv[2 * j + hh] = (uint32_t)s0r | ((uint32_t)s1r << 16);
            }
        }
        wgmma_wait<0>();
        if (threadIdx.x == 0) STAMP(3, 4);
        {
            uint32_t remote, rbar;
            asm volatile("mapa.shared::cluster.u32 %0, %1, %2;" : "=r"(remote) : "r"(sXch + threadIdx.x * 16), "r"(kh ^ 1));
            asm volatile("mapa.shared::cluster.u32 %0, %1, %2;" : "=r"(rbar) : "r"(bar_xch), "r"(kh ^ 1));
            if (kh == 0) {
#pragma unroll
                for (int i = 0; i < 8; i++)
                    asm volatile("st.async.shared::cluster.mbarrier::complete_tx::bytes.v4.f32 [%0], {%1,%2,%3,%4}, [%5];" ::"r"(remote + i * 4096),
                                 "f"(acc[32 + 4 * i]), "f"(acc[33 + 4 * i]), "f"(acc[34 + 4 * i]), "f"(acc[35 + 4 * i]), "r"(rbar) : "memory");
            } else {
#pragma unroll
                for (int i = 0; i < 8; i++)
                    asm volatile("st.async.shared::cluster.mbarrier::complete_tx::bytes.v4.f32 [%0], {%1,%2,%3,%4}, [%5];" ::"r"(remote + i * 4096),
                                 "f"(acc[4 * i]), "f"(acc[1 + 4 * i]), "f"(acc[2 + 4 * i]), "f"(acc[3 + 4 * i]), "r"(rbar) : "memory");
#pragma unroll
                for (int i = 0; i < 32; i++) acc[i] = acc[32 + i];
            }
        }
        if (threadIdx.x == 0) STAMP(3, 6);
        mbar_wait(bar_xch, 0);
        if (threadIdx.x == 0) STAMP(3, 7);
#pragma unroll
        for (int j = 0; j < 8; j++) {
            float4 o;
            asm volatile("ld.shared.v4.f32 {%0,%1,%2,%3}, [%4];" : "=f"(o.x), "=f"(o.y), "=f"(o.z), "=f"(o.w) : "r"(sXch + threadIdx.x * 16 + j * 4096));
            acc[4 * j] += o.x; acc[4 * j + 1] += o.y; acc[4 * j + 2] += o.z; acc[4 * j + 3] += o.w;
        }
#pragma unroll
        for (int i = 0; i < 16; i++) {
            float f0 = bf16_round(acc[2 * i]), f1 = bf16_round(acc[2 * i + 1]);
            float g0 = bf16_round(__fdividef(f0, 1.0f + __expf(-f0)));
            float g1 = bf16_round(__fdividef(f1, 1.0f + __expf(-f1)));
            float o0 = bf_lo(xv[i]) + bf16_round(bf_lo(sv[i]) * g0);
            float o1 = bf_hi(xv[i]) + bf16_round(bf_hi(sv[i]) * g1);
            xv[i] = pack_bf16(o0, o1);
        }
#pragma unroll
        for (int j = 0; j < 8; j++) {
#pragma unroll
            for (int hh = 0; hh < 2; hh++) {
                const int r = lr + 8 * hh;
                asm volatile("st.shared.u32 [%0], %1;" ::"r"(sX + r * 128 + ((j ^ (r & 7)) << 4) + 4 * t), "r"(xv[2 * j + hh]) : "memory");
            }
        }
        if (threadIdx.x == 0) STAMP(3, 9);
        fence_async_smem();
        __syncwarp();
        if (lane == 0) {
            tma_store_2d(&tm_out, sX + (wg * 64 + (warp & 3) * 16) * 128, col_fin, rb * 128 + wg * 64 + (warp & 3) * 16);
            bulk_commit();
            bulk_wait_read<0>();
        }
        }
        if (threadIdx.x == 0) STAMP(3, 5);
        named_bar(4, 256);
        if (threadIdx.x == 0) {
            const unsigned int old = atomicAdd(&g_done_count, 1u);
            if (old == gridDim.x - 1) {
                g_ln_count = 0; g_conv_count = 0; g_done_count = 0;
                for (int i = 0; i < 32; i++) g_h_count[i] = 0;
            }
        }
    }
}

typedef CUresult (*EncodeFn)(CUtensorMap*, CUtensorMapDataType, cuuint32_t, void*, const cuuint64_t*, const cuuint64_t*,
                             const cuuint32_t*, const cuuint32_t*, CUtensorMapInterleave, CUtensorMapSwizzle,
                             CUtensorMapL2promotion, CUtensorMapFloatOOBfill);

void make_map(EncodeFn fn, CUtensorMap* m, const void* ptr, uint64_t inner, uint64_t outer, uint32_t box_in, uint32_t box_out,
              CUtensorMapSwizzle swz = CU_TENSOR_MAP_SWIZZLE_128B) {
    cuuint64_t dims[2] = {inner, outer};
    cuuint64_t strides[1] = {inner * 2};
    cuuint32_t box[2] = {box_in, box_out};
    cuuint32_t es[2] = {1, 1};
    fn(m, CU_TENSOR_MAP_DATA_TYPE_BFLOAT16, 2, const_cast<void*>(ptr), dims, strides, box, es, CU_TENSOR_MAP_INTERLEAVE_NONE,
       swz, CU_TENSOR_MAP_L2_PROMOTION_L2_256B, CU_TENSOR_MAP_FLOAT_OOB_FILL_NONE);
}
void make_map3(EncodeFn fn, CUtensorMap* m, const void* ptr, uint64_t cols, uint64_t rows, uint32_t atom, uint32_t box_rows,
               uint32_t box_atoms, CUtensorMapSwizzle swz) {
    cuuint64_t dims[3] = {atom, rows, cols / atom};
    cuuint64_t strides[2] = {cols * 2, (cuuint64_t)atom * 2};
    cuuint32_t box[3] = {atom, box_rows, box_atoms};
    cuuint32_t es[3] = {1, 1, 1};
    fn(m, CU_TENSOR_MAP_DATA_TYPE_BFLOAT16, 3, const_cast<void*>(ptr), dims, strides, box, es, CU_TENSOR_MAP_INTERLEAVE_NONE,
       swz, CU_TENSOR_MAP_L2_PROMOTION_L2_256B, CU_TENSOR_MAP_FLOAT_OOB_FILL_NONE);
}

template <typename... Args>
void launch_pdl(void (*kern)(Args...), int grid, int block, int smem, bool pdl, int cluster, Args... args) {
    cudaLaunchConfig_t cfg = {};
    cfg.gridDim = dim3(grid); cfg.blockDim = dim3(block); cfg.dynamicSmemBytes = smem; cfg.stream = cudaStreamPerThread;
    cudaLaunchAttribute at[2];
    int n = 0;
    if (pdl) {
        at[n].id = cudaLaunchAttributeProgrammaticStreamSerialization;
        at[n].val.programmaticStreamSerializationAllowed = 1;
        n++;
    }
    if (cluster > 1) {
        at[n].id = cudaLaunchAttributeClusterDimension;
        at[n].val.clusterDim.x = cluster; at[n].val.clusterDim.y = 1; at[n].val.clusterDim.z = 1;
        n++;
    }
    cfg.attrs = at; cfg.numAttrs = n;
    cudaLaunchKernelEx(&cfg, kern, args...);
}

}

extern "C" void kernel_launch(void* const* d_in, const int* in_sizes, int n_in, void* d_out, int out_size) {
    const __nv_bfloat16* x = (const __nv_bfloat16*)d_in[0];
    const __nv_bfloat16* A_re = (const __nv_bfloat16*)d_in[1];
    const __nv_bfloat16* A_im = (const __nv_bfloat16*)d_in[2];
    const __nv_bfloat16* B_re = (const __nv_bfloat16*)d_in[3];
    const __nv_bfloat16* B_im = (const __nv_bfloat16*)d_in[4];
    const __nv_bfloat16* C_re = (const __nv_bfloat16*)d_in[5];
    const __nv_bfloat16* C_im = (const __nv_bfloat16*)d_in[6];
    const __nv_bfloat16* log_dt = (const __nv_bfloat16*)d_in[7];
    const __nv_bfloat16* Dskip = (const __nv_bfloat16*)d_in[8];
    const __nv_bfloat16* wg = (const __nv_bfloat16*)d_in[10];
    const __nv_bfloat16* wu = (const __nv_bfloat16*)d_in[11];
    const __nv_bfloat16* wd = (const __nv_bfloat16*)d_in[12];
    __nv_bfloat16* out = (__nv_bfloat16*)d_out;

    static bool init = false;
    static CUtensorMap tm_xn, tm_wg4, tm_wu4, tm_wg3, tm_wu3, tm_hst, tm_hst96, tm_h, tm_wd, tm_x, tm_sT, tm_out;
    static const void* last_ptrs[5] = {nullptr, nullptr, nullptr, nullptr, nullptr};
    if (!init || last_ptrs[0] != wg || last_ptrs[1] != wu || last_ptrs[2] != wd || last_ptrs[3] != x || last_ptrs[4] != out) {
        void* fnp = nullptr;
        cudaDriverEntryPointQueryResult qres;
        cudaGetDriverEntryPoint("cuTensorMapEncodeTiled", &fnp, cudaEnableDefault, &qres);
        EncodeFn fn = (EncodeFn)fnp;
        void *p_xn, *p_h, *p_sT;
        cudaGetSymbolAddress(&p_xn, g_xn);
        cudaGetSymbolAddress(&p_h, g_h);
        cudaGetSymbolAddress(&p_sT, g_sT);
        make_map(fn, &tm_xn, p_xn, D_, L_, 64, 128);
        make_map3(fn, &tm_wg4, wg, F_, D_, 32, 32, 4, CU_TENSOR_MAP_SWIZZLE_64B);
        make_map3(fn, &tm_wu4, wu, F_, D_, 32, 32, 4, CU_TENSOR_MAP_SWIZZLE_64B);
        make_map3(fn, &tm_wg3, wg, F_, D_, 32, 32, 3, CU_TENSOR_MAP_SWIZZLE_64B);
        make_map3(fn, &tm_wu3, wu, F_, D_, 32, 32, 3, CU_TENSOR_MAP_SWIZZLE_64B);
        make_map(fn, &tm_hst, p_h, F_, L_, 16, 16, CU_TENSOR_MAP_SWIZZLE_NONE);
        make_map(fn, &tm_hst96, p_h, F_, L_, 96, 16, CU_TENSOR_MAP_SWIZZLE_NONE);
        make_map(fn, &tm_h, p_h, F_, L_, 64, 128);
        make_map3(fn, &tm_wd, wd, D_, F_, 64, 64, 2, CU_TENSOR_MAP_SWIZZLE_128B);
        make_map(fn, &tm_x, x, D_, L_, 64, 128);
        make_map(fn, &tm_sT, p_sT, L_, D_, 64, 64);
        make_map(fn, &tm_out, out, D_, L_, 64, 16);
        cudaFuncSetAttribute(mega_kernel, cudaFuncAttributeMaxDynamicSharedMemorySize, MG_SMEM);
        last_ptrs[0] = wg; last_ptrs[1] = wu; last_ptrs[2] = wd; last_ptrs[3] = x; last_ptrs[4] = out;
        init = true;
    }
    MegaParams P = {x, A_re, A_im, B_re, B_im, C_re, C_im, log_dt, Dskip, wg, wu, wd};
    launch_pdl(mega_kernel, 128, 384, MG_SMEM, false, 2, P, tm_xn, tm_wg4, tm_wu4, tm_wg3, tm_wu3, tm_h, tm_wd, tm_x, tm_sT, tm_out);
}
```

```cpp
#include <cuda_runtime.h>
#include <cuda_bf16.h>
#include <cuda.h>
#include <stdint.h>

namespace {

constexpr int L_ = 2048, D_ = 512, NS_ = 128, F_ = 1792;

__device__ __align__(1024) __nv_bfloat16 g_xn[L_ * D_];
__device__ __align__(1024) __nv_bfloat16 g_xnT[D_ * L_];
__device__ __align__(1024) __nv_bfloat16 g_sT[D_ * L_];
__device__ __align__(1024) __nv_bfloat16 g_h[L_ * F_];
__device__ unsigned int g_ln_count, g_conv_count, g_done_count, g_h_count[32];

#define STAMP(k, i)

__device__ __forceinline__ uint32_t smem_u32(const void* p) { return (uint32_t)__cvta_generic_to_shared(p); }
__device__ __forceinline__ void pdl_wait() { asm volatile("griddepcontrol.wait;" ::: "memory"); }
__device__ __forceinline__ void pdl_launch() { asm volatile("griddepcontrol.launch_dependents;" ::: "memory"); }

__device__ __forceinline__ void mbar_init(uint32_t bar, uint32_t cnt) {
    asm volatile("mbarrier.init.shared::cta.b64 [%0], %1;" ::"r"(bar), "r"(cnt) : "memory");
}
__device__ __forceinline__ void mbar_expect_tx(uint32_t bar, uint32_t bytes) {
    asm volatile("mbarrier.arrive.expect_tx.shared::cta.b64 _, [%0], %1;" ::"r"(bar), "r"(bytes) : "memory");
}
__device__ __forceinline__ void mbar_arrive(uint32_t bar) {
    asm volatile("mbarrier.arrive.shared::cta.b64 _, [%0];" ::"r"(bar) : "memory");
}
__device__ __forceinline__ void mbar_wait(uint32_t bar, uint32_t parity) {
    asm volatile(
        "{\n.reg .pred p;\n"
        "WAIT_LOOP:\n"
        "mbarrier.try_wait.parity.shared::cta.b64 p, [%0], %1;\n"
        "@p bra WAIT_DONE;\n"
        "bra WAIT_LOOP;\n"
        "WAIT_DONE:\n}\n" ::"r"(bar), "r"(parity) : "memory");
}
__device__ __forceinline__ void tma_load_2d(uint32_t dst, const CUtensorMap* tm, int c0, int c1, uint32_t bar) {
    asm volatile(
        "cp.async.bulk.tensor.2d.shared::cluster.global.mbarrier::complete_tx::bytes [%0], [%1, {%3, %4}], [%2];"
        ::"r"(dst), "l"((uint64_t)tm), "r"(bar), "r"(c0), "r"(c1) : "memory");
}
__device__ __forceinline__ void prefetch_tmap(const CUtensorMap* tm) {
    asm volatile("prefetch.tensormap [%0];" ::"l"((uint64_t)tm) : "memory");
}
__device__ __forceinline__ uint64_t make_desc(uint32_t addr, uint32_t lbo, uint32_t sbo, uint64_t mode = 1) {
    uint64_t d = 0;
    d |= (uint64_t)((addr & 0x3FFFF) >> 4);
    d |= (uint64_t)((lbo >> 4) & 0x3FFF) << 16;
    d |= (uint64_t)((sbo >> 4) & 0x3FFF) << 32;
    d |= mode << 62;
    return d;
}
__device__ __forceinline__ void fence_async_smem() { asm volatile("fence.proxy.async.shared::cta;" ::: "memory"); }
__device__ __forceinline__ void wgmma_fence() { asm volatile("wgmma.fence.sync.aligned;" ::: "memory"); }
__device__ __forceinline__ void wgmma_commit() { asm volatile("wgmma.commit_group.sync.aligned;" ::: "memory"); }
template <int N> __device__ __forceinline__ void wgmma_wait() {
    asm volatile("wgmma.wait_group.sync.aligned %0;" ::"n"(N) : "memory");
}

#define R8(a, i) "+f"(a[i + 0]), "+f"(a[i + 1]), "+f"(a[i + 2]), "+f"(a[i + 3]), "+f"(a[i + 4]), "+f"(a[i + 5]), "+f"(a[i + 6]), "+f"(a[i + 7])

__device__ __forceinline__ void wgmma_n256_k32(float* a, uint64_t da0, uint64_t da1, uint64_t db0, uint64_t db1, int scale_d) {
    asm volatile(
        "{\n.reg .pred p;\nsetp.ne.b32 p, %132, 0;\n"
        "wgmma.mma_async.sync.aligned.m64n256k16.f32.bf16.bf16 {%0,%1,%2,%3,%4,%5,%6,%7,%8,%9,%10,%11,%12,%13,%14,%15,%16,%17,%18,%19,%20,%21,%22,%23,%24,%25,%26,%27,%28,%29,%30,%31,%32,%33,%34,%35,%36,%37,%38,%39,%40,%41,%42,%43,%44,%45,%46,%47,%48,%49,%50,%51,%52,%53,%54,%55,%56,%57,%58,%59,%60,%61,%62,%63,%64,%65,%66,%67,%68,%69,%70,%71,%72,%73,%74,%75,%76,%77,%78,%79,%80,%81,%82,%83,%84,%85,%86,%87,%88,%89,%90,%91,%92,%93,%94,%95,%96,%97,%98,%99,%100,%101,%102,%103,%104,%105,%106,%107,%108,%109,%110,%111,%112,%113,%114,%115,%116,%117,%118,%119,%120,%121,%122,%123,%124,%125,%126,%127}, %128, %130, p, 1, 1, 0, 1;\n"
        "wgmma.mma_async.sync.aligned.m64n256k16.f32.bf16.bf16 {%0,%1,%2,%3,%4,%5,%6,%7,%8,%9,%10,%11,%12,%13,%14,%15,%16,%17,%18,%19,%20,%21,%22,%23,%24,%25,%26,%27,%28,%29,%30,%31,%32,%33,%34,%35,%36,%37,%38,%39,%40,%41,%42,%43,%44,%45,%46,%47,%48,%49,%50,%51,%52,%53,%54,%55,%56,%57,%58,%59,%60,%61,%62,%63,%64,%65,%66,%67,%68,%69,%70,%71,%72,%73,%74,%75,%76,%77,%78,%79,%80,%81,%82,%83,%84,%85,%86,%87,%88,%89,%90,%91,%92,%93,%94,%95,%96,%97,%98,%99,%100,%101,%102,%103,%104,%105,%106,%107,%108,%109,%110,%111,%112,%113,%114,%115,%116,%117,%118,%119,%120,%121,%122,%123,%124,%125,%126,%127}, %129, %131, 1, 1, 1, 0, 1;\n"
        "}\n"
        : R8(a, 0), R8(a, 8), R8(a, 16), R8(a, 24), R8(a, 32), R8(a, 40), R8(a, 48), R8(a, 56), R8(a, 64), R8(a, 72), R8(a, 80), R8(a, 88), R8(a, 96), R8(a, 104), R8(a, 112), R8(a, 120)
        : "l"(da0), "l"(da1), "l"(db0), "l"(db1), "r"(scale_d));
}
__device__ __forceinline__ void wgmma_n192_k32(float* a, uint64_t da0, uint64_t da1, uint64_t db0, uint64_t db1, int scale_d) {
    asm volatile(
        "{\n.reg .pred p;\nsetp.ne.b32 p, %100, 0;\n"
        "wgmma.mma_async.sync.aligned.m64n192k16.f32.bf16.bf16 {%0,%1,%2,%3,%4,%5,%6,%7,%8,%9,%10,%11,%12,%13,%14,%15,%16,%17,%18,%19,%20,%21,%22,%23,%24,%25,%26,%27,%28,%29,%30,%31,%32,%33,%34,%35,%36,%37,%38,%39,%40,%41,%42,%43,%44,%45,%46,%47,%48,%49,%50,%51,%52,%53,%54,%55,%56,%57,%58,%59,%60,%61,%62,%63,%64,%65,%66,%67,%68,%69,%70,%71,%72,%73,%74,%75,%76,%77,%78,%79,%80,%81,%82,%83,%84,%85,%86,%87,%88,%89,%90,%91,%92,%93,%94,%95}, %96, %98, p, 1, 1, 0, 1;\n"
        "wgmma.mma_async.sync.aligned.m64n192k16.f32.bf16.bf16 {%0,%1,%2,%3,%4,%5,%6,%7,%8,%9,%10,%11,%12,%13,%14,%15,%16,%17,%18,%19,%20,%21,%22,%23,%24,%25,%26,%27,%28,%29,%30,%31,%32,%33,%34,%35,%36,%37,%38,%39,%40,%41,%42,%43,%44,%45,%46,%47,%48,%49,%50,%51,%52,%53,%54,%55,%56,%57,%58,%59,%60,%61,%62,%63,%64,%65,%66,%67,%68,%69,%70,%71,%72,%73,%74,%75,%76,%77,%78,%79,%80,%81,%82,%83,%84,%85,%86,%87,%88,%89,%90,%91,%92,%93,%94,%95}, %97, %99, 1, 1, 1, 0, 1;\n"
        "}\n"
        : R8(a, 0), R8(a, 8), R8(a, 16), R8(a, 24), R8(a, 32), R8(a, 40), R8(a, 48), R8(a, 56), R8(a, 64), R8(a, 72), R8(a, 80), R8(a, 88)
        : "l"(da0), "l"(da1), "l"(db0), "l"(db1), "r"(scale_d));
}
__device__ __forceinline__ void wgmma_n192(float* a, uint64_t da0, uint64_t db0, int scale_d) {
    asm volatile(
        "{\n.reg .pred p;\nsetp.ne.b32 p, %98, 0;\n"
        "wgmma.mma_async.sync.aligned.m64n192k16.f32.bf16.bf16 {%0,%1,%2,%3,%4,%5,%6,%7,%8,%9,%10,%11,%12,%13,%14,%15,%16,%17,%18,%19,%20,%21,%22,%23,%24,%25,%26,%27,%28,%29,%30,%31,%32,%33,%34,%35,%36,%37,%38,%39,%40,%41,%42,%43,%44,%45,%46,%47,%48,%49,%50,%51,%52,%53,%54,%55,%56,%57,%58,%59,%60,%61,%62,%63,%64,%65,%66,%67,%68,%69,%70,%71,%72,%73,%74,%75,%76,%77,%78,%79,%80,%81,%82,%83,%84,%85,%86,%87,%88,%89,%90,%91,%92,%93,%94,%95}, %96, %97, p, 1, 1, 0, 1;\n"
        "}\n"
        : R8(a, 0), R8(a, 8), R8(a, 16), R8(a, 24), R8(a, 32), R8(a, 40), R8(a, 48), R8(a, 56), R8(a, 64), R8(a, 72), R8(a, 80), R8(a, 88)
        : "l"(da0), "l"(db0), "r"(scale_d));
}
__device__ __forceinline__ void wgmma_n128_k64(float* a, uint64_t da0, uint64_t da1, uint64_t da2, uint64_t da3,
                                               uint64_t db0, uint64_t db1, uint64_t db2, uint64_t db3, int scale_d) {
    asm volatile(
        "{\n.reg .pred p;\nsetp.ne.b32 p, %72, 0;\n"
        "wgmma.mma_async.sync.aligned.m64n128k16.f32.bf16.bf16 {%0,%1,%2,%3,%4,%5,%6,%7,%8,%9,%10,%11,%12,%13,%14,%15,%16,%17,%18,%19,%20,%21,%22,%23,%24,%25,%26,%27,%28,%29,%30,%31,%32,%33,%34,%35,%36,%37,%38,%39,%40,%41,%42,%43,%44,%45,%46,%47,%48,%49,%50,%51,%52,%53,%54,%55,%56,%57,%58,%59,%60,%61,%62,%63}, %64, %68, p, 1, 1, 0, 1;\n"
        "wgmma.mma_async.sync.aligned.m64n128k16.f32.bf16.bf16 {%0,%1,%2,%3,%4,%5,%6,%7,%8,%9,%10,%11,%12,%13,%14,%15,%16,%17,%18,%19,%20,%21,%22,%23,%24,%25,%26,%27,%28,%29,%30,%31,%32,%33,%34,%35,%36,%37,%38,%39,%40,%41,%42,%43,%44,%45,%46,%47,%48,%49,%50,%51,%52,%53,%54,%55,%56,%57,%58,%59,%60,%61,%62,%63}, %65, %69, 1, 1, 1, 0, 1;\n"
        "wgmma.mma_async.sync.aligned.m64n128k16.f32.bf16.bf16 {%0,%1,%2,%3,%4,%5,%6,%7,%8,%9,%10,%11,%12,%13,%14,%15,%16,%17,%18,%19,%20,%21,%22,%23,%24,%25,%26,%27,%28,%29,%30,%31,%32,%33,%34,%35,%36,%37,%38,%39,%40,%41,%42,%43,%44,%45,%46,%47,%48,%49,%50,%51,%52,%53,%54,%55,%56,%57,%58,%59,%60,%61,%62,%63}, %66, %70, 1, 1, 1, 0, 1;\n"
        "wgmma.mma_async.sync.aligned.m64n128k16.f32.bf16.bf16 {%0,%1,%2,%3,%4,%5,%6,%7,%8,%9,%10,%11,%12,%13,%14,%15,%16,%17,%18,%19,%20,%21,%22,%23,%24,%25,%26,%27,%28,%29,%30,%31,%32,%33,%34,%35,%36,%37,%38,%39,%40,%41,%42,%43,%44,%45,%46,%47,%48,%49,%50,%51,%52,%53,%54,%55,%56,%57,%58,%59,%60,%61,%62,%63}, %67, %71, 1, 1, 1, 0, 1;\n"
        "}\n"
        : R8(a, 0), R8(a, 8), R8(a, 16), R8(a, 24), R8(a, 32), R8(a, 40), R8(a, 48), R8(a, 56)
        : "l"(da0), "l"(da1), "l"(da2), "l"(da3), "l"(db0), "l"(db1), "l"(db2), "l"(db3), "r"(scale_d));
}

__device__ __forceinline__ float bf16_round(float x) {
    uint32_t p; asm("cvt.rn.bf16x2.f32 %0, %1, %2;" : "=r"(p) : "f"(x), "f"(0.0f));
    return __uint_as_float(p);
}
__device__ __forceinline__ uint32_t pack_bf16(float lo, float hi) {
    __nv_bfloat162 v = __floats2bfloat162_rn(lo, hi);
    return *reinterpret_cast<uint32_t*>(&v);
}
__device__ __forceinline__ float bf_lo(uint32_t v) { return __uint_as_float(v << 16); }
__device__ __forceinline__ float bf_hi(uint32_t v) { return __uint_as_float(v & 0xFFFF0000u); }

struct cplx { float r, i; };
__device__ __forceinline__ cplx cmul(cplx a, cplx b) {
    cplx c; c.r = a.r * b.r - a.i * b.i; c.i = a.r * b.i + a.i * b.r; return c;
}
__device__ __forceinline__ cplx csq(cplx a) {
    cplx c; c.r = a.r * a.r - a.i * a.i; c.i = 2.0f * a.r * a.i; return c;
}
__device__ __forceinline__ cplx cexp_m(float ar2, float ai2, float m) {
    float mag;
    asm("ex2.approx.ftz.f32 %0, %1;" : "=f"(mag) : "f"(ar2 * m));
    float rr = ai2 * m;
    rr -= (rr + 12582912.0f) - 12582912.0f;
    float th = rr * 6.283185307179586f;
    cplx c; c.r = mag * __cosf(th); c.i = mag * __sinf(th);
    return c;
}
__device__ __forceinline__ uint32_t to_tf32(float x) { return __float_as_uint(x) + 0x1000u; }
__device__ __forceinline__ void mma_tf32(float* c, uint32_t a0, uint32_t a1, uint32_t a2, uint32_t a3, uint32_t b0, uint32_t b1) {
    asm volatile("mma.sync.aligned.m16n8k8.row.col.f32.tf32.tf32.f32 {%0,%1,%2,%3}, {%4,%5,%6,%7}, {%8,%9}, {%0,%1,%2,%3};"
                 : "+f"(c[0]), "+f"(c[1]), "+f"(c[2]), "+f"(c[3])
                 : "r"(a0), "r"(a1), "r"(a2), "r"(a3), "r"(b0), "r"(b1));
}
__device__ __forceinline__ void mma_bf16(float* c, uint32_t a0, uint32_t a1, uint32_t a2, uint32_t a3, uint32_t b0, uint32_t b1) {
    asm volatile("mma.sync.aligned.m16n8k16.row.col.f32.bf16.bf16.f32 {%0,%1,%2,%3}, {%4,%5,%6,%7}, {%8,%9}, {%0,%1,%2,%3};"
                 : "+f"(c[0]), "+f"(c[1]), "+f"(c[2]), "+f"(c[3])
                 : "r"(a0), "r"(a1), "r"(a2), "r"(a3), "r"(b0), "r"(b1));
}
__device__ __forceinline__ void named_bar(int id, int n) { asm volatile("bar.sync %0, %1;" ::"r"(id), "r"(n) : "memory"); }
__device__ __forceinline__ void ldsm_x4(uint32_t addr, uint32_t& r0, uint32_t& r1, uint32_t& r2, uint32_t& r3) {
    asm volatile("ldmatrix.sync.aligned.m8n8.x4.shared.b16 {%0,%1,%2,%3}, [%4];" : "=r"(r0), "=r"(r1), "=r"(r2), "=r"(r3) : "r"(addr));
}
__device__ __forceinline__ void ldsm_x4_t(uint32_t addr, uint32_t& r0, uint32_t& r1, uint32_t& r2, uint32_t& r3) {
    asm volatile("ldmatrix.sync.aligned.m8n8.x4.trans.shared.b16 {%0,%1,%2,%3}, [%4];" : "=r"(r0), "=r"(r1), "=r"(r2), "=r"(r3) : "r"(addr));
}

constexpr int CV_CH = 4;
constexpr int CV_O_CONST = 0;
constexpr int CV_O_KP = 12288;
constexpr int CV_EARLY = 12288 + 7776;
constexpr int CV_O_Q = 0;
constexpr int CV_O_Q2 = CV_O_Q + 2304;
constexpr int CV_O_Q3 = CV_O_Q2 + 1024;
constexpr int CV_O_Q4X = CV_O_Q3 + 768;
constexpr int CV_O_W3 = CV_O_Q4X + 256;
constexpr int CV_O_W5 = CV_O_W3 + 3104;
constexpr int CV_O_W7 = CV_O_W5 + 3104;
constexpr int CV_O_W9 = CV_O_W7 + 2048;
constexpr int CV_O_U = CV_O_W9 + 2048;
constexpr int CV_LATE = CV_O_U + 4352;
constexpr int CV_LATE_BASE = 229376 - CV_CH * CV_LATE;
constexpr int CV_TILE_OFF = CV_CH * CV_EARLY;
static_assert(CV_TILE_OFF + 16 * (D_ + 8) * 2 <= CV_LATE_BASE && CV_LATE_BASE >= 131072 + 16384, "front layout");
static_assert(CV_O_W3 >= 4096 && CV_O_U - CV_O_W3 >= 8192 && (CV_LATE % 16) == 0 && (CV_EARLY % 16) == 0, "front layout");

constexpr int LN_ROWS = 16;

template <typename PF>
__device__ __forceinline__ void front_phase(PF prefetch_fn, uint8_t* smem, const __nv_bfloat16* __restrict__ x,
                                            const __nv_bfloat16* __restrict__ A_re, const __nv_bfloat16* __restrict__ A_im,
                                            const __nv_bfloat16* __restrict__ B_re, const __nv_bfloat16* __restrict__ B_im,
                                            const __nv_bfloat16* __restrict__ C_re, const __nv_bfloat16* __restrict__ C_im,
                                            const __nv_bfloat16* __restrict__ log_dt, const __nv_bfloat16* __restrict__ Dskip,
                                            const __nv_bfloat16* __restrict__ wg, const __nv_bfloat16* __restrict__ wu,
                                            const __nv_bfloat16* __restrict__ wd) {
    const int warp = threadIdx.x >> 5, lane = threadIdx.x & 31;
    const int ch = warp / 3, w = warp - 3 * ch, tc = threadIdx.x - 96 * ch;
    const int d = blockIdx.x * CV_CH + ch;
    const int g = lane >> 2, t = lane & 3;
    uint8_t* base = smem + CV_LATE_BASE + ch * CV_LATE;
    float4* s_const = reinterpret_cast<float4*>(smem + ch * CV_EARLY + CV_O_CONST);
    float* s_kp = reinterpret_cast<float*>(smem + ch * CV_EARLY + CV_O_KP);
    uint32_t* s_q = reinterpret_cast<uint32_t*>(base + CV_O_Q);
    uint32_t* s_q2 = reinterpret_cast<uint32_t*>(base + CV_O_Q2);
    uint32_t* s_q3 = reinterpret_cast<uint32_t*>(base + CV_O_Q3);
    uint32_t* s_q4 = reinterpret_cast<uint32_t*>(base + CV_O_Q4X);
    __nv_bfloat16* s_u = reinterpret_cast<__nv_bfloat16*>(base + CV_O_U);
    const int bar_id = 5 + ch;
    const __nv_bfloat16 p_dsk = Dskip[d];
    __nv_bfloat16 (*tile)[D_ + 8] = reinterpret_cast<__nv_bfloat16 (*)[D_ + 8]>(smem + CV_TILE_OFF);

    if (warp < 8) {
        const int row = blockIdx.x * LN_ROWS + warp * 2;
        uint4 xv[2][2];
#pragma unroll
        for (int r = 0; r < 2; r++) {
            xv[r][0] = *reinterpret_cast<const uint4*>(x + (size_t)(row + r) * D_ + lane * 8);
            xv[r][1] = *reinterpret_cast<const uint4*>(x + (size_t)(row + r) * D_ + 256 + lane * 8);
        }
        float f[2][16], sm[2], q[2];
#pragma unroll
        for (int r = 0; r < 2; r++) {
            const uint32_t wv[8] = {xv[r][0].x, xv[r][0].y, xv[r][0].z, xv[r][0].w, xv[r][1].x, xv[r][1].y, xv[r][1].z, xv[r][1].w};
#pragma unroll
            for (int i = 0; i < 8; i++) { f[r][2 * i] = bf_lo(wv[i]); f[r][2 * i + 1] = bf_hi(wv[i]); }
            sm[r] = 0.f;
#pragma unroll
            for (int i = 0; i < 16; i++) sm[r] += f[r][i];
        }
#pragma unroll
        for (int o = 16; o > 0; o >>= 1) { sm[0] += __shfl_xor_sync(0xffffffffu, sm[0], o); sm[1] += __shfl_xor_sync(0xffffffffu, sm[1], o); }
#pragma unroll
        for (int r = 0; r < 2; r++) {
            sm[r] *= (1.0f / D_);
            q[r] = 0.f;
#pragma unroll
            for (int i = 0; i < 16; i++) { float dd = f[r][i] - sm[r]; q[r] += dd * dd; }
        }
#pragma unroll
        for (int o = 16; o > 0; o >>= 1) { q[0] += __shfl_xor_sync(0xffffffffu, q[0], o); q[1] += __shfl_xor_sync(0xffffffffu, q[1], o); }
#pragma unroll
        for (int r = 0; r < 2; r++) {
            const float mb = bf16_round(sm[r]);
            const float vb = bf16_round(q[r] * (1.0f / D_));
            const float den = bf16_round(sqrtf(bf16_round(vb + 1e-5f)));
            uint32_t o[8];
#pragma unroll
            for (int i = 0; i < 8; i++) {
                float a = __fdiv_rn(bf16_round(f[r][2 * i] - mb), den);
                float b = __fdiv_rn(bf16_round(f[r][2 * i + 1] - mb), den);
                o[i] = pack_bf16(a, b);
            }
            __nv_bfloat16* dst = g_xn + (size_t)(row + r) * D_;
            *reinterpret_cast<uint4*>(dst + lane * 8) = make_uint4(o[0], o[1], o[2], o[3]);
            *reinterpret_cast<uint4*>(dst + 256 + lane * 8) = make_uint4(o[4], o[5], o[6], o[7]);
            *reinterpret_cast<uint4*>(&tile[warp * 2 + r][lane * 8]) = make_uint4(o[0], o[1], o[2], o[3]);
            *reinterpret_cast<uint4*>(&tile[warp * 2 + r][256 + lane * 8]) = make_uint4(o[4], o[5], o[6], o[7]);
        }
    } else {
        const int cc_ = warp - 8, dd = blockIdx.x * CV_CH + cc_;
        float4* sc = reinterpret_cast<float4*>(smem + cc_ * CV_EARLY + CV_O_CONST);
        __nv_bfloat16 pr[4][6];
#pragma unroll
        for (int j = 0; j < 4; j++) {
            const size_t off = (size_t)dd * NS_ + lane + 32 * j;
            pr[j][0] = A_re[off]; pr[j][1] = A_im[off]; pr[j][2] = B_re[off]; pr[j][3] = B_im[off]; pr[j][4] = C_re[off]; pr[j][5] = C_im[off];
        }
        const float dt = bf16_round(expf(__bfloat162float(log_dt[dd])));
        float tail = 0.f;
#pragma unroll
        for (int j = 0; j < 4; j++) {
            const float ar = dt * __bfloat162float(pr[j][0]), ai = dt * __bfloat162float(pr[j][1]);
            const cplx db = {dt * __bfloat162float(pr[j][2]), dt * __bfloat162float(pr[j][3])};
            const cplx cc = {__bfloat162float(pr[j][4]), __bfloat162float(pr[j][5])};
            const cplx cb = cmul(cc, db);
            const float ar2 = ar * 1.4426950408889634f, ai2 = ai * 0.15915494309189535f;
            const cplx e8 = cexp_m(ar2, ai2, 8.f), e128 = cexp_m(ar2, ai2, 128.f);
            const cplx cb8 = cmul(cb, e8);
            const cplx e256 = cexp_m(ar2, ai2, 256.f), e512 = cexp_m(ar2, ai2, 512.f), e1024 = cexp_m(ar2, ai2, 1024.f);
            const cplx c256 = cmul(cb, e256), c512 = cmul(cb, e512), c1024 = cmul(cb, e1024);
            const cplx c768 = cmul(c512, e256), c1280 = cmul(c1024, e256), c1536 = cmul(c1024, e512);
            const cplx c1792 = cmul(c1536, e256);
            tail += cmul(c1024, e1024).r;
            float4* c = sc + (lane + 32 * j) * 6;
            c[0] = make_float4(ar2, ai2, cb.r, cb.i);
            c[1] = make_float4(e128.r, e128.i, cb8.r, cb8.i);
            c[2] = make_float4(c256.r, c256.i, e8.r, e8.i);
            c[3] = make_float4(c512.r, c512.i, c768.r, c768.i);
            c[4] = make_float4(c1024.r, c1024.i, c1280.r, c1280.i);
            c[5] = make_float4(c1536.r, c1536.i, c1792.r, c1792.i);
        }
#pragma unroll
        for (int o = 16; o > 0; o >>= 1) tail += __shfl_xor_sync(0xffffffffu, tail, o);
        if (lane == 0) {
            float* kp = reinterpret_cast<float*>(smem + cc_ * CV_EARLY + CV_O_KP);
            kp[640] = tail; kp[648 + 640] = 0.f; kp[1296 + 640] = 0.f;
        }
    }
    __syncthreads();
    if (threadIdx.x == 0) STAMP(0, 3);
#pragma unroll
    for (int rep = 0; rep < 2; rep++) {
        const int c = threadIdx.x + 384 * rep;
        if (c < D_) {
            uint32_t ot[8];
#pragma unroll
            for (int i = 0; i < 8; i++) {
                uint32_t lo = *reinterpret_cast<const uint16_t*>(&tile[2 * i][c]);
                uint32_t hi = *reinterpret_cast<const uint16_t*>(&tile[2 * i + 1][c]);
                ot[i] = lo | (hi << 16);
            }
            __nv_bfloat16* dT = g_xnT + (size_t)c * L_ + blockIdx.x * LN_ROWS;
            *reinterpret_cast<uint4*>(dT) = make_uint4(ot[0], ot[1], ot[2], ot[3]);
            *reinterpret_cast<uint4*>(dT + 8) = make_uint4(ot[4], ot[5], ot[6], ot[7]);
        }
    }
    if (threadIdx.x < 336) {
        const int m = threadIdx.x / 112, i = threadIdx.x - m * 112;
        const char* wp = (const char*)(m == 0 ? wg : (m == 1 ? wu : wd));
        asm volatile("prefetch.global.L2 [%0];" ::"l"(wp + ((size_t)blockIdx.x * 112 + i) * 128));
    }
    __syncthreads();
    if (threadIdx.x == 0) STAMP(1, 1);
    {
        float acc[5][4];
#pragma unroll
        for (int i = 0; i < 5; i++) { acc[i][0] = acc[i][1] = acc[i][2] = acc[i][3] = 0.f; }
        const float gf = (float)g;
        const int src4 = ((g & 3) << 2) | t;
#pragma unroll 2
        for (int s = w; s < 32; s += 3) {
            if (s == 17 && threadIdx.x == 352) asm volatile("red.release.gpu.global.add.u32 [%0], 1;" ::"l"(&g_ln_count) : "memory");
            const float4* c = s_const + (s * 4 + t) * 6;
            const float4 k0 = c[0], k1 = c[1], k2 = c[2];
            const float2 k3 = reinterpret_cast<const float2*>(c + 3)[g >> 2];
            const float2 k4 = reinterpret_cast<const float2*>(c + 4)[g >> 1];
            const cplx cb = {k0.z, k0.w}, e128 = {k1.x, k1.y}, cb8 = {k1.z, k1.w}, c256 = {k2.x, k2.y}, e8 = {k2.z, k2.w};
            const cplx c2 = {k3.x, k3.y}, c3 = {k4.x, k4.y};
            const cplx p1 = cexp_m(k0.x, k0.y, gf);
            const cplx p2 = csq(p1), p4 = csq(p2);
            const cplx r16a = csq(csq(p4));
            cplx q4;
            q4.r = __shfl_sync(0xffffffffu, p4.r, src4);
            q4.i = __shfl_sync(0xffffffffu, p4.i, src4);
            const cplx r16b = cmul(r16a, e128);
            const cplx f0a = cmul(cb, p1), f0b = cmul(cb8, p1), f1 = cmul(c256, p2), f2 = cmul(c2, q4);
            cplx f3 = cmul(c3, e8);
            if (!(g & 1)) f3 = c3;
            const uint32_t a0 = to_tf32(r16a.r), a1 = to_tf32(r16b.r), a2 = to_tf32(-r16a.i), a3 = to_tf32(-r16b.i);
            mma_tf32(acc[0], a0, a1, a2, a3, to_tf32(f0a.r), to_tf32(f0a.i));
            mma_tf32(acc[1], a0, a1, a2, a3, to_tf32(f0b.r), to_tf32(f0b.i));
            mma_tf32(acc[2], a0, a1, a2, a3, to_tf32(f1.r), to_tf32(f1.i));
            mma_tf32(acc[3], a0, a1, a2, a3, to_tf32(f2.r), to_tf32(f2.i));
            mma_tf32(acc[4], a0, a1, a2, a3, to_tf32(f3.r), to_tf32(f3.i));
        }
        float* kv = s_kp + w * 648;
#pragma unroll
        for (int hh = 0; hh < 2; hh++) {
            const int i = g + 8 * hh;
            *reinterpret_cast<float2*>(kv + 16 * i + 2 * t) = make_float2(acc[0][2 * hh], acc[0][2 * hh + 1]);
            *reinterpret_cast<float2*>(kv + 16 * i + 8 + 2 * t) = make_float2(acc[1][2 * hh], acc[1][2 * hh + 1]);
            *reinterpret_cast<float2*>(kv + 256 + 8 * i + 2 * t) = make_float2(acc[2][2 * hh], acc[2][2 * hh + 1]);
            *reinterpret_cast<float2*>(kv + 384 + 64 * (t >> 1) + 2 * (t & 1) + 4 * i) = make_float2(acc[3][2 * hh], acc[3][2 * hh + 1]);
            *reinterpret_cast<float2*>(kv + 512 + 32 * t + 2 * i) = make_float2(acc[4][2 * hh], acc[4][2 * hh + 1]);
        }
    }
    named_bar(bar_id, 96);
    if (threadIdx.x == 0) STAMP(1, 2);
#pragma unroll
    for (int i = 0; i < 7; i++) {
        const int idx = tc + 96 * i;
        if (idx < 641) s_kp[idx] = (s_kp[idx] + s_kp[648 + idx]) + s_kp[1296 + idx];
    }
    named_bar(bar_id, 96);
    {
        auto kdir = [&](int l) -> float {
            if (l < 0 || l > 514) return 0.f;
            const int idx = (l < 256) ? l : (l > 512 ? 384 : 128 + ((l + ((l >> 1) & 1)) >> 1));
            return s_kp[idx];
        };
#pragma unroll
        for (int i = 0; i < 6; i++) {
            const int e = tc + 96 * i;
            s_q[e] = pack_bf16(kdir(e - 16), kdir(e - 17));
        }
        if (tc < 64) {
            const int xx = 1008 + tc;
            const float k1024 = s_kp[512];
            s_q4[tc] = pack_bf16((xx == 1027 || xx == 1028) ? k1024 : 0.f, (xx == 1028 || xx == 1029) ? k1024 : 0.f);
        }
#pragma unroll
        for (int i = 0; i < 3; i++) {
            const int e = tc + 96 * i;
            if (e < 256) {
                const int a = e >> 6, ii = (e & 63) - 16;
                const int b = 385 + (a >> 1) + 2 * (a & 1);
                const float v0 = (ii >= 0 && ii < 32) ? s_kp[b + 4 * ii] : 0.f;
                const float v1 = (ii >= 1 && ii < 33) ? s_kp[b + 4 * (ii - 1)] : 0.f;
                s_q2[e] = pack_bf16(v0, v1);
            }
        }
#pragma unroll
        for (int a = 0; a < 2; a++) {
            const int jj = tc - 16;
            const float v0 = (jj >= 0 && jj < 64) ? s_kp[513 + a + 2 * jj] : 0.f;
            const float v1 = (jj >= 1 && jj < 65) ? s_kp[513 + a + 2 * (jj - 1)] : 0.f;
            s_q3[96 * a + tc] = pack_bf16(v0, v1);
        }
    }
    if (threadIdx.x == 0) STAMP(1, 3);
    if (threadIdx.x == 0) {
        unsigned int v = 0;
        for (int spin = 0; spin < (1 << 22); spin++) {
            asm volatile("ld.acquire.gpu.global.u32 %0, [%1];" : "=r"(v) : "l"(&g_ln_count) : "memory");
            if (v >= gridDim.x) break;
        }
    }
    fence_async_smem();
    __syncthreads();
    if (threadIdx.x == 0) STAMP(1, 4);
    prefetch_fn();
    {
        if (tc < 16) *reinterpret_cast<uint4*>(s_u + tc * 8) = make_uint4(0, 0, 0, 0);
        const uint4* src = reinterpret_cast<const uint4*>(g_xnT + (size_t)d * L_);
        uint4 v[3];
#pragma unroll
        for (int i = 0; i < 3; i++) if (tc + 96 * i < 256) v[i] = src[tc + 96 * i];
#pragma unroll
        for (int i = 0; i < 3; i++) if (tc + 96 * i < 256) *reinterpret_cast<uint4*>(s_u + 128 + (tc + 96 * i) * 8) = v[i];
        if (tc < 2) *reinterpret_cast<uint4*>(base + (tc ? CV_O_W5 : CV_O_W3)) = make_uint4(0, 0, 0, 0);
    }
    named_bar(bar_id, 96);
    if (w == 2) {
#pragma unroll 2
      for (int rep = 0; rep < 6; rep++) {
        const int m = lane + 32 * rep;
        float P[30];
        const uint4* up = reinterpret_cast<const uint4*>(s_u + 128 + 8 * m - 24);
        P[0] = 0.f;
#pragma unroll
        for (int c4 = 0; c4 < 4; c4++) {
            const uint4 v = up[c4];
            const uint32_t ww[4] = {v.x, v.y, v.z, v.w};
#pragma unroll
            for (int j = 0; j < 4; j++) {
                const int k = c4 * 8 + 2 * j;
                if (k + 1 <= 29) P[k + 1] = P[k] + bf_lo(ww[j]);
                if (k + 2 <= 29) P[k + 2] = P[k + 1] + bf_hi(ww[j]);
            }
        }
        uint32_t o3[4], o5[4], o7[4], o9[4];
#pragma unroll
        for (int j = 0; j < 4; j++) {
            const int i = 2 * j;
            o3[j] = pack_bf16(P[i + 22] - P[i + 19], P[i + 23] - P[i + 20]);
            o5[j] = pack_bf16(P[i + 19] - P[i + 14], P[i + 20] - P[i + 15]);
            o7[j] = pack_bf16(P[i + 20] - P[i + 13], P[i + 21] - P[i + 14]);
            o9[j] = pack_bf16(P[i + 13] - P[i + 4], P[i + 14] - P[i + 5]);
        }
        *reinterpret_cast<uint4*>(base + CV_O_W3 + 16 + m * 16) = make_uint4(o3[0], o3[1], o3[2], o3[3]);
        *reinterpret_cast<uint4*>(base + CV_O_W5 + 16 + m * 16) = make_uint4(o5[0], o5[1], o5[2], o5[3]);
        if (m < 128) {
            *reinterpret_cast<uint4*>(base + CV_O_W7 + m * 16) = make_uint4(o7[0], o7[1], o7[2], o7[3]);
            *reinterpret_cast<uint4*>(base + CV_O_W9 + m * 16) = make_uint4(o9[0], o9[1], o9[2], o9[3]);
        }
    }
      named_bar(bar_id, 96);
      return;
    }
    if (threadIdx.x == 0) STAMP(1, 5);
    const int hb = w;
    float acc[16][4];
#pragma unroll
    for (int i = 0; i < 16; i++) { acc[i][0] = acc[i][1] = acc[i][2] = acc[i][3] = 0.f; }
    const uint32_t sb_addr = smem_u32(base);
    const int mi = lane >> 3, rowi = lane & 7;
#pragma unroll 1
    for (int rr = 0; rr < 4; rr++) {
        const int r = 4 * hb + rr;
        uint32_t ub[16][2];
        {
            const uint32_t addr = sb_addr + CV_O_U + (uint32_t)((128 + 16 * (8 * (mi >> 1) + rowi - r) + 8 * (mi & 1)) * 2);
#pragma unroll
            for (int j = 0; j < 16; j += 2) ldsm_x4(addr + (uint32_t)(j * 256), ub[j][0], ub[j][1], ub[j + 1][0], ub[j + 1][1]);
        }
        const uint32_t* qp = s_q + 16 + 16 * r + g - 2 * t;
        uint32_t af[4][3];
#pragma unroll
        for (int q = 0; q < 4; q++) { af[q][0] = qp[128 * q]; af[q][1] = qp[128 * q + 8]; af[q][2] = qp[128 * q - 8]; }
#pragma unroll
        for (int q = 0; q < 4; q++) {
#pragma unroll
            for (int nt = q; nt < 16; nt++) mma_bf16(acc[nt], af[q][0], af[q][1], af[q][2], af[q][0], ub[nt - q][0], ub[nt - q][1]);
        }
        if (r < 2) {
            {
                const uint32_t a0 = qp[512], a1 = qp[520], a2 = qp[504];
#pragma unroll
                for (int nt = 4; nt < 16; nt++) mma_bf16(acc[nt], a0, a1, a2, a0, ub[nt - 4][0], ub[nt - 4][1]);
            }
            {
                const uint32_t* q4p = s_q4 + 16 + 16 * r + g - 2 * t;
                const uint32_t a0 = q4p[0], a1 = q4p[8], a2 = q4p[-8];
#pragma unroll
                for (int nt = 8; nt < 16; nt++) mma_bf16(acc[nt], a0, a1, a2, a0, ub[nt - 8][0], ub[nt - 8][1]);
            }
        }
    }
    named_bar(bar_id, 96);
#pragma unroll 1
    for (int a = hb; a <= 3 * hb; a++) {
        uint32_t bq[7];
        const uint32_t* q2 = s_q2 + a * 64 + 16 + g - 2 * t - 32;
#pragma unroll
        for (int dlt = 3; dlt <= 9; dlt++) bq[dlt - 3] = q2[8 * dlt];
        const uint32_t addr = sb_addr + ((a >> 1) ? CV_O_W5 : CV_O_W3) + (uint32_t)((8 + 16 * (8 * (mi >> 1) + rowi) + 8 * (mi & 1) - 8 * (a & 1)) * 2);
        uint32_t aa[6][4];
#pragma unroll
        for (int kp = 0; kp < 6; kp++) ldsm_x4_t(addr + kp * 512, aa[kp][0], aa[kp][1], aa[kp][2], aa[kp][3]);
#pragma unroll
        for (int kp = 0; kp < 6; kp++) {
#pragma unroll
            for (int dlt = 4; dlt <= 9; dlt++) {
                if (2 * kp + dlt < 16) mma_bf16(acc[2 * kp + dlt], aa[kp][0], aa[kp][1], aa[kp][2], aa[kp][3], bq[dlt - 3], bq[dlt - 4]);
            }
        }
    }
    if (hb == 0) {
#pragma unroll 1
        for (int a = 0; a < 2; a++) {
            uint32_t bq[9];
            const uint32_t* q3 = s_q3 + a * 96 + 16 + g - 2 * t - 64;
#pragma unroll
            for (int dlt = 7; dlt <= 15; dlt++) bq[dlt - 7] = q3[8 * dlt];
            const uint32_t addr = sb_addr + (a ? CV_O_W9 : CV_O_W7) + (uint32_t)((16 * (8 * (mi >> 1) + rowi) + 8 * (mi & 1)) * 2);
            uint32_t aa[4][4];
#pragma unroll
            for (int kp = 0; kp < 4; kp++) ldsm_x4_t(addr + kp * 512, aa[kp][0], aa[kp][1], aa[kp][2], aa[kp][3]);
#pragma unroll
            for (int kp = 0; kp < 4; kp++) {
#pragma unroll
                for (int dlt = 8; dlt <= 15; dlt++) {
                    if (2 * kp + dlt < 16) mma_bf16(acc[2 * kp + dlt], aa[kp][0], aa[kp][1], aa[kp][2], aa[kp][3], bq[dlt - 7], bq[dlt - 8]);
                }
            }
        }
    }
    if (threadIdx.x == 0) STAMP(1, 6);
    named_bar(bar_id, 64);
    {
        float4* xch = reinterpret_cast<float4*>(base + CV_O_W3) + hb * 256;
        if (hb) {
#pragma unroll
            for (int i = 0; i < 8; i++) xch[i * 32 + lane] = make_float4(acc[i][0], acc[i][1], acc[i][2], acc[i][3]);
#pragma unroll
            for (int i = 0; i < 8; i++) { acc[i][0] = acc[8 + i][0]; acc[i][1] = acc[8 + i][1]; acc[i][2] = acc[8 + i][2]; acc[i][3] = acc[8 + i][3]; }
        } else {
#pragma unroll
            for (int i = 0; i < 8; i++) xch[i * 32 + lane] = make_float4(acc[8 + i][0], acc[8 + i][1], acc[8 + i][2], acc[8 + i][3]);
        }
    }
    named_bar(bar_id, 64);
    if (threadIdx.x == 0) STAMP(1, 10);
    {
        const float4* xch = reinterpret_cast<const float4*>(base + CV_O_W3) + (hb ^ 1) * 256 + lane;
        const float dsk = __bfloat162float(p_dsk);
        uint16_t* stg = reinterpret_cast<uint16_t*>(base + CV_O_Q);
        const uint16_t* uu = reinterpret_cast<const uint16_t*>(s_u) + 128;
#pragma unroll
        for (int i = 0; i < 8; i++) {
            const float4 p0 = xch[i * 32];
            const float y[4] = {acc[i][0] + p0.x, acc[i][1] + p0.y, acc[i][2] + p0.z, acc[i][3] + p0.w};
            const int nt = 8 * hb + i;
#pragma unroll
            for (int e = 0; e < 4; e++) {
                const int tau = 16 * (8 * nt + 2 * t + (e & 1)) + g + 8 * (e >> 1);
                const float sv = bf16_round(y[e]) + bf16_round(__uint_as_float((uint32_t)uu[tau] << 16) * dsk);
                stg[tau] = (uint16_t)(__float_as_uint(bf16_round(sv)) >> 16);
            }
        }
        __syncwarp();
        if (threadIdx.x == 0) STAMP(1, 11);
        uint4* dst = reinterpret_cast<uint4*>(g_sT + (size_t)d * L_ + hb * 1024);
        const uint4* srcp = reinterpret_cast<const uint4*>(stg + hb * 1024);
#pragma unroll
        for (int i = 0; i < 4; i++) dst[i * 32 + lane] = srcp[i * 32 + lane];
    }
}

__device__ __forceinline__ uint32_t cluster_rank() { uint32_t r; asm volatile("mov.u32 %0, %%cluster_ctarank;" : "=r"(r)); return r; }
__device__ __forceinline__ void cluster_sync_all() {
    asm volatile("barrier.cluster.arrive.release.aligned;\nbarrier.cluster.wait.acquire.aligned;" ::: "memory");
}
__device__ __forceinline__ void mbar_arrive_remote(uint32_t bar, uint32_t cta) {
    asm volatile("{\n.reg .b32 ra;\nmapa.shared::cluster.u32 ra, %0, %1;\n"
                 "mbarrier.arrive.shared::cluster.b64 _, [ra];\n}\n" ::"r"(bar), "r"(cta) : "memory");
}
__device__ __forceinline__ void tma_load_2d_mc(uint32_t dst, const CUtensorMap* tm, int c0, int c1, uint32_t bar, uint16_t mask) {
    asm volatile(
        "cp.async.bulk.tensor.2d.shared::cluster.global.mbarrier::complete_tx::bytes.multicast::cluster [%0], [%1, {%3, %4}], [%2], %5;"
        ::"r"(dst), "l"((uint64_t)tm), "r"(bar), "r"(c0), "r"(c1), "h"(mask) : "memory");
}
__device__ __forceinline__ void tma_store_2d(const CUtensorMap* tm, uint32_t src, int c0, int c1) {
    asm volatile("cp.async.bulk.tensor.2d.global.shared::cta.bulk_group [%0, {%2, %3}], [%1];"
                 ::"l"((uint64_t)tm), "r"(src), "r"(c0), "r"(c1) : "memory");
}
__device__ __forceinline__ void bulk_commit() { asm volatile("cp.async.bulk.commit_group;" ::: "memory"); }
template <int N> __device__ __forceinline__ void bulk_wait_read() { asm volatile("cp.async.bulk.wait_group.read %0;" ::"n"(N) : "memory"); }
template <int N> __device__ __forceinline__ void bulk_wait() { asm volatile("cp.async.bulk.wait_group %0;" ::"n"(N) : "memory"); }
__device__ __forceinline__ void stmatrix_x4(uint32_t addr, uint32_t r0, uint32_t r1, uint32_t r2, uint32_t r3) {
    asm volatile("stmatrix.sync.aligned.m8n8.x4.shared.b16 [%0], {%1,%2,%3,%4};" ::"r"(addr), "r"(r0), "r"(r1), "r"(r2), "r"(r3) : "memory");
}

constexpr int G1_STAGES = 5;
constexpr int G1_A_BYTES = 8 * 16384;
constexpr int G1_B_STAGE = 16384;
constexpr int G1_STG = 8 * 1024;
constexpr int G1_SMEM = G1_A_BYTES + G1_STAGES * G1_B_STAGE + G1_STG + 1024 + 256;
constexpr int G1_ITERS = 32;

__device__ __forceinline__ void tma_load_3d(uint32_t dst, const CUtensorMap* tm, int c0, int c1, int c2, uint32_t bar) {
    asm volatile(
        "cp.async.bulk.tensor.3d.shared::cluster.global.mbarrier::complete_tx::bytes [%0], [%1, {%3, %4, %5}], [%2];"
        ::"r"(dst), "l"((uint64_t)tm), "r"(bar), "r"(c0), "r"(c1), "r"(c2) : "memory");
}

__device__ __forceinline__ void tma_load_3d_mc(uint32_t dst, const CUtensorMap* tm, int c0, int c1, int c2, uint32_t bar, uint16_t mask) {
    asm volatile(
        "cp.async.bulk.tensor.3d.shared::cluster.global.mbarrier::complete_tx::bytes.multicast::cluster [%0], [%1, {%3, %4, %5}], [%2], %6;"
        ::"r"(dst), "l"((uint64_t)tm), "r"(bar), "r"(c0), "r"(c1), "r"(c2), "h"(mask) : "memory");
}

__device__ __forceinline__ float gelu_tanh(float x) {
    float u = x * (0.7978845608028654f + 0.035677408136300125f * x * x);
    float t; asm("tanh.approx.f32 %0, %1;" : "=f"(t) : "f"(u));
    float hx = 0.5f * x;
    return fmaf(hx, t, hx);
}
__device__ __forceinline__ uint32_t geglu_pair(uint32_t g2, uint32_t u2) {
    uint32_t a = pack_bf16(gelu_tanh(bf_lo(g2)), gelu_tanh(bf_hi(g2)));
    uint32_t r; asm("mul.rn.bf16x2 %0, %1, %2;" : "=r"(r) : "r"(a), "r"(u2));
    return r;
}

constexpr int G2_STAGES = 5;
constexpr int G2_STAGE = 16384 + 16384;
constexpr int G2_XCH = 32768;
constexpr int G2_EPI = 16384 + 16384;
constexpr int G2_SMEM = G2_STAGES * G2_STAGE + G2_XCH + G2_EPI + 1024 + 256;
constexpr int G2_KB = F_ / 64 / 2;

constexpr int MG_BAR_OFF = G2_STAGES * G2_STAGE + G2_XCH + G2_EPI;
constexpr int MG_SMEM = MG_BAR_OFF + 512 + 1024;
static_assert(MG_BAR_OFF == 229376 && G1_A_BYTES + G1_STAGES * G1_B_STAGE + G1_STG <= MG_BAR_OFF, "smem layout");

__device__ __forceinline__ void fence_async_all() { asm volatile("fence.proxy.async;" ::: "memory"); }
__device__ __forceinline__ void spin_until(const unsigned int* p, unsigned int target) {
    unsigned int v = 0;
    for (int spin = 0; spin < (1 << 22); spin++) {
        asm volatile("ld.acquire.gpu.global.u32 %0, [%1];" : "=r"(v) : "l"(p) : "memory");
        if (v >= target) break;
    }
}

struct MegaParams {
    const __nv_bfloat16 *x, *A_re, *A_im, *B_re, *B_im, *C_re, *C_im, *log_dt, *Dskip, *wg, *wu, *wd;
};

__global__ void __launch_bounds__(384, 1) mega_kernel(const __grid_constant__ MegaParams P,
                                                       const __grid_constant__ CUtensorMap tm_xn,
                                                       const __grid_constant__ CUtensorMap tm_wg4,
                                                       const __grid_constant__ CUtensorMap tm_wu4,
                                                       const __grid_constant__ CUtensorMap tm_wg3,
                                                       const __grid_constant__ CUtensorMap tm_wu3,
                                                       const __grid_constant__ CUtensorMap tm_h,
                                                       const __grid_constant__ CUtensorMap tm_wd,
                                                       const __grid_constant__ CUtensorMap tm_x,
                                                       const __grid_constant__ CUtensorMap tm_sT,
                                                       const __grid_constant__ CUtensorMap tm_out) {
    if (threadIdx.x == 0) STAMP(1, 0);
    extern __shared__ uint8_t smem_raw[];
    const uint32_t sraw = smem_u32(smem_raw);
    const uint32_t sbase = (sraw + 1023) & ~1023u;
    uint8_t* smem = smem_raw + (sbase - sraw);
    const int warp = threadIdx.x >> 5, lane = threadIdx.x & 31;
    const uint32_t sA = sbase, sB = sbase + G1_A_BYTES, sStg = sB + G1_STAGES * G1_B_STAGE;
    const uint32_t sXch = sbase + G2_STAGES * G2_STAGE, sX = sXch + G2_XCH, sS = sX + 16384;
    const uint32_t sBar = sbase + MG_BAR_OFF;
    const uint32_t bar_a = sBar, bar_full = sBar + 64, bar_empty = bar_full + 8 * G1_STAGES;
    const uint32_t bar_full2 = bar_empty + 8 * G1_STAGES, bar_empty2 = bar_full2 + 8 * G2_STAGES;
    const uint32_t bar_epi = bar_empty2 + 8 * G2_STAGES, bar_xch = bar_epi + 8, bar_g1done = bar_xch + 8, bar_g1mma = bar_g1done + 8, bar_peer = bar_g1mma + 8;
    const uint32_t kh = blockIdx.x & 1;
    const int rb1 = ((blockIdx.x >> 4) << 1) + (int)kh, cj = (blockIdx.x >> 1) & 7;
    const int rb = blockIdx.x >> 3;
    const int nb = (blockIdx.x >> 1) & 3;
    const int col_fin = nb * 128 + kh * 64;

    if (threadIdx.x == 0) {
        for (int i = 0; i < 8; i++) mbar_init(bar_a + 8 * i, 1);
        for (int i = 0; i < G1_STAGES; i++) { mbar_init(bar_full + 8 * i, 1); mbar_init(bar_empty + 8 * i, 16); }
        for (int i = 0; i < G2_STAGES; i++) { mbar_init(bar_full2 + 8 * i, 1); mbar_init(bar_empty2 + 8 * i, 8); }
        mbar_init(bar_epi, 1);
        mbar_init(bar_xch, 1);
        mbar_init(bar_g1done, 8);
        mbar_init(bar_g1mma, 8);
        mbar_init(bar_peer, 1);
        asm volatile("fence.mbarrier_init.release.cluster;" ::: "memory");
        mbar_expect_tx(bar_xch, G2_XCH);
    }
    if (warp == 11 && lane == 0) {
        prefetch_tmap(&tm_wg4); prefetch_tmap(&tm_wu4); prefetch_tmap(&tm_xn); prefetch_tmap(&tm_wg3); prefetch_tmap(&tm_wu3);
        prefetch_tmap(&tm_wd); prefetch_tmap(&tm_h); prefetch_tmap(&tm_x); prefetch_tmap(&tm_sT); prefetch_tmap(&tm_out);
    }
    asm volatile("barrier.cluster.arrive.release.aligned;" ::: "memory");

    auto g1_prefetch = [&]() {
        if (warp == 8 && lane == 0) {
            fence_async_all();
            mbar_expect_tx(bar_full, 16384);
            tma_load_3d(sB, &tm_wg4, 0, 0, cj * 7, bar_full);
            tma_load_3d(sB + 8192, &tm_wu4, 0, 0, cj * 7, bar_full);
            for (int k = 0; k < 8; k++) {
                mbar_expect_tx(bar_a + 8 * k, 16384);
                tma_load_2d(sA + k * 16384, &tm_xn, k * 64, rb1 * 128, bar_a + 8 * k);
            }
        }
    };
    front_phase(g1_prefetch, smem, P.x, P.A_re, P.A_im, P.B_re, P.B_im, P.C_re, P.C_im, P.log_dt, P.Dskip, P.wg, P.wu, P.wd);
    fence_async_smem();
    asm volatile("barrier.cluster.wait.acquire.aligned;" ::: "memory");
    __syncthreads();
    if (threadIdx.x == 352) mbar_arrive_remote(bar_peer, kh ^ 1);
    if (threadIdx.x == 0) STAMP(1, 7);

    if (warp >= 8) {
        asm volatile("setmaxnreg.dec.sync.aligned.u32 40;");
        if (warp == 11) {
            if (lane == 0) asm volatile("red.release.gpu.global.add.u32 [%0], 1;" ::"l"(&g_conv_count) : "memory");
            named_bar(3, 288);
            if (lane == 0) asm volatile("red.release.gpu.global.add.u32 [%0], 1;" ::"l"(&g_h_count[rb1]) : "memory");
            named_bar(9, 288);
            if (lane == 0) asm volatile("red.release.gpu.global.add.u32 [%0], 1;" ::"l"(&g_h_count[16 + rb1]) : "memory");
        } else if (lane == 0) {
            const int pw = warp - 8;
            mbar_wait(bar_peer, 0);
            for (int it = 1 + pw; it < G1_ITERS; it += 3) {
                const int s = it % G1_STAGES, kb = it & 15;
                if (it >= G1_STAGES) mbar_wait(bar_empty + 8 * s, ((it / G1_STAGES) - 1) & 1);
                const uint32_t dst = sB + s * G1_B_STAGE;
                if (it < 16) {
                    mbar_expect_tx(bar_full + 8 * s, 16384);
                    tma_load_3d_mc(dst + kh * 8192, kh ? &tm_wu4 : &tm_wg4, 0, kb * 32, cj * 7, bar_full + 8 * s, 3);
                } else {
                    mbar_expect_tx(bar_full + 8 * s, 12288);
                    tma_load_3d_mc(dst + kh * 6144, kh ? &tm_wu3 : &tm_wg3, 0, kb * 32, cj * 7 + 4, bar_full + 8 * s, 3);
                }
            }
            const int k0 = kh * G2_KB;
            auto kblk = [&](int it) -> int {
                const unsigned long long tab = 0xDCA96532B87410ull;
                return k0 + (int)((tab >> (4 * it)) & 15);
            };
            mbar_wait(bar_g1mma, 0);
            if (pw == 2) {
                mbar_expect_tx(bar_epi, G2_EPI);
                tma_load_2d(sX, &tm_x, col_fin, rb * 128, bar_epi);
            }
            spin_until(&g_h_count[rb], 8);
            fence_async_all();
            if (pw == 0) STAMP(3, 1);
            for (int it = pw; it < G2_KB; it += 3) {
                const int s = (it + 1) % G2_STAGES;
                if (it == 4) mbar_wait(bar_g1done, 0);
                if (it >= G2_STAGES) mbar_wait(bar_empty2 + 8 * s, ((it / G2_STAGES) - 1) & 1);
                if (it >= 6 && it < 9) { spin_until(&g_h_count[16 + rb], 8); fence_async_all(); }
                mbar_expect_tx(bar_full2 + 8 * s, G2_STAGE);
                const int kb = kblk(it);
                tma_load_3d(sbase + s * G2_STAGE + 16384, &tm_wd, 0, kb * 64, nb * 2, bar_full2 + 8 * s);
                tma_load_2d(sbase + s * G2_STAGE, &tm_h, kb * 64, rb * 128, bar_full2 + 8 * s);
                if (it == 2) {
                    spin_until(&g_conv_count, gridDim.x);
                    fence_async_all();
                    tma_load_2d(sS, &tm_sT, rb * 128, col_fin, bar_epi);
                    tma_load_2d(sS + 8192, &tm_sT, rb * 128 + 64, col_fin, bar_epi);
                }
            }
        }
    } else {
        asm volatile("setmaxnreg.inc.sync.aligned.u32 232;");
        const int wg = __shfl_sync(0xffffffffu, (int)(threadIdx.x >> 7), 0);
        {
        float r[160];
        const int row0 = rb1 * 128 + wg * 64 + (warp & 3) * 16;
        const uint64_t descA = make_desc(sA + wg * 8192, 16, 1024);
        const uint64_t descB = make_desc(sB, 2048, 512, 2);
        const uint32_t stg = sStg + warp * 1024;
        const uint32_t st_off = (uint32_t)(((lane & 7) + ((lane >> 3) & 1) * 8) * 32 + (lane >> 4) * 16);
        __nv_bfloat16* hrow = g_h + (size_t)(row0 + (lane >> 1)) * F_ + (lane & 1) * 8 + cj * 224;
#pragma unroll
        for (int kb = 0; kb < 16; kb++) {
            const int it = kb, s = it % G1_STAGES;
            if ((kb & 1) == 0) mbar_wait(bar_a + 8 * (kb >> 1), 0);
            mbar_wait(bar_full + 8 * s, (it / G1_STAGES) & 1);
            if (threadIdx.x == 0 && (it & 7) == 0) STAMP(2, 2 + it / 8);
            wgmma_fence();
            const uint64_t da = descA + (uint64_t)(((kb >> 1) * 16384 + (kb & 1) * 64) >> 4);
            const uint64_t db = descB + (uint64_t)((s * G1_B_STAGE) >> 4);
            wgmma_n256_k32(r, da, da + 2, db, db + 64, kb != 0);
            wgmma_commit();
            if (kb > 0) {
                wgmma_wait<1>();
                if (lane < 2) mbar_arrive_remote(bar_empty + 8 * ((it - 1) % G1_STAGES), lane);
            }
        }
        wgmma_wait<0>();
        if (lane < 2) mbar_arrive_remote(bar_empty + 8 * (15 % G1_STAGES), lane);
#pragma unroll
        for (int i = 0; i < 32; i++) r[128 + i] = __uint_as_float(pack_bf16(r[2 * i], r[2 * i + 1]));
#pragma unroll
        for (int i = 31; i >= 0; i--) r[96 + i] = __uint_as_float(pack_bf16(r[64 + 2 * i], r[65 + 2 * i]));
        uint32_t eo[4];
        uint4 pv = make_uint4(0, 0, 0, 0);
#pragma unroll
        for (int kb = 0; kb < 16; kb++) {
            const int it = 16 + kb, s = it % G1_STAGES;
            mbar_wait(bar_full + 8 * s, (it / G1_STAGES) & 1);
            if (threadIdx.x == 0 && (it & 7) == 0) STAMP(2, 2 + it / 8);
            wgmma_fence();
            const uint64_t da = descA + (uint64_t)(((kb >> 1) * 16384 + (kb & 1) * 64) >> 4);
            const uint64_t db = descB + (uint64_t)((s * G1_B_STAGE) >> 4);
            wgmma_n192(r, da, db, kb != 0);
            if (kb < 8) {
                eo[0] = geglu_pair(__float_as_uint(r[128 + 4 * kb]), __float_as_uint(r[96 + 4 * kb]));
                eo[1] = geglu_pair(__float_as_uint(r[129 + 4 * kb]), __float_as_uint(r[97 + 4 * kb]));
            }
            wgmma_n192(r, da + 2, db + 64, 1);
            wgmma_commit();
            if (kb >= 2 && kb < 10) *reinterpret_cast<uint4*>(hrow + (kb - 2) * 16) = pv;
            if (kb >= 1 && kb < 9) {
                __syncwarp();
                asm volatile("ld.shared.v4.u32 {%0,%1,%2,%3}, [%4];" : "=r"(pv.x), "=r"(pv.y), "=r"(pv.z), "=r"(pv.w)
                             : "r"(stg + ((kb - 1) & 1) * 512 + lane * 16));
            }
            if (kb < 8) {
                eo[2] = geglu_pair(__float_as_uint(r[130 + 4 * kb]), __float_as_uint(r[98 + 4 * kb]));
                eo[3] = geglu_pair(__float_as_uint(r[131 + 4 * kb]), __float_as_uint(r[99 + 4 * kb]));
                stmatrix_x4(stg + (kb & 1) * 512 + st_off, eo[0], eo[1], eo[2], eo[3]);
            }
            if (kb == 9) asm volatile("bar.arrive 3, 288;" ::: "memory");
            if (kb > 0 && it - 1 + G1_STAGES < G1_ITERS) {
                wgmma_wait<1>();
                if (lane < 2) mbar_arrive_remote(bar_empty + 8 * ((it - 1) % G1_STAGES), lane);
            }
        }
        wgmma_wait<0>();
        fence_async_smem();
        __syncwarp();
        if (lane == 0) mbar_arrive(bar_g1mma);
        if (threadIdx.x == 0) STAMP(2, 6);
        {
            uint32_t o[24];
#pragma unroll
            for (int i = 0; i < 24; i++) o[i] = geglu_pair(pack_bf16(r[2 * i], r[2 * i + 1]), pack_bf16(r[48 + 2 * i], r[49 + 2 * i]));
            named_bar(1 + wg, 128);
            const uint32_t fbuf = sA + ((warp & 3) >> 1) * 16384 + wg * 8192 + (warp & 1) * 4096;
#pragma unroll
            for (int jj = 0; jj < 6; jj++) stmatrix_x4(fbuf + jj * 512 + st_off, o[4 * jj], o[4 * jj + 1], o[4 * jj + 2], o[4 * jj + 3]);
            __syncwarp();
            uint4 v[6];
#pragma unroll
            for (int jj = 0; jj < 6; jj++)
                asm volatile("ld.shared.v4.u32 {%0,%1,%2,%3}, [%4];" : "=r"(v[jj].x), "=r"(v[jj].y), "=r"(v[jj].z), "=r"(v[jj].w)
                             : "r"(fbuf + jj * 512 + lane * 16));
#pragma unroll
            for (int jj = 0; jj < 6; jj++) *reinterpret_cast<uint4*>(hrow + 128 + jj * 16) = v[jj];
        }
        }
        fence_async_smem();
        __syncwarp();
        if (lane == 0) mbar_arrive(bar_g1done);
        asm volatile("bar.arrive 9, 288;" ::: "memory");
        if (threadIdx.x == 0) STAMP(2, 7);
        {
        const int g = lane >> 2, t = lane & 3;
        float acc[64];
        const uint64_t descA2 = make_desc(sbase + wg * 8192, 16, 1024);
        const uint64_t descB2 = make_desc(sbase + 16384, 8192, 1024);
#pragma unroll
        for (int it = 0; it < G2_KB; it++) {
            const int s = (it + 1) % G2_STAGES;
            mbar_wait(bar_full2 + 8 * s, (it / G2_STAGES) & 1);
            if (threadIdx.x == 0 && (it == 0 || it == 7)) STAMP(3, 2 + it / 7);
            wgmma_fence();
            {
                const uint64_t da = descA2 + (uint64_t)((s * G2_STAGE) >> 4);
                const uint64_t db = descB2 + (uint64_t)((s * G2_STAGE) >> 4);
                wgmma_n128_k64(acc, da, da + 2, da + 4, da + 6, db, db + 128, db + 256, db + 384, it != 0);
            }
            wgmma_commit();
            if (it > 0 && it - 1 + G2_STAGES < G2_KB) {
                wgmma_wait<1>();
                if (lane == 0) mbar_arrive(bar_empty2 + 8 * (it % G2_STAGES));
            }
        }
        const int lr = wg * 64 + (warp & 3) * 16 + g;
        uint32_t xv[16], sv[16];
        mbar_wait(bar_epi, 0);
#pragma unroll
        for (int j = 0; j < 8; j++) {
#pragma unroll
            for (int hh = 0; hh < 2; hh++) {
                const int r = lr + 8 * hh;
                asm volatile("ld.shared.u32 %0, [%1];" : "=r"(xv[2 * j + hh]) : "r"(sX + r * 128 + ((j ^ (r & 7)) << 4) + 4 * t));
                const int c0 = 8 * j + 2 * t;
                const uint32_t sa = sS + (r >> 6) * 8192 + (((r & 63) >> 3) << 4) + (r & 7) * 2;
                uint16_t s0r, s1r;
                asm volatile("ld.shared.u16 %0, [%1];" : "=h"(s0r) : "r"((sa + c0 * 128) ^ ((c0 & 7) << 4)));
                asm volatile("ld.shared.u16 %0, [%1];" : "=h"(s1r) : "r"((sa + (c0 + 1) * 128) ^ (((c0 + 1) & 7) << 4)));
                sv[2 * j + hh] = (uint32_t)s0r | ((uint32_t)s1r << 16);
            }
        }
        wgmma_wait<0>();
        if (threadIdx.x == 0) STAMP(3, 4);
        {
            uint32_t remote, rbar;
            asm volatile("mapa.shared::cluster.u32 %0, %1, %2;" : "=r"(remote) : "r"(sXch + threadIdx.x * 16), "r"(kh ^ 1));
            asm volatile("mapa.shared::cluster.u32 %0, %1, %2;" : "=r"(rbar) : "r"(bar_xch), "r"(kh ^ 1));
            if (kh == 0) {
#pragma unroll
                for (int i = 0; i < 8; i++)
                    asm volatile("st.async.shared::cluster.mbarrier::complete_tx::bytes.v4.f32 [%0], {%1,%2,%3,%4}, [%5];" ::"r"(remote + i * 4096),
                                 "f"(acc[32 + 4 * i]), "f"(acc[33 + 4 * i]), "f"(acc[34 + 4 * i]), "f"(acc[35 + 4 * i]), "r"(rbar) : "memory");
            } else {
#pragma unroll
                for (int i = 0; i < 8; i++)
                    asm volatile("st.async.shared::cluster.mbarrier::complete_tx::bytes.v4.f32 [%0], {%1,%2,%3,%4}, [%5];" ::"r"(remote + i * 4096),
                                 "f"(acc[4 * i]), "f"(acc[1 + 4 * i]), "f"(acc[2 + 4 * i]), "f"(acc[3 + 4 * i]), "r"(rbar) : "memory");
#pragma unroll
                for (int i = 0; i < 32; i++) acc[i] = acc[32 + i];
            }
        }
        if (threadIdx.x == 0) STAMP(3, 6);
        mbar_wait(bar_xch, 0);
        if (threadIdx.x == 0) STAMP(3, 7);
#pragma unroll
        for (int j = 0; j < 8; j++) {
            float4 o;
            asm volatile("ld.shared.v4.f32 {%0,%1,%2,%3}, [%4];" : "=f"(o.x), "=f"(o.y), "=f"(o.z), "=f"(o.w) : "r"(sXch + threadIdx.x * 16 + j * 4096));
            acc[4 * j] += o.x; acc[4 * j + 1] += o.y; acc[4 * j + 2] += o.z; acc[4 * j + 3] += o.w;
        }
#pragma unroll
        for (int i = 0; i < 16; i++) {
            float f0 = bf16_round(acc[2 * i]), f1 = bf16_round(acc[2 * i + 1]);
            float g0 = bf16_round(__fdividef(f0, 1.0f + __expf(-f0)));
            float g1 = bf16_round(__fdividef(f1, 1.0f + __expf(-f1)));
            float o0 = bf_lo(xv[i]) + bf16_round(bf_lo(sv[i]) * g0);
            float o1 = bf_hi(xv[i]) + bf16_round(bf_hi(sv[i]) * g1);
            xv[i] = pack_bf16(o0, o1);
        }
#pragma unroll
        for (int j = 0; j < 8; j++) {
#pragma unroll
            for (int hh = 0; hh < 2; hh++) {
                const int r = lr + 8 * hh;
                asm volatile("st.shared.u32 [%0], %1;" ::"r"(sX + r * 128 + ((j ^ (r & 7)) << 4) + 4 * t), "r"(xv[2 * j + hh]) : "memory");
            }
        }
        if (threadIdx.x == 0) STAMP(3, 9);
        fence_async_smem();
        __syncwarp();
        if (lane == 0) {
            tma_store_2d(&tm_out, sX + (wg * 64 + (warp & 3) * 16) * 128, col_fin, rb * 128 + wg * 64 + (warp & 3) * 16);
            bulk_commit();
            bulk_wait_read<0>();
        }
        }
        if (threadIdx.x == 0) STAMP(3, 5);
        named_bar(4, 256);
        if (threadIdx.x == 0) {
            const unsigned int old = atomicAdd(&g_done_count, 1u);
            if (old == gridDim.x - 1) {
                g_ln_count = 0; g_conv_count = 0; g_done_count = 0;
                for (int i = 0; i < 32; i++) g_h_count[i] = 0;
            }
        }
    }
}

typedef CUresult (*EncodeFn)(CUtensorMap*, CUtensorMapDataType, cuuint32_t, void*, const cuuint64_t*, const cuuint64_t*,
                             const cuuint32_t*, const cuuint32_t*, CUtensorMapInterleave, CUtensorMapSwizzle,
                             CUtensorMapL2promotion, CUtensorMapFloatOOBfill);

void make_map(EncodeFn fn, CUtensorMap* m, const void* ptr, uint64_t inner, uint64_t outer, uint32_t box_in, uint32_t box_out,
              CUtensorMapSwizzle swz = CU_TENSOR_MAP_SWIZZLE_128B) {
    cuuint64_t dims[2] = {inner, outer};
    cuuint64_t strides[1] = {inner * 2};
    cuuint32_t box[2] = {box_in, box_out};
    cuuint32_t es[2] = {1, 1};
    fn(m, CU_TENSOR_MAP_DATA_TYPE_BFLOAT16, 2, const_cast<void*>(ptr), dims, strides, box, es, CU_TENSOR_MAP_INTERLEAVE_NONE,
       swz, CU_TENSOR_MAP_L2_PROMOTION_L2_256B, CU_TENSOR_MAP_FLOAT_OOB_FILL_NONE);
}
void make_map3(EncodeFn fn, CUtensorMap* m, const void* ptr, uint64_t cols, uint64_t rows, uint32_t atom, uint32_t box_rows,
               uint32_t box_atoms, CUtensorMapSwizzle swz) {
    cuuint64_t dims[3] = {atom, rows, cols / atom};
    cuuint64_t strides[2] = {cols * 2, (cuuint64_t)atom * 2};
    cuuint32_t box[3] = {atom, box_rows, box_atoms};
    cuuint32_t es[3] = {1, 1, 1};
    fn(m, CU_TENSOR_MAP_DATA_TYPE_BFLOAT16, 3, const_cast<void*>(ptr), dims, strides, box, es, CU_TENSOR_MAP_INTERLEAVE_NONE,
       swz, CU_TENSOR_MAP_L2_PROMOTION_L2_256B, CU_TENSOR_MAP_FLOAT_OOB_FILL_NONE);
}

template <typename... Args>
void launch_pdl(void (*kern)(Args...), int grid, int block, int smem, bool pdl, int cluster, Args... args) {
    cudaLaunchConfig_t cfg = {};
    cfg.gridDim = dim3(grid); cfg.blockDim = dim3(block); cfg.dynamicSmemBytes = smem; cfg.stream = cudaStreamPerThread;
    cudaLaunchAttribute at[2];
    int n = 0;
    if (pdl) {
        at[n].id = cudaLaunchAttributeProgrammaticStreamSerialization;
        at[n].val.programmaticStreamSerializationAllowed = 1;
        n++;
    }
    if (cluster > 1) {
        at[n].id = cudaLaunchAttributeClusterDimension;
        at[n].val.clusterDim.x = cluster; at[n].val.clusterDim.y = 1; at[n].val.clusterDim.z = 1;
        n++;
    }
    cfg.attrs = at; cfg.numAttrs = n;
    cudaLaunchKernelEx(&cfg, kern, args...);
}

}

extern "C" void kernel_launch(void* const* d_in, const int* in_sizes, int n_in, void* d_out, int out_size) {
    const __nv_bfloat16* x = (const __nv_bfloat16*)d_in[0];
    const __nv_bfloat16* A_re = (const __nv_bfloat16*)d_in[1];
    const __nv_bfloat16* A_im = (const __nv_bfloat16*)d_in[2];
    const __nv_bfloat16* B_re = (const __nv_bfloat16*)d_in[3];
    const __nv_bfloat16* B_im = (const __nv_bfloat16*)d_in[4];
    const __nv_bfloat16* C_re = (const __nv_bfloat16*)d_in[5];
    const __nv_bfloat16* C_im = (const __nv_bfloat16*)d_in[6];
    const __nv_bfloat16* log_dt = (const __nv_bfloat16*)d_in[7];
    const __nv_bfloat16* Dskip = (const __nv_bfloat16*)d_in[8];
    const __nv_bfloat16* wg = (const __nv_bfloat16*)d_in[10];
    const __nv_bfloat16* wu = (const __nv_bfloat16*)d_in[11];
    const __nv_bfloat16* wd = (const __nv_bfloat16*)d_in[12];
    __nv_bfloat16* out = (__nv_bfloat16*)d_out;

    static bool init = false;
    static CUtensorMap tm_xn, tm_wg4, tm_wu4, tm_wg3, tm_wu3, tm_hst, tm_hst96, tm_h, tm_wd, tm_x, tm_sT, tm_out;
    static const void* last_ptrs[5] = {nullptr, nullptr, nullptr, nullptr, nullptr};
    if (!init || last_ptrs[0] != wg || last_ptrs[1] != wu || last_ptrs[2] != wd || last_ptrs[3] != x || last_ptrs[4] != out) {
        void* fnp = nullptr;
        cudaDriverEntryPointQueryResult qres;
        cudaGetDriverEntryPoint("cuTensorMapEncodeTiled", &fnp, cudaEnableDefault, &qres);
        EncodeFn fn = (EncodeFn)fnp;
        void *p_xn, *p_h, *p_sT;
        cudaGetSymbolAddress(&p_xn, g_xn);
        cudaGetSymbolAddress(&p_h, g_h);
        cudaGetSymbolAddress(&p_sT, g_sT);
        make_map(fn, &tm_xn, p_xn, D_, L_, 64, 128);
        make_map3(fn, &tm_wg4, wg, F_, D_, 32, 32, 4, CU_TENSOR_MAP_SWIZZLE_64B);
        make_map3(fn, &tm_wu4, wu, F_, D_, 32, 32, 4, CU_TENSOR_MAP_SWIZZLE_64B);
        make_map3(fn, &tm_wg3, wg, F_, D_, 32, 32, 3, CU_TENSOR_MAP_SWIZZLE_64B);
        make_map3(fn, &tm_wu3, wu, F_, D_, 32, 32, 3, CU_TENSOR_MAP_SWIZZLE_64B);
        make_map(fn, &tm_hst, p_h, F_, L_, 16, 16, CU_TENSOR_MAP_SWIZZLE_NONE);
        make_map(fn, &tm_hst96, p_h, F_, L_, 96, 16, CU_TENSOR_MAP_SWIZZLE_NONE);
        make_map(fn, &tm_h, p_h, F_, L_, 64, 128);
        make_map3(fn, &tm_wd, wd, D_, F_, 64, 64, 2, CU_TENSOR_MAP_SWIZZLE_128B);
        make_map(fn, &tm_x, x, D_, L_, 64, 128);
        make_map(fn, &tm_sT, p_sT, L_, D_, 64, 64);
        make_map(fn, &tm_out, out, D_, L_, 64, 16);
        cudaFuncSetAttribute(mega_kernel, cudaFuncAttributeMaxDynamicSharedMemorySize, MG_SMEM);
        last_ptrs[0] = wg; last_ptrs[1] = wu; last_ptrs[2] = wd; last_ptrs[3] = x; last_ptrs[4] = out;
        init = true;
    }
    MegaParams P = {x, A_re, A_im, B_re, B_im, C_re, C_im, log_dt, Dskip, wg, wu, wd};
    launch_pdl(mega_kernel, 128, 384, MG_SMEM, false, 2, P, tm_xn, tm_wg4, tm_wu4, tm_wg3, tm_wu3, tm_h, tm_wd, tm_x, tm_sT, tm_out);
}
```

```cpp
#include <cuda_runtime.h>
#include <cuda_bf16.h>
#include <cuda.h>
#include <stdint.h>

namespace {

constexpr int L_ = 2048, D_ = 512, NS_ = 128, F_ = 1792;

__device__ __align__(1024) __nv_bfloat16 g_xn[L_ * D_];
__device__ __align__(1024) __nv_bfloat16 g_xnT[D_ * L_];
__device__ __align__(1024) __nv_bfloat16 g_sT[D_ * L_];
__device__ __align__(1024) __nv_bfloat16 g_h[L_ * F_];
__device__ unsigned int g_ln_count, g_conv_count, g_done_count, g_h_count[32];

#define STAMP(k, i)

__device__ __forceinline__ uint32_t smem_u32(const void* p) { return (uint32_t)__cvta_generic_to_shared(p); }
__device__ __forceinline__ void pdl_wait() { asm volatile("griddepcontrol.wait;" ::: "memory"); }
__device__ __forceinline__ void pdl_launch() { asm volatile("griddepcontrol.launch_dependents;" ::: "memory"); }

__device__ __forceinline__ void mbar_init(uint32_t bar, uint32_t cnt) {
    asm volatile("mbarrier.init.shared::cta.b64 [%0], %1;" ::"r"(bar), "r"(cnt) : "memory");
}
__device__ __forceinline__ void mbar_expect_tx(uint32_t bar, uint32_t bytes) {
    asm volatile("mbarrier.arrive.expect_tx.shared::cta.b64 _, [%0], %1;" ::"r"(bar), "r"(bytes) : "memory");
}
__device__ __forceinline__ void mbar_arrive(uint32_t bar) {
    asm volatile("mbarrier.arrive.shared::cta.b64 _, [%0];" ::"r"(bar) : "memory");
}
__device__ __forceinline__ void mbar_wait(uint32_t bar, uint32_t parity) {
    asm volatile(
        "{\n.reg .pred p;\n"
        "WAIT_LOOP:\n"
        "mbarrier.try_wait.parity.shared::cta.b64 p, [%0], %1;\n"
        "@p bra WAIT_DONE;\n"
        "bra WAIT_LOOP;\n"
        "WAIT_DONE:\n}\n" ::"r"(bar), "r"(parity) : "memory");
}
__device__ __forceinline__ void tma_load_2d(uint32_t dst, const CUtensorMap* tm, int c0, int c1, uint32_t bar) {
    asm volatile(
        "cp.async.bulk.tensor.2d.shared::cluster.global.mbarrier::complete_tx::bytes [%0], [%1, {%3, %4}], [%2];"
        ::"r"(dst), "l"((uint64_t)tm), "r"(bar), "r"(c0), "r"(c1) : "memory");
}
__device__ __forceinline__ void prefetch_tmap(const CUtensorMap* tm) {
    asm volatile("prefetch.tensormap [%0];" ::"l"((uint64_t)tm) : "memory");
}
__device__ __forceinline__ uint64_t make_desc(uint32_t addr, uint32_t lbo, uint32_t sbo, uint64_t mode = 1) {
    uint64_t d = 0;
    d |= (uint64_t)((addr & 0x3FFFF) >> 4);
    d |= (uint64_t)((lbo >> 4) & 0x3FFF) << 16;
    d |= (uint64_t)((sbo >> 4) & 0x3FFF) << 32;
    d |= mode << 62;
    return d;
}
__device__ __forceinline__ void fence_async_smem() { asm volatile("fence.proxy.async.shared::cta;" ::: "memory"); }
__device__ __forceinline__ void wgmma_fence() { asm volatile("wgmma.fence.sync.aligned;" ::: "memory"); }
__device__ __forceinline__ void wgmma_commit() { asm volatile("wgmma.commit_group.sync.aligned;" ::: "memory"); }
template <int N> __device__ __forceinline__ void wgmma_wait() {
    asm volatile("wgmma.wait_group.sync.aligned %0;" ::"n"(N) : "memory");
}

#define R8(a, i) "+f"(a[i + 0]), "+f"(a[i + 1]), "+f"(a[i + 2]), "+f"(a[i + 3]), "+f"(a[i + 4]), "+f"(a[i + 5]), "+f"(a[i + 6]), "+f"(a[i + 7])

__device__ __forceinline__ void wgmma_n256_k32(float* a, uint64_t da0, uint64_t da1, uint64_t db0, uint64_t db1, int scale_d) {
    asm volatile(
        "{\n.reg .pred p;\nsetp.ne.b32 p, %132, 0;\n"
        "wgmma.mma_async.sync.aligned.m64n256k16.f32.bf16.bf16 {%0,%1,%2,%3,%4,%5,%6,%7,%8,%9,%10,%11,%12,%13,%14,%15,%16,%17,%18,%19,%20,%21,%22,%23,%24,%25,%26,%27,%28,%29,%30,%31,%32,%33,%34,%35,%36,%37,%38,%39,%40,%41,%42,%43,%44,%45,%46,%47,%48,%49,%50,%51,%52,%53,%54,%55,%56,%57,%58,%59,%60,%61,%62,%63,%64,%65,%66,%67,%68,%69,%70,%71,%72,%73,%74,%75,%76,%77,%78,%79,%80,%81,%82,%83,%84,%85,%86,%87,%88,%89,%90,%91,%92,%93,%94,%95,%96,%97,%98,%99,%100,%101,%102,%103,%104,%105,%106,%107,%108,%109,%110,%111,%112,%113,%114,%115,%116,%117,%118,%119,%120,%121,%122,%123,%124,%125,%126,%127}, %128, %130, p, 1, 1, 0, 1;\n"
        "wgmma.mma_async.sync.aligned.m64n256k16.f32.bf16.bf16 {%0,%1,%2,%3,%4,%5,%6,%7,%8,%9,%10,%11,%12,%13,%14,%15,%16,%17,%18,%19,%20,%21,%22,%23,%24,%25,%26,%27,%28,%29,%30,%31,%32,%33,%34,%35,%36,%37,%38,%39,%40,%41,%42,%43,%44,%45,%46,%47,%48,%49,%50,%51,%52,%53,%54,%55,%56,%57,%58,%59,%60,%61,%62,%63,%64,%65,%66,%67,%68,%69,%70,%71,%72,%73,%74,%75,%76,%77,%78,%79,%80,%81,%82,%83,%84,%85,%86,%87,%88,%89,%90,%91,%92,%93,%94,%95,%96,%97,%98,%99,%100,%101,%102,%103,%104,%105,%106,%107,%108,%109,%110,%111,%112,%113,%114,%115,%116,%117,%118,%119,%120,%121,%122,%123,%124,%125,%126,%127}, %129, %131, 1, 1, 1, 0, 1;\n"
        "}\n"
        : R8(a, 0), R8(a, 8), R8(a, 16), R8(a, 24), R8(a, 32), R8(a, 40), R8(a, 48), R8(a, 56), R8(a, 64), R8(a, 72), R8(a, 80), R8(a, 88), R8(a, 96), R8(a, 104), R8(a, 112), R8(a, 120)
        : "l"(da0), "l"(da1), "l"(db0), "l"(db1), "r"(scale_d));
}
__device__ __forceinline__ void wgmma_n192_k32(float* a, uint64_t da0, uint64_t da1, uint64_t db0, uint64_t db1, int scale_d) {
    asm volatile(
        "{\n.reg .pred p;\nsetp.ne.b32 p, %100, 0;\n"
        "wgmma.mma_async.sync.aligned.m64n192k16.f32.bf16.bf16 {%0,%1,%2,%3,%4,%5,%6,%7,%8,%9,%10,%11,%12,%13,%14,%15,%16,%17,%18,%19,%20,%21,%22,%23,%24,%25,%26,%27,%28,%29,%30,%31,%32,%33,%34,%35,%36,%37,%38,%39,%40,%41,%42,%43,%44,%45,%46,%47,%48,%49,%50,%51,%52,%53,%54,%55,%56,%57,%58,%59,%60,%61,%62,%63,%64,%65,%66,%67,%68,%69,%70,%71,%72,%73,%74,%75,%76,%77,%78,%79,%80,%81,%82,%83,%84,%85,%86,%87,%88,%89,%90,%91,%92,%93,%94,%95}, %96, %98, p, 1, 1, 0, 1;\n"
        "wgmma.mma_async.sync.aligned.m64n192k16.f32.bf16.bf16 {%0,%1,%2,%3,%4,%5,%6,%7,%8,%9,%10,%11,%12,%13,%14,%15,%16,%17,%18,%19,%20,%21,%22,%23,%24,%25,%26,%27,%28,%29,%30,%31,%32,%33,%34,%35,%36,%37,%38,%39,%40,%41,%42,%43,%44,%45,%46,%47,%48,%49,%50,%51,%52,%53,%54,%55,%56,%57,%58,%59,%60,%61,%62,%63,%64,%65,%66,%67,%68,%69,%70,%71,%72,%73,%74,%75,%76,%77,%78,%79,%80,%81,%82,%83,%84,%85,%86,%87,%88,%89,%90,%91,%92,%93,%94,%95}, %97, %99, 1, 1, 1, 0, 1;\n"
        "}\n"
        : R8(a, 0), R8(a, 8), R8(a, 16), R8(a, 24), R8(a, 32), R8(a, 40), R8(a, 48), R8(a, 56), R8(a, 64), R8(a, 72), R8(a, 80), R8(a, 88)
        : "l"(da0), "l"(da1), "l"(db0), "l"(db1), "r"(scale_d));
}
__device__ __forceinline__ void wgmma_n192(float* a, uint64_t da0, uint64_t db0, int scale_d) {
    asm volatile(
        "{\n.reg .pred p;\nsetp.ne.b32 p, %98, 0;\n"
        "wgmma.mma_async.sync.aligned.m64n192k16.f32.bf16.bf16 {%0,%1,%2,%3,%4,%5,%6,%7,%8,%9,%10,%11,%12,%13,%14,%15,%16,%17,%18,%19,%20,%21,%22,%23,%24,%25,%26,%27,%28,%29,%30,%31,%32,%33,%34,%35,%36,%37,%38,%39,%40,%41,%42,%43,%44,%45,%46,%47,%48,%49,%50,%51,%52,%53,%54,%55,%56,%57,%58,%59,%60,%61,%62,%63,%64,%65,%66,%67,%68,%69,%70,%71,%72,%73,%74,%75,%76,%77,%78,%79,%80,%81,%82,%83,%84,%85,%86,%87,%88,%89,%90,%91,%92,%93,%94,%95}, %96, %97, p, 1, 1, 0, 1;\n"
        "}\n"
        : R8(a, 0), R8(a, 8), R8(a, 16), R8(a, 24), R8(a, 32), R8(a, 40), R8(a, 48), R8(a, 56), R8(a, 64), R8(a, 72), R8(a, 80), R8(a, 88)
        : "l"(da0), "l"(db0), "r"(scale_d));
}
__device__ __forceinline__ void wgmma_n128_k64(float* a, uint64_t da0, uint64_t da1, uint64_t da2, uint64_t da3,
                                               uint64_t db0, uint64_t db1, uint64_t db2, uint64_t db3, int scale_d) {
    asm volatile(
        "{\n.reg .pred p;\nsetp.ne.b32 p, %72, 0;\n"
        "wgmma.mma_async.sync.aligned.m64n128k16.f32.bf16.bf16 {%0,%1,%2,%3,%4,%5,%6,%7,%8,%9,%10,%11,%12,%13,%14,%15,%16,%17,%18,%19,%20,%21,%22,%23,%24,%25,%26,%27,%28,%29,%30,%31,%32,%33,%34,%35,%36,%37,%38,%39,%40,%41,%42,%43,%44,%45,%46,%47,%48,%49,%50,%51,%52,%53,%54,%55,%56,%57,%58,%59,%60,%61,%62,%63}, %64, %68, p, 1, 1, 0, 1;\n"
        "wgmma.mma_async.sync.aligned.m64n128k16.f32.bf16.bf16 {%0,%1,%2,%3,%4,%5,%6,%7,%8,%9,%10,%11,%12,%13,%14,%15,%16,%17,%18,%19,%20,%21,%22,%23,%24,%25,%26,%27,%28,%29,%30,%31,%32,%33,%34,%35,%36,%37,%38,%39,%40,%41,%42,%43,%44,%45,%46,%47,%48,%49,%50,%51,%52,%53,%54,%55,%56,%57,%58,%59,%60,%61,%62,%63}, %65, %69, 1, 1, 1, 0, 1;\n"
        "wgmma.mma_async.sync.aligned.m64n128k16.f32.bf16.bf16 {%0,%1,%2,%3,%4,%5,%6,%7,%8,%9,%10,%11,%12,%13,%14,%15,%16,%17,%18,%19,%20,%21,%22,%23,%24,%25,%26,%27,%28,%29,%30,%31,%32,%33,%34,%35,%36,%37,%38,%39,%40,%41,%42,%43,%44,%45,%46,%47,%48,%49,%50,%51,%52,%53,%54,%55,%56,%57,%58,%59,%60,%61,%62,%63}, %66, %70, 1, 1, 1, 0, 1;\n"
        "wgmma.mma_async.sync.aligned.m64n128k16.f32.bf16.bf16 {%0,%1,%2,%3,%4,%5,%6,%7,%8,%9,%10,%11,%12,%13,%14,%15,%16,%17,%18,%19,%20,%21,%22,%23,%24,%25,%26,%27,%28,%29,%30,%31,%32,%33,%34,%35,%36,%37,%38,%39,%40,%41,%42,%43,%44,%45,%46,%47,%48,%49,%50,%51,%52,%53,%54,%55,%56,%57,%58,%59,%60,%61,%62,%63}, %67, %71, 1, 1, 1, 0, 1;\n"
        "}\n"
        : R8(a, 0), R8(a, 8), R8(a, 16), R8(a, 24), R8(a, 32), R8(a, 40), R8(a, 48), R8(a, 56)
        : "l"(da0), "l"(da1), "l"(da2), "l"(da3), "l"(db0), "l"(db1), "l"(db2), "l"(db3), "r"(scale_d));
}

__device__ __forceinline__ float bf16_round(float x) {
    uint32_t p; asm("cvt.rn.bf16x2.f32 %0, %1, %2;" : "=r"(p) : "f"(x), "f"(0.0f));
    return __uint_as_float(p);
}
__device__ __forceinline__ uint32_t pack_bf16(float lo, float hi) {
    __nv_bfloat162 v = __floats2bfloat162_rn(lo, hi);
    return *reinterpret_cast<uint32_t*>(&v);
}
__device__ __forceinline__ float bf_lo(uint32_t v) { return __uint_as_float(v << 16); }
__device__ __forceinline__ float bf_hi(uint32_t v) { return __uint_as_float(v & 0xFFFF0000u); }

struct cplx { float r, i; };
__device__ __forceinline__ cplx cmul(cplx a, cplx b) {
    cplx c; c.r = a.r * b.r - a.i * b.i; c.i = a.r * b.i + a.i * b.r; return c;
}
__device__ __forceinline__ cplx csq(cplx a) {
    cplx c; c.r = a.r * a.r - a.i * a.i; c.i = 2.0f * a.r * a.i; return c;
}
__device__ __forceinline__ cplx cexp_m(float ar2, float ai2, float m) {
    float mag;
    asm("ex2.approx.ftz.f32 %0, %1;" : "=f"(mag) : "f"(ar2 * m));
    float rr = ai2 * m;
    rr -= (rr + 12582912.0f) - 12582912.0f;
    float th = rr * 6.283185307179586f;
    cplx c; c.r = mag * __cosf(th); c.i = mag * __sinf(th);
    return c;
}
__device__ __forceinline__ uint32_t to_tf32(float x) { return __float_as_uint(x) + 0x1000u; }
__device__ __forceinline__ void mma_tf32(float* c, uint32_t a0, uint32_t a1, uint32_t a2, uint32_t a3, uint32_t b0, uint32_t b1) {
    asm volatile("mma.sync.aligned.m16n8k8.row.col.f32.tf32.tf32.f32 {%0,%1,%2,%3}, {%4,%5,%6,%7}, {%8,%9}, {%0,%1,%2,%3};"
                 : "+f"(c[0]), "+f"(c[1]), "+f"(c[2]), "+f"(c[3])
                 : "r"(a0), "r"(a1), "r"(a2), "r"(a3), "r"(b0), "r"(b1));
}
__device__ __forceinline__ void mma_bf16(float* c, uint32_t a0, uint32_t a1, uint32_t a2, uint32_t a3, uint32_t b0, uint32_t b1) {
    asm volatile("mma.sync.aligned.m16n8k16.row.col.f32.bf16.bf16.f32 {%0,%1,%2,%3}, {%4,%5,%6,%7}, {%8,%9}, {%0,%1,%2,%3};"
                 : "+f"(c[0]), "+f"(c[1]), "+f"(c[2]), "+f"(c[3])
                 : "r"(a0), "r"(a1), "r"(a2), "r"(a3), "r"(b0), "r"(b1));
}
__device__ __forceinline__ void named_bar(int id, int n) { asm volatile("bar.sync %0, %1;" ::"r"(id), "r"(n) : "memory"); }
__device__ __forceinline__ void ldsm_x4(uint32_t addr, uint32_t& r0, uint32_t& r1, uint32_t& r2, uint32_t& r3) {
    asm volatile("ldmatrix.sync.aligned.m8n8.x4.shared.b16 {%0,%1,%2,%3}, [%4];" : "=r"(r0), "=r"(r1), "=r"(r2), "=r"(r3) : "r"(addr));
}
__device__ __forceinline__ void ldsm_x4_t(uint32_t addr, uint32_t& r0, uint32_t& r1, uint32_t& r2, uint32_t& r3) {
    asm volatile("ldmatrix.sync.aligned.m8n8.x4.trans.shared.b16 {%0,%1,%2,%3}, [%4];" : "=r"(r0), "=r"(r1), "=r"(r2), "=r"(r3) : "r"(addr));
}

constexpr int CV_CH = 4;
constexpr int CV_O_CONST = 0;
constexpr int CV_O_KP = 12288;
constexpr int CV_EARLY = 12288 + 7776;
constexpr int CV_O_Q = 0;
constexpr int CV_O_Q2 = CV_O_Q + 2304;
constexpr int CV_O_Q3 = CV_O_Q2 + 1024;
constexpr int CV_O_Q4X = CV_O_Q3 + 768;
constexpr int CV_O_W3 = CV_O_Q4X + 256;
constexpr int CV_O_W5 = CV_O_W3 + 3104;
constexpr int CV_O_W7 = CV_O_W5 + 3104;
constexpr int CV_O_W9 = CV_O_W7 + 2048;
constexpr int CV_O_U = CV_O_W9 + 2048;
constexpr int CV_LATE = CV_O_U + 4352;
constexpr int CV_LATE_BASE = 229376 - CV_CH * CV_LATE;
constexpr int CV_TILE_OFF = CV_CH * CV_EARLY;
static_assert(CV_TILE_OFF + 16 * (D_ + 8) * 2 <= CV_LATE_BASE && CV_LATE_BASE >= 131072 + 16384, "front layout");
static_assert(CV_O_W3 >= 4096 && CV_O_U - CV_O_W3 >= 8192 && (CV_LATE % 16) == 0 && (CV_EARLY % 16) == 0, "front layout");

constexpr int LN_ROWS = 16;

struct MegaParams {
    const __nv_bfloat16 *x, *A_re, *A_im, *B_re, *B_im, *C_re, *C_im, *log_dt, *Dskip, *wg, *wu, *wd;
};

__device__ __forceinline__ void channel_consts(uint8_t* smem, int cc_, int dd, const MegaParams& P) {
    const int lane = threadIdx.x & 31;
    const __nv_bfloat16 *A_re = P.A_re, *A_im = P.A_im, *B_re = P.B_re, *B_im = P.B_im, *C_re = P.C_re, *C_im = P.C_im, *log_dt = P.log_dt;
    float4* sc = reinterpret_cast<float4*>(smem + cc_ * CV_EARLY + CV_O_CONST);
    {
        __nv_bfloat16 pr[4][6];
#pragma unroll
        for (int j = 0; j < 4; j++) {
            const size_t off = (size_t)dd * NS_ + lane + 32 * j;
            pr[j][0] = A_re[off]; pr[j][1] = A_im[off]; pr[j][2] = B_re[off]; pr[j][3] = B_im[off]; pr[j][4] = C_re[off]; pr[j][5] = C_im[off];
        }
        const float dt = bf16_round(expf(__bfloat162float(log_dt[dd])));
        float tail = 0.f;
#pragma unroll
        for (int j = 0; j < 4; j++) {
            const float ar = dt * __bfloat162float(pr[j][0]), ai = dt * __bfloat162float(pr[j][1]);
            const cplx db = {dt * __bfloat162float(pr[j][2]), dt * __bfloat162float(pr[j][3])};
            const cplx cc = {__bfloat162float(pr[j][4]), __bfloat162float(pr[j][5])};
            const cplx cb = cmul(cc, db);
            const float ar2 = ar * 1.4426950408889634f, ai2 = ai * 0.15915494309189535f;
            const cplx e8 = cexp_m(ar2, ai2, 8.f), e128 = cexp_m(ar2, ai2, 128.f);
            const cplx cb8 = cmul(cb, e8);
            const cplx e256 = cexp_m(ar2, ai2, 256.f), e512 = cexp_m(ar2, ai2, 512.f), e1024 = cexp_m(ar2, ai2, 1024.f);
            const cplx c256 = cmul(cb, e256), c512 = cmul(cb, e512), c1024 = cmul(cb, e1024);
            const cplx c768 = cmul(c512, e256), c1280 = cmul(c1024, e256), c1536 = cmul(c1024, e512);
            const cplx c1792 = cmul(c1536, e256);
            tail += cmul(c1024, e1024).r;
            float4* c = sc + (lane + 32 * j) * 6;
            c[0] = make_float4(ar2, ai2, cb.r, cb.i);
            c[1] = make_float4(e128.r, e128.i, cb8.r, cb8.i);
            c[2] = make_float4(c256.r, c256.i, e8.r, e8.i);
            c[3] = make_float4(c512.r, c512.i, c768.r, c768.i);
            c[4] = make_float4(c1024.r, c1024.i, c1280.r, c1280.i);
            c[5] = make_float4(c1536.r, c1536.i, c1792.r, c1792.i);
        }
#pragma unroll
        for (int o = 16; o > 0; o >>= 1) tail += __shfl_xor_sync(0xffffffffu, tail, o);
        if (lane == 0) {
            float* kp = reinterpret_cast<float*>(smem + cc_ * CV_EARLY + CV_O_KP);
            kp[640] = tail; kp[648 + 640] = 0.f; kp[1296 + 640] = 0.f;
        }
    }
}

__device__ __forceinline__ void ln_phase(uint8_t* smem, bool is_conv, int d0, const MegaParams& P) {
    const int warp = threadIdx.x >> 5, lane = threadIdx.x & 31;
    const __nv_bfloat16 *x = P.x, *wg = P.wg, *wu = P.wu, *wd = P.wd;
    __nv_bfloat16 (*tile)[D_ + 8] = reinterpret_cast<__nv_bfloat16 (*)[D_ + 8]>(smem + CV_TILE_OFF);
    if (warp < 8) {
        const int row = blockIdx.x * LN_ROWS + warp * 2;
        uint4 xv[2][2];
#pragma unroll
        for (int r = 0; r < 2; r++) {
            xv[r][0] = *reinterpret_cast<const uint4*>(x + (size_t)(row + r) * D_ + lane * 8);
            xv[r][1] = *reinterpret_cast<const uint4*>(x + (size_t)(row + r) * D_ + 256 + lane * 8);
        }
        float f[2][16], sm[2], q[2];
#pragma unroll
        for (int r = 0; r < 2; r++) {
            const uint32_t wv[8] = {xv[r][0].x, xv[r][0].y, xv[r][0].z, xv[r][0].w, xv[r][1].x, xv[r][1].y, xv[r][1].z, xv[r][1].w};
#pragma unroll
            for (int i = 0; i < 8; i++) { f[r][2 * i] = bf_lo(wv[i]); f[r][2 * i + 1] = bf_hi(wv[i]); }
            sm[r] = 0.f;
#pragma unroll
            for (int i = 0; i < 16; i++) sm[r] += f[r][i];
        }
#pragma unroll
        for (int o = 16; o > 0; o >>= 1) { sm[0] += __shfl_xor_sync(0xffffffffu, sm[0], o); sm[1] += __shfl_xor_sync(0xffffffffu, sm[1], o); }
#pragma unroll
        for (int r = 0; r < 2; r++) {
            sm[r] *= (1.0f / D_);
            q[r] = 0.f;
#pragma unroll
            for (int i = 0; i < 16; i++) { float dd = f[r][i] - sm[r]; q[r] += dd * dd; }
        }
#pragma unroll
        for (int o = 16; o > 0; o >>= 1) { q[0] += __shfl_xor_sync(0xffffffffu, q[0], o); q[1] += __shfl_xor_sync(0xffffffffu, q[1], o); }
#pragma unroll
        for (int r = 0; r < 2; r++) {
            const float mb = bf16_round(sm[r]);
            const float vb = bf16_round(q[r] * (1.0f / D_));
            const float den = bf16_round(sqrtf(bf16_round(vb + 1e-5f)));
            uint32_t o[8];
#pragma unroll
            for (int i = 0; i < 8; i++) {
                float a = __fdiv_rn(bf16_round(f[r][2 * i] - mb), den);
                float b = __fdiv_rn(bf16_round(f[r][2 * i + 1] - mb), den);
                o[i] = pack_bf16(a, b);
            }
            __nv_bfloat16* dst = g_xn + (size_t)(row + r) * D_;
            *reinterpret_cast<uint4*>(dst + lane * 8) = make_uint4(o[0], o[1], o[2], o[3]);
            *reinterpret_cast<uint4*>(dst + 256 + lane * 8) = make_uint4(o[4], o[5], o[6], o[7]);
            *reinterpret_cast<uint4*>(&tile[warp * 2 + r][lane * 8]) = make_uint4(o[0], o[1], o[2], o[3]);
            *reinterpret_cast<uint4*>(&tile[warp * 2 + r][256 + lane * 8]) = make_uint4(o[4], o[5], o[6], o[7]);
        }
    } else if (is_conv) {
        channel_consts(smem, warp - 8, d0 + warp - 8, P);
    }
    __syncthreads();
    if (threadIdx.x == 0) STAMP(0, 3);
#pragma unroll
    for (int rep = 0; rep < 2; rep++) {
        const int c = threadIdx.x + 384 * rep;
        if (c < D_) {
            uint32_t ot[8];
#pragma unroll
            for (int i = 0; i < 8; i++) {
                uint32_t lo = *reinterpret_cast<const uint16_t*>(&tile[2 * i][c]);
                uint32_t hi = *reinterpret_cast<const uint16_t*>(&tile[2 * i + 1][c]);
                ot[i] = lo | (hi << 16);
            }
            __nv_bfloat16* dT = g_xnT + (size_t)c * L_ + blockIdx.x * LN_ROWS;
            *reinterpret_cast<uint4*>(dT) = make_uint4(ot[0], ot[1], ot[2], ot[3]);
            *reinterpret_cast<uint4*>(dT + 8) = make_uint4(ot[4], ot[5], ot[6], ot[7]);
        }
    }
    if (threadIdx.x < 336) {
        const int m = threadIdx.x / 112, i = threadIdx.x - m * 112;
        const char* wp = (const char*)(m == 0 ? wg : (m == 1 ? wu : wd));
        asm volatile("prefetch.global.L2 [%0];" ::"l"(wp + ((size_t)blockIdx.x * 112 + i) * 128));
    }
    fence_async_smem();
    __syncthreads();
    if (threadIdx.x == 0) STAMP(1, 1);
}

__device__ __forceinline__ void conv_round(uint8_t* smem, int d0, bool first, const MegaParams& P) {
    const int warp = threadIdx.x >> 5, lane = threadIdx.x & 31;
    const int ch = warp / 3, w = warp - 3 * ch, tc = threadIdx.x - 96 * ch;
    const int d = d0 + ch;
    const int g = lane >> 2, t = lane & 3;
    uint8_t* base = smem + CV_LATE_BASE + ch * CV_LATE;
    float4* s_const = reinterpret_cast<float4*>(smem + ch * CV_EARLY + CV_O_CONST);
    float* s_kp = reinterpret_cast<float*>(smem + ch * CV_EARLY + CV_O_KP);
    uint32_t* s_q = reinterpret_cast<uint32_t*>(base + CV_O_Q);
    uint32_t* s_q2 = reinterpret_cast<uint32_t*>(base + CV_O_Q2);
    uint32_t* s_q3 = reinterpret_cast<uint32_t*>(base + CV_O_Q3);
    uint32_t* s_q4 = reinterpret_cast<uint32_t*>(base + CV_O_Q4X);
    __nv_bfloat16* s_u = reinterpret_cast<__nv_bfloat16*>(base + CV_O_U);
    const int bar_id = 5 + ch;
    const __nv_bfloat16 p_dsk = P.Dskip[d];
    {
        float acc[5][4];
#pragma unroll
        for (int i = 0; i < 5; i++) { acc[i][0] = acc[i][1] = acc[i][2] = acc[i][3] = 0.f; }
        const float gf = (float)g;
        const int src4 = ((g & 3) << 2) | t;
#pragma unroll 2
        for (int s = w; s < 32; s += 3) {
            if (first && s == 17 && threadIdx.x == 352) asm volatile("red.release.gpu.global.add.u32 [%0], 1;" ::"l"(&g_ln_count) : "memory");
            const float4* c = s_const + (s * 4 + t) * 6;
            const float4 k0 = c[0], k1 = c[1], k2 = c[2];
            const float2 k3 = reinterpret_cast<const float2*>(c + 3)[g >> 2];
            const float2 k4 = reinterpret_cast<const float2*>(c + 4)[g >> 1];
            const cplx cb = {k0.z, k0.w}, e128 = {k1.x, k1.y}, cb8 = {k1.z, k1.w}, c256 = {k2.x, k2.y}, e8 = {k2.z, k2.w};
            const cplx c2 = {k3.x, k3.y}, c3 = {k4.x, k4.y};
            const cplx p1 = cexp_m(k0.x, k0.y, gf);
            const cplx p2 = csq(p1), p4 = csq(p2);
            const cplx r16a = csq(csq(p4));
            cplx q4;
            q4.r = __shfl_sync(0xffffffffu, p4.r, src4);
            q4.i = __shfl_sync(0xffffffffu, p4.i, src4);
            const cplx r16b = cmul(r16a, e128);
            const cplx f0a = cmul(cb, p1), f0b = cmul(cb8, p1), f1 = cmul(c256, p2), f2 = cmul(c2, q4);
            cplx f3 = cmul(c3, e8);
            if (!(g & 1)) f3 = c3;
            const uint32_t a0 = to_tf32(r16a.r), a1 = to_tf32(r16b.r), a2 = to_tf32(-r16a.i), a3 = to_tf32(-r16b.i);
            mma_tf32(acc[0], a0, a1, a2, a3, to_tf32(f0a.r), to_tf32(f0a.i));
            mma_tf32(acc[1], a0, a1, a2, a3, to_tf32(f0b.r), to_tf32(f0b.i));
            mma_tf32(acc[2], a0, a1, a2, a3, to_tf32(f1.r), to_tf32(f1.i));
            mma_tf32(acc[3], a0, a1, a2, a3, to_tf32(f2.r), to_tf32(f2.i));
            mma_tf32(acc[4], a0, a1, a2, a3, to_tf32(f3.r), to_tf32(f3.i));
        }
        float* kv = s_kp + w * 648;
#pragma unroll
        for (int hh = 0; hh < 2; hh++) {
            const int i = g + 8 * hh;
            *reinterpret_cast<float2*>(kv + 16 * i + 2 * t) = make_float2(acc[0][2 * hh], acc[0][2 * hh + 1]);
            *reinterpret_cast<float2*>(kv + 16 * i + 8 + 2 * t) = make_float2(acc[1][2 * hh], acc[1][2 * hh + 1]);
            *reinterpret_cast<float2*>(kv + 256 + 8 * i + 2 * t) = make_float2(acc[2][2 * hh], acc[2][2 * hh + 1]);
            *reinterpret_cast<float2*>(kv + 384 + 64 * (t >> 1) + 2 * (t & 1) + 4 * i) = make_float2(acc[3][2 * hh], acc[3][2 * hh + 1]);
            *reinterpret_cast<float2*>(kv + 512 + 32 * t + 2 * i) = make_float2(acc[4][2 * hh], acc[4][2 * hh + 1]);
        }
    }
    named_bar(bar_id, 96);
    if (threadIdx.x == 0) STAMP(1, 2);
#pragma unroll
    for (int i = 0; i < 7; i++) {
        const int idx = tc + 96 * i;
        if (idx < 641) s_kp[idx] = (s_kp[idx] + s_kp[648 + idx]) + s_kp[1296 + idx];
    }
    named_bar(bar_id, 96);
    {
        auto kdir = [&](int l) -> float {
            if (l < 0 || l > 514) return 0.f;
            const int idx = (l < 256) ? l : (l > 512 ? 384 : 128 + ((l + ((l >> 1) & 1)) >> 1));
            return s_kp[idx];
        };
#pragma unroll
        for (int i = 0; i < 6; i++) {
            const int e = tc + 96 * i;
            s_q[e] = pack_bf16(kdir(e - 16), kdir(e - 17));
        }
        if (tc < 64) {
            const int xx = 1008 + tc;
            const float k1024 = s_kp[512];
            s_q4[tc] = pack_bf16((xx == 1027 || xx == 1028) ? k1024 : 0.f, (xx == 1028 || xx == 1029) ? k1024 : 0.f);
        }
#pragma unroll
        for (int i = 0; i < 3; i++) {
            const int e = tc + 96 * i;
            if (e < 256) {
                const int a = e >> 6, ii = (e & 63) - 16;
                const int b = 385 + (a >> 1) + 2 * (a & 1);
                const float v0 = (ii >= 0 && ii < 32) ? s_kp[b + 4 * ii] : 0.f;
                const float v1 = (ii >= 1 && ii < 33) ? s_kp[b + 4 * (ii - 1)] : 0.f;
                s_q2[e] = pack_bf16(v0, v1);
            }
        }
#pragma unroll
        for (int a = 0; a < 2; a++) {
            const int jj = tc - 16;
            const float v0 = (jj >= 0 && jj < 64) ? s_kp[513 + a + 2 * jj] : 0.f;
            const float v1 = (jj >= 1 && jj < 65) ? s_kp[513 + a + 2 * (jj - 1)] : 0.f;
            s_q3[96 * a + tc] = pack_bf16(v0, v1);
        }
    }
    if (threadIdx.x == 0) STAMP(1, 3);
    if (first) {
        if (threadIdx.x == 0) {
            unsigned int v = 0;
            for (int spin = 0; spin < (1 << 22); spin++) {
                asm volatile("ld.acquire.gpu.global.u32 %0, [%1];" : "=r"(v) : "l"(&g_ln_count) : "memory");
                if (v >= gridDim.x) break;
            }
        }
        __syncthreads();
    }
    if (threadIdx.x == 0) STAMP(1, 4);
    {
        if (tc < 16) *reinterpret_cast<uint4*>(s_u + tc * 8) = make_uint4(0, 0, 0, 0);
        const uint4* src = reinterpret_cast<const uint4*>(g_xnT + (size_t)d * L_);
        uint4 v[3];
#pragma unroll
        for (int i = 0; i < 3; i++) if (tc + 96 * i < 256) v[i] = src[tc + 96 * i];
#pragma unroll
        for (int i = 0; i < 3; i++) if (tc + 96 * i < 256) *reinterpret_cast<uint4*>(s_u + 128 + (tc + 96 * i) * 8) = v[i];
        if (tc < 2) *reinterpret_cast<uint4*>(base + (tc ? CV_O_W5 : CV_O_W3)) = make_uint4(0, 0, 0, 0);
    }
    named_bar(bar_id, 96);
    if (w == 2) {
#pragma unroll 2
      for (int rep = 0; rep < 6; rep++) {
        const int m = lane + 32 * rep;
        float P[30];
        const uint4* up = reinterpret_cast<const uint4*>(s_u + 128 + 8 * m - 24);
        P[0] = 0.f;
#pragma unroll
        for (int c4 = 0; c4 < 4; c4++) {
            const uint4 v = up[c4];
            const uint32_t ww[4] = {v.x, v.y, v.z, v.w};
#pragma unroll
            for (int j = 0; j < 4; j++) {
                const int k = c4 * 8 + 2 * j;
                if (k + 1 <= 29) P[k + 1] = P[k] + bf_lo(ww[j]);
                if (k + 2 <= 29) P[k + 2] = P[k + 1] + bf_hi(ww[j]);
            }
        }
        uint32_t o3[4], o5[4], o7[4], o9[4];
#pragma unroll
        for (int j = 0; j < 4; j++) {
            const int i = 2 * j;
            o3[j] = pack_bf16(P[i + 22] - P[i + 19], P[i + 23] - P[i + 20]);
            o5[j] = pack_bf16(P[i + 19] - P[i + 14], P[i + 20] - P[i + 15]);
            o7[j] = pack_bf16(P[i + 20] - P[i + 13], P[i + 21] - P[i + 14]);
            o9[j] = pack_bf16(P[i + 13] - P[i + 4], P[i + 14] - P[i + 5]);
        }
        *reinterpret_cast<uint4*>(base + CV_O_W3 + 16 + m * 16) = make_uint4(o3[0], o3[1], o3[2], o3[3]);
        *reinterpret_cast<uint4*>(base + CV_O_W5 + 16 + m * 16) = make_uint4(o5[0], o5[1], o5[2], o5[3]);
        if (m < 128) {
            *reinterpret_cast<uint4*>(base + CV_O_W7 + m * 16) = make_uint4(o7[0], o7[1], o7[2], o7[3]);
            *reinterpret_cast<uint4*>(base + CV_O_W9 + m * 16) = make_uint4(o9[0], o9[1], o9[2], o9[3]);
        }
    }
      named_bar(bar_id, 96);
      if (first) channel_consts(smem, ch, d + CV_CH, P);
      return;
    }
    if (threadIdx.x == 0) STAMP(1, 5);
    const int hb = w;
    float acc[16][4];
#pragma unroll
    for (int i = 0; i < 16; i++) { acc[i][0] = acc[i][1] = acc[i][2] = acc[i][3] = 0.f; }
    const uint32_t sb_addr = smem_u32(base);
    const int mi = lane >> 3, rowi = lane & 7;
#pragma unroll 1
    for (int rr = 0; rr < 4; rr++) {
        const int r = 4 * hb + rr;
        uint32_t ub[16][2];
        {
            const uint32_t addr = sb_addr + CV_O_U + (uint32_t)((128 + 16 * (8 * (mi >> 1) + rowi - r) + 8 * (mi & 1)) * 2);
#pragma unroll
            for (int j = 0; j < 16; j += 2) ldsm_x4(addr + (uint32_t)(j * 256), ub[j][0], ub[j][1], ub[j + 1][0], ub[j + 1][1]);
        }
        const uint32_t* qp = s_q + 16 + 16 * r + g - 2 * t;
        uint32_t af[4][3];
#pragma unroll
        for (int q = 0; q < 4; q++) { af[q][0] = qp[128 * q]; af[q][1] = qp[128 * q + 8]; af[q][2] = qp[128 * q - 8]; }
#pragma unroll
        for (int q = 0; q < 4; q++) {
#pragma unroll
            for (int nt = q; nt < 16; nt++) mma_bf16(acc[nt], af[q][0], af[q][1], af[q][2], af[q][0], ub[nt - q][0], ub[nt - q][1]);
        }
        if (r < 2) {
            {
                const uint32_t a0 = qp[512], a1 = qp[520], a2 = qp[504];
#pragma unroll
                for (int nt = 4; nt < 16; nt++) mma_bf16(acc[nt], a0, a1, a2, a0, ub[nt - 4][0], ub[nt - 4][1]);
            }
            {
                const uint32_t* q4p = s_q4 + 16 + 16 * r + g - 2 * t;
                const uint32_t a0 = q4p[0], a1 = q4p[8], a2 = q4p[-8];
#pragma unroll
                for (int nt = 8; nt < 16; nt++) mma_bf16(acc[nt], a0, a1, a2, a0, ub[nt - 8][0], ub[nt - 8][1]);
            }
        }
    }
    named_bar(bar_id, 96);
#pragma unroll 1
    for (int a = hb; a <= 3 * hb; a++) {
        uint32_t bq[7];
        const uint32_t* q2 = s_q2 + a * 64 + 16 + g - 2 * t - 32;
#pragma unroll
        for (int dlt = 3; dlt <= 9; dlt++) bq[dlt - 3] = q2[8 * dlt];
        const uint32_t addr = sb_addr + ((a >> 1) ? CV_O_W5 : CV_O_W3) + (uint32_t)((8 + 16 * (8 * (mi >> 1) + rowi) + 8 * (mi & 1) - 8 * (a & 1)) * 2);
        uint32_t aa[6][4];
#pragma unroll
        for (int kp = 0; kp < 6; kp++) ldsm_x4_t(addr + kp * 512, aa[kp][0], aa[kp][1], aa[kp][2], aa[kp][3]);
#pragma unroll
        for (int kp = 0; kp < 6; kp++) {
#pragma unroll
            for (int dlt = 4; dlt <= 9; dlt++) {
                if (2 * kp + dlt < 16) mma_bf16(acc[2 * kp + dlt], aa[kp][0], aa[kp][1], aa[kp][2], aa[kp][3], bq[dlt - 3], bq[dlt - 4]);
            }
        }
    }
    if (hb == 0) {
#pragma unroll 1
        for (int a = 0; a < 2; a++) {
            uint32_t bq[9];
            const uint32_t* q3 = s_q3 + a * 96 + 16 + g - 2 * t - 64;
#pragma unroll
            for (int dlt = 7; dlt <= 15; dlt++) bq[dlt - 7] = q3[8 * dlt];
            const uint32_t addr = sb_addr + (a ? CV_O_W9 : CV_O_W7) + (uint32_t)((16 * (8 * (mi >> 1) + rowi) + 8 * (mi & 1)) * 2);
            uint32_t aa[4][4];
#pragma unroll
            for (int kp = 0; kp < 4; kp++) ldsm_x4_t(addr + kp * 512, aa[kp][0], aa[kp][1], aa[kp][2], aa[kp][3]);
#pragma unroll
            for (int kp = 0; kp < 4; kp++) {
#pragma unroll
                for (int dlt = 8; dlt <= 15; dlt++) {
                    if (2 * kp + dlt < 16) mma_bf16(acc[2 * kp + dlt], aa[kp][0], aa[kp][1], aa[kp][2], aa[kp][3], bq[dlt - 7], bq[dlt - 8]);
                }
            }
        }
    }
    if (threadIdx.x == 0) STAMP(1, 6);
    named_bar(bar_id, 64);
    {
        float4* xch = reinterpret_cast<float4*>(base + CV_O_W3) + hb * 256;
        if (hb) {
#pragma unroll
            for (int i = 0; i < 8; i++) xch[i * 32 + lane] = make_float4(acc[i][0], acc[i][1], acc[i][2], acc[i][3]);
#pragma unroll
            for (int i = 0; i < 8; i++) { acc[i][0] = acc[8 + i][0]; acc[i][1] = acc[8 + i][1]; acc[i][2] = acc[8 + i][2]; acc[i][3] = acc[8 + i][3]; }
        } else {
#pragma unroll
            for (int i = 0; i < 8; i++) xch[i * 32 + lane] = make_float4(acc[8 + i][0], acc[8 + i][1], acc[8 + i][2], acc[8 + i][3]);
        }
    }
    named_bar(bar_id, 64);
    if (threadIdx.x == 0) STAMP(1, 10);
    {
        const float4* xch = reinterpret_cast<const float4*>(base + CV_O_W3) + (hb ^ 1) * 256 + lane;
        const float dsk = __bfloat162float(p_dsk);
        uint16_t* stg = reinterpret_cast<uint16_t*>(base + CV_O_Q);
        const uint16_t* uu = reinterpret_cast<const uint16_t*>(s_u) + 128;
#pragma unroll
        for (int i = 0; i < 8; i++) {
            const float4 p0 = xch[i * 32];
            const float y[4] = {acc[i][0] + p0.x, acc[i][1] + p0.y, acc[i][2] + p0.z, acc[i][3] + p0.w};
            const int nt = 8 * hb + i;
#pragma unroll
            for (int e = 0; e < 4; e++) {
                const int tau = 16 * (8 * nt + 2 * t + (e & 1)) + g + 8 * (e >> 1);
                const float sv = bf16_round(y[e]) + bf16_round(__uint_as_float((uint32_t)uu[tau] << 16) * dsk);
                stg[tau] = (uint16_t)(__float_as_uint(bf16_round(sv)) >> 16);
            }
        }
        __syncwarp();
        if (threadIdx.x == 0) STAMP(1, 11);
        uint4* dst = reinterpret_cast<uint4*>(g_sT + (size_t)d * L_ + hb * 1024);
        const uint4* srcp = reinterpret_cast<const uint4*>(stg + hb * 1024);
#pragma unroll
        for (int i = 0; i < 4; i++) dst[i * 32 + lane] = srcp[i * 32 + lane];
    }
}

__device__ __forceinline__ uint32_t cluster_rank() { uint32_t r; asm volatile("mov.u32 %0, %%cluster_ctarank;" : "=r"(r)); return r; }
__device__ __forceinline__ void cluster_sync_all() {
    asm volatile("barrier.cluster.arrive.release.aligned;\nbarrier.cluster.wait.acquire.aligned;" ::: "memory");
}
__device__ __forceinline__ void mbar_arrive_remote(uint32_t bar, uint32_t cta) {
    asm volatile("{\n.reg .b32 ra;\nmapa.shared::cluster.u32 ra, %0, %1;\n"
                 "mbarrier.arrive.shared::cluster.b64 _, [ra];\n}\n" ::"r"(bar), "r"(cta) : "memory");
}
__device__ __forceinline__ void tma_load_2d_mc(uint32_t dst, const CUtensorMap* tm, int c0, int c1, uint32_t bar, uint16_t mask) {
    asm volatile(
        "cp.async.bulk.tensor.2d.shared::cluster.global.mbarrier::complete_tx::bytes.multicast::cluster [%0], [%1, {%3, %4}], [%2], %5;"
        ::"r"(dst), "l"((uint64_t)tm), "r"(bar), "r"(c0), "r"(c1), "h"(mask) : "memory");
}
__device__ __forceinline__ void tma_store_2d(const CUtensorMap* tm, uint32_t src, int c0, int c1) {
    asm volatile("cp.async.bulk.tensor.2d.global.shared::cta.bulk_group [%0, {%2, %3}], [%1];"
                 ::"l"((uint64_t)tm), "r"(src), "r"(c0), "r"(c1) : "memory");
}
__device__ __forceinline__ void bulk_commit() { asm volatile("cp.async.bulk.commit_group;" ::: "memory"); }
template <int N> __device__ __forceinline__ void bulk_wait_read() { asm volatile("cp.async.bulk.wait_group.read %0;" ::"n"(N) : "memory"); }
template <int N> __device__ __forceinline__ void bulk_wait() { asm volatile("cp.async.bulk.wait_group %0;" ::"n"(N) : "memory"); }
__device__ __forceinline__ void stmatrix_x4(uint32_t addr, uint32_t r0, uint32_t r1, uint32_t r2, uint32_t r3) {
    asm volatile("stmatrix.sync.aligned.m8n8.x4.shared.b16 [%0], {%1,%2,%3,%4};" ::"r"(addr), "r"(r0), "r"(r1), "r"(r2), "r"(r3) : "memory");
}

constexpr int G1_STAGES = 5;
constexpr int G1_A_BYTES = 8 * 16384;
constexpr int G1_B_STAGE = 16384;
constexpr int G1_STG = 8 * 1024;
constexpr int G1_SMEM = G1_A_BYTES + G1_STAGES * G1_B_STAGE + G1_STG + 1024 + 256;
constexpr int G1_ITERS = 32;

__device__ __forceinline__ void tma_load_3d(uint32_t dst, const CUtensorMap* tm, int c0, int c1, int c2, uint32_t bar) {
    asm volatile(
        "cp.async.bulk.tensor.3d.shared::cluster.global.mbarrier::complete_tx::bytes [%0], [%1, {%3, %4, %5}], [%2];"
        ::"r"(dst), "l"((uint64_t)tm), "r"(bar), "r"(c0), "r"(c1), "r"(c2) : "memory");
}

__device__ __forceinline__ void tma_load_3d_mc(uint32_t dst, const CUtensorMap* tm, int c0, int c1, int c2, uint32_t bar, uint16_t mask) {
    asm volatile(
        "cp.async.bulk.tensor.3d.shared::cluster.global.mbarrier::complete_tx::bytes.multicast::cluster [%0], [%1, {%3, %4, %5}], [%2], %6;"
        ::"r"(dst), "l"((uint64_t)tm), "r"(bar), "r"(c0), "r"(c1), "r"(c2), "h"(mask) : "memory");
}

__device__ __forceinline__ float gelu_tanh(float x) {
    float u = x * (0.7978845608028654f + 0.035677408136300125f * x * x);
    float t; asm("tanh.approx.f32 %0, %1;" : "=f"(t) : "f"(u));
    float hx = 0.5f * x;
    return fmaf(hx, t, hx);
}
__device__ __forceinline__ uint32_t geglu_pair(uint32_t g2, uint32_t u2) {
    uint32_t a = pack_bf16(gelu_tanh(bf_lo(g2)), gelu_tanh(bf_hi(g2)));
    uint32_t r; asm("mul.rn.bf16x2 %0, %1, %2;" : "=r"(r) : "r"(a), "r"(u2));
    return r;
}

constexpr int G2_STAGES = 5;
constexpr int G2_STAGE = 16384 + 16384;
constexpr int G2_EPI = 32768 + 32768;
constexpr int G2_KB = F_ / 64;
constexpr int MG_BAR_OFF = G2_STAGES * G2_STAGE + G2_EPI;
constexpr int MG_SMEM = MG_BAR_OFF + 512 + 1024;
static_assert(MG_BAR_OFF == 229376 && G1_A_BYTES + G1_STAGES * G1_B_STAGE + G1_STG <= MG_BAR_OFF, "smem layout");
constexpr int N_GEMM_CTA = 64;

__device__ __forceinline__ void fence_async_all() { asm volatile("fence.proxy.async;" ::: "memory"); }
__device__ __forceinline__ void spin_until(const unsigned int* p, unsigned int target) {
    unsigned int v = 0;
    for (int spin = 0; spin < (1 << 22); spin++) {
        asm volatile("ld.acquire.gpu.global.u32 %0, [%1];" : "=r"(v) : "l"(p) : "memory");
        if (v >= target) break;
    }
}
__device__ __forceinline__ void finish_cta() {
    const unsigned int old = atomicAdd(&g_done_count, 1u);
    if (old == gridDim.x - 1) {
        g_ln_count = 0; g_conv_count = 0; g_done_count = 0;
        for (int i = 0; i < 32; i++) g_h_count[i] = 0;
    }
}

__global__ void __launch_bounds__(384, 1) mega_kernel(const __grid_constant__ MegaParams P,
                                                       const __grid_constant__ CUtensorMap tm_xn,
                                                       const __grid_constant__ CUtensorMap tm_wg4,
                                                       const __grid_constant__ CUtensorMap tm_wu4,
                                                       const __grid_constant__ CUtensorMap tm_wg3,
                                                       const __grid_constant__ CUtensorMap tm_wu3,
                                                       const __grid_constant__ CUtensorMap tm_h,
                                                       const __grid_constant__ CUtensorMap tm_wd,
                                                       const __grid_constant__ CUtensorMap tm_x,
                                                       const __grid_constant__ CUtensorMap tm_sT,
                                                       const __grid_constant__ CUtensorMap tm_out) {
    if (threadIdx.x == 0) STAMP(1, 0);
    extern __shared__ uint8_t smem_raw[];
    const uint32_t sraw = smem_u32(smem_raw);
    const uint32_t sbase = (sraw + 1023) & ~1023u;
    uint8_t* smem = smem_raw + (sbase - sraw);
    const int warp = threadIdx.x >> 5, lane = threadIdx.x & 31;

    if (blockIdx.x >= N_GEMM_CTA) {
        const int d0 = (blockIdx.x - N_GEMM_CTA) * 2 * CV_CH;
        ln_phase(smem, true, d0, P);
        conv_round(smem, d0, true, P);
        __syncthreads();
        if (threadIdx.x == 0) STAMP(1, 7);
        conv_round(smem, d0 + CV_CH, false, P);
        __syncthreads();
        if (threadIdx.x == 0) {
            asm volatile("red.release.gpu.global.add.u32 [%0], 1;" ::"l"(&g_conv_count) : "memory");
            STAMP(1, 8);
            finish_cta();
        }
        return;
    }

    const uint32_t sA = sbase, sB = sbase + G1_A_BYTES, sStg = sB + G1_STAGES * G1_B_STAGE;
    const uint32_t sX = sbase + G2_STAGES * G2_STAGE, sS = sX + 32768;
    const uint32_t sBar = sbase + MG_BAR_OFF;
    const uint32_t bar_a = sBar, bar_full = sBar + 64, bar_empty = bar_full + 8 * G1_STAGES;
    const uint32_t bar_full2 = bar_empty + 8 * G1_STAGES, bar_empty2 = bar_full2 + 8 * G2_STAGES;
    const uint32_t bar_epi = bar_empty2 + 8 * G2_STAGES, bar_g1done = bar_epi + 8, bar_g1mma = bar_g1done + 8;
    const uint32_t kh = blockIdx.x & 1;
    const int rb = ((blockIdx.x >> 3) << 1) + (int)kh;
    const int cq = (blockIdx.x >> 1) & 3;

    if (threadIdx.x == 0) {
        for (int i = 0; i < 8; i++) mbar_init(bar_a + 8 * i, 1);
        for (int i = 0; i < G1_STAGES; i++) { mbar_init(bar_full + 8 * i, 1); mbar_init(bar_empty + 8 * i, 16); }
        for (int i = 0; i < G2_STAGES; i++) { mbar_init(bar_full2 + 8 * i, 1); mbar_init(bar_empty2 + 8 * i, 16); }
        mbar_init(bar_epi, 1);
        mbar_init(bar_g1done, 8);
        mbar_init(bar_g1mma, 16);
        asm volatile("fence.mbarrier_init.release.cluster;" ::: "memory");
    }
    if (warp == 11 && lane == 0) {
        prefetch_tmap(&tm_wg4); prefetch_tmap(&tm_wu4); prefetch_tmap(&tm_xn); prefetch_tmap(&tm_wg3); prefetch_tmap(&tm_wu3);
        prefetch_tmap(&tm_wd); prefetch_tmap(&tm_h); prefetch_tmap(&tm_x); prefetch_tmap(&tm_sT); prefetch_tmap(&tm_out);
    }
    asm volatile("barrier.cluster.arrive.release.aligned;" ::: "memory");
    ln_phase(smem, false, 0, P);
    asm volatile("barrier.cluster.wait.acquire.aligned;" ::: "memory");

    if (warp >= 8) {
        asm volatile("setmaxnreg.dec.sync.aligned.u32 40;");
        if (warp == 11) {
            if (lane == 0) asm volatile("red.release.gpu.global.add.u32 [%0], 1;" ::"l"(&g_ln_count) : "memory");
            named_bar(3, 288);
            if (lane == 0) asm volatile("red.release.gpu.global.add.u32 [%0], 1;" ::"l"(&g_h_count[rb]) : "memory");
            named_bar(9, 288);
            if (lane == 0) asm volatile("red.release.gpu.global.add.u32 [%0], 1;" ::"l"(&g_h_count[16 + rb]) : "memory");
        } else if (lane == 0) {
            const int pw = warp - 8;
            for (int it = pw; it < 2 * G1_ITERS; it += 3) {
                const int s = it % G1_STAGES, kb = it & 15, cj = 2 * cq + (it >> 5);
                if (it >= G1_STAGES) mbar_wait(bar_empty + 8 * s, ((it / G1_STAGES) - 1) & 1);
                const uint32_t dst = sB + s * G1_B_STAGE;
                if ((it & 16) == 0) {
                    mbar_expect_tx(bar_full + 8 * s, 16384);
                    tma_load_3d_mc(dst + kh * 8192, kh ? &tm_wu4 : &tm_wg4, 0, kb * 32, cj * 7, bar_full + 8 * s, 3);
                } else {
                    mbar_expect_tx(bar_full + 8 * s, 12288);
                    tma_load_3d_mc(dst + kh * 6144, kh ? &tm_wu3 : &tm_wg3, 0, kb * 32, cj * 7 + 4, bar_full + 8 * s, 3);
                }
                if (it < 3) {
                    spin_until(&g_ln_count, gridDim.x);
                    fence_async_all();
                    for (int k = pw; k < 8; k += 3) {
                        mbar_expect_tx(bar_a + 8 * k, 16384);
                        tma_load_2d(sA + k * 16384, &tm_xn, k * 64, rb * 128, bar_a + 8 * k);
                    }
                }
            }
            mbar_wait(bar_g1mma, 0);
            spin_until(&g_h_count[rb], 4);
            fence_async_all();
            if (pw == 0) STAMP(3, 1);
            for (int it = pw; it < G2_KB; it += 3) {
                const int s = it % G2_STAGES;
                if (it >= G2_STAGES) mbar_wait(bar_empty2 + 8 * s, ((it / G2_STAGES) - 1) & 1);
                if (it >= 12 && it < 15) { spin_until(&g_h_count[16 + rb], 4); fence_async_all(); }
                const int kb = (it < 12) ? (7 * (it / 3) + it % 3) : (7 * ((it - 12) >> 2) + 3 + ((it - 12) & 3));
                mbar_expect_tx(bar_full2 + 8 * s, G2_STAGE);
                tma_load_3d_mc(sbase + s * G2_STAGE + 16384 + kh * 8192, &tm_wd, 0, kb * 64, cq * 2 + (int)kh, bar_full2 + 8 * s, 3);
                tma_load_2d(sbase + s * G2_STAGE, &tm_h, kb * 64, rb * 128, bar_full2 + 8 * s);
                if (it == 8) {
                    mbar_wait(bar_g1done, 0);
                    mbar_expect_tx(bar_epi, G2_EPI);
                    tma_load_2d(sX, &tm_x, cq * 128, rb * 128, bar_epi);
                    tma_load_2d(sX + 16384, &tm_x, cq * 128 + 64, rb * 128, bar_epi);
                }
                if (it == 20) {
                    spin_until(&g_conv_count, gridDim.x - N_GEMM_CTA);
                    fence_async_all();
#pragma unroll
                    for (int b = 0; b < 4; b++)
                        tma_load_2d(sS + b * 8192, &tm_sT, rb * 128 + (b & 1) * 64, cq * 128 + (b >> 1) * 64, bar_epi);
                }
            }
        }
    } else {
        asm volatile("setmaxnreg.inc.sync.aligned.u32 232;");
        const int wg = __shfl_sync(0xffffffffu, (int)(threadIdx.x >> 7), 0);
#pragma unroll 1
        for (int pass = 0; pass < 2; pass++) {
            const int cj = 2 * cq + pass, it0 = pass * G1_ITERS;
        float r[160];
        const int row0 = rb * 128 + wg * 64 + (warp & 3) * 16;
        const uint64_t descA = make_desc(sA + wg * 8192, 16, 1024);
        const uint64_t descB = make_desc(sB, 2048, 512, 2);
        const uint32_t stg = sStg + warp * 1024;
        const uint32_t st_off = (uint32_t)(((lane & 7) + ((lane >> 3) & 1) * 8) * 32 + (lane >> 4) * 16);
        __nv_bfloat16* hrow = g_h + (size_t)(row0 + (lane >> 1)) * F_ + (lane & 1) * 8 + cj * 224;
#pragma unroll
        for (int kb = 0; kb < 16; kb++) {
            const int it = it0 + kb, s = it % G1_STAGES;
            if ((kb & 1) == 0) mbar_wait(bar_a + 8 * (kb >> 1), 0);
            mbar_wait(bar_full + 8 * s, (it / G1_STAGES) & 1);
            if (threadIdx.x == 0 && (it & 15) == 0) STAMP(2, 2 + it / 16);
            wgmma_fence();
            const uint64_t da = descA + (uint64_t)(((kb >> 1) * 16384 + (kb & 1) * 64) >> 4);
            const uint64_t db = descB + (uint64_t)((s * G1_B_STAGE) >> 4);
            wgmma_n256_k32(r, da, da + 2, db, db + 64, kb != 0);
            wgmma_commit();
            if (kb > 0) {
                wgmma_wait<1>();
                if (lane < 2) mbar_arrive_remote(bar_empty + 8 * ((it - 1) % G1_STAGES), lane);
            }
        }
        wgmma_wait<0>();
        if (lane < 2) mbar_arrive_remote(bar_empty + 8 * ((it0 + 15) % G1_STAGES), lane);
#pragma unroll
        for (int i = 0; i < 32; i++) r[128 + i] = __uint_as_float(pack_bf16(r[2 * i], r[2 * i + 1]));
#pragma unroll
        for (int i = 31; i >= 0; i--) r[96 + i] = __uint_as_float(pack_bf16(r[64 + 2 * i], r[65 + 2 * i]));
        uint32_t eo[4];
        uint4 pv = make_uint4(0, 0, 0, 0);
#pragma unroll
        for (int kb = 0; kb < 16; kb++) {
            const int it = it0 + 16 + kb, s = it % G1_STAGES;
            mbar_wait(bar_full + 8 * s, (it / G1_STAGES) & 1);
            if (threadIdx.x == 0 && (it & 15) == 0) STAMP(2, 2 + it / 16);
            wgmma_fence();
            const uint64_t da = descA + (uint64_t)(((kb >> 1) * 16384 + (kb & 1) * 64) >> 4);
            const uint64_t db = descB + (uint64_t)((s * G1_B_STAGE) >> 4);
            wgmma_n192(r, da, db, kb != 0);
            if (kb < 8) {
                eo[0] = geglu_pair(__float_as_uint(r[128 + 4 * kb]), __float_as_uint(r[96 + 4 * kb]));
                eo[1] = geglu_pair(__float_as_uint(r[129 + 4 * kb]), __float_as_uint(r[97 + 4 * kb]));
            }
            wgmma_n192(r, da + 2, db + 64, 1);
            wgmma_commit();
            if (kb >= 2 && kb < 10) *reinterpret_cast<uint4*>(hrow + (kb - 2) * 16) = pv;
            if (kb >= 1 && kb < 9) {
                __syncwarp();
                asm volatile("ld.shared.v4.u32 {%0,%1,%2,%3}, [%4];" : "=r"(pv.x), "=r"(pv.y), "=r"(pv.z), "=r"(pv.w)
                             : "r"(stg + ((kb - 1) & 1) * 512 + lane * 16));
            }
            if (kb < 8) {
                eo[2] = geglu_pair(__float_as_uint(r[130 + 4 * kb]), __float_as_uint(r[98 + 4 * kb]));
                eo[3] = geglu_pair(__float_as_uint(r[131 + 4 * kb]), __float_as_uint(r[99 + 4 * kb]));
                stmatrix_x4(stg + (kb & 1) * 512 + st_off, eo[0], eo[1], eo[2], eo[3]);
            }
            if (kb > 0 && it - 1 + G1_STAGES < 2 * G1_ITERS) {
                wgmma_wait<1>();
                if (lane < 2) mbar_arrive_remote(bar_empty + 8 * ((it - 1) % G1_STAGES), lane);
            }
        }
        wgmma_wait<0>();
        if (pass == 0) {
            if (lane < 2) mbar_arrive_remote(bar_empty + 8 * ((it0 + 31) % G1_STAGES), lane);
        } else {
            fence_async_smem();
            __syncwarp();
            if (lane < 2) mbar_arrive_remote(bar_g1mma, lane);
        }
        if (threadIdx.x == 0 && pass == 1) STAMP(2, 6);
        {
            uint32_t o[24];
#pragma unroll
            for (int i = 0; i < 24; i++) o[i] = geglu_pair(pack_bf16(r[2 * i], r[2 * i + 1]), pack_bf16(r[48 + 2 * i], r[49 + 2 * i]));
            uint4 v[6];
#pragma unroll
            for (int jj = 0; jj < 6; jj += 2) {
                __syncwarp();
                stmatrix_x4(stg + st_off, o[4 * jj], o[4 * jj + 1], o[4 * jj + 2], o[4 * jj + 3]);
                stmatrix_x4(stg + 512 + st_off, o[4 * jj + 4], o[4 * jj + 5], o[4 * jj + 6], o[4 * jj + 7]);
                __syncwarp();
                asm volatile("ld.shared.v4.u32 {%0,%1,%2,%3}, [%4];" : "=r"(v[jj].x), "=r"(v[jj].y), "=r"(v[jj].z), "=r"(v[jj].w) : "r"(stg + lane * 16));
                asm volatile("ld.shared.v4.u32 {%0,%1,%2,%3}, [%4];" : "=r"(v[jj + 1].x), "=r"(v[jj + 1].y), "=r"(v[jj + 1].z), "=r"(v[jj + 1].w) : "r"(stg + 512 + lane * 16));
            }
#pragma unroll
            for (int jj = 0; jj < 6; jj++) *reinterpret_cast<uint4*>(hrow + 128 + jj * 16) = v[jj];
        }
            if (pass == 0) asm volatile("bar.arrive 3, 288;" ::: "memory");
        }
        fence_async_smem();
        __syncwarp();
        if (lane == 0) mbar_arrive(bar_g1done);
        asm volatile("bar.arrive 9, 288;" ::: "memory");
        if (threadIdx.x == 0) STAMP(2, 7);
        {
            const int g = lane >> 2, t = lane & 3;
            float acc[64];
            const uint64_t descA2 = make_desc(sbase + wg * 8192, 16, 1024);
            const uint64_t descB2 = make_desc(sbase + 16384, 8192, 1024);
#pragma unroll 5
            for (int it = 0; it < G2_KB; it++) {
                const int s = it % G2_STAGES;
                mbar_wait(bar_full2 + 8 * s, (it / G2_STAGES) & 1);
                if (threadIdx.x == 0 && (it == 0 || it == 14)) STAMP(3, 2 + it / 14);
                wgmma_fence();
                {
                    const uint64_t da = descA2 + (uint64_t)((s * G2_STAGE) >> 4);
                    const uint64_t db = descB2 + (uint64_t)((s * G2_STAGE) >> 4);
                    wgmma_n128_k64(acc, da, da + 2, da + 4, da + 6, db, db + 128, db + 256, db + 384, it != 0);
                }
                wgmma_commit();
                if (it > 0 && it - 1 + G2_STAGES < G2_KB) {
                    wgmma_wait<1>();
                    if (lane < 2) mbar_arrive_remote(bar_empty2 + 8 * ((it - 1) % G2_STAGES), lane);
                }
            }
            const int lr = wg * 64 + (warp & 3) * 16 + g;
            uint32_t xv[32], sv[32];
            mbar_wait(bar_epi, 0);
#pragma unroll
            for (int j = 0; j < 16; j++) {
#pragma unroll
                for (int hh = 0; hh < 2; hh++) {
                    const int r = lr + 8 * hh;
                    asm volatile("ld.shared.u32 %0, [%1];" : "=r"(xv[2 * j + hh])
                                 : "r"(sX + (j >> 3) * 16384 + r * 128 + (((j & 7) ^ (r & 7)) << 4) + 4 * t));
                    const int c0 = 8 * (j & 7) + 2 * t;
                    const uint32_t sa = sS + (j >> 3) * 16384 + (r >> 6) * 8192 + (((r & 63) >> 3) << 4) + (r & 7) * 2;
                    uint16_t s0r, s1r;
                    asm volatile("ld.shared.u16 %0, [%1];" : "=h"(s0r) : "r"((sa + c0 * 128) ^ ((c0 & 7) << 4)));
                    asm volatile("ld.shared.u16 %0, [%1];" : "=h"(s1r) : "r"((sa + (c0 + 1) * 128) ^ (((c0 + 1) & 7) << 4)));
                    sv[2 * j + hh] = (uint32_t)s0r | ((uint32_t)s1r << 16);
                }
            }
            wgmma_wait<0>();
            if (threadIdx.x == 0) STAMP(3, 4);
#pragma unroll
            for (int i = 0; i < 32; i++) {
                float f0 = bf16_round(acc[2 * i]), f1 = bf16_round(acc[2 * i + 1]);
                float g0 = bf16_round(__fdividef(f0, 1.0f + __expf(-f0)));
                float g1 = bf16_round(__fdividef(f1, 1.0f + __expf(-f1)));
                float o0 = bf_lo(xv[i]) + bf16_round(bf_lo(sv[i]) * g0);
                float o1 = bf_hi(xv[i]) + bf16_round(bf_hi(sv[i]) * g1);
                xv[i] = pack_bf16(o0, o1);
            }
#pragma unroll
            for (int j = 0; j < 16; j++) {
#pragma unroll
                for (int hh = 0; hh < 2; hh++) {
                    const int r = lr + 8 * hh;
                    asm volatile("st.shared.u32 [%0], %1;" ::"r"(sX + (j >> 3) * 16384 + r * 128 + (((j & 7) ^ (r & 7)) << 4) + 4 * t),
                                 "r"(xv[2 * j + hh]) : "memory");
                }
            }
            fence_async_smem();
            __syncwarp();
            if (lane == 0) {
                const int r0 = wg * 64 + (warp & 3) * 16;
                tma_store_2d(&tm_out, sX + r0 * 128, cq * 128, rb * 128 + r0);
                tma_store_2d(&tm_out, sX + 16384 + r0 * 128, cq * 128 + 64, rb * 128 + r0);
                bulk_commit();
                bulk_wait_read<0>();
            }
        }
        if (threadIdx.x == 0) STAMP(3, 5);
        named_bar(4, 256);
        if (threadIdx.x == 0) finish_cta();
    }
    cluster_sync_all();
}

typedef CUresult (*EncodeFn)(CUtensorMap*, CUtensorMapDataType, cuuint32_t, void*, const cuuint64_t*, const cuuint64_t*,
                             const cuuint32_t*, const cuuint32_t*, CUtensorMapInterleave, CUtensorMapSwizzle,
                             CUtensorMapL2promotion, CUtensorMapFloatOOBfill);

void make_map(EncodeFn fn, CUtensorMap* m, const void* ptr, uint64_t inner, uint64_t outer, uint32_t box_in, uint32_t box_out,
              CUtensorMapSwizzle swz = CU_TENSOR_MAP_SWIZZLE_128B) {
    cuuint64_t dims[2] = {inner, outer};
    cuuint64_t strides[1] = {inner * 2};
    cuuint32_t box[2] = {box_in, box_out};
    cuuint32_t es[2] = {1, 1};
    fn(m, CU_TENSOR_MAP_DATA_TYPE_BFLOAT16, 2, const_cast<void*>(ptr), dims, strides, box, es, CU_TENSOR_MAP_INTERLEAVE_NONE,
       swz, CU_TENSOR_MAP_L2_PROMOTION_L2_256B, CU_TENSOR_MAP_FLOAT_OOB_FILL_NONE);
}
void make_map3(EncodeFn fn, CUtensorMap* m, const void* ptr, uint64_t cols, uint64_t rows, uint32_t atom, uint32_t box_rows,
               uint32_t box_atoms, CUtensorMapSwizzle swz) {
    cuuint64_t dims[3] = {atom, rows, cols / atom};
    cuuint64_t strides[2] = {cols * 2, (cuuint64_t)atom * 2};
    cuuint32_t box[3] = {atom, box_rows, box_atoms};
    cuuint32_t es[3] = {1, 1, 1};
    fn(m, CU_TENSOR_MAP_DATA_TYPE_BFLOAT16, 3, const_cast<void*>(ptr), dims, strides, box, es, CU_TENSOR_MAP_INTERLEAVE_NONE,
       swz, CU_TENSOR_MAP_L2_PROMOTION_L2_256B, CU_TENSOR_MAP_FLOAT_OOB_FILL_NONE);
}

template <typename... Args>
void launch_pdl(void (*kern)(Args...), int grid, int block, int smem, bool pdl, int cluster, Args... args) {
    cudaLaunchConfig_t cfg = {};
    cfg.gridDim = dim3(grid); cfg.blockDim = dim3(block); cfg.dynamicSmemBytes = smem; cfg.stream = cudaStreamPerThread;
    cudaLaunchAttribute at[2];
    int n = 0;
    if (pdl) {
        at[n].id = cudaLaunchAttributeProgrammaticStreamSerialization;
        at[n].val.programmaticStreamSerializationAllowed = 1;
        n++;
    }
    if (cluster > 1) {
        at[n].id = cudaLaunchAttributeClusterDimension;
        at[n].val.clusterDim.x = cluster; at[n].val.clusterDim.y = 1; at[n].val.clusterDim.z = 1;
        n++;
    }
    cfg.attrs = at; cfg.numAttrs = n;
    cudaLaunchKernelEx(&cfg, kern, args...);
}

}

extern "C" void kernel_launch(void* const* d_in, const int* in_sizes, int n_in, void* d_out, int out_size) {
    const __nv_bfloat16* x = (const __nv_bfloat16*)d_in[0];
    const __nv_bfloat16* A_re = (const __nv_bfloat16*)d_in[1];
    const __nv_bfloat16* A_im = (const __nv_bfloat16*)d_in[2];
    const __nv_bfloat16* B_re = (const __nv_bfloat16*)d_in[3];
    const __nv_bfloat16* B_im = (const __nv_bfloat16*)d_in[4];
    const __nv_bfloat16* C_re = (const __nv_bfloat16*)d_in[5];
    const __nv_bfloat16* C_im = (const __nv_bfloat16*)d_in[6];
    const __nv_bfloat16* log_dt = (const __nv_bfloat16*)d_in[7];
    const __nv_bfloat16* Dskip = (const __nv_bfloat16*)d_in[8];
    const __nv_bfloat16* wg = (const __nv_bfloat16*)d_in[10];
    const __nv_bfloat16* wu = (const __nv_bfloat16*)d_in[11];
    const __nv_bfloat16* wd = (const __nv_bfloat16*)d_in[12];
    __nv_bfloat16* out = (__nv_bfloat16*)d_out;

    static bool init = false;
    static CUtensorMap tm_xn, tm_wg4, tm_wu4, tm_wg3, tm_wu3, tm_hst, tm_hst96, tm_h, tm_wd, tm_x, tm_sT, tm_out;
    static const void* last_ptrs[5] = {nullptr, nullptr, nullptr, nullptr, nullptr};
    if (!init || last_ptrs[0] != wg || last_ptrs[1] != wu || last_ptrs[2] != wd || last_ptrs[3] != x || last_ptrs[4] != out) {
        void* fnp = nullptr;
        cudaDriverEntryPointQueryResult qres;
        cudaGetDriverEntryPoint("cuTensorMapEncodeTiled", &fnp, cudaEnableDefault, &qres);
        EncodeFn fn = (EncodeFn)fnp;
        void *p_xn, *p_h, *p_sT;
        cudaGetSymbolAddress(&p_xn, g_xn);
        cudaGetSymbolAddress(&p_h, g_h);
        cudaGetSymbolAddress(&p_sT, g_sT);
        make_map(fn, &tm_xn, p_xn, D_, L_, 64, 128);
        make_map3(fn, &tm_wg4, wg, F_, D_, 32, 32, 4, CU_TENSOR_MAP_SWIZZLE_64B);
        make_map3(fn, &tm_wu4, wu, F_, D_, 32, 32, 4, CU_TENSOR_MAP_SWIZZLE_64B);
        make_map3(fn, &tm_wg3, wg, F_, D_, 32, 32, 3, CU_TENSOR_MAP_SWIZZLE_64B);
        make_map3(fn, &tm_wu3, wu, F_, D_, 32, 32, 3, CU_TENSOR_MAP_SWIZZLE_64B);
        make_map(fn, &tm_hst, p_h, F_, L_, 16, 16, CU_TENSOR_MAP_SWIZZLE_NONE);
        make_map(fn, &tm_hst96, p_h, F_, L_, 96, 16, CU_TENSOR_MAP_SWIZZLE_NONE);
        make_map(fn, &tm_h, p_h, F_, L_, 64, 128);
        make_map3(fn, &tm_wd, wd, D_, F_, 64, 64, 1, CU_TENSOR_MAP_SWIZZLE_128B);
        make_map(fn, &tm_x, x, D_, L_, 64, 128);
        make_map(fn, &tm_sT, p_sT, L_, D_, 64, 64);
        make_map(fn, &tm_out, out, D_, L_, 64, 16);
        cudaFuncSetAttribute(mega_kernel, cudaFuncAttributeMaxDynamicSharedMemorySize, MG_SMEM);
        last_ptrs[0] = wg; last_ptrs[1] = wu; last_ptrs[2] = wd; last_ptrs[3] = x; last_ptrs[4] = out;
        init = true;
    }
    MegaParams P = {x, A_re, A_im, B_re, B_im, C_re, C_im, log_dt, Dskip, wg, wu, wd};
    launch_pdl(mega_kernel, 128, 384, MG_SMEM, false, 2, P, tm_xn, tm_wg4, tm_wu4, tm_wg3, tm_wu3, tm_h, tm_wd, tm_x, tm_sT, tm_out);
}
```

```cpp
#include <cuda_runtime.h>
#include <cuda_bf16.h>
#include <cuda.h>
#include <stdint.h>

namespace {

constexpr int L_ = 2048, D_ = 512, NS_ = 128, F_ = 1792;

__device__ __align__(1024) __nv_bfloat16 g_xn[L_ * D_];
__device__ __align__(1024) __nv_bfloat16 g_xnT[D_ * L_];
__device__ __align__(1024) __nv_bfloat16 g_sT[D_ * L_];
__device__ __align__(1024) __nv_bfloat16 g_h[L_ * F_];
__device__ unsigned int g_ln_count, g_conv_count, g_done_count, g_h_count[32];

#define STAMP(k, i)

__device__ __forceinline__ uint32_t smem_u32(const void* p) { return (uint32_t)__cvta_generic_to_shared(p); }
__device__ __forceinline__ void pdl_wait() { asm volatile("griddepcontrol.wait;" ::: "memory"); }
__device__ __forceinline__ void pdl_launch() { asm volatile("griddepcontrol.launch_dependents;" ::: "memory"); }

__device__ __forceinline__ void mbar_init(uint32_t bar, uint32_t cnt) {
    asm volatile("mbarrier.init.shared::cta.b64 [%0], %1;" ::"r"(bar), "r"(cnt) : "memory");
}
__device__ __forceinline__ void mbar_expect_tx(uint32_t bar, uint32_t bytes) {
    asm volatile("mbarrier.arrive.expect_tx.shared::cta.b64 _, [%0], %1;" ::"r"(bar), "r"(bytes) : "memory");
}
__device__ __forceinline__ void mbar_arrive(uint32_t bar) {
    asm volatile("mbarrier.arrive.shared::cta.b64 _, [%0];" ::"r"(bar) : "memory");
}
__device__ __forceinline__ void mbar_wait(uint32_t bar, uint32_t parity) {
    asm volatile(
        "{\n.reg .pred p;\n"
        "WAIT_LOOP:\n"
        "mbarrier.try_wait.parity.shared::cta.b64 p, [%0], %1;\n"
        "@p bra WAIT_DONE;\n"
        "bra WAIT_LOOP;\n"
        "WAIT_DONE:\n}\n" ::"r"(bar), "r"(parity) : "memory");
}
__device__ __forceinline__ void tma_load_2d(uint32_t dst, const CUtensorMap* tm, int c0, int c1, uint32_t bar) {
    asm volatile(
        "cp.async.bulk.tensor.2d.shared::cluster.global.mbarrier::complete_tx::bytes [%0], [%1, {%3, %4}], [%2];"
        ::"r"(dst), "l"((uint64_t)tm), "r"(bar), "r"(c0), "r"(c1) : "memory");
}
__device__ __forceinline__ void prefetch_tmap(const CUtensorMap* tm) {
    asm volatile("prefetch.tensormap [%0];" ::"l"((uint64_t)tm) : "memory");
}
__device__ __forceinline__ uint64_t make_desc(uint32_t addr, uint32_t lbo, uint32_t sbo, uint64_t mode = 1) {
    uint64_t d = 0;
    d |= (uint64_t)((addr & 0x3FFFF) >> 4);
    d |= (uint64_t)((lbo >> 4) & 0x3FFF) << 16;
    d |= (uint64_t)((sbo >> 4) & 0x3FFF) << 32;
    d |= mode << 62;
    return d;
}
__device__ __forceinline__ void fence_async_smem() { asm volatile("fence.proxy.async.shared::cta;" ::: "memory"); }
__device__ __forceinline__ void wgmma_fence() { asm volatile("wgmma.fence.sync.aligned;" ::: "memory"); }
__device__ __forceinline__ void wgmma_commit() { asm volatile("wgmma.commit_group.sync.aligned;" ::: "memory"); }
template <int N> __device__ __forceinline__ void wgmma_wait() {
    asm volatile("wgmma.wait_group.sync.aligned %0;" ::"n"(N) : "memory");
}

#define R8(a, i) "+f"(a[i + 0]), "+f"(a[i + 1]), "+f"(a[i + 2]), "+f"(a[i + 3]), "+f"(a[i + 4]), "+f"(a[i + 5]), "+f"(a[i + 6]), "+f"(a[i + 7])

__device__ __forceinline__ void wgmma_n256_k32(float* a, uint64_t da0, uint64_t da1, uint64_t db0, uint64_t db1, int scale_d) {
    asm volatile(
        "{\n.reg .pred p;\nsetp.ne.b32 p, %132, 0;\n"
        "wgmma.mma_async.sync.aligned.m64n256k16.f32.bf16.bf16 {%0,%1,%2,%3,%4,%5,%6,%7,%8,%9,%10,%11,%12,%13,%14,%15,%16,%17,%18,%19,%20,%21,%22,%23,%24,%25,%26,%27,%28,%29,%30,%31,%32,%33,%34,%35,%36,%37,%38,%39,%40,%41,%42,%43,%44,%45,%46,%47,%48,%49,%50,%51,%52,%53,%54,%55,%56,%57,%58,%59,%60,%61,%62,%63,%64,%65,%66,%67,%68,%69,%70,%71,%72,%73,%74,%75,%76,%77,%78,%79,%80,%81,%82,%83,%84,%85,%86,%87,%88,%89,%90,%91,%92,%93,%94,%95,%96,%97,%98,%99,%100,%101,%102,%103,%104,%105,%106,%107,%108,%109,%110,%111,%112,%113,%114,%115,%116,%117,%118,%119,%120,%121,%122,%123,%124,%125,%126,%127}, %128, %130, p, 1, 1, 0, 1;\n"
        "wgmma.mma_async.sync.aligned.m64n256k16.f32.bf16.bf16 {%0,%1,%2,%3,%4,%5,%6,%7,%8,%9,%10,%11,%12,%13,%14,%15,%16,%17,%18,%19,%20,%21,%22,%23,%24,%25,%26,%27,%28,%29,%30,%31,%32,%33,%34,%35,%36,%37,%38,%39,%40,%41,%42,%43,%44,%45,%46,%47,%48,%49,%50,%51,%52,%53,%54,%55,%56,%57,%58,%59,%60,%61,%62,%63,%64,%65,%66,%67,%68,%69,%70,%71,%72,%73,%74,%75,%76,%77,%78,%79,%80,%81,%82,%83,%84,%85,%86,%87,%88,%89,%90,%91,%92,%93,%94,%95,%96,%97,%98,%99,%100,%101,%102,%103,%104,%105,%106,%107,%108,%109,%110,%111,%112,%113,%114,%115,%116,%117,%118,%119,%120,%121,%122,%123,%124,%125,%126,%127}, %129, %131, 1, 1, 1, 0, 1;\n"
        "}\n"
        : R8(a, 0), R8(a, 8), R8(a, 16), R8(a, 24), R8(a, 32), R8(a, 40), R8(a, 48), R8(a, 56), R8(a, 64), R8(a, 72), R8(a, 80), R8(a, 88), R8(a, 96), R8(a, 104), R8(a, 112), R8(a, 120)
        : "l"(da0), "l"(da1), "l"(db0), "l"(db1), "r"(scale_d));
}
__device__ __forceinline__ void wgmma_n192_k32(float* a, uint64_t da0, uint64_t da1, uint64_t db0, uint64_t db1, int scale_d) {
    asm volatile(
        "{\n.reg .pred p;\nsetp.ne.b32 p, %100, 0;\n"
        "wgmma.mma_async.sync.aligned.m64n192k16.f32.bf16.bf16 {%0,%1,%2,%3,%4,%5,%6,%7,%8,%9,%10,%11,%12,%13,%14,%15,%16,%17,%18,%19,%20,%21,%22,%23,%24,%25,%26,%27,%28,%29,%30,%31,%32,%33,%34,%35,%36,%37,%38,%39,%40,%41,%42,%43,%44,%45,%46,%47,%48,%49,%50,%51,%52,%53,%54,%55,%56,%57,%58,%59,%60,%61,%62,%63,%64,%65,%66,%67,%68,%69,%70,%71,%72,%73,%74,%75,%76,%77,%78,%79,%80,%81,%82,%83,%84,%85,%86,%87,%88,%89,%90,%91,%92,%93,%94,%95}, %96, %98, p, 1, 1, 0, 1;\n"
        "wgmma.mma_async.sync.aligned.m64n192k16.f32.bf16.bf16 {%0,%1,%2,%3,%4,%5,%6,%7,%8,%9,%10,%11,%12,%13,%14,%15,%16,%17,%18,%19,%20,%21,%22,%23,%24,%25,%26,%27,%28,%29,%30,%31,%32,%33,%34,%35,%36,%37,%38,%39,%40,%41,%42,%43,%44,%45,%46,%47,%48,%49,%50,%51,%52,%53,%54,%55,%56,%57,%58,%59,%60,%61,%62,%63,%64,%65,%66,%67,%68,%69,%70,%71,%72,%73,%74,%75,%76,%77,%78,%79,%80,%81,%82,%83,%84,%85,%86,%87,%88,%89,%90,%91,%92,%93,%94,%95}, %97, %99, 1, 1, 1, 0, 1;\n"
        "}\n"
        : R8(a, 0), R8(a, 8), R8(a, 16), R8(a, 24), R8(a, 32), R8(a, 40), R8(a, 48), R8(a, 56), R8(a, 64), R8(a, 72), R8(a, 80), R8(a, 88)
        : "l"(da0), "l"(da1), "l"(db0), "l"(db1), "r"(scale_d));
}
__device__ __forceinline__ void wgmma_n192(float* a, uint64_t da0, uint64_t db0, int scale_d) {
    asm volatile(
        "{\n.reg .pred p;\nsetp.ne.b32 p, %98, 0;\n"
        "wgmma.mma_async.sync.aligned.m64n192k16.f32.bf16.bf16 {%0,%1,%2,%3,%4,%5,%6,%7,%8,%9,%10,%11,%12,%13,%14,%15,%16,%17,%18,%19,%20,%21,%22,%23,%24,%25,%26,%27,%28,%29,%30,%31,%32,%33,%34,%35,%36,%37,%38,%39,%40,%41,%42,%43,%44,%45,%46,%47,%48,%49,%50,%51,%52,%53,%54,%55,%56,%57,%58,%59,%60,%61,%62,%63,%64,%65,%66,%67,%68,%69,%70,%71,%72,%73,%74,%75,%76,%77,%78,%79,%80,%81,%82,%83,%84,%85,%86,%87,%88,%89,%90,%91,%92,%93,%94,%95}, %96, %97, p, 1, 1, 0, 1;\n"
        "}\n"
        : R8(a, 0), R8(a, 8), R8(a, 16), R8(a, 24), R8(a, 32), R8(a, 40), R8(a, 48), R8(a, 56), R8(a, 64), R8(a, 72), R8(a, 80), R8(a, 88)
        : "l"(da0), "l"(db0), "r"(scale_d));
}
__device__ __forceinline__ void wgmma_n128_k64(float* a, uint64_t da0, uint64_t da1, uint64_t da2, uint64_t da3,
                                               uint64_t db0, uint64_t db1, uint64_t db2, uint64_t db3, int scale_d) {
    asm volatile(
        "{\n.reg .pred p;\nsetp.ne.b32 p, %72, 0;\n"
        "wgmma.mma_async.sync.aligned.m64n128k16.f32.bf16.bf16 {%0,%1,%2,%3,%4,%5,%6,%7,%8,%9,%10,%11,%12,%13,%14,%15,%16,%17,%18,%19,%20,%21,%22,%23,%24,%25,%26,%27,%28,%29,%30,%31,%32,%33,%34,%35,%36,%37,%38,%39,%40,%41,%42,%43,%44,%45,%46,%47,%48,%49,%50,%51,%52,%53,%54,%55,%56,%57,%58,%59,%60,%61,%62,%63}, %64, %68, p, 1, 1, 0, 1;\n"
        "wgmma.mma_async.sync.aligned.m64n128k16.f32.bf16.bf16 {%0,%1,%2,%3,%4,%5,%6,%7,%8,%9,%10,%11,%12,%13,%14,%15,%16,%17,%18,%19,%20,%21,%22,%23,%24,%25,%26,%27,%28,%29,%30,%31,%32,%33,%34,%35,%36,%37,%38,%39,%40,%41,%42,%43,%44,%45,%46,%47,%48,%49,%50,%51,%52,%53,%54,%55,%56,%57,%58,%59,%60,%61,%62,%63}, %65, %69, 1, 1, 1, 0, 1;\n"
        "wgmma.mma_async.sync.aligned.m64n128k16.f32.bf16.bf16 {%0,%1,%2,%3,%4,%5,%6,%7,%8,%9,%10,%11,%12,%13,%14,%15,%16,%17,%18,%19,%20,%21,%22,%23,%24,%25,%26,%27,%28,%29,%30,%31,%32,%33,%34,%35,%36,%37,%38,%39,%40,%41,%42,%43,%44,%45,%46,%47,%48,%49,%50,%51,%52,%53,%54,%55,%56,%57,%58,%59,%60,%61,%62,%63}, %66, %70, 1, 1, 1, 0, 1;\n"
        "wgmma.mma_async.sync.aligned.m64n128k16.f32.bf16.bf16 {%0,%1,%2,%3,%4,%5,%6,%7,%8,%9,%10,%11,%12,%13,%14,%15,%16,%17,%18,%19,%20,%21,%22,%23,%24,%25,%26,%27,%28,%29,%30,%31,%32,%33,%34,%35,%36,%37,%38,%39,%40,%41,%42,%43,%44,%45,%46,%47,%48,%49,%50,%51,%52,%53,%54,%55,%56,%57,%58,%59,%60,%61,%62,%63}, %67, %71, 1, 1, 1, 0, 1;\n"
        "}\n"
        : R8(a, 0), R8(a, 8), R8(a, 16), R8(a, 24), R8(a, 32), R8(a, 40), R8(a, 48), R8(a, 56)
        : "l"(da0), "l"(da1), "l"(da2), "l"(da3), "l"(db0), "l"(db1), "l"(db2), "l"(db3), "r"(scale_d));
}

__device__ __forceinline__ float bf16_round(float x) {
    uint32_t p; asm("cvt.rn.bf16x2.f32 %0, %1, %2;" : "=r"(p) : "f"(x), "f"(0.0f));
    return __uint_as_float(p);
}
__device__ __forceinline__ uint32_t pack_bf16(float lo, float hi) {
    __nv_bfloat162 v = __floats2bfloat162_rn(lo, hi);
    return *reinterpret_cast<uint32_t*>(&v);
}
__device__ __forceinline__ float bf_lo(uint32_t v) { return __uint_as_float(v << 16); }
__device__ __forceinline__ float bf_hi(uint32_t v) { return __uint_as_float(v & 0xFFFF0000u); }

struct cplx { float r, i; };
__device__ __forceinline__ cplx cmul(cplx a, cplx b) {
    cplx c; c.r = a.r * b.r - a.i * b.i; c.i = a.r * b.i + a.i * b.r; return c;
}
__device__ __forceinline__ cplx csq(cplx a) {
    cplx c; c.r = a.r * a.r - a.i * a.i; c.i = 2.0f * a.r * a.i; return c;
}
__device__ __forceinline__ cplx cexp_m(float ar2, float ai2, float m) {
    float mag;
    asm("ex2.approx.ftz.f32 %0, %1;" : "=f"(mag) : "f"(ar2 * m));
    float rr = ai2 * m;
    rr -= (rr + 12582912.0f) - 12582912.0f;
    float th = rr * 6.283185307179586f;
    cplx c; c.r = mag * __cosf(th); c.i = mag * __sinf(th);
    return c;
}
__device__ __forceinline__ uint32_t to_tf32(float x) { return __float_as_uint(x) + 0x1000u; }
__device__ __forceinline__ void mma_tf32(float* c, uint32_t a0, uint32_t a1, uint32_t a2, uint32_t a3, uint32_t b0, uint32_t b1) {
    asm volatile("mma.sync.aligned.m16n8k8.row.col.f32.tf32.tf32.f32 {%0,%1,%2,%3}, {%4,%5,%6,%7}, {%8,%9}, {%0,%1,%2,%3};"
                 : "+f"(c[0]), "+f"(c[1]), "+f"(c[2]), "+f"(c[3])
                 : "r"(a0), "r"(a1), "r"(a2), "r"(a3), "r"(b0), "r"(b1));
}
__device__ __forceinline__ void mma_bf16(float* c, uint32_t a0, uint32_t a1, uint32_t a2, uint32_t a3, uint32_t b0, uint32_t b1) {
    asm volatile("mma.sync.aligned.m16n8k16.row.col.f32.bf16.bf16.f32 {%0,%1,%2,%3}, {%4,%5,%6,%7}, {%8,%9}, {%0,%1,%2,%3};"
                 : "+f"(c[0]), "+f"(c[1]), "+f"(c[2]), "+f"(c[3])
                 : "r"(a0), "r"(a1), "r"(a2), "r"(a3), "r"(b0), "r"(b1));
}
__device__ __forceinline__ void named_bar(int id, int n) { asm volatile("bar.sync %0, %1;" ::"r"(id), "r"(n) : "memory"); }
__device__ __forceinline__ void ldsm_x4(uint32_t addr, uint32_t& r0, uint32_t& r1, uint32_t& r2, uint32_t& r3) {
    asm volatile("ldmatrix.sync.aligned.m8n8.x4.shared.b16 {%0,%1,%2,%3}, [%4];" : "=r"(r0), "=r"(r1), "=r"(r2), "=r"(r3) : "r"(addr));
}
__device__ __forceinline__ void ldsm_x4_t(uint32_t addr, uint32_t& r0, uint32_t& r1, uint32_t& r2, uint32_t& r3) {
    asm volatile("ldmatrix.sync.aligned.m8n8.x4.trans.shared.b16 {%0,%1,%2,%3}, [%4];" : "=r"(r0), "=r"(r1), "=r"(r2), "=r"(r3) : "r"(addr));
}

constexpr int CV_CH = 4;
constexpr int CV_O_CONST = 0;
constexpr int CV_O_KP = 12288;
constexpr int CV_EARLY = 12288 + 7776;
constexpr int CV_O_Q = 0;
constexpr int CV_O_Q2 = CV_O_Q + 2304;
constexpr int CV_O_Q3 = CV_O_Q2 + 1024;
constexpr int CV_O_Q4X = CV_O_Q3 + 768;
constexpr int CV_O_W3 = CV_O_Q4X + 256;
constexpr int CV_O_W5 = CV_O_W3 + 3104;
constexpr int CV_O_W7 = CV_O_W5 + 3104;
constexpr int CV_O_W9 = CV_O_W7 + 2048;
constexpr int CV_O_U = CV_O_W9 + 2048;
constexpr int CV_LATE = CV_O_U + 4352;
constexpr int CV_LATE_BASE = 229376 - CV_CH * CV_LATE;
constexpr int CV_TILE_OFF = CV_CH * CV_EARLY;
static_assert(CV_TILE_OFF + 16 * (D_ + 8) * 2 <= CV_LATE_BASE && CV_LATE_BASE >= 131072 + 16384, "front layout");
static_assert(CV_O_W3 >= 4096 && CV_O_U - CV_O_W3 >= 8192 && (CV_LATE % 16) == 0 && (CV_EARLY % 16) == 0, "front layout");

constexpr int LN_ROWS = 16;

struct MegaParams {
    const __nv_bfloat16 *x, *A_re, *A_im, *B_re, *B_im, *C_re, *C_im, *log_dt, *Dskip, *wg, *wu, *wd;
};

__device__ __noinline__ void channel_consts(uint8_t* smem, int cc_, int dd, const MegaParams& P) {
    const int lane = threadIdx.x & 31;
    const __nv_bfloat16 *A_re = P.A_re, *A_im = P.A_im, *B_re = P.B_re, *B_im = P.B_im, *C_re = P.C_re, *C_im = P.C_im, *log_dt = P.log_dt;
    float4* sc = reinterpret_cast<float4*>(smem + cc_ * CV_EARLY + CV_O_CONST);
    {
        __nv_bfloat16 pr[4][6];
#pragma unroll
        for (int j = 0; j < 4; j++) {
            const size_t off = (size_t)dd * NS_ + lane + 32 * j;
            pr[j][0] = A_re[off]; pr[j][1] = A_im[off]; pr[j][2] = B_re[off]; pr[j][3] = B_im[off]; pr[j][4] = C_re[off]; pr[j][5] = C_im[off];
        }
        const float dt = bf16_round(expf(__bfloat162float(log_dt[dd])));
        float tail = 0.f;
#pragma unroll
        for (int j = 0; j < 4; j++) {
            const float ar = dt * __bfloat162float(pr[j][0]), ai = dt * __bfloat162float(pr[j][1]);
            const cplx db = {dt * __bfloat162float(pr[j][2]), dt * __bfloat162float(pr[j][3])};
            const cplx cc = {__bfloat162float(pr[j][4]), __bfloat162float(pr[j][5])};
            const cplx cb = cmul(cc, db);
            const float ar2 = ar * 1.4426950408889634f, ai2 = ai * 0.15915494309189535f;
            const cplx e8 = cexp_m(ar2, ai2, 8.f), e128 = cexp_m(ar2, ai2, 128.f);
            const cplx cb8 = cmul(cb, e8);
            const cplx e256 = cexp_m(ar2, ai2, 256.f), e512 = cexp_m(ar2, ai2, 512.f), e1024 = cexp_m(ar2, ai2, 1024.f);
            const cplx c256 = cmul(cb, e256), c512 = cmul(cb, e512), c1024 = cmul(cb, e1024);
            const cplx c768 = cmul(c512, e256), c1280 = cmul(c1024, e256), c1536 = cmul(c1024, e512);
            const cplx c1792 = cmul(c1536, e256);
            tail += cmul(c1024, e1024).r;
            float4* c = sc + (lane + 32 * j) * 6;
            c[0] = make_float4(ar2, ai2, cb.r, cb.i);
            c[1] = make_float4(e128.r, e128.i, cb8.r, cb8.i);
            c[2] = make_float4(c256.r, c256.i, e8.r, e8.i);
            c[3] = make_float4(c512.r, c512.i, c768.r, c768.i);
            c[4] = make_float4(c1024.r, c1024.i, c1280.r, c1280.i);
            c[5] = make_float4(c1536.r, c1536.i, c1792.r, c1792.i);
        }
#pragma unroll
        for (int o = 16; o > 0; o >>= 1) tail += __shfl_xor_sync(0xffffffffu, tail, o);
        if (lane == 0) {
            float* kp = reinterpret_cast<float*>(smem + cc_ * CV_EARLY + CV_O_KP);
            kp[640] = tail; kp[648 + 640] = 0.f; kp[1296 + 640] = 0.f;
        }
    }
}

__device__ __forceinline__ void ln_phase(uint8_t* smem, bool is_conv, int d0, const MegaParams& P) {
    const int warp = threadIdx.x >> 5, lane = threadIdx.x & 31;
    const __nv_bfloat16 *x = P.x, *wg = P.wg, *wu = P.wu, *wd = P.wd;
    __nv_bfloat16 (*tile)[D_ + 8] = reinterpret_cast<__nv_bfloat16 (*)[D_ + 8]>(smem + CV_TILE_OFF);
    if (warp < 8) {
        const int row = blockIdx.x * LN_ROWS + warp * 2;
        uint4 xv[2][2];
#pragma unroll
        for (int r = 0; r < 2; r++) {
            xv[r][0] = *reinterpret_cast<const uint4*>(x + (size_t)(row + r) * D_ + lane * 8);
            xv[r][1] = *reinterpret_cast<const uint4*>(x + (size_t)(row + r) * D_ + 256 + lane * 8);
        }
        float f[2][16], sm[2], q[2];
#pragma unroll
        for (int r = 0; r < 2; r++) {
            const uint32_t wv[8] = {xv[r][0].x, xv[r][0].y, xv[r][0].z, xv[r][0].w, xv[r][1].x, xv[r][1].y, xv[r][1].z, xv[r][1].w};
#pragma unroll
            for (int i = 0; i < 8; i++) { f[r][2 * i] = bf_lo(wv[i]); f[r][2 * i + 1] = bf_hi(wv[i]); }
            sm[r] = 0.f;
#pragma unroll
            for (int i = 0; i < 16; i++) sm[r] += f[r][i];
        }
#pragma unroll
        for (int o = 16; o > 0; o >>= 1) { sm[0] += __shfl_xor_sync(0xffffffffu, sm[0], o); sm[1] += __shfl_xor_sync(0xffffffffu, sm[1], o); }
#pragma unroll
        for (int r = 0; r < 2; r++) {
            sm[r] *= (1.0f / D_);
            q[r] = 0.f;
#pragma unroll
            for (int i = 0; i < 16; i++) { float dd = f[r][i] - sm[r]; q[r] += dd * dd; }
        }
#pragma unroll
        for (int o = 16; o > 0; o >>= 1) { q[0] += __shfl_xor_sync(0xffffffffu, q[0], o); q[1] += __shfl_xor_sync(0xffffffffu, q[1], o); }
#pragma unroll
        for (int r = 0; r < 2; r++) {
            const float mb = bf16_round(sm[r]);
            const float vb = bf16_round(q[r] * (1.0f / D_));
            const float den = bf16_round(sqrtf(bf16_round(vb + 1e-5f)));
            uint32_t o[8];
#pragma unroll
            for (int i = 0; i < 8; i++) {
                float a = __fdiv_rn(bf16_round(f[r][2 * i] - mb), den);
                float b = __fdiv_rn(bf16_round(f[r][2 * i + 1] - mb), den);
                o[i] = pack_bf16(a, b);
            }
            __nv_bfloat16* dst = g_xn + (size_t)(row + r) * D_;
            *reinterpret_cast<uint4*>(dst + lane * 8) = make_uint4(o[0], o[1], o[2], o[3]);
            *reinterpret_cast<uint4*>(dst + 256 + lane * 8) = make_uint4(o[4], o[5], o[6], o[7]);
            *reinterpret_cast<uint4*>(&tile[warp * 2 + r][lane * 8]) = make_uint4(o[0], o[1], o[2], o[3]);
            *reinterpret_cast<uint4*>(&tile[warp * 2 + r][256 + lane * 8]) = make_uint4(o[4], o[5], o[6], o[7]);
        }
    } else if (is_conv) {
        channel_consts(smem, warp - 8, d0 + warp - 8, P);
    }
    __syncthreads();
    if (threadIdx.x == 0) STAMP(0, 3);
#pragma unroll
    for (int rep = 0; rep < 2; rep++) {
        const int c = threadIdx.x + 384 * rep;
        if (c < D_) {
            uint32_t ot[8];
#pragma unroll
            for (int i = 0; i < 8; i++) {
                uint32_t lo = *reinterpret_cast<const uint16_t*>(&tile[2 * i][c]);
                uint32_t hi = *reinterpret_cast<const uint16_t*>(&tile[2 * i + 1][c]);
                ot[i] = lo | (hi << 16);
            }
            __nv_bfloat16* dT = g_xnT + (size_t)c * L_ + blockIdx.x * LN_ROWS;
            *reinterpret_cast<uint4*>(dT) = make_uint4(ot[0], ot[1], ot[2], ot[3]);
            *reinterpret_cast<uint4*>(dT + 8) = make_uint4(ot[4], ot[5], ot[6], ot[7]);
        }
    }
    if (threadIdx.x < 336) {
        const int m = threadIdx.x / 112, i = threadIdx.x - m * 112;
        const char* wp = (const char*)(m == 0 ? wg : (m == 1 ? wu : wd));
        asm volatile("prefetch.global.L2 [%0];" ::"l"(wp + ((size_t)blockIdx.x * 112 + i) * 128));
    }
    fence_async_smem();
    __syncthreads();
    if (threadIdx.x == 0) STAMP(1, 1);
}

__device__ __forceinline__ void conv_round(uint8_t* smem, int d0, bool first, const MegaParams& P) {
    const int warp = threadIdx.x >> 5, lane = threadIdx.x & 31;
    const int ch = warp / 3, w = warp - 3 * ch, tc = threadIdx.x - 96 * ch;
    const int d = d0 + ch;
    const int g = lane >> 2, t = lane & 3;
    uint8_t* base = smem + CV_LATE_BASE + ch * CV_LATE;
    float4* s_const = reinterpret_cast<float4*>(smem + ch * CV_EARLY + CV_O_CONST);
    float* s_kp = reinterpret_cast<float*>(smem + ch * CV_EARLY + CV_O_KP);
    uint32_t* s_q = reinterpret_cast<uint32_t*>(base + CV_O_Q);
    uint32_t* s_q2 = reinterpret_cast<uint32_t*>(base + CV_O_Q2);
    uint32_t* s_q3 = reinterpret_cast<uint32_t*>(base + CV_O_Q3);
    uint32_t* s_q4 = reinterpret_cast<uint32_t*>(base + CV_O_Q4X);
    __nv_bfloat16* s_u = reinterpret_cast<__nv_bfloat16*>(base + CV_O_U);
    const int bar_id = 5 + ch;
    const __nv_bfloat16 p_dsk = P.Dskip[d];
    {
        float acc[5][4];
#pragma unroll
        for (int i = 0; i < 5; i++) { acc[i][0] = acc[i][1] = acc[i][2] = acc[i][3] = 0.f; }
        const float gf = (float)g;
        const int src4 = ((g & 3) << 2) | t;
#pragma unroll 2
        for (int s = w; s < 32; s += 3) {
            if (first && s == 17 && threadIdx.x == 352) asm volatile("red.release.gpu.global.add.u32 [%0], 1;" ::"l"(&g_ln_count) : "memory");
            const float4* c = s_const + (s * 4 + t) * 6;
            const float4 k0 = c[0], k1 = c[1], k2 = c[2];
            const float2 k3 = reinterpret_cast<const float2*>(c + 3)[g >> 2];
            const float2 k4 = reinterpret_cast<const float2*>(c + 4)[g >> 1];
            const cplx cb = {k0.z, k0.w}, e128 = {k1.x, k1.y}, cb8 = {k1.z, k1.w}, c256 = {k2.x, k2.y}, e8 = {k2.z, k2.w};
            const cplx c2 = {k3.x, k3.y}, c3 = {k4.x, k4.y};
            const cplx p1 = cexp_m(k0.x, k0.y, gf);
            const cplx p2 = csq(p1), p4 = csq(p2);
            const cplx r16a = csq(csq(p4));
            cplx q4;
            q4.r = __shfl_sync(0xffffffffu, p4.r, src4);
            q4.i = __shfl_sync(0xffffffffu, p4.i, src4);
            const cplx r16b = cmul(r16a, e128);
            const cplx f0a = cmul(cb, p1), f0b = cmul(cb8, p1), f1 = cmul(c256, p2), f2 = cmul(c2, q4);
            cplx f3 = cmul(c3, e8);
            if (!(g & 1)) f3 = c3;
            const uint32_t a0 = to_tf32(r16a.r), a1 = to_tf32(r16b.r), a2 = to_tf32(-r16a.i), a3 = to_tf32(-r16b.i);
            mma_tf32(acc[0], a0, a1, a2, a3, to_tf32(f0a.r), to_tf32(f0a.i));
            mma_tf32(acc[1], a0, a1, a2, a3, to_tf32(f0b.r), to_tf32(f0b.i));
            mma_tf32(acc[2], a0, a1, a2, a3, to_tf32(f1.r), to_tf32(f1.i));
            mma_tf32(acc[3], a0, a1, a2, a3, to_tf32(f2.r), to_tf32(f2.i));
            mma_tf32(acc[4], a0, a1, a2, a3, to_tf32(f3.r), to_tf32(f3.i));
        }
        float* kv = s_kp + w * 648;
#pragma unroll
        for (int hh = 0; hh < 2; hh++) {
            const int i = g + 8 * hh;
            *reinterpret_cast<float2*>(kv + 16 * i + 2 * t) = make_float2(acc[0][2 * hh], acc[0][2 * hh + 1]);
            *reinterpret_cast<float2*>(kv + 16 * i + 8 + 2 * t) = make_float2(acc[1][2 * hh], acc[1][2 * hh + 1]);
            *reinterpret_cast<float2*>(kv + 256 + 8 * i + 2 * t) = make_float2(acc[2][2 * hh], acc[2][2 * hh + 1]);
            *reinterpret_cast<float2*>(kv + 384 + 64 * (t >> 1) + 2 * (t & 1) + 4 * i) = make_float2(acc[3][2 * hh], acc[3][2 * hh + 1]);
            *reinterpret_cast<float2*>(kv + 512 + 32 * t + 2 * i) = make_float2(acc[4][2 * hh], acc[4][2 * hh + 1]);
        }
    }
    named_bar(bar_id, 96);
    if (threadIdx.x == 0) STAMP(1, 2);
#pragma unroll
    for (int i = 0; i < 7; i++) {
        const int idx = tc + 96 * i;
        if (idx < 641) s_kp[idx] = (s_kp[idx] + s_kp[648 + idx]) + s_kp[1296 + idx];
    }
    named_bar(bar_id, 96);
    {
        auto kdir = [&](int l) -> float {
            if (l < 0 || l > 514) return 0.f;
            const int idx = (l < 256) ? l : (l > 512 ? 384 : 128 + ((l + ((l >> 1) & 1)) >> 1));
            return s_kp[idx];
        };
#pragma unroll
        for (int i = 0; i < 6; i++) {
            const int e = tc + 96 * i;
            s_q[e] = pack_bf16(kdir(e - 16), kdir(e - 17));
        }
        if (tc < 64) {
            const int xx = 1008 + tc;
            const float k1024 = s_kp[512];
            s_q4[tc] = pack_bf16((xx == 1027 || xx == 1028) ? k1024 : 0.f, (xx == 1028 || xx == 1029) ? k1024 : 0.f);
        }
#pragma unroll
        for (int i = 0; i < 3; i++) {
            const int e = tc + 96 * i;
            if (e < 256) {
                const int a = e >> 6, ii = (e & 63) - 16;
                const int b = 385 + (a >> 1) + 2 * (a & 1);
                const float v0 = (ii >= 0 && ii < 32) ? s_kp[b + 4 * ii] : 0.f;
                const float v1 = (ii >= 1 && ii < 33) ? s_kp[b + 4 * (ii - 1)] : 0.f;
                s_q2[e] = pack_bf16(v0, v1);
            }
        }
#pragma unroll
        for (int a = 0; a < 2; a++) {
            const int jj = tc - 16;
            const float v0 = (jj >= 0 && jj < 64) ? s_kp[513 + a + 2 * jj] : 0.f;
            const float v1 = (jj >= 1 && jj < 65) ? s_kp[513 + a + 2 * (jj - 1)] : 0.f;
            s_q3[96 * a + tc] = pack_bf16(v0, v1);
        }
    }
    if (threadIdx.x == 0) STAMP(1, 3);
    if (first) {
        if (threadIdx.x == 0) {
            unsigned int v = 0;
            for (int spin = 0; spin < (1 << 22); spin++) {
                asm volatile("ld.acquire.gpu.global.u32 %0, [%1];" : "=r"(v) : "l"(&g_ln_count) : "memory");
                if (v >= gridDim.x) break;
            }
        }
        __syncthreads();
    }
    if (threadIdx.x == 0) STAMP(1, 4);
    {
        if (tc < 16) *reinterpret_cast<uint4*>(s_u + tc * 8) = make_uint4(0, 0, 0, 0);
        const uint4* src = reinterpret_cast<const uint4*>(g_xnT + (size_t)d * L_);
        uint4 v[3];
#pragma unroll
        for (int i = 0; i < 3; i++) if (tc + 96 * i < 256) v[i] = src[tc + 96 * i];
#pragma unroll
        for (int i = 0; i < 3; i++) if (tc + 96 * i < 256) *reinterpret_cast<uint4*>(s_u + 128 + (tc + 96 * i) * 8) = v[i];
        if (tc < 2) *reinterpret_cast<uint4*>(base + (tc ? CV_O_W5 : CV_O_W3)) = make_uint4(0, 0, 0, 0);
    }
    named_bar(bar_id, 96);
    if (w == 2) {
#pragma unroll 2
      for (int rep = 0; rep < 6; rep++) {
        const int m = lane + 32 * rep;
        float P[30];
        const uint4* up = reinterpret_cast<const uint4*>(s_u + 128 + 8 * m - 24);
        P[0] = 0.f;
#pragma unroll
        for (int c4 = 0; c4 < 4; c4++) {
            const uint4 v = up[c4];
            const uint32_t ww[4] = {v.x, v.y, v.z, v.w};
#pragma unroll
            for (int j = 0; j < 4; j++) {
                const int k = c4 * 8 + 2 * j;
                if (k + 1 <= 29) P[k + 1] = P[k] + bf_lo(ww[j]);
                if (k + 2 <= 29) P[k + 2] = P[k + 1] + bf_hi(ww[j]);
            }
        }
        uint32_t o3[4], o5[4], o7[4], o9[4];
#pragma unroll
        for (int j = 0; j < 4; j++) {
            const int i = 2 * j;
            o3[j] = pack_bf16(P[i + 22] - P[i + 19], P[i + 23] - P[i + 20]);
            o5[j] = pack_bf16(P[i + 19] - P[i + 14], P[i + 20] - P[i + 15]);
            o7[j] = pack_bf16(P[i + 20] - P[i + 13], P[i + 21] - P[i + 14]);
            o9[j] = pack_bf16(P[i + 13] - P[i + 4], P[i + 14] - P[i + 5]);
        }
        *reinterpret_cast<uint4*>(base + CV_O_W3 + 16 + m * 16) = make_uint4(o3[0], o3[1], o3[2], o3[3]);
        *reinterpret_cast<uint4*>(base + CV_O_W5 + 16 + m * 16) = make_uint4(o5[0], o5[1], o5[2], o5[3]);
        if (m < 128) {
            *reinterpret_cast<uint4*>(base + CV_O_W7 + m * 16) = make_uint4(o7[0], o7[1], o7[2], o7[3]);
            *reinterpret_cast<uint4*>(base + CV_O_W9 + m * 16) = make_uint4(o9[0], o9[1], o9[2], o9[3]);
        }
    }
      named_bar(bar_id, 96);
      if (first) channel_consts(smem, ch, d + CV_CH, P);
      return;
    }
    if (threadIdx.x == 0) STAMP(1, 5);
    const int hb = w;
    float acc[16][4];
#pragma unroll
    for (int i = 0; i < 16; i++) { acc[i][0] = acc[i][1] = acc[i][2] = acc[i][3] = 0.f; }
    const uint32_t sb_addr = smem_u32(base);
    const int mi = lane >> 3, rowi = lane & 7;
#pragma unroll 1
    for (int rr = 0; rr < 4; rr++) {
        const int r = 4 * hb + rr;
        uint32_t ub[16][2];
        {
            const uint32_t addr = sb_addr + CV_O_U + (uint32_t)((128 + 16 * (8 * (mi >> 1) + rowi - r) + 8 * (mi & 1)) * 2);
#pragma unroll
            for (int j = 0; j < 16; j += 2) ldsm_x4(addr + (uint32_t)(j * 256), ub[j][0], ub[j][1], ub[j + 1][0], ub[j + 1][1]);
        }
        const uint32_t* qp = s_q + 16 + 16 * r + g - 2 * t;
        uint32_t af[4][3];
#pragma unroll
        for (int q = 0; q < 4; q++) { af[q][0] = qp[128 * q]; af[q][1] = qp[128 * q + 8]; af[q][2] = qp[128 * q - 8]; }
#pragma unroll
        for (int q = 0; q < 4; q++) {
#pragma unroll
            for (int nt = q; nt < 16; nt++) mma_bf16(acc[nt], af[q][0], af[q][1], af[q][2], af[q][0], ub[nt - q][0], ub[nt - q][1]);
        }
        if (r < 2) {
            {
                const uint32_t a0 = qp[512], a1 = qp[520], a2 = qp[504];
#pragma unroll
                for (int nt = 4; nt < 16; nt++) mma_bf16(acc[nt], a0, a1, a2, a0, ub[nt - 4][0], ub[nt - 4][1]);
            }
            {
                const uint32_t* q4p = s_q4 + 16 + 16 * r + g - 2 * t;
                const uint32_t a0 = q4p[0], a1 = q4p[8], a2 = q4p[-8];
#pragma unroll
                for (int nt = 8; nt < 16; nt++) mma_bf16(acc[nt], a0, a1, a2, a0, ub[nt - 8][0], ub[nt - 8][1]);
            }
        }
    }
    named_bar(bar_id, 96);
#pragma unroll 1
    for (int a = hb; a <= 3 * hb; a++) {
        uint32_t bq[7];
        const uint32_t* q2 = s_q2 + a * 64 + 16 + g - 2 * t - 32;
#pragma unroll
        for (int dlt = 3; dlt <= 9; dlt++) bq[dlt - 3] = q2[8 * dlt];
        const uint32_t addr = sb_addr + ((a >> 1) ? CV_O_W5 : CV_O_W3) + (uint32_t)((8 + 16 * (8 * (mi >> 1) + rowi) + 8 * (mi & 1) - 8 * (a & 1)) * 2);
        uint32_t aa[6][4];
#pragma unroll
        for (int kp = 0; kp < 6; kp++) ldsm_x4_t(addr + kp * 512, aa[kp][0], aa[kp][1], aa[kp][2], aa[kp][3]);
#pragma unroll
        for (int kp = 0; kp < 6; kp++) {
#pragma unroll
            for (int dlt = 4; dlt <= 9; dlt++) {
                if (2 * kp + dlt < 16) mma_bf16(acc[2 * kp + dlt], aa[kp][0], aa[kp][1], aa[kp][2], aa[kp][3], bq[dlt - 3], bq[dlt - 4]);
            }
        }
    }
    if (hb == 0) {
#pragma unroll 1
        for (int a = 0; a < 2; a++) {
            uint32_t bq[9];
            const uint32_t* q3 = s_q3 + a * 96 + 16 + g - 2 * t - 64;
#pragma unroll
            for (int dlt = 7; dlt <= 15; dlt++) bq[dlt - 7] = q3[8 * dlt];
            const uint32_t addr = sb_addr + (a ? CV_O_W9 : CV_O_W7) + (uint32_t)((16 * (8 * (mi >> 1) + rowi) + 8 * (mi & 1)) * 2);
            uint32_t aa[4][4];
#pragma unroll
            for (int kp = 0; kp < 4; kp++) ldsm_x4_t(addr + kp * 512, aa[kp][0], aa[kp][1], aa[kp][2], aa[kp][3]);
#pragma unroll
            for (int kp = 0; kp < 4; kp++) {
#pragma unroll
                for (int dlt = 8; dlt <= 15; dlt++) {
                    if (2 * kp + dlt < 16) mma_bf16(acc[2 * kp + dlt], aa[kp][0], aa[kp][1], aa[kp][2], aa[kp][3], bq[dlt - 7], bq[dlt - 8]);
                }
            }
        }
    }
    if (threadIdx.x == 0) STAMP(1, 6);
    named_bar(bar_id, 64);
    {
        float4* xch = reinterpret_cast<float4*>(base + CV_O_W3) + hb * 256;
        if (hb) {
#pragma unroll
            for (int i = 0; i < 8; i++) xch[i * 32 + lane] = make_float4(acc[i][0], acc[i][1], acc[i][2], acc[i][3]);
#pragma unroll
            for (int i = 0; i < 8; i++) { acc[i][0] = acc[8 + i][0]; acc[i][1] = acc[8 + i][1]; acc[i][2] = acc[8 + i][2]; acc[i][3] = acc[8 + i][3]; }
        } else {
#pragma unroll
            for (int i = 0; i < 8; i++) xch[i * 32 + lane] = make_float4(acc[8 + i][0], acc[8 + i][1], acc[8 + i][2], acc[8 + i][3]);
        }
    }
    named_bar(bar_id, 64);
    if (threadIdx.x == 0) STAMP(1, 10);
    {
        const float4* xch = reinterpret_cast<const float4*>(base + CV_O_W3) + (hb ^ 1) * 256 + lane;
        const float dsk = __bfloat162float(p_dsk);
        uint16_t* stg = reinterpret_cast<uint16_t*>(base + CV_O_Q);
        const uint16_t* uu = reinterpret_cast<const uint16_t*>(s_u) + 128;
#pragma unroll
        for (int i = 0; i < 8; i++) {
            const float4 p0 = xch[i * 32];
            const float y[4] = {acc[i][0] + p0.x, acc[i][1] + p0.y, acc[i][2] + p0.z, acc[i][3] + p0.w};
            const int nt = 8 * hb + i;
#pragma unroll
            for (int e = 0; e < 4; e++) {
                const int tau = 16 * (8 * nt + 2 * t + (e & 1)) + g + 8 * (e >> 1);
                const float sv = bf16_round(y[e]) + bf16_round(__uint_as_float((uint32_t)uu[tau] << 16) * dsk);
                stg[tau] = (uint16_t)(__float_as_uint(bf16_round(sv)) >> 16);
            }
        }
        __syncwarp();
        if (threadIdx.x == 0) STAMP(1, 11);
        uint4* dst = reinterpret_cast<uint4*>(g_sT + (size_t)d * L_ + hb * 1024);
        const uint4* srcp = reinterpret_cast<const uint4*>(stg + hb * 1024);
#pragma unroll
        for (int i = 0; i < 4; i++) dst[i * 32 + lane] = srcp[i * 32 + lane];
    }
}

__device__ __forceinline__ uint32_t cluster_rank() { uint32_t r; asm volatile("mov.u32 %0, %%cluster_ctarank;" : "=r"(r)); return r; }
__device__ __forceinline__ void cluster_sync_all() {
    asm volatile("barrier.cluster.arrive.release.aligned;\nbarrier.cluster.wait.acquire.aligned;" ::: "memory");
}
__device__ __forceinline__ void mbar_arrive_remote(uint32_t bar, uint32_t cta) {
    asm volatile("{\n.reg .b32 ra;\nmapa.shared::cluster.u32 ra, %0, %1;\n"
                 "mbarrier.arrive.shared::cluster.b64 _, [ra];\n}\n" ::"r"(bar), "r"(cta) : "memory");
}
__device__ __forceinline__ void tma_load_2d_mc(uint32_t dst, const CUtensorMap* tm, int c0, int c1, uint32_t bar, uint16_t mask) {
    asm volatile(
        "cp.async.bulk.tensor.2d.shared::cluster.global.mbarrier::complete_tx::bytes.multicast::cluster [%0], [%1, {%3, %4}], [%2], %5;"
        ::"r"(dst), "l"((uint64_t)tm), "r"(bar), "r"(c0), "r"(c1), "h"(mask) : "memory");
}
__device__ __forceinline__ void tma_store_2d(const CUtensorMap* tm, uint32_t src, int c0, int c1) {
    asm volatile("cp.async.bulk.tensor.2d.global.shared::cta.bulk_group [%0, {%2, %3}], [%1];"
                 ::"l"((uint64_t)tm), "r"(src), "r"(c0), "r"(c1) : "memory");
}
__device__ __forceinline__ void bulk_commit() { asm volatile("cp.async.bulk.commit_group;" ::: "memory"); }
template <int N> __device__ __forceinline__ void bulk_wait_read() { asm volatile("cp.async.bulk.wait_group.read %0;" ::"n"(N) : "memory"); }
template <int N> __device__ __forceinline__ void bulk_wait() { asm volatile("cp.async.bulk.wait_group %0;" ::"n"(N) : "memory"); }
__device__ __forceinline__ void stmatrix_x4(uint32_t addr, uint32_t r0, uint32_t r1, uint32_t r2, uint32_t r3) {
    asm volatile("stmatrix.sync.aligned.m8n8.x4.shared.b16 [%0], {%1,%2,%3,%4};" ::"r"(addr), "r"(r0), "r"(r1), "r"(r2), "r"(r3) : "memory");
}

constexpr int G1_STAGES = 5;
constexpr int G1_A_BYTES = 8 * 16384;
constexpr int G1_B_STAGE = 16384;
constexpr int G1_STG = 8 * 1024;
constexpr int G1_SMEM = G1_A_BYTES + G1_STAGES * G1_B_STAGE + G1_STG + 1024 + 256;
constexpr int G1_ITERS = 32;

__device__ __forceinline__ void tma_load_3d(uint32_t dst, const CUtensorMap* tm, int c0, int c1, int c2, uint32_t bar) {
    asm volatile(
        "cp.async.bulk.tensor.3d.shared::cluster.global.mbarrier::complete_tx::bytes [%0], [%1, {%3, %4, %5}], [%2];"
        ::"r"(dst), "l"((uint64_t)tm), "r"(bar), "r"(c0), "r"(c1), "r"(c2) : "memory");
}

__device__ __forceinline__ void tma_load_3d_mc(uint32_t dst, const CUtensorMap* tm, int c0, int c1, int c2, uint32_t bar, uint16_t mask) {
    asm volatile(
        "cp.async.bulk.tensor.3d.shared::cluster.global.mbarrier::complete_tx::bytes.multicast::cluster [%0], [%1, {%3, %4, %5}], [%2], %6;"
        ::"r"(dst), "l"((uint64_t)tm), "r"(bar), "r"(c0), "r"(c1), "r"(c2), "h"(mask) : "memory");
}

__device__ __forceinline__ float gelu_tanh(float x) {
    float u = x * (0.7978845608028654f + 0.035677408136300125f * x * x);
    float t; asm("tanh.approx.f32 %0, %1;" : "=f"(t) : "f"(u));
    float hx = 0.5f * x;
    return fmaf(hx, t, hx);
}
__device__ __forceinline__ uint32_t geglu_pair(uint32_t g2, uint32_t u2) {
    uint32_t a = pack_bf16(gelu_tanh(bf_lo(g2)), gelu_tanh(bf_hi(g2)));
    uint32_t r; asm("mul.rn.bf16x2 %0, %1, %2;" : "=r"(r) : "r"(a), "r"(u2));
    return r;
}

constexpr int G2_STAGES = 5;
constexpr int G2_STAGE = 16384 + 16384;
constexpr int G2_EPI = 32768 + 32768;
constexpr int G2_KB = F_ / 64;
constexpr int MG_BAR_OFF = G2_STAGES * G2_STAGE + G2_EPI;
constexpr int MG_SMEM = MG_BAR_OFF + 512 + 1024;
static_assert(MG_BAR_OFF == 229376 && G1_A_BYTES + G1_STAGES * G1_B_STAGE + G1_STG <= MG_BAR_OFF, "smem layout");
constexpr int N_GEMM_CTA = 64;

__device__ __forceinline__ void fence_async_all() { asm volatile("fence.proxy.async;" ::: "memory"); }
__device__ __forceinline__ void spin_until(const unsigned int* p, unsigned int target) {
    unsigned int v = 0;
    for (int spin = 0; spin < (1 << 22); spin++) {
        asm volatile("ld.acquire.gpu.global.u32 %0, [%1];" : "=r"(v) : "l"(p) : "memory");
        if (v >= target) break;
    }
}
__device__ __forceinline__ void finish_cta() {
    const unsigned int old = atomicAdd(&g_done_count, 1u);
    if (old == gridDim.x - 1) {
        g_ln_count = 0; g_conv_count = 0; g_done_count = 0;
        for (int i = 0; i < 32; i++) g_h_count[i] = 0;
    }
}

__global__ void __launch_bounds__(384, 1) mega_kernel(const __grid_constant__ MegaParams P,
                                                       const __grid_constant__ CUtensorMap tm_xn,
                                                       const __grid_constant__ CUtensorMap tm_wg4,
                                                       const __grid_constant__ CUtensorMap tm_wu4,
                                                       const __grid_constant__ CUtensorMap tm_wg3,
                                                       const __grid_constant__ CUtensorMap tm_wu3,
                                                       const __grid_constant__ CUtensorMap tm_h,
                                                       const __grid_constant__ CUtensorMap tm_wd,
                                                       const __grid_constant__ CUtensorMap tm_x,
                                                       const __grid_constant__ CUtensorMap tm_sT,
                                                       const __grid_constant__ CUtensorMap tm_out) {
    if (threadIdx.x == 0) STAMP(1, 0);
    extern __shared__ uint8_t smem_raw[];
    const uint32_t sraw = smem_u32(smem_raw);
    const uint32_t sbase = (sraw + 1023) & ~1023u;
    uint8_t* smem = smem_raw + (sbase - sraw);
    const int warp = threadIdx.x >> 5, lane = threadIdx.x & 31;

    if (blockIdx.x >= N_GEMM_CTA) {
        const int d0 = (blockIdx.x - N_GEMM_CTA) * 2 * CV_CH;
        ln_phase(smem, true, d0, P);
#pragma unroll 1
        for (int rnd = 0; rnd < 2; rnd++) {
            conv_round(smem, d0 + rnd * CV_CH, rnd == 0, P);
            __syncthreads();
            if (threadIdx.x == 0 && rnd == 0) STAMP(1, 7);
        }
        if (threadIdx.x == 0) {
            asm volatile("red.release.gpu.global.add.u32 [%0], 1;" ::"l"(&g_conv_count) : "memory");
            STAMP(1, 8);
            finish_cta();
        }
        return;
    }

    const uint32_t sA = sbase, sB = sbase + G1_A_BYTES, sStg = sB + G1_STAGES * G1_B_STAGE;
    const uint32_t sX = sbase + G2_STAGES * G2_STAGE, sS = sX + 32768;
    const uint32_t sBar = sbase + MG_BAR_OFF;
    const uint32_t bar_a = sBar, bar_full = sBar + 64, bar_empty = bar_full + 8 * G1_STAGES;
    const uint32_t bar_full2 = bar_empty + 8 * G1_STAGES, bar_empty2 = bar_full2 + 8 * G2_STAGES;
    const uint32_t bar_epi = bar_empty2 + 8 * G2_STAGES, bar_g1done = bar_epi + 8, bar_g1mma = bar_g1done + 8;
    const uint32_t kh = blockIdx.x & 1;
    const int rb = ((blockIdx.x >> 3) << 1) + (int)kh;
    const int cq = (blockIdx.x >> 1) & 3;

    if (threadIdx.x == 0) {
        for (int i = 0; i < 8; i++) mbar_init(bar_a + 8 * i, 1);
        for (int i = 0; i < G1_STAGES; i++) { mbar_init(bar_full + 8 * i, 1); mbar_init(bar_empty + 8 * i, 16); }
        for (int i = 0; i < G2_STAGES; i++) { mbar_init(bar_full2 + 8 * i, 1); mbar_init(bar_empty2 + 8 * i, 16); }
        mbar_init(bar_epi, 1);
        mbar_init(bar_g1done, 8);
        mbar_init(bar_g1mma, 16);
        asm volatile("fence.mbarrier_init.release.cluster;" ::: "memory");
    }
    if (warp == 11 && lane == 0) {
        prefetch_tmap(&tm_wg4); prefetch_tmap(&tm_wu4); prefetch_tmap(&tm_xn); prefetch_tmap(&tm_wg3); prefetch_tmap(&tm_wu3);
        prefetch_tmap(&tm_wd); prefetch_tmap(&tm_h); prefetch_tmap(&tm_x); prefetch_tmap(&tm_sT); prefetch_tmap(&tm_out);
    }
    asm volatile("barrier.cluster.arrive.release.aligned;" ::: "memory");
    ln_phase(smem, false, 0, P);
    asm volatile("barrier.cluster.wait.acquire.aligned;" ::: "memory");

    if (warp >= 8) {
        asm volatile("setmaxnreg.dec.sync.aligned.u32 40;");
        if (warp == 11) {
            if (lane == 0) asm volatile("red.release.gpu.global.add.u32 [%0], 1;" ::"l"(&g_ln_count) : "memory");
            named_bar(3, 288);
            if (lane == 0) asm volatile("red.release.gpu.global.add.u32 [%0], 1;" ::"l"(&g_h_count[rb]) : "memory");
            named_bar(9, 288);
            if (lane == 0) asm volatile("red.release.gpu.global.add.u32 [%0], 1;" ::"l"(&g_h_count[16 + rb]) : "memory");
        } else if (lane == 0) {
            const int pw = warp - 8;
            for (int it = pw; it < 2 * G1_ITERS; it += 3) {
                const int s = it % G1_STAGES, kb = it & 15, cj = 2 * cq + (it >> 5);
                if (it >= G1_STAGES) mbar_wait(bar_empty + 8 * s, ((it / G1_STAGES) - 1) & 1);
                const uint32_t dst = sB + s * G1_B_STAGE;
                if ((it & 16) == 0) {
                    mbar_expect_tx(bar_full + 8 * s, 16384);
                    tma_load_3d_mc(dst + kh * 8192, kh ? &tm_wu4 : &tm_wg4, 0, kb * 32, cj * 7, bar_full + 8 * s, 3);
                } else {
                    mbar_expect_tx(bar_full + 8 * s, 12288);
                    tma_load_3d_mc(dst + kh * 6144, kh ? &tm_wu3 : &tm_wg3, 0, kb * 32, cj * 7 + 4, bar_full + 8 * s, 3);
                }
                if (it < 3) {
                    spin_until(&g_ln_count, gridDim.x);
                    fence_async_all();
                    for (int k = pw; k < 8; k += 3) {
                        mbar_expect_tx(bar_a + 8 * k, 16384);
                        tma_load_2d(sA + k * 16384, &tm_xn, k * 64, rb * 128, bar_a + 8 * k);
                    }
                }
            }
            mbar_wait(bar_g1mma, 0);
            spin_until(&g_h_count[rb], 4);
            fence_async_all();
            if (pw == 0) STAMP(3, 1);
            for (int it = pw; it < G2_KB; it += 3) {
                const int s = it % G2_STAGES;
                if (it >= G2_STAGES) mbar_wait(bar_empty2 + 8 * s, ((it / G2_STAGES) - 1) & 1);
                if (it >= 12 && it < 15) { spin_until(&g_h_count[16 + rb], 4); fence_async_all(); }
                const int kb = (it < 12) ? (7 * (it / 3) + it % 3) : (7 * ((it - 12) >> 2) + 3 + ((it - 12) & 3));
                mbar_expect_tx(bar_full2 + 8 * s, G2_STAGE);
                tma_load_3d_mc(sbase + s * G2_STAGE + 16384 + kh * 8192, &tm_wd, 0, kb * 64, cq * 2 + (int)kh, bar_full2 + 8 * s, 3);
                tma_load_2d(sbase + s * G2_STAGE, &tm_h, kb * 64, rb * 128, bar_full2 + 8 * s);
                if (it == 8) {
                    mbar_wait(bar_g1done, 0);
                    mbar_expect_tx(bar_epi, G2_EPI);
                    tma_load_2d(sX, &tm_x, cq * 128, rb * 128, bar_epi);
                    tma_load_2d(sX + 16384, &tm_x, cq * 128 + 64, rb * 128, bar_epi);
                }
                if (it == 20) {
                    spin_until(&g_conv_count, gridDim.x - N_GEMM_CTA);
                    fence_async_all();
#pragma unroll
                    for (int b = 0; b < 4; b++)
                        tma_load_2d(sS + b * 8192, &tm_sT, rb * 128 + (b & 1) * 64, cq * 128 + (b >> 1) * 64, bar_epi);
                }
            }
        }
    } else {
        asm volatile("setmaxnreg.inc.sync.aligned.u32 232;");
        const int wg = __shfl_sync(0xffffffffu, (int)(threadIdx.x >> 7), 0);
#pragma unroll 1
        for (int pass = 0; pass < 2; pass++) {
            const int cj = 2 * cq + pass, it0 = pass * G1_ITERS;
        float r[160];
        const int row0 = rb * 128 + wg * 64 + (warp & 3) * 16;
        const uint64_t descA = make_desc(sA + wg * 8192, 16, 1024);
        const uint64_t descB = make_desc(sB, 2048, 512, 2);
        const uint32_t stg = sStg + warp * 1024;
        const uint32_t st_off = (uint32_t)(((lane & 7) + ((lane >> 3) & 1) * 8) * 32 + (lane >> 4) * 16);
        __nv_bfloat16* hrow = g_h + (size_t)(row0 + (lane >> 1)) * F_ + (lane & 1) * 8 + cj * 224;
#pragma unroll 1
        for (int kb = 0; kb < 16; kb++) {
            const int it = it0 + kb, s = it % G1_STAGES;
            if ((kb & 1) == 0) mbar_wait(bar_a + 8 * (kb >> 1), 0);
            mbar_wait(bar_full + 8 * s, (it / G1_STAGES) & 1);
            if (threadIdx.x == 0 && (it & 15) == 0) STAMP(2, 2 + it / 16);
            wgmma_fence();
            const uint64_t da = descA + (uint64_t)(((kb >> 1) * 16384 + (kb & 1) * 64) >> 4);
            const uint64_t db = descB + (uint64_t)((s * G1_B_STAGE) >> 4);
            wgmma_n256_k32(r, da, da + 2, db, db + 64, kb != 0);
            wgmma_commit();
            if (kb > 0) {
                wgmma_wait<1>();
                if (lane < 2) mbar_arrive_remote(bar_empty + 8 * ((it - 1) % G1_STAGES), lane);
            }
        }
        wgmma_wait<0>();
        if (lane < 2) mbar_arrive_remote(bar_empty + 8 * ((it0 + 15) % G1_STAGES), lane);
#pragma unroll
        for (int i = 0; i < 32; i++) r[128 + i] = __uint_as_float(pack_bf16(r[2 * i], r[2 * i + 1]));
#pragma unroll
        for (int i = 31; i >= 0; i--) r[96 + i] = __uint_as_float(pack_bf16(r[64 + 2 * i], r[65 + 2 * i]));
        uint32_t eo[4];
        uint4 pv = make_uint4(0, 0, 0, 0);
#pragma unroll
        for (int kb = 0; kb < 16; kb++) {
            const int it = it0 + 16 + kb, s = it % G1_STAGES;
            mbar_wait(bar_full + 8 * s, (it / G1_STAGES) & 1);
            if (threadIdx.x == 0 && (it & 15) == 0) STAMP(2, 2 + it / 16);
            wgmma_fence();
            const uint64_t da = descA + (uint64_t)(((kb >> 1) * 16384 + (kb & 1) * 64) >> 4);
            const uint64_t db = descB + (uint64_t)((s * G1_B_STAGE) >> 4);
            wgmma_n192(r, da, db, kb != 0);
            if (kb < 8) {
                eo[0] = geglu_pair(__float_as_uint(r[128 + 4 * kb]), __float_as_uint(r[96 + 4 * kb]));
                eo[1] = geglu_pair(__float_as_uint(r[129 + 4 * kb]), __float_as_uint(r[97 + 4 * kb]));
            }
            wgmma_n192(r, da + 2, db + 64, 1);
            wgmma_commit();
            if (kb >= 2 && kb < 10) *reinterpret_cast<uint4*>(hrow + (kb - 2) * 16) = pv;
            if (kb >= 1 && kb < 9) {
                __syncwarp();
                asm volatile("ld.shared.v4.u32 {%0,%1,%2,%3}, [%4];" : "=r"(pv.x), "=r"(pv.y), "=r"(pv.z), "=r"(pv.w)
                             : "r"(stg + ((kb - 1) & 1) * 512 + lane * 16));
            }
            if (kb < 8) {
                eo[2] = geglu_pair(__float_as_uint(r[130 + 4 * kb]), __float_as_uint(r[98 + 4 * kb]));
                eo[3] = geglu_pair(__float_as_uint(r[131 + 4 * kb]), __float_as_uint(r[99 + 4 * kb]));
                stmatrix_x4(stg + (kb & 1) * 512 + st_off, eo[0], eo[1], eo[2], eo[3]);
            }
            if (kb > 0 && it - 1 + G1_STAGES < 2 * G1_ITERS) {
                wgmma_wait<1>();
                if (lane < 2) mbar_arrive_remote(bar_empty + 8 * ((it - 1) % G1_STAGES), lane);
            }
        }
        wgmma_wait<0>();
        if (pass == 0) {
            if (lane < 2) mbar_arrive_remote(bar_empty + 8 * ((it0 + 31) % G1_STAGES), lane);
        } else {
            fence_async_smem();
            __syncwarp();
            if (lane < 2) mbar_arrive_remote(bar_g1mma, lane);
        }
        if (threadIdx.x == 0 && pass == 1) STAMP(2, 6);
        {
            uint32_t o[24];
#pragma unroll
            for (int i = 0; i < 24; i++) o[i] = geglu_pair(pack_bf16(r[2 * i], r[2 * i + 1]), pack_bf16(r[48 + 2 * i], r[49 + 2 * i]));
            uint4 v[6];
#pragma unroll
            for (int jj = 0; jj < 6; jj += 2) {
                __syncwarp();
                stmatrix_x4(stg + st_off, o[4 * jj], o[4 * jj + 1], o[4 * jj + 2], o[4 * jj + 3]);
                stmatrix_x4(stg + 512 + st_off, o[4 * jj + 4], o[4 * jj + 5], o[4 * jj + 6], o[4 * jj + 7]);
                __syncwarp();
                asm volatile("ld.shared.v4.u32 {%0,%1,%2,%3}, [%4];" : "=r"(v[jj].x), "=r"(v[jj].y), "=r"(v[jj].z), "=r"(v[jj].w) : "r"(stg + lane * 16));
                asm volatile("ld.shared.v4.u32 {%0,%1,%2,%3}, [%4];" : "=r"(v[jj + 1].x), "=r"(v[jj + 1].y), "=r"(v[jj + 1].z), "=r"(v[jj + 1].w) : "r"(stg + 512 + lane * 16));
            }
#pragma unroll
            for (int jj = 0; jj < 6; jj++) *reinterpret_cast<uint4*>(hrow + 128 + jj * 16) = v[jj];
        }
            if (pass == 0) asm volatile("bar.arrive 3, 288;" ::: "memory");
        }
        fence_async_smem();
        __syncwarp();
        if (lane == 0) mbar_arrive(bar_g1done);
        asm volatile("bar.arrive 9, 288;" ::: "memory");
        if (threadIdx.x == 0) STAMP(2, 7);
        {
            const int g = lane >> 2, t = lane & 3;
            float acc[64];
            const uint64_t descA2 = make_desc(sbase + wg * 8192, 16, 1024);
            const uint64_t descB2 = make_desc(sbase + 16384, 8192, 1024);
#pragma unroll 1
            for (int it = 0; it < G2_KB; it++) {
                const int s = it % G2_STAGES;
                mbar_wait(bar_full2 + 8 * s, (it / G2_STAGES) & 1);
                if (threadIdx.x == 0 && (it == 0 || it == 14)) STAMP(3, 2 + it / 14);
                wgmma_fence();
                {
                    const uint64_t da = descA2 + (uint64_t)((s * G2_STAGE) >> 4);
                    const uint64_t db = descB2 + (uint64_t)((s * G2_STAGE) >> 4);
                    wgmma_n128_k64(acc, da, da + 2, da + 4, da + 6, db, db + 128, db + 256, db + 384, it != 0);
                }
                wgmma_commit();
                if (it > 0 && it - 1 + G2_STAGES < G2_KB) {
                    wgmma_wait<1>();
                    if (lane < 2) mbar_arrive_remote(bar_empty2 + 8 * ((it - 1) % G2_STAGES), lane);
                }
            }
            const int lr = wg * 64 + (warp & 3) * 16 + g;
            uint32_t xv[32], sv[32];
            mbar_wait(bar_epi, 0);
#pragma unroll
            for (int j = 0; j < 16; j++) {
#pragma unroll
                for (int hh = 0; hh < 2; hh++) {
                    const int r = lr + 8 * hh;
                    asm volatile("ld.shared.u32 %0, [%1];" : "=r"(xv[2 * j + hh])
                                 : "r"(sX + (j >> 3) * 16384 + r * 128 + (((j & 7) ^ (r & 7)) << 4) + 4 * t));
                    const int c0 = 8 * (j & 7) + 2 * t;
                    const uint32_t sa = sS + (j >> 3) * 16384 + (r >> 6) * 8192 + (((r & 63) >> 3) << 4) + (r & 7) * 2;
                    uint16_t s0r, s1r;
                    asm volatile("ld.shared.u16 %0, [%1];" : "=h"(s0r) : "r"((sa + c0 * 128) ^ ((c0 & 7) << 4)));
                    asm volatile("ld.shared.u16 %0, [%1];" : "=h"(s1r) : "r"((sa + (c0 + 1) * 128) ^ (((c0 + 1) & 7) << 4)));
                    sv[2 * j + hh] = (uint32_t)s0r | ((uint32_t)s1r << 16);
                }
            }
            wgmma_wait<0>();
            if (threadIdx.x == 0) STAMP(3, 4);
#pragma unroll
            for (int i = 0; i < 32; i++) {
                float f0 = bf16_round(acc[2 * i]), f1 = bf16_round(acc[2 * i + 1]);
                float g0 = bf16_round(__fdividef(f0, 1.0f + __expf(-f0)));
                float g1 = bf16_round(__fdividef(f1, 1.0f + __expf(-f1)));
                float o0 = bf_lo(xv[i]) + bf16_round(bf_lo(sv[i]) * g0);
                float o1 = bf_hi(xv[i]) + bf16_round(bf_hi(sv[i]) * g1);
                xv[i] = pack_bf16(o0, o1);
            }
#pragma unroll
            for (int j = 0; j < 16; j++) {
#pragma unroll
                for (int hh = 0; hh < 2; hh++) {
                    const int r = lr + 8 * hh;
                    asm volatile("st.shared.u32 [%0], %1;" ::"r"(sX + (j >> 3) * 16384 + r * 128 + (((j & 7) ^ (r & 7)) << 4) + 4 * t),
                                 "r"(xv[2 * j + hh]) : "memory");
                }
            }
            fence_async_smem();
            __syncwarp();
            if (lane == 0) {
                const int r0 = wg * 64 + (warp & 3) * 16;
                tma_store_2d(&tm_out, sX + r0 * 128, cq * 128, rb * 128 + r0);
                tma_store_2d(&tm_out, sX + 16384 + r0 * 128, cq * 128 + 64, rb * 128 + r0);
                bulk_commit();
                bulk_wait_read<0>();
            }
        }
        if (threadIdx.x == 0) STAMP(3, 5);
        named_bar(4, 256);
        if (threadIdx.x == 0) finish_cta();
    }
    cluster_sync_all();
}

typedef CUresult (*EncodeFn)(CUtensorMap*, CUtensorMapDataType, cuuint32_t, void*, const cuuint64_t*, const cuuint64_t*,
                             const cuuint32_t*, const cuuint32_t*, CUtensorMapInterleave, CUtensorMapSwizzle,
                             CUtensorMapL2promotion, CUtensorMapFloatOOBfill);

void make_map(EncodeFn fn, CUtensorMap* m, const void* ptr, uint64_t inner, uint64_t outer, uint32_t box_in, uint32_t box_out,
              CUtensorMapSwizzle swz = CU_TENSOR_MAP_SWIZZLE_128B) {
    cuuint64_t dims[2] = {inner, outer};
    cuuint64_t strides[1] = {inner * 2};
    cuuint32_t box[2] = {box_in, box_out};
    cuuint32_t es[2] = {1, 1};
    fn(m, CU_TENSOR_MAP_DATA_TYPE_BFLOAT16, 2, const_cast<void*>(ptr), dims, strides, box, es, CU_TENSOR_MAP_INTERLEAVE_NONE,
       swz, CU_TENSOR_MAP_L2_PROMOTION_L2_256B, CU_TENSOR_MAP_FLOAT_OOB_FILL_NONE);
}
void make_map3(EncodeFn fn, CUtensorMap* m, const void* ptr, uint64_t cols, uint64_t rows, uint32_t atom, uint32_t box_rows,
               uint32_t box_atoms, CUtensorMapSwizzle swz) {
    cuuint64_t dims[3] = {atom, rows, cols / atom};
    cuuint64_t strides[2] = {cols * 2, (cuuint64_t)atom * 2};
    cuuint32_t box[3] = {atom, box_rows, box_atoms};
    cuuint32_t es[3] = {1, 1, 1};
    fn(m, CU_TENSOR_MAP_DATA_TYPE_BFLOAT16, 3, const_cast<void*>(ptr), dims, strides, box, es, CU_TENSOR_MAP_INTERLEAVE_NONE,
       swz, CU_TENSOR_MAP_L2_PROMOTION_L2_256B, CU_TENSOR_MAP_FLOAT_OOB_FILL_NONE);
}

template <typename... Args>
void launch_pdl(void (*kern)(Args...), int grid, int block, int smem, bool pdl, int cluster, Args... args) {
    cudaLaunchConfig_t cfg = {};
    cfg.gridDim = dim3(grid); cfg.blockDim = dim3(block); cfg.dynamicSmemBytes = smem; cfg.stream = cudaStreamPerThread;
    cudaLaunchAttribute at[2];
    int n = 0;
    if (pdl) {
        at[n].id = cudaLaunchAttributeProgrammaticStreamSerialization;
        at[n].val.programmaticStreamSerializationAllowed = 1;
        n++;
    }
    if (cluster > 1) {
        at[n].id = cudaLaunchAttributeClusterDimension;
        at[n].val.clusterDim.x = cluster; at[n].val.clusterDim.y = 1; at[n].val.clusterDim.z = 1;
        n++;
    }
    cfg.attrs = at; cfg.numAttrs = n;
    cudaLaunchKernelEx(&cfg, kern, args...);
}

}

extern "C" void kernel_launch(void* const* d_in, const int* in_sizes, int n_in, void* d_out, int out_size) {
    const __nv_bfloat16* x = (const __nv_bfloat16*)d_in[0];
    const __nv_bfloat16* A_re = (const __nv_bfloat16*)d_in[1];
    const __nv_bfloat16* A_im = (const __nv_bfloat16*)d_in[2];
    const __nv_bfloat16* B_re = (const __nv_bfloat16*)d_in[3];
    const __nv_bfloat16* B_im = (const __nv_bfloat16*)d_in[4];
    const __nv_bfloat16* C_re = (const __nv_bfloat16*)d_in[5];
    const __nv_bfloat16* C_im = (const __nv_bfloat16*)d_in[6];
    const __nv_bfloat16* log_dt = (const __nv_bfloat16*)d_in[7];
    const __nv_bfloat16* Dskip = (const __nv_bfloat16*)d_in[8];
    const __nv_bfloat16* wg = (const __nv_bfloat16*)d_in[10];
    const __nv_bfloat16* wu = (const __nv_bfloat16*)d_in[11];
    const __nv_bfloat16* wd = (const __nv_bfloat16*)d_in[12];
    __nv_bfloat16* out = (__nv_bfloat16*)d_out;

    static bool init = false;
    static CUtensorMap tm_xn, tm_wg4, tm_wu4, tm_wg3, tm_wu3, tm_hst, tm_hst96, tm_h, tm_wd, tm_x, tm_sT, tm_out;
    static const void* last_ptrs[5] = {nullptr, nullptr, nullptr, nullptr, nullptr};
    if (!init || last_ptrs[0] != wg || last_ptrs[1] != wu || last_ptrs[2] != wd || last_ptrs[3] != x || last_ptrs[4] != out) {
        void* fnp = nullptr;
        cudaDriverEntryPointQueryResult qres;
        cudaGetDriverEntryPoint("cuTensorMapEncodeTiled", &fnp, cudaEnableDefault, &qres);
        EncodeFn fn = (EncodeFn)fnp;
        void *p_xn, *p_h, *p_sT;
        cudaGetSymbolAddress(&p_xn, g_xn);
        cudaGetSymbolAddress(&p_h, g_h);
        cudaGetSymbolAddress(&p_sT, g_sT);
        make_map(fn, &tm_xn, p_xn, D_, L_, 64, 128);
        make_map3(fn, &tm_wg4, wg, F_, D_, 32, 32, 4, CU_TENSOR_MAP_SWIZZLE_64B);
        make_map3(fn, &tm_wu4, wu, F_, D_, 32, 32, 4, CU_TENSOR_MAP_SWIZZLE_64B);
        make_map3(fn, &tm_wg3, wg, F_, D_, 32, 32, 3, CU_TENSOR_MAP_SWIZZLE_64B);
        make_map3(fn, &tm_wu3, wu, F_, D_, 32, 32, 3, CU_TENSOR_MAP_SWIZZLE_64B);
        make_map(fn, &tm_hst, p_h, F_, L_, 16, 16, CU_TENSOR_MAP_SWIZZLE_NONE);
        make_map(fn, &tm_hst96, p_h, F_, L_, 96, 16, CU_TENSOR_MAP_SWIZZLE_NONE);
        make_map(fn, &tm_h, p_h, F_, L_, 64, 128);
        make_map3(fn, &tm_wd, wd, D_, F_, 64, 64, 1, CU_TENSOR_MAP_SWIZZLE_128B);
        make_map(fn, &tm_x, x, D_, L_, 64, 128);
        make_map(fn, &tm_sT, p_sT, L_, D_, 64, 64);
        make_map(fn, &tm_out, out, D_, L_, 64, 16);
        cudaFuncSetAttribute(mega_kernel, cudaFuncAttributeMaxDynamicSharedMemorySize, MG_SMEM);
        last_ptrs[0] = wg; last_ptrs[1] = wu; last_ptrs[2] = wd; last_ptrs[3] = x; last_ptrs[4] = out;
        init = true;
    }
    MegaParams P = {x, A_re, A_im, B_re, B_im, C_re, C_im, log_dt, Dskip, wg, wu, wd};
    launch_pdl(mega_kernel, 128, 384, MG_SMEM, false, 2, P, tm_xn, tm_wg4, tm_wu4, tm_wg3, tm_wu3, tm_h, tm_wd, tm_x, tm_sT, tm_out);
}
```

```cpp
#include <cuda_runtime.h>
#include <cuda_bf16.h>
#include <cuda.h>
#include <stdint.h>

namespace {

constexpr int L_ = 2048, D_ = 512, NS_ = 128, F_ = 1792;

__device__ __align__(1024) __nv_bfloat16 g_xn[L_ * D_];
__device__ __align__(1024) __nv_bfloat16 g_xnT[D_ * L_];
__device__ __align__(1024) __nv_bfloat16 g_sT[D_ * L_];
__device__ __align__(1024) __nv_bfloat16 g_h[L_ * F_];
__device__ unsigned int g_ln_count, g_conv_count, g_done_count, g_h_count[32];

#define STAMP(k, i)

__device__ __forceinline__ uint32_t smem_u32(const void* p) { return (uint32_t)__cvta_generic_to_shared(p); }
__device__ __forceinline__ void pdl_wait() { asm volatile("griddepcontrol.wait;" ::: "memory"); }
__device__ __forceinline__ void pdl_launch() { asm volatile("griddepcontrol.launch_dependents;" ::: "memory"); }

__device__ __forceinline__ void mbar_init(uint32_t bar, uint32_t cnt) {
    asm volatile("mbarrier.init.shared::cta.b64 [%0], %1;" ::"r"(bar), "r"(cnt) : "memory");
}
__device__ __forceinline__ void mbar_expect_tx(uint32_t bar, uint32_t bytes) {
    asm volatile("mbarrier.arrive.expect_tx.shared::cta.b64 _, [%0], %1;" ::"r"(bar), "r"(bytes) : "memory");
}
__device__ __forceinline__ void mbar_arrive(uint32_t bar) {
    asm volatile("mbarrier.arrive.shared::cta.b64 _, [%0];" ::"r"(bar) : "memory");
}
__device__ __forceinline__ void mbar_wait(uint32_t bar, uint32_t parity) {
    asm volatile(
        "{\n.reg .pred p;\n"
        "WAIT_LOOP:\n"
        "mbarrier.try_wait.parity.shared::cta.b64 p, [%0], %1;\n"
        "@p bra WAIT_DONE;\n"
        "bra WAIT_LOOP;\n"
        "WAIT_DONE:\n}\n" ::"r"(bar), "r"(parity) : "memory");
}
__device__ __forceinline__ void tma_load_2d(uint32_t dst, const CUtensorMap* tm, int c0, int c1, uint32_t bar) {
    asm volatile(
        "cp.async.bulk.tensor.2d.shared::cluster.global.mbarrier::complete_tx::bytes [%0], [%1, {%3, %4}], [%2];"
        ::"r"(dst), "l"((uint64_t)tm), "r"(bar), "r"(c0), "r"(c1) : "memory");
}
__device__ __forceinline__ void prefetch_tmap(const CUtensorMap* tm) {
    asm volatile("prefetch.tensormap [%0];" ::"l"((uint64_t)tm) : "memory");
}
__device__ __forceinline__ uint64_t make_desc(uint32_t addr, uint32_t lbo, uint32_t sbo, uint64_t mode = 1) {
    uint64_t d = 0;
    d |= (uint64_t)((addr & 0x3FFFF) >> 4);
    d |= (uint64_t)((lbo >> 4) & 0x3FFF) << 16;
    d |= (uint64_t)((sbo >> 4) & 0x3FFF) << 32;
    d |= mode << 62;
    return d;
}
__device__ __forceinline__ void fence_async_smem() { asm volatile("fence.proxy.async.shared::cta;" ::: "memory"); }
__device__ __forceinline__ void wgmma_fence() { asm volatile("wgmma.fence.sync.aligned;" ::: "memory"); }
__device__ __forceinline__ void wgmma_commit() { asm volatile("wgmma.commit_group.sync.aligned;" ::: "memory"); }
template <int N> __device__ __forceinline__ void wgmma_wait() {
    asm volatile("wgmma.wait_group.sync.aligned %0;" ::"n"(N) : "memory");
}

#define R8(a, i) "+f"(a[i + 0]), "+f"(a[i + 1]), "+f"(a[i + 2]), "+f"(a[i + 3]), "+f"(a[i + 4]), "+f"(a[i + 5]), "+f"(a[i + 6]), "+f"(a[i + 7])

__device__ __forceinline__ void wgmma_n256_k32(float* a, uint64_t da0, uint64_t da1, uint64_t db0, uint64_t db1, int scale_d) {
    asm volatile(
        "{\n.reg .pred p;\nsetp.ne.b32 p, %132, 0;\n"
        "wgmma.mma_async.sync.aligned.m64n256k16.f32.bf16.bf16 {%0,%1,%2,%3,%4,%5,%6,%7,%8,%9,%10,%11,%12,%13,%14,%15,%16,%17,%18,%19,%20,%21,%22,%23,%24,%25,%26,%27,%28,%29,%30,%31,%32,%33,%34,%35,%36,%37,%38,%39,%40,%41,%42,%43,%44,%45,%46,%47,%48,%49,%50,%51,%52,%53,%54,%55,%56,%57,%58,%59,%60,%61,%62,%63,%64,%65,%66,%67,%68,%69,%70,%71,%72,%73,%74,%75,%76,%77,%78,%79,%80,%81,%82,%83,%84,%85,%86,%87,%88,%89,%90,%91,%92,%93,%94,%95,%96,%97,%98,%99,%100,%101,%102,%103,%104,%105,%106,%107,%108,%109,%110,%111,%112,%113,%114,%115,%116,%117,%118,%119,%120,%121,%122,%123,%124,%125,%126,%127}, %128, %130, p, 1, 1, 0, 1;\n"
        "wgmma.mma_async.sync.aligned.m64n256k16.f32.bf16.bf16 {%0,%1,%2,%3,%4,%5,%6,%7,%8,%9,%10,%11,%12,%13,%14,%15,%16,%17,%18,%19,%20,%21,%22,%23,%24,%25,%26,%27,%28,%29,%30,%31,%32,%33,%34,%35,%36,%37,%38,%39,%40,%41,%42,%43,%44,%45,%46,%47,%48,%49,%50,%51,%52,%53,%54,%55,%56,%57,%58,%59,%60,%61,%62,%63,%64,%65,%66,%67,%68,%69,%70,%71,%72,%73,%74,%75,%76,%77,%78,%79,%80,%81,%82,%83,%84,%85,%86,%87,%88,%89,%90,%91,%92,%93,%94,%95,%96,%97,%98,%99,%100,%101,%102,%103,%104,%105,%106,%107,%108,%109,%110,%111,%112,%113,%114,%115,%116,%117,%118,%119,%120,%121,%122,%123,%124,%125,%126,%127}, %129, %131, 1, 1, 1, 0, 1;\n"
        "}\n"
        : R8(a, 0), R8(a, 8), R8(a, 16), R8(a, 24), R8(a, 32), R8(a, 40), R8(a, 48), R8(a, 56), R8(a, 64), R8(a, 72), R8(a, 80), R8(a, 88), R8(a, 96), R8(a, 104), R8(a, 112), R8(a, 120)
        : "l"(da0), "l"(da1), "l"(db0), "l"(db1), "r"(scale_d));
}
__device__ __forceinline__ void wgmma_n192_k32(float* a, uint64_t da0, uint64_t da1, uint64_t db0, uint64_t db1, int scale_d) {
    asm volatile(
        "{\n.reg .pred p;\nsetp.ne.b32 p, %100, 0;\n"
        "wgmma.mma_async.sync.aligned.m64n192k16.f32.bf16.bf16 {%0,%1,%2,%3,%4,%5,%6,%7,%8,%9,%10,%11,%12,%13,%14,%15,%16,%17,%18,%19,%20,%21,%22,%23,%24,%25,%26,%27,%28,%29,%30,%31,%32,%33,%34,%35,%36,%37,%38,%39,%40,%41,%42,%43,%44,%45,%46,%47,%48,%49,%50,%51,%52,%53,%54,%55,%56,%57,%58,%59,%60,%61,%62,%63,%64,%65,%66,%67,%68,%69,%70,%71,%72,%73,%74,%75,%76,%77,%78,%79,%80,%81,%82,%83,%84,%85,%86,%87,%88,%89,%90,%91,%92,%93,%94,%95}, %96, %98, p, 1, 1, 0, 1;\n"
        "wgmma.mma_async.sync.aligned.m64n192k16.f32.bf16.bf16 {%0,%1,%2,%3,%4,%5,%6,%7,%8,%9,%10,%11,%12,%13,%14,%15,%16,%17,%18,%19,%20,%21,%22,%23,%24,%25,%26,%27,%28,%29,%30,%31,%32,%33,%34,%35,%36,%37,%38,%39,%40,%41,%42,%43,%44,%45,%46,%47,%48,%49,%50,%51,%52,%53,%54,%55,%56,%57,%58,%59,%60,%61,%62,%63,%64,%65,%66,%67,%68,%69,%70,%71,%72,%73,%74,%75,%76,%77,%78,%79,%80,%81,%82,%83,%84,%85,%86,%87,%88,%89,%90,%91,%92,%93,%94,%95}, %97, %99, 1, 1, 1, 0, 1;\n"
        "}\n"
        : R8(a, 0), R8(a, 8), R8(a, 16), R8(a, 24), R8(a, 32), R8(a, 40), R8(a, 48), R8(a, 56), R8(a, 64), R8(a, 72), R8(a, 80), R8(a, 88)
        : "l"(da0), "l"(da1), "l"(db0), "l"(db1), "r"(scale_d));
}
__device__ __forceinline__ void wgmma_n192(float* a, uint64_t da0, uint64_t db0, int scale_d) {
    asm volatile(
        "{\n.reg .pred p;\nsetp.ne.b32 p, %98, 0;\n"
        "wgmma.mma_async.sync.aligned.m64n192k16.f32.bf16.bf16 {%0,%1,%2,%3,%4,%5,%6,%7,%8,%9,%10,%11,%12,%13,%14,%15,%16,%17,%18,%19,%20,%21,%22,%23,%24,%25,%26,%27,%28,%29,%30,%31,%32,%33,%34,%35,%36,%37,%38,%39,%40,%41,%42,%43,%44,%45,%46,%47,%48,%49,%50,%51,%52,%53,%54,%55,%56,%57,%58,%59,%60,%61,%62,%63,%64,%65,%66,%67,%68,%69,%70,%71,%72,%73,%74,%75,%76,%77,%78,%79,%80,%81,%82,%83,%84,%85,%86,%87,%88,%89,%90,%91,%92,%93,%94,%95}, %96, %97, p, 1, 1, 0, 1;\n"
        "}\n"
        : R8(a, 0), R8(a, 8), R8(a, 16), R8(a, 24), R8(a, 32), R8(a, 40), R8(a, 48), R8(a, 56), R8(a, 64), R8(a, 72), R8(a, 80), R8(a, 88)
        : "l"(da0), "l"(db0), "r"(scale_d));
}
__device__ __forceinline__ void wgmma_n128_k64(float* a, uint64_t da0, uint64_t da1, uint64_t da2, uint64_t da3,
                                               uint64_t db0, uint64_t db1, uint64_t db2, uint64_t db3, int scale_d) {
    asm volatile(
        "{\n.reg .pred p;\nsetp.ne.b32 p, %72, 0;\n"
        "wgmma.mma_async.sync.aligned.m64n128k16.f32.bf16.bf16 {%0,%1,%2,%3,%4,%5,%6,%7,%8,%9,%10,%11,%12,%13,%14,%15,%16,%17,%18,%19,%20,%21,%22,%23,%24,%25,%26,%27,%28,%29,%30,%31,%32,%33,%34,%35,%36,%37,%38,%39,%40,%41,%42,%43,%44,%45,%46,%47,%48,%49,%50,%51,%52,%53,%54,%55,%56,%57,%58,%59,%60,%61,%62,%63}, %64, %68, p, 1, 1, 0, 1;\n"
        "wgmma.mma_async.sync.aligned.m64n128k16.f32.bf16.bf16 {%0,%1,%2,%3,%4,%5,%6,%7,%8,%9,%10,%11,%12,%13,%14,%15,%16,%17,%18,%19,%20,%21,%22,%23,%24,%25,%26,%27,%28,%29,%30,%31,%32,%33,%34,%35,%36,%37,%38,%39,%40,%41,%42,%43,%44,%45,%46,%47,%48,%49,%50,%51,%52,%53,%54,%55,%56,%57,%58,%59,%60,%61,%62,%63}, %65, %69, 1, 1, 1, 0, 1;\n"
        "wgmma.mma_async.sync.aligned.m64n128k16.f32.bf16.bf16 {%0,%1,%2,%3,%4,%5,%6,%7,%8,%9,%10,%11,%12,%13,%14,%15,%16,%17,%18,%19,%20,%21,%22,%23,%24,%25,%26,%27,%28,%29,%30,%31,%32,%33,%34,%35,%36,%37,%38,%39,%40,%41,%42,%43,%44,%45,%46,%47,%48,%49,%50,%51,%52,%53,%54,%55,%56,%57,%58,%59,%60,%61,%62,%63}, %66, %70, 1, 1, 1, 0, 1;\n"
        "wgmma.mma_async.sync.aligned.m64n128k16.f32.bf16.bf16 {%0,%1,%2,%3,%4,%5,%6,%7,%8,%9,%10,%11,%12,%13,%14,%15,%16,%17,%18,%19,%20,%21,%22,%23,%24,%25,%26,%27,%28,%29,%30,%31,%32,%33,%34,%35,%36,%37,%38,%39,%40,%41,%42,%43,%44,%45,%46,%47,%48,%49,%50,%51,%52,%53,%54,%55,%56,%57,%58,%59,%60,%61,%62,%63}, %67, %71, 1, 1, 1, 0, 1;\n"
        "}\n"
        : R8(a, 0), R8(a, 8), R8(a, 16), R8(a, 24), R8(a, 32), R8(a, 40), R8(a, 48), R8(a, 56)
        : "l"(da0), "l"(da1), "l"(da2), "l"(da3), "l"(db0), "l"(db1), "l"(db2), "l"(db3), "r"(scale_d));
}

__device__ __forceinline__ float bf16_round(float x) {
    uint32_t p; asm("cvt.rn.bf16x2.f32 %0, %1, %2;" : "=r"(p) : "f"(x), "f"(0.0f));
    return __uint_as_float(p);
}
__device__ __forceinline__ uint32_t pack_bf16(float lo, float hi) {
    __nv_bfloat162 v = __floats2bfloat162_rn(lo, hi);
    return *reinterpret_cast<uint32_t*>(&v);
}
__device__ __forceinline__ float bf_lo(uint32_t v) { return __uint_as_float(v << 16); }
__device__ __forceinline__ float bf_hi(uint32_t v) { return __uint_as_float(v & 0xFFFF0000u); }

struct cplx { float r, i; };
__device__ __forceinline__ cplx cmul(cplx a, cplx b) {
    cplx c; c.r = a.r * b.r - a.i * b.i; c.i = a.r * b.i + a.i * b.r; return c;
}
__device__ __forceinline__ cplx csq(cplx a) {
    cplx c; c.r = a.r * a.r - a.i * a.i; c.i = 2.0f * a.r * a.i; return c;
}
__device__ __forceinline__ cplx cexp_m(float ar2, float ai2, float m) {
    float mag;
    asm("ex2.approx.ftz.f32 %0, %1;" : "=f"(mag) : "f"(ar2 * m));
    float rr = ai2 * m;
    rr -= (rr + 12582912.0f) - 12582912.0f;
    float th = rr * 6.283185307179586f;
    cplx c; c.r = mag * __cosf(th); c.i = mag * __sinf(th);
    return c;
}
__device__ __forceinline__ uint32_t to_tf32(float x) { return __float_as_uint(x) + 0x1000u; }
__device__ __forceinline__ void mma_tf32(float* c, uint32_t a0, uint32_t a1, uint32_t a2, uint32_t a3, uint32_t b0, uint32_t b1) {
    asm volatile("mma.sync.aligned.m16n8k8.row.col.f32.tf32.tf32.f32 {%0,%1,%2,%3}, {%4,%5,%6,%7}, {%8,%9}, {%0,%1,%2,%3};"
                 : "+f"(c[0]), "+f"(c[1]), "+f"(c[2]), "+f"(c[3])
                 : "r"(a0), "r"(a1), "r"(a2), "r"(a3), "r"(b0), "r"(b1));
}
__device__ __forceinline__ void mma_bf16(float* c, uint32_t a0, uint32_t a1, uint32_t a2, uint32_t a3, uint32_t b0, uint32_t b1) {
    asm volatile("mma.sync.aligned.m16n8k16.row.col.f32.bf16.bf16.f32 {%0,%1,%2,%3}, {%4,%5,%6,%7}, {%8,%9}, {%0,%1,%2,%3};"
                 : "+f"(c[0]), "+f"(c[1]), "+f"(c[2]), "+f"(c[3])
                 : "r"(a0), "r"(a1), "r"(a2), "r"(a3), "r"(b0), "r"(b1));
}
__device__ __forceinline__ void named_bar(int id, int n) { asm volatile("bar.sync %0, %1;" ::"r"(id), "r"(n) : "memory"); }
__device__ __forceinline__ void ldsm_x4(uint32_t addr, uint32_t& r0, uint32_t& r1, uint32_t& r2, uint32_t& r3) {
    asm volatile("ldmatrix.sync.aligned.m8n8.x4.shared.b16 {%0,%1,%2,%3}, [%4];" : "=r"(r0), "=r"(r1), "=r"(r2), "=r"(r3) : "r"(addr));
}
__device__ __forceinline__ void ldsm_x4_t(uint32_t addr, uint32_t& r0, uint32_t& r1, uint32_t& r2, uint32_t& r3) {
    asm volatile("ldmatrix.sync.aligned.m8n8.x4.trans.shared.b16 {%0,%1,%2,%3}, [%4];" : "=r"(r0), "=r"(r1), "=r"(r2), "=r"(r3) : "r"(addr));
}

constexpr int CV_CH = 4;
constexpr int CV_O_CONST = 0;
constexpr int CV_O_KP = 12288;
constexpr int CV_EARLY = 12288 + 7776;
constexpr int CV_O_Q = 0;
constexpr int CV_O_Q2 = CV_O_Q + 2304;
constexpr int CV_O_Q3 = CV_O_Q2 + 1024;
constexpr int CV_O_Q4X = CV_O_Q3 + 768;
constexpr int CV_O_W3 = CV_O_Q4X + 256;
constexpr int CV_O_W5 = CV_O_W3 + 3104;
constexpr int CV_O_W7 = CV_O_W5 + 3104;
constexpr int CV_O_W9 = CV_O_W7 + 2048;
constexpr int CV_O_U = CV_O_W9 + 2048;
constexpr int CV_LATE = CV_O_U + 4352;
constexpr int CV_LATE_BASE = 229376 - CV_CH * CV_LATE;
constexpr int CV_TILE_OFF = CV_CH * CV_EARLY;
static_assert(CV_TILE_OFF + 16 * (D_ + 8) * 2 <= CV_LATE_BASE && CV_LATE_BASE >= 131072 + 16384, "front layout");
static_assert(CV_O_W3 >= 4096 && CV_O_U - CV_O_W3 >= 8192 && (CV_LATE % 16) == 0 && (CV_EARLY % 16) == 0, "front layout");

constexpr int LN_ROWS = 16;

template <typename PF>
__device__ __forceinline__ void front_phase(PF prefetch_fn, uint8_t* smem, const __nv_bfloat16* __restrict__ x,
                                            const __nv_bfloat16* __restrict__ A_re, const __nv_bfloat16* __restrict__ A_im,
                                            const __nv_bfloat16* __restrict__ B_re, const __nv_bfloat16* __restrict__ B_im,
                                            const __nv_bfloat16* __restrict__ C_re, const __nv_bfloat16* __restrict__ C_im,
                                            const __nv_bfloat16* __restrict__ log_dt, const __nv_bfloat16* __restrict__ Dskip,
                                            const __nv_bfloat16* __restrict__ wg, const __nv_bfloat16* __restrict__ wu,
                                            const __nv_bfloat16* __restrict__ wd) {
    const int warp = threadIdx.x >> 5, lane = threadIdx.x & 31;
    const int ch = warp / 3, w = warp - 3 * ch, tc = threadIdx.x - 96 * ch;
    const int d = blockIdx.x * CV_CH + ch;
    const int g = lane >> 2, t = lane & 3;
    uint8_t* base = smem + CV_LATE_BASE + ch * CV_LATE;
    float4* s_const = reinterpret_cast<float4*>(smem + ch * CV_EARLY + CV_O_CONST);
    float* s_kp = reinterpret_cast<float*>(smem + ch * CV_EARLY + CV_O_KP);
    uint32_t* s_q = reinterpret_cast<uint32_t*>(base + CV_O_Q);
    uint32_t* s_q2 = reinterpret_cast<uint32_t*>(base + CV_O_Q2);
    uint32_t* s_q3 = reinterpret_cast<uint32_t*>(base + CV_O_Q3);
    uint32_t* s_q4 = reinterpret_cast<uint32_t*>(base + CV_O_Q4X);
    __nv_bfloat16* s_u = reinterpret_cast<__nv_bfloat16*>(base + CV_O_U);
    const int bar_id = 5 + ch;
    const __nv_bfloat16 p_dsk = Dskip[d];
    __nv_bfloat16 (*tile)[D_ + 8] = reinterpret_cast<__nv_bfloat16 (*)[D_ + 8]>(smem + CV_TILE_OFF);

    if (warp < 8) {
        const int row = blockIdx.x * LN_ROWS + warp * 2;
        uint4 xv[2][2];
#pragma unroll
        for (int r = 0; r < 2; r++) {
            xv[r][0] = *reinterpret_cast<const uint4*>(x + (size_t)(row + r) * D_ + lane * 8);
            xv[r][1] = *reinterpret_cast<const uint4*>(x + (size_t)(row + r) * D_ + 256 + lane * 8);
        }
        float f[2][16], sm[2], q[2];
#pragma unroll
        for (int r = 0; r < 2; r++) {
            const uint32_t wv[8] = {xv[r][0].x, xv[r][0].y, xv[r][0].z, xv[r][0].w, xv[r][1].x, xv[r][1].y, xv[r][1].z, xv[r][1].w};
#pragma unroll
            for (int i = 0; i < 8; i++) { f[r][2 * i] = bf_lo(wv[i]); f[r][2 * i + 1] = bf_hi(wv[i]); }
            sm[r] = 0.f;
#pragma unroll
            for (int i = 0; i < 16; i++) sm[r] += f[r][i];
        }
#pragma unroll
        for (int o = 16; o > 0; o >>= 1) { sm[0] += __shfl_xor_sync(0xffffffffu, sm[0], o); sm[1] += __shfl_xor_sync(0xffffffffu, sm[1], o); }
#pragma unroll
        for (int r = 0; r < 2; r++) {
            sm[r] *= (1.0f / D_);
            q[r] = 0.f;
#pragma unroll
            for (int i = 0; i < 16; i++) { float dd = f[r][i] - sm[r]; q[r] += dd * dd; }
        }
#pragma unroll
        for (int o = 16; o > 0; o >>= 1) { q[0] += __shfl_xor_sync(0xffffffffu, q[0], o); q[1] += __shfl_xor_sync(0xffffffffu, q[1], o); }
#pragma unroll
        for (int r = 0; r < 2; r++) {
            const float mb = bf16_round(sm[r]);
            const float vb = bf16_round(q[r] * (1.0f / D_));
            const float den = bf16_round(sqrtf(bf16_round(vb + 1e-5f)));
            uint32_t o[8];
#pragma unroll
            for (int i = 0; i < 8; i++) {
                float a = __fdiv_rn(bf16_round(f[r][2 * i] - mb), den);
                float b = __fdiv_rn(bf16_round(f[r][2 * i + 1] - mb), den);
                o[i] = pack_bf16(a, b);
            }
            __nv_bfloat16* dst = g_xn + (size_t)(row + r) * D_;
            *reinterpret_cast<uint4*>(dst + lane * 8) = make_uint4(o[0], o[1], o[2], o[3]);
            *reinterpret_cast<uint4*>(dst + 256 + lane * 8) = make_uint4(o[4], o[5], o[6], o[7]);
            *reinterpret_cast<uint4*>(&tile[warp * 2 + r][lane * 8]) = make_uint4(o[0], o[1], o[2], o[3]);
            *reinterpret_cast<uint4*>(&tile[warp * 2 + r][256 + lane * 8]) = make_uint4(o[4], o[5], o[6], o[7]);
        }
    } else {
        const int cc_ = warp - 8, dd = blockIdx.x * CV_CH + cc_;
        float4* sc = reinterpret_cast<float4*>(smem + cc_ * CV_EARLY + CV_O_CONST);
        __nv_bfloat16 pr[4][6];
#pragma unroll
        for (int j = 0; j < 4; j++) {
            const size_t off = (size_t)dd * NS_ + lane + 32 * j;
            pr[j][0] = A_re[off]; pr[j][1] = A_im[off]; pr[j][2] = B_re[off]; pr[j][3] = B_im[off]; pr[j][4] = C_re[off]; pr[j][5] = C_im[off];
        }
        const float dt = bf16_round(expf(__bfloat162float(log_dt[dd])));
        float tail = 0.f;
#pragma unroll 1
        for (int j = 0; j < 4; j++) {
            __nv_bfloat16 q6[6];
#pragma unroll
            for (int e = 0; e < 6; e++) q6[e] = j == 0 ? pr[0][e] : (j == 1 ? pr[1][e] : (j == 2 ? pr[2][e] : pr[3][e]));
            const float ar = dt * __bfloat162float(q6[0]), ai = dt * __bfloat162float(q6[1]);
            const cplx db = {dt * __bfloat162float(q6[2]), dt * __bfloat162float(q6[3])};
            const cplx cc = {__bfloat162float(q6[4]), __bfloat162float(q6[5])};
            const cplx cb = cmul(cc, db);
            const float ar2 = ar * 1.4426950408889634f, ai2 = ai * 0.15915494309189535f;
            const cplx e8 = cexp_m(ar2, ai2, 8.f), e128 = cexp_m(ar2, ai2, 128.f);
            const cplx cb8 = cmul(cb, e8);
            const cplx e256 = cexp_m(ar2, ai2, 256.f), e512 = cexp_m(ar2, ai2, 512.f), e1024 = cexp_m(ar2, ai2, 1024.f);
            const cplx c256 = cmul(cb, e256), c512 = cmul(cb, e512), c1024 = cmul(cb, e1024);
            const cplx c768 = cmul(c512, e256), c1280 = cmul(c1024, e256), c1536 = cmul(c1024, e512);
            const cplx c1792 = cmul(c1536, e256);
            tail += cmul(c1024, e1024).r;
            float4* c = sc + (lane + 32 * j) * 6;
            c[0] = make_float4(ar2, ai2, cb.r, cb.i);
            c[1] = make_float4(e128.r, e128.i, cb8.r, cb8.i);
            c[2] = make_float4(c256.r, c256.i, e8.r, e8.i);
            c[3] = make_float4(c512.r, c512.i, c768.r, c768.i);
            c[4] = make_float4(c1024.r, c1024.i, c1280.r, c1280.i);
            c[5] = make_float4(c1536.r, c1536.i, c1792.r, c1792.i);
        }
#pragma unroll
        for (int o = 16; o > 0; o >>= 1) tail += __shfl_xor_sync(0xffffffffu, tail, o);
        if (lane == 0) {
            float* kp = reinterpret_cast<float*>(smem + cc_ * CV_EARLY + CV_O_KP);
            kp[640] = tail; kp[648 + 640] = 0.f; kp[1296 + 640] = 0.f;
        }
    }
    __syncthreads();
    if (threadIdx.x == 0) STAMP(0, 3);
#pragma unroll
    for (int rep = 0; rep < 2; rep++) {
        const int c = threadIdx.x + 384 * rep;
        if (c < D_) {
            uint32_t ot[8];
#pragma unroll
            for (int i = 0; i < 8; i++) {
                uint32_t lo = *reinterpret_cast<const uint16_t*>(&tile[2 * i][c]);
                uint32_t hi = *reinterpret_cast<const uint16_t*>(&tile[2 * i + 1][c]);
                ot[i] = lo | (hi << 16);
            }
            __nv_bfloat16* dT = g_xnT + (size_t)c * L_ + blockIdx.x * LN_ROWS;
            *reinterpret_cast<uint4*>(dT) = make_uint4(ot[0], ot[1], ot[2], ot[3]);
            *reinterpret_cast<uint4*>(dT + 8) = make_uint4(ot[4], ot[5], ot[6], ot[7]);
        }
    }
    if (threadIdx.x < 336) {
        const int m = threadIdx.x / 112, i = threadIdx.x - m * 112;
        const char* wp = (const char*)(m == 0 ? wg : (m == 1 ? wu : wd));
        asm volatile("prefetch.global.L2 [%0];" ::"l"(wp + ((size_t)blockIdx.x * 112 + i) * 128));
    }
    __syncthreads();
    if (threadIdx.x == 0) STAMP(1, 1);
    {
        float acc[5][4];
#pragma unroll
        for (int i = 0; i < 5; i++) { acc[i][0] = acc[i][1] = acc[i][2] = acc[i][3] = 0.f; }
        const float gf = (float)g;
        const int src4 = ((g & 3) << 2) | t;
#pragma unroll 2
        for (int s = w; s < 32; s += 3) {
            if (s == 17 && threadIdx.x == 352) asm volatile("red.release.gpu.global.add.u32 [%0], 1;" ::"l"(&g_ln_count) : "memory");
            const float4* c = s_const + (s * 4 + t) * 6;
            const float4 k0 = c[0], k1 = c[1], k2 = c[2];
            const float2 k3 = reinterpret_cast<const float2*>(c + 3)[g >> 2];
            const float2 k4 = reinterpret_cast<const float2*>(c + 4)[g >> 1];
            const cplx cb = {k0.z, k0.w}, e128 = {k1.x, k1.y}, cb8 = {k1.z, k1.w}, c256 = {k2.x, k2.y}, e8 = {k2.z, k2.w};
            const cplx c2 = {k3.x, k3.y}, c3 = {k4.x, k4.y};
            const cplx p1 = cexp_m(k0.x, k0.y, gf);
            const cplx p2 = csq(p1), p4 = csq(p2);
            const cplx r16a = csq(csq(p4));
            cplx q4;
            q4.r = __shfl_sync(0xffffffffu, p4.r, src4);
            q4.i = __shfl_sync(0xffffffffu, p4.i, src4);
            const cplx r16b = cmul(r16a, e128);
            const cplx f0a = cmul(cb, p1), f0b = cmul(cb8, p1), f1 = cmul(c256, p2), f2 = cmul(c2, q4);
            cplx f3 = cmul(c3, e8);
            if (!(g & 1)) f3 = c3;
            const uint32_t a0 = to_tf32(r16a.r), a1 = to_tf32(r16b.r), a2 = to_tf32(-r16a.i), a3 = to_tf32(-r16b.i);
            mma_tf32(acc[0], a0, a1, a2, a3, to_tf32(f0a.r), to_tf32(f0a.i));
            mma_tf32(acc[1], a0, a1, a2, a3, to_tf32(f0b.r), to_tf32(f0b.i));
            mma_tf32(acc[2], a0, a1, a2, a3, to_tf32(f1.r), to_tf32(f1.i));
            mma_tf32(acc[3], a0, a1, a2, a3, to_tf32(f2.r), to_tf32(f2.i));
            mma_tf32(acc[4], a0, a1, a2, a3, to_tf32(f3.r), to_tf32(f3.i));
        }
        float* kv = s_kp + w * 648;
#pragma unroll
        for (int hh = 0; hh < 2; hh++) {
            const int i = g + 8 * hh;
            *reinterpret_cast<float2*>(kv + 16 * i + 2 * t) = make_float2(acc[0][2 * hh], acc[0][2 * hh + 1]);
            *reinterpret_cast<float2*>(kv + 16 * i + 8 + 2 * t) = make_float2(acc[1][2 * hh], acc[1][2 * hh + 1]);
            *reinterpret_cast<float2*>(kv + 256 + 8 * i + 2 * t) = make_float2(acc[2][2 * hh], acc[2][2 * hh + 1]);
            *reinterpret_cast<float2*>(kv + 384 + 64 * (t >> 1) + 2 * (t & 1) + 4 * i) = make_float2(acc[3][2 * hh], acc[3][2 * hh + 1]);
            *reinterpret_cast<float2*>(kv + 512 + 32 * t + 2 * i) = make_float2(acc[4][2 * hh], acc[4][2 * hh + 1]);
        }
    }
    named_bar(bar_id, 96);
    if (threadIdx.x == 0) STAMP(1, 2);
#pragma unroll 1
    for (int i = 0; i < 7; i++) {
        const int idx = tc + 96 * i;
        if (idx < 641) s_kp[idx] = (s_kp[idx] + s_kp[648 + idx]) + s_kp[1296 + idx];
    }
    named_bar(bar_id, 96);
    {
        auto kdir = [&](int l) -> float {
            if (l < 0 || l > 514) return 0.f;
            const int idx = (l < 256) ? l : (l > 512 ? 384 : 128 + ((l + ((l >> 1) & 1)) >> 1));
            return s_kp[idx];
        };
#pragma unroll 2
        for (int i = 0; i < 6; i++) {
            const int e = tc + 96 * i;
            s_q[e] = pack_bf16(kdir(e - 16), kdir(e - 17));
        }
        if (tc < 64) {
            const int xx = 1008 + tc;
            const float k1024 = s_kp[512];
            s_q4[tc] = pack_bf16((xx == 1027 || xx == 1028) ? k1024 : 0.f, (xx == 1028 || xx == 1029) ? k1024 : 0.f);
        }
#pragma unroll 1
        for (int i = 0; i < 3; i++) {
            const int e = tc + 96 * i;
            if (e < 256) {
                const int a = e >> 6, ii = (e & 63) - 16;
                const int b = 385 + (a >> 1) + 2 * (a & 1);
                const float v0 = (ii >= 0 && ii < 32) ? s_kp[b + 4 * ii] : 0.f;
                const float v1 = (ii >= 1 && ii < 33) ? s_kp[b + 4 * (ii - 1)] : 0.f;
                s_q2[e] = pack_bf16(v0, v1);
            }
        }
#pragma unroll
        for (int a = 0; a < 2; a++) {
            const int jj = tc - 16;
            const float v0 = (jj >= 0 && jj < 64) ? s_kp[513 + a + 2 * jj] : 0.f;
            const float v1 = (jj >= 1 && jj < 65) ? s_kp[513 + a + 2 * (jj - 1)] : 0.f;
            s_q3[96 * a + tc] = pack_bf16(v0, v1);
        }
    }
    if (threadIdx.x == 0) STAMP(1, 3);
    if (threadIdx.x == 0) {
        unsigned int v = 0;
        for (int spin = 0; spin < (1 << 22); spin++) {
            asm volatile("ld.acquire.gpu.global.u32 %0, [%1];" : "=r"(v) : "l"(&g_ln_count) : "memory");
            if (v >= gridDim.x) break;
        }
    }
    fence_async_smem();
    __syncthreads();
    if (threadIdx.x == 0) STAMP(1, 4);
    prefetch_fn();
    {
        if (tc < 16) *reinterpret_cast<uint4*>(s_u + tc * 8) = make_uint4(0, 0, 0, 0);
        const uint4* src = reinterpret_cast<const uint4*>(g_xnT + (size_t)d * L_);
        uint4 v[3];
#pragma unroll
        for (int i = 0; i < 3; i++) if (tc + 96 * i < 256) v[i] = src[tc + 96 * i];
#pragma unroll
        for (int i = 0; i < 3; i++) if (tc + 96 * i < 256) *reinterpret_cast<uint4*>(s_u + 128 + (tc + 96 * i) * 8) = v[i];
        if (tc < 2) *reinterpret_cast<uint4*>(base + (tc ? CV_O_W5 : CV_O_W3)) = make_uint4(0, 0, 0, 0);
    }
    named_bar(bar_id, 96);
    if (w == 2) {
#pragma unroll 1
      for (int rep = 0; rep < 6; rep++) {
        const int m = lane + 32 * rep;
        float P[30];
        const uint4* up = reinterpret_cast<const uint4*>(s_u + 128 + 8 * m - 24);
        P[0] = 0.f;
#pragma unroll
        for (int c4 = 0; c4 < 4; c4++) {
            const uint4 v = up[c4];
            const uint32_t ww[4] = {v.x, v.y, v.z, v.w};
#pragma unroll
            for (int j = 0; j < 4; j++) {
                const int k = c4 * 8 + 2 * j;
                if (k + 1 <= 29) P[k + 1] = P[k] + bf_lo(ww[j]);
                if (k + 2 <= 29) P[k + 2] = P[k + 1] + bf_hi(ww[j]);
            }
        }
        uint32_t o3[4], o5[4], o7[4], o9[4];
#pragma unroll
        for (int j = 0; j < 4; j++) {
            const int i = 2 * j;
            o3[j] = pack_bf16(P[i + 22] - P[i + 19], P[i + 23] - P[i + 20]);
            o5[j] = pack_bf16(P[i + 19] - P[i + 14], P[i + 20] - P[i + 15]);
            o7[j] = pack_bf16(P[i + 20] - P[i + 13], P[i + 21] - P[i + 14]);
            o9[j] = pack_bf16(P[i + 13] - P[i + 4], P[i + 14] - P[i + 5]);
        }
        *reinterpret_cast<uint4*>(base + CV_O_W3 + 16 + m * 16) = make_uint4(o3[0], o3[1], o3[2], o3[3]);
        *reinterpret_cast<uint4*>(base + CV_O_W5 + 16 + m * 16) = make_uint4(o5[0], o5[1], o5[2], o5[3]);
        if (m < 128) {
            *reinterpret_cast<uint4*>(base + CV_O_W7 + m * 16) = make_uint4(o7[0], o7[1], o7[2], o7[3]);
            *reinterpret_cast<uint4*>(base + CV_O_W9 + m * 16) = make_uint4(o9[0], o9[1], o9[2], o9[3]);
        }
    }
      named_bar(bar_id, 96);
      return;
    }
    if (threadIdx.x == 0) STAMP(1, 5);
    const int hb = w;
    float acc[16][4];
#pragma unroll
    for (int i = 0; i < 16; i++) { acc[i][0] = acc[i][1] = acc[i][2] = acc[i][3] = 0.f; }
    const uint32_t sb_addr = smem_u32(base);
    const int mi = lane >> 3, rowi = lane & 7;
#pragma unroll 1
    for (int rr = 0; rr < 4; rr++) {
        const int r = 4 * hb + rr;
        uint32_t ub[16][2];
        {
            const uint32_t addr = sb_addr + CV_O_U + (uint32_t)((128 + 16 * (8 * (mi >> 1) + rowi - r) + 8 * (mi & 1)) * 2);
#pragma unroll
            for (int j = 0; j < 16; j += 2) ldsm_x4(addr + (uint32_t)(j * 256), ub[j][0], ub[j][1], ub[j + 1][0], ub[j + 1][1]);
        }
        const uint32_t* qp = s_q + 16 + 16 * r + g - 2 * t;
        uint32_t af[4][3];
#pragma unroll
        for (int q = 0; q < 4; q++) { af[q][0] = qp[128 * q]; af[q][1] = qp[128 * q + 8]; af[q][2] = qp[128 * q - 8]; }
#pragma unroll
        for (int q = 0; q < 4; q++) {
#pragma unroll
            for (int nt = q; nt < 16; nt++) mma_bf16(acc[nt], af[q][0], af[q][1], af[q][2], af[q][0], ub[nt - q][0], ub[nt - q][1]);
        }
        if (r < 2) {
            {
                const uint32_t a0 = qp[512], a1 = qp[520], a2 = qp[504];
#pragma unroll
                for (int nt = 4; nt < 16; nt++) mma_bf16(acc[nt], a0, a1, a2, a0, ub[nt - 4][0], ub[nt - 4][1]);
            }
            {
                const uint32_t* q4p = s_q4 + 16 + 16 * r + g - 2 * t;
                const uint32_t a0 = q4p[0], a1 = q4p[8], a2 = q4p[-8];
#pragma unroll
                for (int nt = 8; nt < 16; nt++) mma_bf16(acc[nt], a0, a1, a2, a0, ub[nt - 8][0], ub[nt - 8][1]);
            }
        }
    }
    named_bar(bar_id, 96);
#pragma unroll 1
    for (int a = hb; a <= 3 * hb; a++) {
        uint32_t bq[7];
        const uint32_t* q2 = s_q2 + a * 64 + 16 + g - 2 * t - 32;
#pragma unroll
        for (int dlt = 3; dlt <= 9; dlt++) bq[dlt - 3] = q2[8 * dlt];
        const uint32_t addr = sb_addr + ((a >> 1) ? CV_O_W5 : CV_O_W3) + (uint32_t)((8 + 16 * (8 * (mi >> 1) + rowi) + 8 * (mi & 1) - 8 * (a & 1)) * 2);
        uint32_t aa[6][4];
#pragma unroll
        for (int kp = 0; kp < 6; kp++) ldsm_x4_t(addr + kp * 512, aa[kp][0], aa[kp][1], aa[kp][2], aa[kp][3]);
#pragma unroll
        for (int kp = 0; kp < 6; kp++) {
#pragma unroll
            for (int dlt = 4; dlt <= 9; dlt++) {
                if (2 * kp + dlt < 16) mma_bf16(acc[2 * kp + dlt], aa[kp][0], aa[kp][1], aa[kp][2], aa[kp][3], bq[dlt - 3], bq[dlt - 4]);
            }
        }
    }
    if (hb == 0) {
#pragma unroll 1
        for (int a = 0; a < 2; a++) {
            uint32_t bq[9];
            const uint32_t* q3 = s_q3 + a * 96 + 16 + g - 2 * t - 64;
#pragma unroll
            for (int dlt = 7; dlt <= 15; dlt++) bq[dlt - 7] = q3[8 * dlt];
            const uint32_t addr = sb_addr + (a ? CV_O_W9 : CV_O_W7) + (uint32_t)((16 * (8 * (mi >> 1) + rowi) + 8 * (mi & 1)) * 2);
            uint32_t aa[4][4];
#pragma unroll
            for (int kp = 0; kp < 4; kp++) ldsm_x4_t(addr + kp * 512, aa[kp][0], aa[kp][1], aa[kp][2], aa[kp][3]);
#pragma unroll
            for (int kp = 0; kp < 4; kp++) {
#pragma unroll
                for (int dlt = 8; dlt <= 15; dlt++) {
                    if (2 * kp + dlt < 16) mma_bf16(acc[2 * kp + dlt], aa[kp][0], aa[kp][1], aa[kp][2], aa[kp][3], bq[dlt - 7], bq[dlt - 8]);
                }
            }
        }
    }
    if (threadIdx.x == 0) STAMP(1, 6);
    named_bar(bar_id, 64);
    {
        float4* xch = reinterpret_cast<float4*>(base + CV_O_W3) + hb * 256;
        if (hb) {
#pragma unroll
            for (int i = 0; i < 8; i++) xch[i * 32 + lane] = make_float4(acc[i][0], acc[i][1], acc[i][2], acc[i][3]);
#pragma unroll
            for (int i = 0; i < 8; i++) { acc[i][0] = acc[8 + i][0]; acc[i][1] = acc[8 + i][1]; acc[i][2] = acc[8 + i][2]; acc[i][3] = acc[8 + i][3]; }
        } else {
#pragma unroll
            for (int i = 0; i < 8; i++) xch[i * 32 + lane] = make_float4(acc[8 + i][0], acc[8 + i][1], acc[8 + i][2], acc[8 + i][3]);
        }
    }
    named_bar(bar_id, 64);
    if (threadIdx.x == 0) STAMP(1, 10);
    {
        const float4* xch = reinterpret_cast<const float4*>(base + CV_O_W3) + (hb ^ 1) * 256 + lane;
        const float dsk = __bfloat162float(p_dsk);
        uint16_t* stg = reinterpret_cast<uint16_t*>(base + CV_O_Q);
        const uint16_t* uu = reinterpret_cast<const uint16_t*>(s_u) + 128;
#pragma unroll
        for (int i = 0; i < 8; i++) {
            const float4 p0 = xch[i * 32];
            const float y[4] = {acc[i][0] + p0.x, acc[i][1] + p0.y, acc[i][2] + p0.z, acc[i][3] + p0.w};
            const int nt = 8 * hb + i;
#pragma unroll
            for (int e = 0; e < 4; e++) {
                const int tau = 16 * (8 * nt + 2 * t + (e & 1)) + g + 8 * (e >> 1);
                const float sv = bf16_round(y[e]) + bf16_round(__uint_as_float((uint32_t)uu[tau] << 16) * dsk);
                stg[tau] = (uint16_t)(__float_as_uint(bf16_round(sv)) >> 16);
            }
        }
        __syncwarp();
        if (threadIdx.x == 0) STAMP(1, 11);
        uint4* dst = reinterpret_cast<uint4*>(g_sT + (size_t)d * L_ + hb * 1024);
        const uint4* srcp = reinterpret_cast<const uint4*>(stg + hb * 1024);
#pragma unroll
        for (int i = 0; i < 4; i++) dst[i * 32 + lane] = srcp[i * 32 + lane];
    }
}

__device__ __forceinline__ uint32_t cluster_rank() { uint32_t r; asm volatile("mov.u32 %0, %%cluster_ctarank;" : "=r"(r)); return r; }
__device__ __forceinline__ void cluster_sync_all() {
    asm volatile("barrier.cluster.arrive.release.aligned;\nbarrier.cluster.wait.acquire.aligned;" ::: "memory");
}
__device__ __forceinline__ void mbar_arrive_remote(uint32_t bar, uint32_t cta) {
    asm volatile("{\n.reg .b32 ra;\nmapa.shared::cluster.u32 ra, %0, %1;\n"
                 "mbarrier.arrive.shared::cluster.b64 _, [ra];\n}\n" ::"r"(bar), "r"(cta) : "memory");
}
__device__ __forceinline__ void tma_load_2d_mc(uint32_t dst, const CUtensorMap* tm, int c0, int c1, uint32_t bar, uint16_t mask) {
    asm volatile(
        "cp.async.bulk.tensor.2d.shared::cluster.global.mbarrier::complete_tx::bytes.multicast::cluster [%0], [%1, {%3, %4}], [%2], %5;"
        ::"r"(dst), "l"((uint64_t)tm), "r"(bar), "r"(c0), "r"(c1), "h"(mask) : "memory");
}
__device__ __forceinline__ void tma_store_2d(const CUtensorMap* tm, uint32_t src, int c0, int c1) {
    asm volatile("cp.async.bulk.tensor.2d.global.shared::cta.bulk_group [%0, {%2, %3}], [%1];"
                 ::"l"((uint64_t)tm), "r"(src), "r"(c0), "r"(c1) : "memory");
}
__device__ __forceinline__ void bulk_commit() { asm volatile("cp.async.bulk.commit_group;" ::: "memory"); }
template <int N> __device__ __forceinline__ void bulk_wait_read() { asm volatile("cp.async.bulk.wait_group.read %0;" ::"n"(N) : "memory"); }
template <int N> __device__ __forceinline__ void bulk_wait() { asm volatile("cp.async.bulk.wait_group %0;" ::"n"(N) : "memory"); }
__device__ __forceinline__ void stmatrix_x4(uint32_t addr, uint32_t r0, uint32_t r1, uint32_t r2, uint32_t r3) {
    asm volatile("stmatrix.sync.aligned.m8n8.x4.shared.b16 [%0], {%1,%2,%3,%4};" ::"r"(addr), "r"(r0), "r"(r1), "r"(r2), "r"(r3) : "memory");
}

constexpr int G1_STAGES = 5;
constexpr int G1_A_BYTES = 8 * 16384;
constexpr int G1_B_STAGE = 16384;
constexpr int G1_STG = 8 * 1024;
constexpr int G1_SMEM = G1_A_BYTES + G1_STAGES * G1_B_STAGE + G1_STG + 1024 + 256;
constexpr int G1_ITERS = 32;

__device__ __forceinline__ void tma_load_3d(uint32_t dst, const CUtensorMap* tm, int c0, int c1, int c2, uint32_t bar) {
    asm volatile(
        "cp.async.bulk.tensor.3d.shared::cluster.global.mbarrier::complete_tx::bytes [%0], [%1, {%3, %4, %5}], [%2];"
        ::"r"(dst), "l"((uint64_t)tm), "r"(bar), "r"(c0), "r"(c1), "r"(c2) : "memory");
}

__device__ __forceinline__ void tma_load_3d_mc(uint32_t dst, const CUtensorMap* tm, int c0, int c1, int c2, uint32_t bar, uint16_t mask) {
    asm volatile(
        "cp.async.bulk.tensor.3d.shared::cluster.global.mbarrier::complete_tx::bytes.multicast::cluster [%0], [%1, {%3, %4, %5}], [%2], %6;"
        ::"r"(dst), "l"((uint64_t)tm), "r"(bar), "r"(c0), "r"(c1), "r"(c2), "h"(mask) : "memory");
}

__device__ __forceinline__ float gelu_tanh(float x) {
    float u = x * (0.7978845608028654f + 0.035677408136300125f * x * x);
    float t; asm("tanh.approx.f32 %0, %1;" : "=f"(t) : "f"(u));
    float hx = 0.5f * x;
    return fmaf(hx, t, hx);
}
__device__ __forceinline__ uint32_t geglu_pair(uint32_t g2, uint32_t u2) {
    uint32_t a = pack_bf16(gelu_tanh(bf_lo(g2)), gelu_tanh(bf_hi(g2)));
    uint32_t r; asm("mul.rn.bf16x2 %0, %1, %2;" : "=r"(r) : "r"(a), "r"(u2));
    return r;
}

constexpr int G2_STAGES = 5;
constexpr int G2_STAGE = 16384 + 16384;
constexpr int G2_XCH = 32768;
constexpr int G2_EPI = 16384 + 16384;
constexpr int G2_SMEM = G2_STAGES * G2_STAGE + G2_XCH + G2_EPI + 1024 + 256;
constexpr int G2_KB = F_ / 64 / 2;

constexpr int MG_BAR_OFF = G2_STAGES * G2_STAGE + G2_XCH + G2_EPI;
constexpr int MG_SMEM = MG_BAR_OFF + 512 + 1024;
static_assert(MG_BAR_OFF == 229376 && G1_A_BYTES + G1_STAGES * G1_B_STAGE + G1_STG <= MG_BAR_OFF, "smem layout");

__device__ __forceinline__ void fence_async_all() { asm volatile("fence.proxy.async;" ::: "memory"); }
__device__ __forceinline__ void spin_until(const unsigned int* p, unsigned int target) {
    unsigned int v = 0;
    for (int spin = 0; spin < (1 << 22); spin++) {
        asm volatile("ld.acquire.gpu.global.u32 %0, [%1];" : "=r"(v) : "l"(p) : "memory");
        if (v >= target) break;
    }
}

struct MegaParams {
    const __nv_bfloat16 *x, *A_re, *A_im, *B_re, *B_im, *C_re, *C_im, *log_dt, *Dskip, *wg, *wu, *wd;
};

__global__ void __launch_bounds__(384, 1) mega_kernel(const __grid_constant__ MegaParams P,
                                                       const __grid_constant__ CUtensorMap tm_xn,
                                                       const __grid_constant__ CUtensorMap tm_wg4,
                                                       const __grid_constant__ CUtensorMap tm_wu4,
                                                       const __grid_constant__ CUtensorMap tm_wg3,
                                                       const __grid_constant__ CUtensorMap tm_wu3,
                                                       const __grid_constant__ CUtensorMap tm_h,
                                                       const __grid_constant__ CUtensorMap tm_wd,
                                                       const __grid_constant__ CUtensorMap tm_x,
                                                       const __grid_constant__ CUtensorMap tm_sT,
                                                       const __grid_constant__ CUtensorMap tm_out) {
    if (threadIdx.x == 0) STAMP(1, 0);
    extern __shared__ uint8_t smem_raw[];
    const uint32_t sraw = smem_u32(smem_raw);
    const uint32_t sbase = (sraw + 1023) & ~1023u;
    uint8_t* smem = smem_raw + (sbase - sraw);
    const int warp = threadIdx.x >> 5, lane = threadIdx.x & 31;
    const uint32_t sA = sbase, sB = sbase + G1_A_BYTES, sStg = sB + G1_STAGES * G1_B_STAGE;
    const uint32_t sXch = sbase + G2_STAGES * G2_STAGE, sX = sXch + G2_XCH, sS = sX + 16384;
    const uint32_t sBar = sbase + MG_BAR_OFF;
    const uint32_t bar_a = sBar, bar_full = sBar + 64, bar_empty = bar_full + 8 * G1_STAGES;
    const uint32_t bar_full2 = bar_empty + 8 * G1_STAGES, bar_empty2 = bar_full2 + 8 * G2_STAGES;
    const uint32_t bar_epi = bar_empty2 + 8 * G2_STAGES, bar_xch = bar_epi + 8, bar_g1done = bar_xch + 8, bar_g1mma = bar_g1done + 8, bar_peer = bar_g1mma + 8;
    const uint32_t kh = blockIdx.x & 1;
    const int rb1 = ((blockIdx.x >> 4) << 1) + (int)kh, cj = (blockIdx.x >> 1) & 7;
    const int rb = blockIdx.x >> 3;
    const int nb = (blockIdx.x >> 1) & 3;
    const int col_fin = nb * 128 + kh * 64;

    if (threadIdx.x == 0) {
        for (int i = 0; i < 8; i++) mbar_init(bar_a + 8 * i, 1);
        for (int i = 0; i < G1_STAGES; i++) { mbar_init(bar_full + 8 * i, 1); mbar_init(bar_empty + 8 * i, 16); }
        for (int i = 0; i < G2_STAGES; i++) { mbar_init(bar_full2 + 8 * i, 1); mbar_init(bar_empty2 + 8 * i, 8); }
        mbar_init(bar_epi, 1);
        mbar_init(bar_xch, 1);
        mbar_init(bar_g1done, 8);
        mbar_init(bar_g1mma, 8);
        mbar_init(bar_peer, 1);
        asm volatile("fence.mbarrier_init.release.cluster;" ::: "memory");
        mbar_expect_tx(bar_xch, G2_XCH);
    }
    if (warp == 11 && lane == 0) {
        prefetch_tmap(&tm_wg4); prefetch_tmap(&tm_wu4); prefetch_tmap(&tm_xn); prefetch_tmap(&tm_wg3); prefetch_tmap(&tm_wu3);
        prefetch_tmap(&tm_wd); prefetch_tmap(&tm_h); prefetch_tmap(&tm_x); prefetch_tmap(&tm_sT); prefetch_tmap(&tm_out);
    }
    asm volatile("barrier.cluster.arrive.release.aligned;" ::: "memory");

    auto g1_prefetch = [&]() {
        if (warp == 8 && lane == 0) {
            fence_async_all();
            mbar_expect_tx(bar_full, 16384);
            tma_load_3d(sB, &tm_wg4, 0, 0, cj * 7, bar_full);
            tma_load_3d(sB + 8192, &tm_wu4, 0, 0, cj * 7, bar_full);
            for (int k = 0; k < 8; k++) {
                mbar_expect_tx(bar_a + 8 * k, 16384);
                tma_load_2d(sA + k * 16384, &tm_xn, k * 64, rb1 * 128, bar_a + 8 * k);
            }
        }
    };
    front_phase(g1_prefetch, smem, P.x, P.A_re, P.A_im, P.B_re, P.B_im, P.C_re, P.C_im, P.log_dt, P.Dskip, P.wg, P.wu, P.wd);
    fence_async_smem();
    asm volatile("barrier.cluster.wait.acquire.aligned;" ::: "memory");
    __syncthreads();
    if (threadIdx.x == 352) mbar_arrive_remote(bar_peer, kh ^ 1);
    if (threadIdx.x == 0) STAMP(1, 7);

    if (warp >= 8) {
        asm volatile("setmaxnreg.dec.sync.aligned.u32 40;");
        if (warp == 11) {
            if (lane == 0) asm volatile("red.release.gpu.global.add.u32 [%0], 1;" ::"l"(&g_conv_count) : "memory");
            named_bar(3, 288);
            if (lane == 0) asm volatile("red.release.gpu.global.add.u32 [%0], 1;" ::"l"(&g_h_count[rb1]) : "memory");
            named_bar(9, 288);
            if (lane == 0) asm volatile("red.release.gpu.global.add.u32 [%0], 1;" ::"l"(&g_h_count[16 + rb1]) : "memory");
        } else if (lane == 0) {
            const int pw = warp - 8;
            mbar_wait(bar_peer, 0);
            for (int it = 1 + pw; it < G1_ITERS; it += 3) {
                const int s = it % G1_STAGES, kb = it & 15;
                if (it >= G1_STAGES) mbar_wait(bar_empty + 8 * s, ((it / G1_STAGES) - 1) & 1);
                const uint32_t dst = sB + s * G1_B_STAGE;
                if (it < 16) {
                    mbar_expect_tx(bar_full + 8 * s, 16384);
                    tma_load_3d_mc(dst + kh * 8192, kh ? &tm_wu4 : &tm_wg4, 0, kb * 32, cj * 7, bar_full + 8 * s, 3);
                } else {
                    mbar_expect_tx(bar_full + 8 * s, 12288);
                    tma_load_3d_mc(dst + kh * 6144, kh ? &tm_wu3 : &tm_wg3, 0, kb * 32, cj * 7 + 4, bar_full + 8 * s, 3);
                }
            }
            const int k0 = kh * G2_KB;
            auto kblk = [&](int it) -> int {
                const unsigned long long tab = 0xDCA96532B87410ull;
                return k0 + (int)((tab >> (4 * it)) & 15);
            };
            mbar_wait(bar_g1mma, 0);
            if (pw == 2) {
                mbar_expect_tx(bar_epi, G2_EPI);
                tma_load_2d(sX, &tm_x, col_fin, rb * 128, bar_epi);
            }
            spin_until(&g_h_count[rb], 8);
            fence_async_all();
            if (pw == 0) STAMP(3, 1);
            for (int it = pw; it < G2_KB; it += 3) {
                const int s = (it + 1) % G2_STAGES;
                if (it == 4) mbar_wait(bar_g1done, 0);
                if (it >= G2_STAGES) mbar_wait(bar_empty2 + 8 * s, ((it / G2_STAGES) - 1) & 1);
                if (it >= 6 && it < 9) { spin_until(&g_h_count[16 + rb], 8); fence_async_all(); }
                mbar_expect_tx(bar_full2 + 8 * s, G2_STAGE);
                const int kb = kblk(it);
                tma_load_3d(sbase + s * G2_STAGE + 16384, &tm_wd, 0, kb * 64, nb * 2, bar_full2 + 8 * s);
                tma_load_2d(sbase + s * G2_STAGE, &tm_h, kb * 64, rb * 128, bar_full2 + 8 * s);
                if (it == 2) {
                    spin_until(&g_conv_count, gridDim.x);
                    fence_async_all();
                    tma_load_2d(sS, &tm_sT, rb * 128, col_fin, bar_epi);
                    tma_load_2d(sS + 8192, &tm_sT, rb * 128 + 64, col_fin, bar_epi);
                }
            }
        }
    } else {
        asm volatile("setmaxnreg.inc.sync.aligned.u32 232;");
        const int wg = __shfl_sync(0xffffffffu, (int)(threadIdx.x >> 7), 0);
        {
        float r[160];
        const int row0 = rb1 * 128 + wg * 64 + (warp & 3) * 16;
        const uint64_t descA = make_desc(sA + wg * 8192, 16, 1024);
        const uint64_t descB = make_desc(sB, 2048, 512, 2);
        const uint32_t stg = sStg + warp * 1024;
        const uint32_t st_off = (uint32_t)(((lane & 7) + ((lane >> 3) & 1) * 8) * 32 + (lane >> 4) * 16);
        __nv_bfloat16* hrow = g_h + (size_t)(row0 + (lane >> 1)) * F_ + (lane & 1) * 8 + cj * 224;
#pragma unroll 1
        for (int kb = 0; kb < 16; kb++) {
            const int it = kb, s = it % G1_STAGES;
            if ((kb & 1) == 0) mbar_wait(bar_a + 8 * (kb >> 1), 0);
            mbar_wait(bar_full + 8 * s, (it / G1_STAGES) & 1);
            if (threadIdx.x == 0 && (it & 7) == 0) STAMP(2, 2 + it / 8);
            wgmma_fence();
            const uint64_t da = descA + (uint64_t)(((kb >> 1) * 16384 + (kb & 1) * 64) >> 4);
            const uint64_t db = descB + (uint64_t)((s * G1_B_STAGE) >> 4);
            wgmma_n256_k32(r, da, da + 2, db, db + 64, kb != 0);
            wgmma_commit();
            if (kb > 0) {
                wgmma_wait<1>();
                if (lane < 2) mbar_arrive_remote(bar_empty + 8 * ((it - 1) % G1_STAGES), lane);
            }
        }
        wgmma_wait<0>();
        if (lane < 2) mbar_arrive_remote(bar_empty + 8 * (15 % G1_STAGES), lane);
#pragma unroll
        for (int i = 0; i < 32; i++) r[128 + i] = __uint_as_float(pack_bf16(r[2 * i], r[2 * i + 1]));
#pragma unroll
        for (int i = 31; i >= 0; i--) r[96 + i] = __uint_as_float(pack_bf16(r[64 + 2 * i], r[65 + 2 * i]));
        uint32_t eo[4];
        uint4 pv = make_uint4(0, 0, 0, 0);
#pragma unroll
        for (int kb = 0; kb < 16; kb++) {
            const int it = 16 + kb, s = it % G1_STAGES;
            mbar_wait(bar_full + 8 * s, (it / G1_STAGES) & 1);
            if (threadIdx.x == 0 && (it & 7) == 0) STAMP(2, 2 + it / 8);
            wgmma_fence();
            const uint64_t da = descA + (uint64_t)(((kb >> 1) * 16384 + (kb & 1) * 64) >> 4);
            const uint64_t db = descB + (uint64_t)((s * G1_B_STAGE) >> 4);
            wgmma_n192(r, da, db, kb != 0);
            if (kb < 8) {
                eo[0] = geglu_pair(__float_as_uint(r[128 + 4 * kb]), __float_as_uint(r[96 + 4 * kb]));
                eo[1] = geglu_pair(__float_as_uint(r[129 + 4 * kb]), __float_as_uint(r[97 + 4 * kb]));
            }
            wgmma_n192(r, da + 2, db + 64, 1);
            wgmma_commit();
            if (kb >= 2 && kb < 10) *reinterpret_cast<uint4*>(hrow + (kb - 2) * 16) = pv;
            if (kb >= 1 && kb < 9) {
                __syncwarp();
                asm volatile("ld.shared.v4.u32 {%0,%1,%2,%3}, [%4];" : "=r"(pv.x), "=r"(pv.y), "=r"(pv.z), "=r"(pv.w)
                             : "r"(stg + ((kb - 1) & 1) * 512 + lane * 16));
            }
            if (kb < 8) {
                eo[2] = geglu_pair(__float_as_uint(r[130 + 4 * kb]), __float_as_uint(r[98 + 4 * kb]));
                eo[3] = geglu_pair(__float_as_uint(r[131 + 4 * kb]), __float_as_uint(r[99 + 4 * kb]));
                stmatrix_x4(stg + (kb & 1) * 512 + st_off, eo[0], eo[1], eo[2], eo[3]);
            }
            if (kb == 9) asm volatile("bar.arrive 3, 288;" ::: "memory");
            if (kb > 0 && it - 1 + G1_STAGES < G1_ITERS) {
                wgmma_wait<1>();
                if (lane < 2) mbar_arrive_remote(bar_empty + 8 * ((it - 1) % G1_STAGES), lane);
            }
        }
        wgmma_wait<0>();
        fence_async_smem();
        __syncwarp();
        if (lane == 0) mbar_arrive(bar_g1mma);
        if (threadIdx.x == 0) STAMP(2, 6);
        {
            uint32_t o[24];
#pragma unroll
            for (int i = 0; i < 24; i++) o[i] = geglu_pair(pack_bf16(r[2 * i], r[2 * i + 1]), pack_bf16(r[48 + 2 * i], r[49 + 2 * i]));
            named_bar(1 + wg, 128);
            const uint32_t fbuf = sA + ((warp & 3) >> 1) * 16384 + wg * 8192 + (warp & 1) * 4096;
#pragma unroll
            for (int jj = 0; jj < 6; jj++) stmatrix_x4(fbuf + jj * 512 + st_off, o[4 * jj], o[4 * jj + 1], o[4 * jj + 2], o[4 * jj + 3]);
            __syncwarp();
            uint4 v[6];
#pragma unroll
            for (int jj = 0; jj < 6; jj++)
                asm volatile("ld.shared.v4.u32 {%0,%1,%2,%3}, [%4];" : "=r"(v[jj].x), "=r"(v[jj].y), "=r"(v[jj].z), "=r"(v[jj].w)
                             : "r"(fbuf + jj * 512 + lane * 16));
#pragma unroll
            for (int jj = 0; jj < 6; jj++) *reinterpret_cast<uint4*>(hrow + 128 + jj * 16) = v[jj];
        }
        }
        fence_async_smem();
        __syncwarp();
        if (lane == 0) mbar_arrive(bar_g1done);
        asm volatile("bar.arrive 9, 288;" ::: "memory");
        if (threadIdx.x == 0) STAMP(2, 7);
        {
        const int g = lane >> 2, t = lane & 3;
        float acc[64];
        const uint64_t descA2 = make_desc(sbase + wg * 8192, 16, 1024);
        const uint64_t descB2 = make_desc(sbase + 16384, 8192, 1024);
#pragma unroll 1
        for (int it = 0; it < G2_KB; it++) {
            const int s = (it + 1) % G2_STAGES;
            mbar_wait(bar_full2 + 8 * s, (it / G2_STAGES) & 1);
            if (threadIdx.x == 0 && (it == 0 || it == 7)) STAMP(3, 2 + it / 7);
            wgmma_fence();
            {
                const uint64_t da = descA2 + (uint64_t)((s * G2_STAGE) >> 4);
                const uint64_t db = descB2 + (uint64_t)((s * G2_STAGE) >> 4);
                wgmma_n128_k64(acc, da, da + 2, da + 4, da + 6, db, db + 128, db + 256, db + 384, it != 0);
            }
            wgmma_commit();
            if (it > 0 && it - 1 + G2_STAGES < G2_KB) {
                wgmma_wait<1>();
                if (lane == 0) mbar_arrive(bar_empty2 + 8 * (it % G2_STAGES));
            }
        }
        const int lr = wg * 64 + (warp & 3) * 16 + g;
        uint32_t xv[16], sv[16];
        mbar_wait(bar_epi, 0);
#pragma unroll
        for (int j = 0; j < 8; j++) {
#pragma unroll
            for (int hh = 0; hh < 2; hh++) {
                const int r = lr + 8 * hh;
                asm volatile("ld.shared.u32 %0, [%1];" : "=r"(xv[2 * j + hh]) : "r"(sX + r * 128 + ((j ^ (r & 7)) << 4) + 4 * t));
                const int c0 = 8 * j + 2 * t;
                const uint32_t sa = sS + (r >> 6) * 8192 + (((r & 63) >> 3) << 4) + (r & 7) * 2;
                uint16_t s0r, s1r;
                asm volatile("ld.shared.u16 %0, [%1];" : "=h"(s0r) : "r"((sa + c0 * 128) ^ ((c0 & 7) << 4)));
                asm volatile("ld.shared.u16 %0, [%1];" : "=h"(s1r) : "r"((sa + (c0 + 1) * 128) ^ (((c0 + 1) & 7) << 4)));
                sv[2 * j + hh] = (uint32_t)s0r | ((uint32_t)s1r << 16);
            }
        }
        wgmma_wait<0>();
        if (threadIdx.x == 0) STAMP(3, 4);
        {
            uint32_t remote, rbar;
            asm volatile("mapa.shared::cluster.u32 %0, %1, %2;" : "=r"(remote) : "r"(sXch + threadIdx.x * 16), "r"(kh ^ 1));
            asm volatile("mapa.shared::cluster.u32 %0, %1, %2;" : "=r"(rbar) : "r"(bar_xch), "r"(kh ^ 1));
            if (kh == 0) {
#pragma unroll
                for (int i = 0; i < 8; i++)
                    asm volatile("st.async.shared::cluster.mbarrier::complete_tx::bytes.v4.f32 [%0], {%1,%2,%3,%4}, [%5];" ::"r"(remote + i * 4096),
                                 "f"(acc[32 + 4 * i]), "f"(acc[33 + 4 * i]), "f"(acc[34 + 4 * i]), "f"(acc[35 + 4 * i]), "r"(rbar) : "memory");
            } else {
#pragma unroll
                for (int i = 0; i < 8; i++)
                    asm volatile("st.async.shared::cluster.mbarrier::complete_tx::bytes.v4.f32 [%0], {%1,%2,%3,%4}, [%5];" ::"r"(remote + i * 4096),
                                 "f"(acc[4 * i]), "f"(acc[1 + 4 * i]), "f"(acc[2 + 4 * i]), "f"(acc[3 + 4 * i]), "r"(rbar) : "memory");
#pragma unroll
                for (int i = 0; i < 32; i++) acc[i] = acc[32 + i];
            }
        }
        if (threadIdx.x == 0) STAMP(3, 6);
        mbar_wait(bar_xch, 0);
        if (threadIdx.x == 0) STAMP(3, 7);
#pragma unroll
        for (int j = 0; j < 8; j++) {
            float4 o;
            asm volatile("ld.shared.v4.f32 {%0,%1,%2,%3}, [%4];" : "=f"(o.x), "=f"(o.y), "=f"(o.z), "=f"(o.w) : "r"(sXch + threadIdx.x * 16 + j * 4096));
            acc[4 * j] += o.x; acc[4 * j + 1] += o.y; acc[4 * j + 2] += o.z; acc[4 * j + 3] += o.w;
        }
#pragma unroll
        for (int i = 0; i < 16; i++) {
            float f0 = bf16_round(acc[2 * i]), f1 = bf16_round(acc[2 * i + 1]);
            float g0 = bf16_round(__fdividef(f0, 1.0f + __expf(-f0)));
            float g1 = bf16_round(__fdividef(f1, 1.0f + __expf(-f1)));
            float o0 = bf_lo(xv[i]) + bf16_round(bf_lo(sv[i]) * g0);
            float o1 = bf_hi(xv[i]) + bf16_round(bf_hi(sv[i]) * g1);
            xv[i] = pack_bf16(o0, o1);
        }
#pragma unroll
        for (int j = 0; j < 8; j++) {
#pragma unroll
            for (int hh = 0; hh < 2; hh++) {
                const int r = lr + 8 * hh;
                asm volatile("st.shared.u32 [%0], %1;" ::"r"(sX + r * 128 + ((j ^ (r & 7)) << 4) + 4 * t), "r"(xv[2 * j + hh]) : "memory");
            }
        }
        if (threadIdx.x == 0) STAMP(3, 9);
        fence_async_smem();
        __syncwarp();
        if (lane == 0) {
            tma_store_2d(&tm_out, sX + (wg * 64 + (warp & 3) * 16) * 128, col_fin, rb * 128 + wg * 64 + (warp & 3) * 16);
            bulk_commit();
            bulk_wait_read<0>();
        }
        }
        if (threadIdx.x == 0) STAMP(3, 5);
        named_bar(4, 256);
        if (threadIdx.x == 0) {
            const unsigned int old = atomicAdd(&g_done_count, 1u);
            if (old == gridDim.x - 1) {
                g_ln_count = 0; g_conv_count = 0; g_done_count = 0;
                for (int i = 0; i < 32; i++) g_h_count[i] = 0;
            }
        }
    }
}

typedef CUresult (*EncodeFn)(CUtensorMap*, CUtensorMapDataType, cuuint32_t, void*, const cuuint64_t*, const cuuint64_t*,
                             const cuuint32_t*, const cuuint32_t*, CUtensorMapInterleave, CUtensorMapSwizzle,
                             CUtensorMapL2promotion, CUtensorMapFloatOOBfill);

void make_map(EncodeFn fn, CUtensorMap* m, const void* ptr, uint64_t inner, uint64_t outer, uint32_t box_in, uint32_t box_out,
              CUtensorMapSwizzle swz = CU_TENSOR_MAP_SWIZZLE_128B) {
    cuuint64_t dims[2] = {inner, outer};
    cuuint64_t strides[1] = {inner * 2};
    cuuint32_t box[2] = {box_in, box_out};
    cuuint32_t es[2] = {1, 1};
    fn(m, CU_TENSOR_MAP_DATA_TYPE_BFLOAT16, 2, const_cast<void*>(ptr), dims, strides, box, es, CU_TENSOR_MAP_INTERLEAVE_NONE,
       swz, CU_TENSOR_MAP_L2_PROMOTION_L2_256B, CU_TENSOR_MAP_FLOAT_OOB_FILL_NONE);
}
void make_map3(EncodeFn fn, CUtensorMap* m, const void* ptr, uint64_t cols, uint64_t rows, uint32_t atom, uint32_t box_rows,
               uint32_t box_atoms, CUtensorMapSwizzle swz) {
    cuuint64_t dims[3] = {atom, rows, cols / atom};
    cuuint64_t strides[2] = {cols * 2, (cuuint64_t)atom * 2};
    cuuint32_t box[3] = {atom, box_rows, box_atoms};
    cuuint32_t es[3] = {1, 1, 1};
    fn(m, CU_TENSOR_MAP_DATA_TYPE_BFLOAT16, 3, const_cast<void*>(ptr), dims, strides, box, es, CU_TENSOR_MAP_INTERLEAVE_NONE,
       swz, CU_TENSOR_MAP_L2_PROMOTION_L2_256B, CU_TENSOR_MAP_FLOAT_OOB_FILL_NONE);
}

template <typename... Args>
void launch_pdl(void (*kern)(Args...), int grid, int block, int smem, bool pdl, int cluster, Args... args) {
    cudaLaunchConfig_t cfg = {};
    cfg.gridDim = dim3(grid); cfg.blockDim = dim3(block); cfg.dynamicSmemBytes = smem; cfg.stream = cudaStreamPerThread;
    cudaLaunchAttribute at[2];
    int n = 0;
    if (pdl) {
        at[n].id = cudaLaunchAttributeProgrammaticStreamSerialization;
        at[n].val.programmaticStreamSerializationAllowed = 1;
        n++;
    }
    if (cluster > 1) {
        at[n].id = cudaLaunchAttributeClusterDimension;
        at[n].val.clusterDim.x = cluster; at[n].val.clusterDim.y = 1; at[n].val.clusterDim.z = 1;
        n++;
    }
    cfg.attrs = at; cfg.numAttrs = n;
    cudaLaunchKernelEx(&cfg, kern, args...);
}

}

extern "C" void kernel_launch(void* const* d_in, const int* in_sizes, int n_in, void* d_out, int out_size) {
    const __nv_bfloat16* x = (const __nv_bfloat16*)d_in[0];
    const __nv_bfloat16* A_re = (const __nv_bfloat16*)d_in[1];
    const __nv_bfloat16* A_im = (const __nv_bfloat16*)d_in[2];
    const __nv_bfloat16* B_re = (const __nv_bfloat16*)d_in[3];
    const __nv_bfloat16* B_im = (const __nv_bfloat16*)d_in[4];
    const __nv_bfloat16* C_re = (const __nv_bfloat16*)d_in[5];
    const __nv_bfloat16* C_im = (const __nv_bfloat16*)d_in[6];
    const __nv_bfloat16* log_dt = (const __nv_bfloat16*)d_in[7];
    const __nv_bfloat16* Dskip = (const __nv_bfloat16*)d_in[8];
    const __nv_bfloat16* wg = (const __nv_bfloat16*)d_in[10];
    const __nv_bfloat16* wu = (const __nv_bfloat16*)d_in[11];
    const __nv_bfloat16* wd = (const __nv_bfloat16*)d_in[12];
    __nv_bfloat16* out = (__nv_bfloat16*)d_out;

    static bool init = false;
    static CUtensorMap tm_xn, tm_wg4, tm_wu4, tm_wg3, tm_wu3, tm_hst, tm_hst96, tm_h, tm_wd, tm_x, tm_sT, tm_out;
    static const void* last_ptrs[5] = {nullptr, nullptr, nullptr, nullptr, nullptr};
    if (!init || last_ptrs[0] != wg || last_ptrs[1] != wu || last_ptrs[2] != wd || last_ptrs[3] != x || last_ptrs[4] != out) {
        void* fnp = nullptr;
        cudaDriverEntryPointQueryResult qres;
        cudaGetDriverEntryPoint("cuTensorMapEncodeTiled", &fnp, cudaEnableDefault, &qres);
        EncodeFn fn = (EncodeFn)fnp;
        void *p_xn, *p_h, *p_sT;
        cudaGetSymbolAddress(&p_xn, g_xn);
        cudaGetSymbolAddress(&p_h, g_h);
        cudaGetSymbolAddress(&p_sT, g_sT);
        make_map(fn, &tm_xn, p_xn, D_, L_, 64, 128);
        make_map3(fn, &tm_wg4, wg, F_, D_, 32, 32, 4, CU_TENSOR_MAP_SWIZZLE_64B);
        make_map3(fn, &tm_wu4, wu, F_, D_, 32, 32, 4, CU_TENSOR_MAP_SWIZZLE_64B);
        make_map3(fn, &tm_wg3, wg, F_, D_, 32, 32, 3, CU_TENSOR_MAP_SWIZZLE_64B);
        make_map3(fn, &tm_wu3, wu, F_, D_, 32, 32, 3, CU_TENSOR_MAP_SWIZZLE_64B);
        make_map(fn, &tm_hst, p_h, F_, L_, 16, 16, CU_TENSOR_MAP_SWIZZLE_NONE);
        make_map(fn, &tm_hst96, p_h, F_, L_, 96, 16, CU_TENSOR_MAP_SWIZZLE_NONE);
        make_map(fn, &tm_h, p_h, F_, L_, 64, 128);
        make_map3(fn, &tm_wd, wd, D_, F_, 64, 64, 2, CU_TENSOR_MAP_SWIZZLE_128B);
        make_map(fn, &tm_x, x, D_, L_, 64, 128);
        make_map(fn, &tm_sT, p_sT, L_, D_, 64, 64);
        make_map(fn, &tm_out, out, D_, L_, 64, 16);
        cudaFuncSetAttribute(mega_kernel, cudaFuncAttributeMaxDynamicSharedMemorySize, MG_SMEM);
        last_ptrs[0] = wg; last_ptrs[1] = wu; last_ptrs[2] = wd; last_ptrs[3] = x; last_ptrs[4] = out;
        init = true;
    }
    MegaParams P = {x, A_re, A_im, B_re, B_im, C_re, C_im, log_dt, Dskip, wg, wu, wd};
    launch_pdl(mega_kernel, 128, 384, MG_SMEM, false, 2, P, tm_xn, tm_wg4, tm_wu4, tm_wg3, tm_wu3, tm_h, tm_wd, tm_x, tm_sT, tm_out);
}
```

```cpp
#include <cuda_runtime.h>
#include <cuda_bf16.h>
#include <cuda.h>
#include <stdint.h>

namespace {

constexpr int L_ = 2048, D_ = 512, NS_ = 128, F_ = 1792;

__device__ __align__(1024) __nv_bfloat16 g_xn[L_ * D_];
__device__ __align__(1024) __nv_bfloat16 g_xnT[D_ * L_];
__device__ __align__(1024) __nv_bfloat16 g_sT[D_ * L_];
__device__ __align__(1024) __nv_bfloat16 g_h[L_ * F_];
__device__ unsigned int g_ln_count, g_conv_count, g_done_count, g_h_count[32];

#define STAMP(k, i)

__device__ __forceinline__ uint32_t smem_u32(const void* p) { return (uint32_t)__cvta_generic_to_shared(p); }
__device__ __forceinline__ void pdl_wait() { asm volatile("griddepcontrol.wait;" ::: "memory"); }
__device__ __forceinline__ void pdl_launch() { asm volatile("griddepcontrol.launch_dependents;" ::: "memory"); }

__device__ __forceinline__ void mbar_init(uint32_t bar, uint32_t cnt) {
    asm volatile("mbarrier.init.shared::cta.b64 [%0], %1;" ::"r"(bar), "r"(cnt) : "memory");
}
__device__ __forceinline__ void mbar_expect_tx(uint32_t bar, uint32_t bytes) {
    asm volatile("mbarrier.arrive.expect_tx.shared::cta.b64 _, [%0], %1;" ::"r"(bar), "r"(bytes) : "memory");
}
__device__ __forceinline__ void mbar_arrive(uint32_t bar) {
    asm volatile("mbarrier.arrive.shared::cta.b64 _, [%0];" ::"r"(bar) : "memory");
}
__device__ __forceinline__ void mbar_wait(uint32_t bar, uint32_t parity) {
    asm volatile(
        "{\n.reg .pred p;\n"
        "WAIT_LOOP:\n"
        "mbarrier.try_wait.parity.shared::cta.b64 p, [%0], %1;\n"
        "@p bra WAIT_DONE;\n"
        "bra WAIT_LOOP;\n"
        "WAIT_DONE:\n}\n" ::"r"(bar), "r"(parity) : "memory");
}
__device__ __forceinline__ void tma_load_2d(uint32_t dst, const CUtensorMap* tm, int c0, int c1, uint32_t bar) {
    asm volatile(
        "cp.async.bulk.tensor.2d.shared::cluster.global.mbarrier::complete_tx::bytes [%0], [%1, {%3, %4}], [%2];"
        ::"r"(dst), "l"((uint64_t)tm), "r"(bar), "r"(c0), "r"(c1) : "memory");
}
__device__ __forceinline__ void prefetch_tmap(const CUtensorMap* tm) {
    asm volatile("prefetch.tensormap [%0];" ::"l"((uint64_t)tm) : "memory");
}
__device__ __forceinline__ uint64_t make_desc(uint32_t addr, uint32_t lbo, uint32_t sbo, uint64_t mode = 1) {
    uint64_t d = 0;
    d |= (uint64_t)((addr & 0x3FFFF) >> 4);
    d |= (uint64_t)((lbo >> 4) & 0x3FFF) << 16;
    d |= (uint64_t)((sbo >> 4) & 0x3FFF) << 32;
    d |= mode << 62;
    return d;
}
__device__ __forceinline__ void fence_async_smem() { asm volatile("fence.proxy.async.shared::cta;" ::: "memory"); }
__device__ __forceinline__ void wgmma_fence() { asm volatile("wgmma.fence.sync.aligned;" ::: "memory"); }
__device__ __forceinline__ void wgmma_commit() { asm volatile("wgmma.commit_group.sync.aligned;" ::: "memory"); }
template <int N> __device__ __forceinline__ void wgmma_wait() {
    asm volatile("wgmma.wait_group.sync.aligned %0;" ::"n"(N) : "memory");
}

#define R8(a, i) "+f"(a[i + 0]), "+f"(a[i + 1]), "+f"(a[i + 2]), "+f"(a[i + 3]), "+f"(a[i + 4]), "+f"(a[i + 5]), "+f"(a[i + 6]), "+f"(a[i + 7])

__device__ __forceinline__ void wgmma_n256_k32(float* a, uint64_t da0, uint64_t da1, uint64_t db0, uint64_t db1, int scale_d) {
    asm volatile(
        "{\n.reg .pred p;\nsetp.ne.b32 p, %132, 0;\n"
        "wgmma.mma_async.sync.aligned.m64n256k16.f32.bf16.bf16 {%0,%1,%2,%3,%4,%5,%6,%7,%8,%9,%10,%11,%12,%13,%14,%15,%16,%17,%18,%19,%20,%21,%22,%23,%24,%25,%26,%27,%28,%29,%30,%31,%32,%33,%34,%35,%36,%37,%38,%39,%40,%41,%42,%43,%44,%45,%46,%47,%48,%49,%50,%51,%52,%53,%54,%55,%56,%57,%58,%59,%60,%61,%62,%63,%64,%65,%66,%67,%68,%69,%70,%71,%72,%73,%74,%75,%76,%77,%78,%79,%80,%81,%82,%83,%84,%85,%86,%87,%88,%89,%90,%91,%92,%93,%94,%95,%96,%97,%98,%99,%100,%101,%102,%103,%104,%105,%106,%107,%108,%109,%110,%111,%112,%113,%114,%115,%116,%117,%118,%119,%120,%121,%122,%123,%124,%125,%126,%127}, %128, %130, p, 1, 1, 0, 1;\n"
        "wgmma.mma_async.sync.aligned.m64n256k16.f32.bf16.bf16 {%0,%1,%2,%3,%4,%5,%6,%7,%8,%9,%10,%11,%12,%13,%14,%15,%16,%17,%18,%19,%20,%21,%22,%23,%24,%25,%26,%27,%28,%29,%30,%31,%32,%33,%34,%35,%36,%37,%38,%39,%40,%41,%42,%43,%44,%45,%46,%47,%48,%49,%50,%51,%52,%53,%54,%55,%56,%57,%58,%59,%60,%61,%62,%63,%64,%65,%66,%67,%68,%69,%70,%71,%72,%73,%74,%75,%76,%77,%78,%79,%80,%81,%82,%83,%84,%85,%86,%87,%88,%89,%90,%91,%92,%93,%94,%95,%96,%97,%98,%99,%100,%101,%102,%103,%104,%105,%106,%107,%108,%109,%110,%111,%112,%113,%114,%115,%116,%117,%118,%119,%120,%121,%122,%123,%124,%125,%126,%127}, %129, %131, 1, 1, 1, 0, 1;\n"
        "}\n"
        : R8(a, 0), R8(a, 8), R8(a, 16), R8(a, 24), R8(a, 32), R8(a, 40), R8(a, 48), R8(a, 56), R8(a, 64), R8(a, 72), R8(a, 80), R8(a, 88), R8(a, 96), R8(a, 104), R8(a, 112), R8(a, 120)
        : "l"(da0), "l"(da1), "l"(db0), "l"(db1), "r"(scale_d));
}
__device__ __forceinline__ void wgmma_n192_k32(float* a, uint64_t da0, uint64_t da1, uint64_t db0, uint64_t db1, int scale_d) {
    asm volatile(
        "{\n.reg .pred p;\nsetp.ne.b32 p, %100, 0;\n"
        "wgmma.mma_async.sync.aligned.m64n192k16.f32.bf16.bf16 {%0,%1,%2,%3,%4,%5,%6,%7,%8,%9,%10,%11,%12,%13,%14,%15,%16,%17,%18,%19,%20,%21,%22,%23,%24,%25,%26,%27,%28,%29,%30,%31,%32,%33,%34,%35,%36,%37,%38,%39,%40,%41,%42,%43,%44,%45,%46,%47,%48,%49,%50,%51,%52,%53,%54,%55,%56,%57,%58,%59,%60,%61,%62,%63,%64,%65,%66,%67,%68,%69,%70,%71,%72,%73,%74,%75,%76,%77,%78,%79,%80,%81,%82,%83,%84,%85,%86,%87,%88,%89,%90,%91,%92,%93,%94,%95}, %96, %98, p, 1, 1, 0, 1;\n"
        "wgmma.mma_async.sync.aligned.m64n192k16.f32.bf16.bf16 {%0,%1,%2,%3,%4,%5,%6,%7,%8,%9,%10,%11,%12,%13,%14,%15,%16,%17,%18,%19,%20,%21,%22,%23,%24,%25,%26,%27,%28,%29,%30,%31,%32,%33,%34,%35,%36,%37,%38,%39,%40,%41,%42,%43,%44,%45,%46,%47,%48,%49,%50,%51,%52,%53,%54,%55,%56,%57,%58,%59,%60,%61,%62,%63,%64,%65,%66,%67,%68,%69,%70,%71,%72,%73,%74,%75,%76,%77,%78,%79,%80,%81,%82,%83,%84,%85,%86,%87,%88,%89,%90,%91,%92,%93,%94,%95}, %97, %99, 1, 1, 1, 0, 1;\n"
        "}\n"
        : R8(a, 0), R8(a, 8), R8(a, 16), R8(a, 24), R8(a, 32), R8(a, 40), R8(a, 48), R8(a, 56), R8(a, 64), R8(a, 72), R8(a, 80), R8(a, 88)
        : "l"(da0), "l"(da1), "l"(db0), "l"(db1), "r"(scale_d));
}
__device__ __forceinline__ void wgmma_n192(float* a, uint64_t da0, uint64_t db0, int scale_d) {
    asm volatile(
        "{\n.reg .pred p;\nsetp.ne.b32 p, %98, 0;\n"
        "wgmma.mma_async.sync.aligned.m64n192k16.f32.bf16.bf16 {%0,%1,%2,%3,%4,%5,%6,%7,%8,%9,%10,%11,%12,%13,%14,%15,%16,%17,%18,%19,%20,%21,%22,%23,%24,%25,%26,%27,%28,%29,%30,%31,%32,%33,%34,%35,%36,%37,%38,%39,%40,%41,%42,%43,%44,%45,%46,%47,%48,%49,%50,%51,%52,%53,%54,%55,%56,%57,%58,%59,%60,%61,%62,%63,%64,%65,%66,%67,%68,%69,%70,%71,%72,%73,%74,%75,%76,%77,%78,%79,%80,%81,%82,%83,%84,%85,%86,%87,%88,%89,%90,%91,%92,%93,%94,%95}, %96, %97, p, 1, 1, 0, 1;\n"
        "}\n"
        : R8(a, 0), R8(a, 8), R8(a, 16), R8(a, 24), R8(a, 32), R8(a, 40), R8(a, 48), R8(a, 56), R8(a, 64), R8(a, 72), R8(a, 80), R8(a, 88)
        : "l"(da0), "l"(db0), "r"(scale_d));
}
__device__ __forceinline__ void wgmma_n128_k64(float* a, uint64_t da0, uint64_t da1, uint64_t da2, uint64_t da3,
                                               uint64_t db0, uint64_t db1, uint64_t db2, uint64_t db3, int scale_d) {
    asm volatile(
        "{\n.reg .pred p;\nsetp.ne.b32 p, %72, 0;\n"
        "wgmma.mma_async.sync.aligned.m64n128k16.f32.bf16.bf16 {%0,%1,%2,%3,%4,%5,%6,%7,%8,%9,%10,%11,%12,%13,%14,%15,%16,%17,%18,%19,%20,%21,%22,%23,%24,%25,%26,%27,%28,%29,%30,%31,%32,%33,%34,%35,%36,%37,%38,%39,%40,%41,%42,%43,%44,%45,%46,%47,%48,%49,%50,%51,%52,%53,%54,%55,%56,%57,%58,%59,%60,%61,%62,%63}, %64, %68, p, 1, 1, 0, 1;\n"
        "wgmma.mma_async.sync.aligned.m64n128k16.f32.bf16.bf16 {%0,%1,%2,%3,%4,%5,%6,%7,%8,%9,%10,%11,%12,%13,%14,%15,%16,%17,%18,%19,%20,%21,%22,%23,%24,%25,%26,%27,%28,%29,%30,%31,%32,%33,%34,%35,%36,%37,%38,%39,%40,%41,%42,%43,%44,%45,%46,%47,%48,%49,%50,%51,%52,%53,%54,%55,%56,%57,%58,%59,%60,%61,%62,%63}, %65, %69, 1, 1, 1, 0, 1;\n"
        "wgmma.mma_async.sync.aligned.m64n128k16.f32.bf16.bf16 {%0,%1,%2,%3,%4,%5,%6,%7,%8,%9,%10,%11,%12,%13,%14,%15,%16,%17,%18,%19,%20,%21,%22,%23,%24,%25,%26,%27,%28,%29,%30,%31,%32,%33,%34,%35,%36,%37,%38,%39,%40,%41,%42,%43,%44,%45,%46,%47,%48,%49,%50,%51,%52,%53,%54,%55,%56,%57,%58,%59,%60,%61,%62,%63}, %66, %70, 1, 1, 1, 0, 1;\n"
        "wgmma.mma_async.sync.aligned.m64n128k16.f32.bf16.bf16 {%0,%1,%2,%3,%4,%5,%6,%7,%8,%9,%10,%11,%12,%13,%14,%15,%16,%17,%18,%19,%20,%21,%22,%23,%24,%25,%26,%27,%28,%29,%30,%31,%32,%33,%34,%35,%36,%37,%38,%39,%40,%41,%42,%43,%44,%45,%46,%47,%48,%49,%50,%51,%52,%53,%54,%55,%56,%57,%58,%59,%60,%61,%62,%63}, %67, %71, 1, 1, 1, 0, 1;\n"
        "}\n"
        : R8(a, 0), R8(a, 8), R8(a, 16), R8(a, 24), R8(a, 32), R8(a, 40), R8(a, 48), R8(a, 56)
        : "l"(da0), "l"(da1), "l"(da2), "l"(da3), "l"(db0), "l"(db1), "l"(db2), "l"(db3), "r"(scale_d));
}

__device__ __forceinline__ float bf16_round(float x) {
    uint32_t p; asm("cvt.rn.bf16x2.f32 %0, %1, %2;" : "=r"(p) : "f"(x), "f"(0.0f));
    return __uint_as_float(p);
}
__device__ __forceinline__ uint32_t pack_bf16(float lo, float hi) {
    __nv_bfloat162 v = __floats2bfloat162_rn(lo, hi);
    return *reinterpret_cast<uint32_t*>(&v);
}
__device__ __forceinline__ float bf_lo(uint32_t v) { return __uint_as_float(v << 16); }
__device__ __forceinline__ float bf_hi(uint32_t v) { return __uint_as_float(v & 0xFFFF0000u); }

struct cplx { float r, i; };
__device__ __forceinline__ cplx cmul(cplx a, cplx b) {
    cplx c; c.r = a.r * b.r - a.i * b.i; c.i = a.r * b.i + a.i * b.r; return c;
}
__device__ __forceinline__ cplx csq(cplx a) {
    cplx c; c.r = a.r * a.r - a.i * a.i; c.i = 2.0f * a.r * a.i; return c;
}
__device__ __forceinline__ cplx cexp_m(float ar2, float ai2, float m) {
    float mag;
    asm("ex2.approx.ftz.f32 %0, %1;" : "=f"(mag) : "f"(ar2 * m));
    float rr = ai2 * m;
    rr -= (rr + 12582912.0f) - 12582912.0f;
    float th = rr * 6.283185307179586f;
    cplx c; c.r = mag * __cosf(th); c.i = mag * __sinf(th);
    return c;
}
__device__ __forceinline__ uint32_t to_tf32(float x) { return __float_as_uint(x) + 0x1000u; }
__device__ __forceinline__ void mma_tf32(float* c, uint32_t a0, uint32_t a1, uint32_t a2, uint32_t a3, uint32_t b0, uint32_t b1) {
    asm volatile("mma.sync.aligned.m16n8k8.row.col.f32.tf32.tf32.f32 {%0,%1,%2,%3}, {%4,%5,%6,%7}, {%8,%9}, {%0,%1,%2,%3};"
                 : "+f"(c[0]), "+f"(c[1]), "+f"(c[2]), "+f"(c[3])
                 : "r"(a0), "r"(a1), "r"(a2), "r"(a3), "r"(b0), "r"(b1));
}
__device__ __forceinline__ void mma_bf16(float* c, uint32_t a0, uint32_t a1, uint32_t a2, uint32_t a3, uint32_t b0, uint32_t b1) {
    asm volatile("mma.sync.aligned.m16n8k16.row.col.f32.bf16.bf16.f32 {%0,%1,%2,%3}, {%4,%5,%6,%7}, {%8,%9}, {%0,%1,%2,%3};"
                 : "+f"(c[0]), "+f"(c[1]), "+f"(c[2]), "+f"(c[3])
                 : "r"(a0), "r"(a1), "r"(a2), "r"(a3), "r"(b0), "r"(b1));
}
__device__ __forceinline__ void named_bar(int id, int n) { asm volatile("bar.sync %0, %1;" ::"r"(id), "r"(n) : "memory"); }
__device__ __forceinline__ void ldsm_x4(uint32_t addr, uint32_t& r0, uint32_t& r1, uint32_t& r2, uint32_t& r3) {
    asm volatile("ldmatrix.sync.aligned.m8n8.x4.shared.b16 {%0,%1,%2,%3}, [%4];" : "=r"(r0), "=r"(r1), "=r"(r2), "=r"(r3) : "r"(addr));
}
__device__ __forceinline__ void ldsm_x4_t(uint32_t addr, uint32_t& r0, uint32_t& r1, uint32_t& r2, uint32_t& r3) {
    asm volatile("ldmatrix.sync.aligned.m8n8.x4.trans.shared.b16 {%0,%1,%2,%3}, [%4];" : "=r"(r0), "=r"(r1), "=r"(r2), "=r"(r3) : "r"(addr));
}

constexpr int CV_CH = 4;
constexpr int CV_O_CONST = 0;
constexpr int CV_O_KP = 12288;
constexpr int CV_EARLY = 12288 + 7776;
constexpr int CV_O_Q = 0;
constexpr int CV_O_Q2 = CV_O_Q + 2304;
constexpr int CV_O_Q3 = CV_O_Q2 + 1024;
constexpr int CV_O_Q4X = CV_O_Q3 + 768;
constexpr int CV_O_W3 = CV_O_Q4X + 256;
constexpr int CV_O_W5 = CV_O_W3 + 3104;
constexpr int CV_O_W7 = CV_O_W5 + 3104;
constexpr int CV_O_W9 = CV_O_W7 + 2048;
constexpr int CV_O_U = CV_O_W9 + 2048;
constexpr int CV_LATE = CV_O_U + 4352;
constexpr int CV_LATE_BASE = 229376 - CV_CH * CV_LATE;
constexpr int CV_TILE_OFF = CV_CH * CV_EARLY;
static_assert(CV_TILE_OFF + 16 * (D_ + 8) * 2 <= CV_LATE_BASE && CV_LATE_BASE >= 131072 + 16384, "front layout");
static_assert(CV_O_W3 >= 4096 && CV_O_U - CV_O_W3 >= 8192 && (CV_LATE % 16) == 0 && (CV_EARLY % 16) == 0, "front layout");

constexpr int LN_ROWS = 16;

template <typename PF>
__device__ __forceinline__ void front_phase(PF prefetch_fn, uint8_t* smem, const __nv_bfloat16* __restrict__ x,
                                            const __nv_bfloat16* __restrict__ A_re, const __nv_bfloat16* __restrict__ A_im,
                                            const __nv_bfloat16* __restrict__ B_re, const __nv_bfloat16* __restrict__ B_im,
                                            const __nv_bfloat16* __restrict__ C_re, const __nv_bfloat16* __restrict__ C_im,
                                            const __nv_bfloat16* __restrict__ log_dt, const __nv_bfloat16* __restrict__ Dskip,
                                            const __nv_bfloat16* __restrict__ wg, const __nv_bfloat16* __restrict__ wu,
                                            const __nv_bfloat16* __restrict__ wd) {
    const int warp = threadIdx.x >> 5, lane = threadIdx.x & 31;
    const int ch = warp / 3, w = warp - 3 * ch, tc = threadIdx.x - 96 * ch;
    const int d = blockIdx.x * CV_CH + ch;
    const int g = lane >> 2, t = lane & 3;
    uint8_t* base = smem + CV_LATE_BASE + ch * CV_LATE;
    float4* s_const = reinterpret_cast<float4*>(smem + ch * CV_EARLY + CV_O_CONST);
    float* s_kp = reinterpret_cast<float*>(smem + ch * CV_EARLY + CV_O_KP);
    uint32_t* s_q = reinterpret_cast<uint32_t*>(base + CV_O_Q);
    uint32_t* s_q2 = reinterpret_cast<uint32_t*>(base + CV_O_Q2);
    uint32_t* s_q3 = reinterpret_cast<uint32_t*>(base + CV_O_Q3);
    uint32_t* s_q4 = reinterpret_cast<uint32_t*>(base + CV_O_Q4X);
    __nv_bfloat16* s_u = reinterpret_cast<__nv_bfloat16*>(base + CV_O_U);
    const int bar_id = 5 + ch;
    const __nv_bfloat16 p_dsk = Dskip[d];
    __nv_bfloat16 (*tile)[D_ + 8] = reinterpret_cast<__nv_bfloat16 (*)[D_ + 8]>(smem + CV_TILE_OFF);

    if (warp < 8) {
        const int row = blockIdx.x * LN_ROWS + warp * 2;
        uint4 xv[2][2];
#pragma unroll
        for (int r = 0; r < 2; r++) {
            xv[r][0] = *reinterpret_cast<const uint4*>(x + (size_t)(row + r) * D_ + lane * 8);
            xv[r][1] = *reinterpret_cast<const uint4*>(x + (size_t)(row + r) * D_ + 256 + lane * 8);
        }
        float f[2][16], sm[2], q[2];
#pragma unroll
        for (int r = 0; r < 2; r++) {
            const uint32_t wv[8] = {xv[r][0].x, xv[r][0].y, xv[r][0].z, xv[r][0].w, xv[r][1].x, xv[r][1].y, xv[r][1].z, xv[r][1].w};
#pragma unroll
            for (int i = 0; i < 8; i++) { f[r][2 * i] = bf_lo(wv[i]); f[r][2 * i + 1] = bf_hi(wv[i]); }
            sm[r] = 0.f;
#pragma unroll
            for (int i = 0; i < 16; i++) sm[r] += f[r][i];
        }
#pragma unroll
        for (int o = 16; o > 0; o >>= 1) { sm[0] += __shfl_xor_sync(0xffffffffu, sm[0], o); sm[1] += __shfl_xor_sync(0xffffffffu, sm[1], o); }
#pragma unroll
        for (int r = 0; r < 2; r++) {
            sm[r] *= (1.0f / D_);
            q[r] = 0.f;
#pragma unroll
            for (int i = 0; i < 16; i++) { float dd = f[r][i] - sm[r]; q[r] += dd * dd; }
        }
#pragma unroll
        for (int o = 16; o > 0; o >>= 1) { q[0] += __shfl_xor_sync(0xffffffffu, q[0], o); q[1] += __shfl_xor_sync(0xffffffffu, q[1], o); }
#pragma unroll
        for (int r = 0; r < 2; r++) {
            const float mb = bf16_round(sm[r]);
            const float vb = bf16_round(q[r] * (1.0f / D_));
            const float den = bf16_round(sqrtf(bf16_round(vb + 1e-5f)));
            uint32_t o[8];
#pragma unroll
            for (int i = 0; i < 8; i++) {
                float a = __fdiv_rn(bf16_round(f[r][2 * i] - mb), den);
                float b = __fdiv_rn(bf16_round(f[r][2 * i + 1] - mb), den);
                o[i] = pack_bf16(a, b);
            }
            __nv_bfloat16* dst = g_xn + (size_t)(row + r) * D_;
            *reinterpret_cast<uint4*>(dst + lane * 8) = make_uint4(o[0], o[1], o[2], o[3]);
            *reinterpret_cast<uint4*>(dst + 256 + lane * 8) = make_uint4(o[4], o[5], o[6], o[7]);
            *reinterpret_cast<uint4*>(&tile[warp * 2 + r][lane * 8]) = make_uint4(o[0], o[1], o[2], o[3]);
            *reinterpret_cast<uint4*>(&tile[warp * 2 + r][256 + lane * 8]) = make_uint4(o[4], o[5], o[6], o[7]);
        }
    } else {
        const int cc_ = warp - 8, dd = blockIdx.x * CV_CH + cc_;
        float4* sc = reinterpret_cast<float4*>(smem + cc_ * CV_EARLY + CV_O_CONST);
        __nv_bfloat16 pr[4][6];
#pragma unroll
        for (int j = 0; j < 4; j++) {
            const size_t off = (size_t)dd * NS_ + lane + 32 * j;
            pr[j][0] = A_re[off]; pr[j][1] = A_im[off]; pr[j][2] = B_re[off]; pr[j][3] = B_im[off]; pr[j][4] = C_re[off]; pr[j][5] = C_im[off];
        }
        const float dt = bf16_round(expf(__bfloat162float(log_dt[dd])));
        float tail = 0.f;
#pragma unroll
        for (int j = 0; j < 4; j++) {
            const float ar = dt * __bfloat162float(pr[j][0]), ai = dt * __bfloat162float(pr[j][1]);
            const cplx db = {dt * __bfloat162float(pr[j][2]), dt * __bfloat162float(pr[j][3])};
            const cplx cc = {__bfloat162float(pr[j][4]), __bfloat162float(pr[j][5])};
            const cplx cb = cmul(cc, db);
            const float ar2 = ar * 1.4426950408889634f, ai2 = ai * 0.15915494309189535f;
            const cplx e8 = cexp_m(ar2, ai2, 8.f), e128 = cexp_m(ar2, ai2, 128.f);
            const cplx cb8 = cmul(cb, e8);
            const cplx e256 = cexp_m(ar2, ai2, 256.f), e512 = cexp_m(ar2, ai2, 512.f), e1024 = cexp_m(ar2, ai2, 1024.f);
            const cplx c256 = cmul(cb, e256), c512 = cmul(cb, e512), c1024 = cmul(cb, e1024);
            const cplx c768 = cmul(c512, e256), c1280 = cmul(c1024, e256), c1536 = cmul(c1024, e512);
            const cplx c1792 = cmul(c1536, e256);
            tail += cmul(c1024, e1024).r;
            float4* c = sc + (lane + 32 * j) * 6;
            c[0] = make_float4(ar2, ai2, cb.r, cb.i);
            c[1] = make_float4(e128.r, e128.i, cb8.r, cb8.i);
            c[2] = make_float4(c256.r, c256.i, e8.r, e8.i);
            c[3] = make_float4(c512.r, c512.i, c768.r, c768.i);
            c[4] = make_float4(c1024.r, c1024.i, c1280.r, c1280.i);
            c[5] = make_float4(c1536.r, c1536.i, c1792.r, c1792.i);
        }
#pragma unroll
        for (int o = 16; o > 0; o >>= 1) tail += __shfl_xor_sync(0xffffffffu, tail, o);
        if (lane == 0) {
            float* kp = reinterpret_cast<float*>(smem + cc_ * CV_EARLY + CV_O_KP);
            kp[640] = tail; kp[648 + 640] = 0.f; kp[1296 + 640] = 0.f;
        }
    }
    __syncthreads();
    if (threadIdx.x == 0) STAMP(0, 3);
#pragma unroll
    for (int rep = 0; rep < 2; rep++) {
        const int c = threadIdx.x + 384 * rep;
        if (c < D_) {
            uint32_t ot[8];
#pragma unroll
            for (int i = 0; i < 8; i++) {
                uint32_t lo = *reinterpret_cast<const uint16_t*>(&tile[2 * i][c]);
                uint32_t hi = *reinterpret_cast<const uint16_t*>(&tile[2 * i + 1][c]);
                ot[i] = lo | (hi << 16);
            }
            __nv_bfloat16* dT = g_xnT + (size_t)c * L_ + blockIdx.x * LN_ROWS;
            *reinterpret_cast<uint4*>(dT) = make_uint4(ot[0], ot[1], ot[2], ot[3]);
            *reinterpret_cast<uint4*>(dT + 8) = make_uint4(ot[4], ot[5], ot[6], ot[7]);
        }
    }
    if (threadIdx.x < 336) {
        const int m = threadIdx.x / 112, i = threadIdx.x - m * 112;
        const char* wp = (const char*)(m == 0 ? wg : (m == 1 ? wu : wd));
        asm volatile("prefetch.global.L2 [%0];" ::"l"(wp + ((size_t)blockIdx.x * 112 + i) * 128));
    }
    __syncthreads();
    if (threadIdx.x == 0) STAMP(1, 1);
    {
        float acc[5][4];
#pragma unroll
        for (int i = 0; i < 5; i++) { acc[i][0] = acc[i][1] = acc[i][2] = acc[i][3] = 0.f; }
        const float gf = (float)g;
        const int src4 = ((g & 3) << 2) | t;
#pragma unroll 2
        for (int s = w; s < 32; s += 3) {
            if (s == 17 && threadIdx.x == 352) asm volatile("red.release.gpu.global.add.u32 [%0], 1;" ::"l"(&g_ln_count) : "memory");
            const float4* c = s_const + (s * 4 + t) * 6;
            const float4 k0 = c[0], k1 = c[1], k2 = c[2];
            const float2 k3 = reinterpret_cast<const float2*>(c + 3)[g >> 2];
            const float2 k4 = reinterpret_cast<const float2*>(c + 4)[g >> 1];
            const cplx cb = {k0.z, k0.w}, e128 = {k1.x, k1.y}, cb8 = {k1.z, k1.w}, c256 = {k2.x, k2.y}, e8 = {k2.z, k2.w};
            const cplx c2 = {k3.x, k3.y}, c3 = {k4.x, k4.y};
            const cplx p1 = cexp_m(k0.x, k0.y, gf);
            const cplx p2 = csq(p1), p4 = csq(p2);
            const cplx r16a = csq(csq(p4));
            cplx q4;
            q4.r = __shfl_sync(0xffffffffu, p4.r, src4);
            q4.i = __shfl_sync(0xffffffffu, p4.i, src4);
            const cplx r16b = cmul(r16a, e128);
            const cplx f0a = cmul(cb, p1), f0b = cmul(cb8, p1), f1 = cmul(c256, p2), f2 = cmul(c2, q4);
            cplx f3 = cmul(c3, e8);
            if (!(g & 1)) f3 = c3;
            const uint32_t a0 = to_tf32(r16a.r), a1 = to_tf32(r16b.r), a2 = to_tf32(-r16a.i), a3 = to_tf32(-r16b.i);
            mma_tf32(acc[0], a0, a1, a2, a3, to_tf32(f0a.r), to_tf32(f0a.i));
            mma_tf32(acc[1], a0, a1, a2, a3, to_tf32(f0b.r), to_tf32(f0b.i));
            mma_tf32(acc[2], a0, a1, a2, a3, to_tf32(f1.r), to_tf32(f1.i));
            mma_tf32(acc[3], a0, a1, a2, a3, to_tf32(f2.r), to_tf32(f2.i));
            mma_tf32(acc[4], a0, a1, a2, a3, to_tf32(f3.r), to_tf32(f3.i));
        }
        float* kv = s_kp + w * 648;
#pragma unroll
        for (int hh = 0; hh < 2; hh++) {
            const int i = g + 8 * hh;
            *reinterpret_cast<float2*>(kv + 16 * i + 2 * t) = make_float2(acc[0][2 * hh], acc[0][2 * hh + 1]);
            *reinterpret_cast<float2*>(kv + 16 * i + 8 + 2 * t) = make_float2(acc[1][2 * hh], acc[1][2 * hh + 1]);
            *reinterpret_cast<float2*>(kv + 256 + 8 * i + 2 * t) = make_float2(acc[2][2 * hh], acc[2][2 * hh + 1]);
            *reinterpret_cast<float2*>(kv + 384 + 64 * (t >> 1) + 2 * (t & 1) + 4 * i) = make_float2(acc[3][2 * hh], acc[3][2 * hh + 1]);
            *reinterpret_cast<float2*>(kv + 512 + 32 * t + 2 * i) = make_float2(acc[4][2 * hh], acc[4][2 * hh + 1]);
        }
    }
    named_bar(bar_id, 96);
    if (threadIdx.x == 0) STAMP(1, 2);
#pragma unroll
    for (int i = 0; i < 7; i++) {
        const int idx = tc + 96 * i;
        if (idx < 641) s_kp[idx] = (s_kp[idx] + s_kp[648 + idx]) + s_kp[1296 + idx];
    }
    named_bar(bar_id, 96);
    {
        auto kdir = [&](int l) -> float {
            if (l < 0 || l > 514) return 0.f;
            const int idx = (l < 256) ? l : (l > 512 ? 384 : 128 + ((l + ((l >> 1) & 1)) >> 1));
            return s_kp[idx];
        };
#pragma unroll
        for (int i = 0; i < 6; i++) {
            const int e = tc + 96 * i;
            s_q[e] = pack_bf16(kdir(e - 16), kdir(e - 17));
        }
        if (tc < 64) {
            const int xx = 1008 + tc;
            const float k1024 = s_kp[512];
            s_q4[tc] = pack_bf16((xx == 1027 || xx == 1028) ? k1024 : 0.f, (xx == 1028 || xx == 1029) ? k1024 : 0.f);
        }
#pragma unroll
        for (int i = 0; i < 3; i++) {
            const int e = tc + 96 * i;
            if (e < 256) {
                const int a = e >> 6, ii = (e & 63) - 16;
                const int b = 385 + (a >> 1) + 2 * (a & 1);
                const float v0 = (ii >= 0 && ii < 32) ? s_kp[b + 4 * ii] : 0.f;
                const float v1 = (ii >= 1 && ii < 33) ? s_kp[b + 4 * (ii - 1)] : 0.f;
                s_q2[e] = pack_bf16(v0, v1);
            }
        }
#pragma unroll
        for (int a = 0; a < 2; a++) {
            const int jj = tc - 16;
            const float v0 = (jj >= 0 && jj < 64) ? s_kp[513 + a + 2 * jj] : 0.f;
            const float v1 = (jj >= 1 && jj < 65) ? s_kp[513 + a + 2 * (jj - 1)] : 0.f;
            s_q3[96 * a + tc] = pack_bf16(v0, v1);
        }
    }
    if (threadIdx.x == 0) STAMP(1, 3);
    if (threadIdx.x == 0) {
        unsigned int v = 0;
        for (int spin = 0; spin < (1 << 22); spin++) {
            asm volatile("ld.acquire.gpu.global.u32 %0, [%1];" : "=r"(v) : "l"(&g_ln_count) : "memory");
            if (v >= gridDim.x) break;
        }
    }
    fence_async_smem();
    __syncthreads();
    if (threadIdx.x == 0) STAMP(1, 4);
    prefetch_fn();
    {
        if (tc < 16) *reinterpret_cast<uint4*>(s_u + tc * 8) = make_uint4(0, 0, 0, 0);
        const uint4* src = reinterpret_cast<const uint4*>(g_xnT + (size_t)d * L_);
        uint4 v[3];
#pragma unroll
        for (int i = 0; i < 3; i++) if (tc + 96 * i < 256) v[i] = src[tc + 96 * i];
#pragma unroll
        for (int i = 0; i < 3; i++) if (tc + 96 * i < 256) *reinterpret_cast<uint4*>(s_u + 128 + (tc + 96 * i) * 8) = v[i];
        if (tc < 2) *reinterpret_cast<uint4*>(base + (tc ? CV_O_W5 : CV_O_W3)) = make_uint4(0, 0, 0, 0);
    }
    named_bar(bar_id, 96);
    if (w == 2) {
#pragma unroll 2
      for (int rep = 0; rep < 6; rep++) {
        const int m = lane + 32 * rep;
        float P[30];
        const uint4* up = reinterpret_cast<const uint4*>(s_u + 128 + 8 * m - 24);
        P[0] = 0.f;
#pragma unroll
        for (int c4 = 0; c4 < 4; c4++) {
            const uint4 v = up[c4];
            const uint32_t ww[4] = {v.x, v.y, v.z, v.w};
#pragma unroll
            for (int j = 0; j < 4; j++) {
                const int k = c4 * 8 + 2 * j;
                if (k + 1 <= 29) P[k + 1] = P[k] + bf_lo(ww[j]);
                if (k + 2 <= 29) P[k + 2] = P[k + 1] + bf_hi(ww[j]);
            }
        }
        uint32_t o3[4], o5[4], o7[4], o9[4];
#pragma unroll
        for (int j = 0; j < 4; j++) {
            const int i = 2 * j;
            o3[j] = pack_bf16(P[i + 22] - P[i + 19], P[i + 23] - P[i + 20]);
            o5[j] = pack_bf16(P[i + 19] - P[i + 14], P[i + 20] - P[i + 15]);
            o7[j] = pack_bf16(P[i + 20] - P[i + 13], P[i + 21] - P[i + 14]);
            o9[j] = pack_bf16(P[i + 13] - P[i + 4], P[i + 14] - P[i + 5]);
        }
        *reinterpret_cast<uint4*>(base + CV_O_W3 + 16 + m * 16) = make_uint4(o3[0], o3[1], o3[2], o3[3]);
        *reinterpret_cast<uint4*>(base + CV_O_W5 + 16 + m * 16) = make_uint4(o5[0], o5[1], o5[2], o5[3]);
        if (m < 128) {
            *reinterpret_cast<uint4*>(base + CV_O_W7 + m * 16) = make_uint4(o7[0], o7[1], o7[2], o7[3]);
            *reinterpret_cast<uint4*>(base + CV_O_W9 + m * 16) = make_uint4(o9[0], o9[1], o9[2], o9[3]);
        }
    }
      named_bar(bar_id, 96);
      return;
    }
    if (threadIdx.x == 0) STAMP(1, 5);
    const int hb = w;
    float acc[16][4];
#pragma unroll
    for (int i = 0; i < 16; i++) { acc[i][0] = acc[i][1] = acc[i][2] = acc[i][3] = 0.f; }
    const uint32_t sb_addr = smem_u32(base);
    const int mi = lane >> 3, rowi = lane & 7;
#pragma unroll 1
    for (int rr = 0; rr < 4; rr++) {
        const int r = 4 * hb + rr;
        uint32_t ub[16][2];
        {
            const uint32_t addr = sb_addr + CV_O_U + (uint32_t)((128 + 16 * (8 * (mi >> 1) + rowi - r) + 8 * (mi & 1)) * 2);
#pragma unroll
            for (int j = 0; j < 16; j += 2) ldsm_x4(addr + (uint32_t)(j * 256), ub[j][0], ub[j][1], ub[j + 1][0], ub[j + 1][1]);
        }
        const uint32_t* qp = s_q + 16 + 16 * r + g - 2 * t;
        uint32_t af[4][3];
#pragma unroll
        for (int q = 0; q < 4; q++) { af[q][0] = qp[128 * q]; af[q][1] = qp[128 * q + 8]; af[q][2] = qp[128 * q - 8]; }
#pragma unroll
        for (int q = 0; q < 4; q++) {
#pragma unroll
            for (int nt = q; nt < 16; nt++) mma_bf16(acc[nt], af[q][0], af[q][1], af[q][2], af[q][0], ub[nt - q][0], ub[nt - q][1]);
        }
        if (r < 2) {
            {
                const uint32_t a0 = qp[512], a1 = qp[520], a2 = qp[504];
#pragma unroll
                for (int nt = 4; nt < 16; nt++) mma_bf16(acc[nt], a0, a1, a2, a0, ub[nt - 4][0], ub[nt - 4][1]);
            }
            {
                const uint32_t* q4p = s_q4 + 16 + 16 * r + g - 2 * t;
                const uint32_t a0 = q4p[0], a1 = q4p[8], a2 = q4p[-8];
#pragma unroll
                for (int nt = 8; nt < 16; nt++) mma_bf16(acc[nt], a0, a1, a2, a0, ub[nt - 8][0], ub[nt - 8][1]);
            }
        }
    }
    named_bar(bar_id, 96);
#pragma unroll 1
    for (int a = hb; a <= 3 * hb; a++) {
        uint32_t bq[7];
        const uint32_t* q2 = s_q2 + a * 64 + 16 + g - 2 * t - 32;
#pragma unroll
        for (int dlt = 3; dlt <= 9; dlt++) bq[dlt - 3] = q2[8 * dlt];
        const uint32_t addr = sb_addr + ((a >> 1) ? CV_O_W5 : CV_O_W3) + (uint32_t)((8 + 16 * (8 * (mi >> 1) + rowi) + 8 * (mi & 1) - 8 * (a & 1)) * 2);
        uint32_t aa[6][4];
#pragma unroll
        for (int kp = 0; kp < 6; kp++) ldsm_x4_t(addr + kp * 512, aa[kp][0], aa[kp][1], aa[kp][2], aa[kp][3]);
#pragma unroll
        for (int kp = 0; kp < 6; kp++) {
#pragma unroll
            for (int dlt = 4; dlt <= 9; dlt++) {
                if (2 * kp + dlt < 16) mma_bf16(acc[2 * kp + dlt], aa[kp][0], aa[kp][1], aa[kp][2], aa[kp][3], bq[dlt - 3], bq[dlt - 4]);
            }
        }
    }
    if (hb == 0) {
#pragma unroll 1
        for (int a = 0; a < 2; a++) {
            uint32_t bq[9];
            const uint32_t* q3 = s_q3 + a * 96 + 16 + g - 2 * t - 64;
#pragma unroll
            for (int dlt = 7; dlt <= 15; dlt++) bq[dlt - 7] = q3[8 * dlt];
            const uint32_t addr = sb_addr + (a ? CV_O_W9 : CV_O_W7) + (uint32_t)((16 * (8 * (mi >> 1) + rowi) + 8 * (mi & 1)) * 2);
            uint32_t aa[4][4];
#pragma unroll
            for (int kp = 0; kp < 4; kp++) ldsm_x4_t(addr + kp * 512, aa[kp][0], aa[kp][1], aa[kp][2], aa[kp][3]);
#pragma unroll
            for (int kp = 0; kp < 4; kp++) {
#pragma unroll
                for (int dlt = 8; dlt <= 15; dlt++) {
                    if (2 * kp + dlt < 16) mma_bf16(acc[2 * kp + dlt], aa[kp][0], aa[kp][1], aa[kp][2], aa[kp][3], bq[dlt - 7], bq[dlt - 8]);
                }
            }
        }
    }
    if (threadIdx.x == 0) STAMP(1, 6);
    named_bar(bar_id, 64);
    {
        float4* xch = reinterpret_cast<float4*>(base + CV_O_W3) + hb * 256;
        if (hb) {
#pragma unroll
            for (int i = 0; i < 8; i++) xch[i * 32 + lane] = make_float4(acc[i][0], acc[i][1], acc[i][2], acc[i][3]);
#pragma unroll
            for (int i = 0; i < 8; i++) { acc[i][0] = acc[8 + i][0]; acc[i][1] = acc[8 + i][1]; acc[i][2] = acc[8 + i][2]; acc[i][3] = acc[8 + i][3]; }
        } else {
#pragma unroll
            for (int i = 0; i < 8; i++) xch[i * 32 + lane] = make_float4(acc[8 + i][0], acc[8 + i][1], acc[8 + i][2], acc[8 + i][3]);
        }
    }
    named_bar(bar_id, 64);
    if (threadIdx.x == 0) STAMP(1, 10);
    {
        const float4* xch = reinterpret_cast<const float4*>(base + CV_O_W3) + (hb ^ 1) * 256 + lane;
        const float dsk = __bfloat162float(p_dsk);
        uint16_t* stg = reinterpret_cast<uint16_t*>(base + CV_O_Q);
        const uint16_t* uu = reinterpret_cast<const uint16_t*>(s_u) + 128;
#pragma unroll
        for (int i = 0; i < 8; i++) {
            const float4 p0 = xch[i * 32];
            const float y[4] = {acc[i][0] + p0.x, acc[i][1] + p0.y, acc[i][2] + p0.z, acc[i][3] + p0.w};
            const int nt = 8 * hb + i;
#pragma unroll
            for (int e = 0; e < 4; e++) {
                const int tau = 16 * (8 * nt + 2 * t + (e & 1)) + g + 8 * (e >> 1);
                const float sv = bf16_round(y[e]) + bf16_round(__uint_as_float((uint32_t)uu[tau] << 16) * dsk);
                stg[tau] = (uint16_t)(__float_as_uint(bf16_round(sv)) >> 16);
            }
        }
        __syncwarp();
        if (threadIdx.x == 0) STAMP(1, 11);
        uint4* dst = reinterpret_cast<uint4*>(g_sT + (size_t)d * L_ + hb * 1024);
        const uint4* srcp = reinterpret_cast<const uint4*>(stg + hb * 1024);
#pragma unroll
        for (int i = 0; i < 4; i++) dst[i * 32 + lane] = srcp[i * 32 + lane];
    }
}

__device__ __forceinline__ uint32_t cluster_rank() { uint32_t r; asm volatile("mov.u32 %0, %%cluster_ctarank;" : "=r"(r)); return r; }
__device__ __forceinline__ void cluster_sync_all() {
    asm volatile("barrier.cluster.arrive.release.aligned;\nbarrier.cluster.wait.acquire.aligned;" ::: "memory");
}
__device__ __forceinline__ void mbar_arrive_remote(uint32_t bar, uint32_t cta) {
    asm volatile("{\n.reg .b32 ra;\nmapa.shared::cluster.u32 ra, %0, %1;\n"
                 "mbarrier.arrive.shared::cluster.b64 _, [ra];\n}\n" ::"r"(bar), "r"(cta) : "memory");
}
__device__ __forceinline__ void tma_load_2d_mc(uint32_t dst, const CUtensorMap* tm, int c0, int c1, uint32_t bar, uint16_t mask) {
    asm volatile(
        "cp.async.bulk.tensor.2d.shared::cluster.global.mbarrier::complete_tx::bytes.multicast::cluster [%0], [%1, {%3, %4}], [%2], %5;"
        ::"r"(dst), "l"((uint64_t)tm), "r"(bar), "r"(c0), "r"(c1), "h"(mask) : "memory");
}
__device__ __forceinline__ void tma_store_2d(const CUtensorMap* tm, uint32_t src, int c0, int c1) {
    asm volatile("cp.async.bulk.tensor.2d.global.shared::cta.bulk_group [%0, {%2, %3}], [%1];"
                 ::"l"((uint64_t)tm), "r"(src), "r"(c0), "r"(c1) : "memory");
}
__device__ __forceinline__ void bulk_commit() { asm volatile("cp.async.bulk.commit_group;" ::: "memory"); }
template <int N> __device__ __forceinline__ void bulk_wait_read() { asm volatile("cp.async.bulk.wait_group.read %0;" ::"n"(N) : "memory"); }
template <int N> __device__ __forceinline__ void bulk_wait() { asm volatile("cp.async.bulk.wait_group %0;" ::"n"(N) : "memory"); }
__device__ __forceinline__ void stmatrix_x4(uint32_t addr, uint32_t r0, uint32_t r1, uint32_t r2, uint32_t r3) {
    asm volatile("stmatrix.sync.aligned.m8n8.x4.shared.b16 [%0], {%1,%2,%3,%4};" ::"r"(addr), "r"(r0), "r"(r1), "r"(r2), "r"(r3) : "memory");
}

constexpr int G1_STAGES = 5;
constexpr int G1_A_BYTES = 8 * 16384;
constexpr int G1_B_STAGE = 16384;
constexpr int G1_STG = 8 * 1024;
constexpr int G1_SMEM = G1_A_BYTES + G1_STAGES * G1_B_STAGE + G1_STG + 1024 + 256;
constexpr int G1_ITERS = 32;

__device__ __forceinline__ void tma_load_3d(uint32_t dst, const CUtensorMap* tm, int c0, int c1, int c2, uint32_t bar) {
    asm volatile(
        "cp.async.bulk.tensor.3d.shared::cluster.global.mbarrier::complete_tx::bytes [%0], [%1, {%3, %4, %5}], [%2];"
        ::"r"(dst), "l"((uint64_t)tm), "r"(bar), "r"(c0), "r"(c1), "r"(c2) : "memory");
}

__device__ __forceinline__ void tma_load_3d_mc(uint32_t dst, const CUtensorMap* tm, int c0, int c1, int c2, uint32_t bar, uint16_t mask) {
    asm volatile(
        "cp.async.bulk.tensor.3d.shared::cluster.global.mbarrier::complete_tx::bytes.multicast::cluster [%0], [%1, {%3, %4, %5}], [%2], %6;"
        ::"r"(dst), "l"((uint64_t)tm), "r"(bar), "r"(c0), "r"(c1), "r"(c2), "h"(mask) : "memory");
}

__device__ __forceinline__ float gelu_tanh(float x) {
    float u = x * (0.7978845608028654f + 0.035677408136300125f * x * x);
    float t; asm("tanh.approx.f32 %0, %1;" : "=f"(t) : "f"(u));
    float hx = 0.5f * x;
    return fmaf(hx, t, hx);
}
__device__ __forceinline__ uint32_t geglu_pair(uint32_t g2, uint32_t u2) {
    uint32_t a = pack_bf16(gelu_tanh(bf_lo(g2)), gelu_tanh(bf_hi(g2)));
    uint32_t r; asm("mul.rn.bf16x2 %0, %1, %2;" : "=r"(r) : "r"(a), "r"(u2));
    return r;
}

constexpr int G2_STAGES = 5;
constexpr int G2_STAGE = 16384 + 16384;
constexpr int G2_XCH = 32768;
constexpr int G2_EPI = 16384 + 16384;
constexpr int G2_SMEM = G2_STAGES * G2_STAGE + G2_XCH + G2_EPI + 1024 + 256;
constexpr int G2_KB = F_ / 64 / 2;

constexpr int MG_BAR_OFF = G2_STAGES * G2_STAGE + G2_XCH + G2_EPI;
constexpr int MG_SMEM = MG_BAR_OFF + 512 + 1024;
static_assert(MG_BAR_OFF == 229376 && G1_A_BYTES + G1_STAGES * G1_B_STAGE + G1_STG <= MG_BAR_OFF, "smem layout");

__device__ __forceinline__ void fence_async_all() { asm volatile("fence.proxy.async;" ::: "memory"); }
__device__ __forceinline__ void spin_until(const unsigned int* p, unsigned int target) {
    unsigned int v = 0;
    for (int spin = 0; spin < (1 << 22); spin++) {
        asm volatile("ld.acquire.gpu.global.u32 %0, [%1];" : "=r"(v) : "l"(p) : "memory");
        if (v >= target) break;
    }
}

struct MegaParams {
    const __nv_bfloat16 *x, *A_re, *A_im, *B_re, *B_im, *C_re, *C_im, *log_dt, *Dskip, *wg, *wu, *wd;
};

__global__ void __launch_bounds__(384, 1) mega_kernel(const __grid_constant__ MegaParams P,
                                                       const __grid_constant__ CUtensorMap tm_xn,
                                                       const __grid_constant__ CUtensorMap tm_wg4,
                                                       const __grid_constant__ CUtensorMap tm_wu4,
                                                       const __grid_constant__ CUtensorMap tm_wg3,
                                                       const __grid_constant__ CUtensorMap tm_wu3,
                                                       const __grid_constant__ CUtensorMap tm_h,
                                                       const __grid_constant__ CUtensorMap tm_wd,
                                                       const __grid_constant__ CUtensorMap tm_x,
                                                       const __grid_constant__ CUtensorMap tm_sT,
                                                       const __grid_constant__ CUtensorMap tm_out) {
    if (threadIdx.x == 0) STAMP(1, 0);
    extern __shared__ uint8_t smem_raw[];
    const uint32_t sraw = smem_u32(smem_raw);
    const uint32_t sbase = (sraw + 1023) & ~1023u;
    uint8_t* smem = smem_raw + (sbase - sraw);
    const int warp = threadIdx.x >> 5, lane = threadIdx.x & 31;
    const uint32_t sA = sbase, sB = sbase + G1_A_BYTES, sStg = sB + G1_STAGES * G1_B_STAGE;
    const uint32_t sXch = sbase + G2_STAGES * G2_STAGE, sX = sXch + G2_XCH, sS = sX + 16384;
    const uint32_t sBar = sbase + MG_BAR_OFF;
    const uint32_t bar_a = sBar, bar_full = sBar + 64, bar_empty = bar_full + 8 * G1_STAGES;
    const uint32_t bar_full2 = bar_empty + 8 * G1_STAGES, bar_empty2 = bar_full2 + 8 * G2_STAGES;
    const uint32_t bar_epi = bar_empty2 + 8 * G2_STAGES, bar_xch = bar_epi + 8, bar_g1done = bar_xch + 8, bar_g1mma = bar_g1done + 8, bar_peer = bar_g1mma + 8, bar_g1early = bar_peer + 8;
    const uint32_t kh = blockIdx.x & 1;
    const int rb1 = ((blockIdx.x >> 4) << 1) + (int)kh, cj = (blockIdx.x >> 1) & 7;
    const int rb = blockIdx.x >> 3;
    const int nb = (blockIdx.x >> 1) & 3;
    const int col_fin = nb * 128 + kh * 64;

    if (threadIdx.x == 0) {
        for (int i = 0; i < 8; i++) mbar_init(bar_a + 8 * i, 1);
        for (int i = 0; i < G1_STAGES; i++) { mbar_init(bar_full + 8 * i, 1); mbar_init(bar_empty + 8 * i, 16); }
        for (int i = 0; i < G2_STAGES; i++) { mbar_init(bar_full2 + 8 * i, 1); mbar_init(bar_empty2 + 8 * i, 8); }
        mbar_init(bar_epi, 1);
        mbar_init(bar_xch, 1);
        mbar_init(bar_g1done, 8);
        mbar_init(bar_g1mma, 8);
        mbar_init(bar_peer, 1);
        mbar_init(bar_g1early, 8);
        asm volatile("fence.mbarrier_init.release.cluster;" ::: "memory");
        mbar_expect_tx(bar_xch, G2_XCH);
    }
    if (warp == 11 && lane == 0) {
        prefetch_tmap(&tm_wg4); prefetch_tmap(&tm_wu4); prefetch_tmap(&tm_xn); prefetch_tmap(&tm_wg3); prefetch_tmap(&tm_wu3);
        prefetch_tmap(&tm_wd); prefetch_tmap(&tm_h); prefetch_tmap(&tm_x); prefetch_tmap(&tm_sT); prefetch_tmap(&tm_out);
    }
    asm volatile("barrier.cluster.arrive.release.aligned;" ::: "memory");

    auto g1_prefetch = [&]() {
        if (warp == 8 && lane == 0) {
            fence_async_all();
            mbar_expect_tx(bar_full, 16384);
            tma_load_3d(sB, &tm_wg4, 0, 0, cj * 7, bar_full);
            tma_load_3d(sB + 8192, &tm_wu4, 0, 0, cj * 7, bar_full);
            for (int k = 0; k < 8; k++) {
                mbar_expect_tx(bar_a + 8 * k, 16384);
                tma_load_2d(sA + k * 16384, &tm_xn, k * 64, rb1 * 128, bar_a + 8 * k);
            }
        }
    };
    front_phase(g1_prefetch, smem, P.x, P.A_re, P.A_im, P.B_re, P.B_im, P.C_re, P.C_im, P.log_dt, P.Dskip, P.wg, P.wu, P.wd);
    fence_async_smem();
    asm volatile("barrier.cluster.wait.acquire.aligned;" ::: "memory");
    __syncthreads();
    if (threadIdx.x == 352) mbar_arrive_remote(bar_peer, kh ^ 1);
    if (threadIdx.x == 0) STAMP(1, 7);

    if (warp >= 8) {
        asm volatile("setmaxnreg.dec.sync.aligned.u32 40;");
        if (warp == 11) {
            if (lane == 0) asm volatile("red.release.gpu.global.add.u32 [%0], 1;" ::"l"(&g_conv_count) : "memory");
            named_bar(3, 288);
            if (lane == 0) asm volatile("red.release.gpu.global.add.u32 [%0], 1;" ::"l"(&g_h_count[rb1]) : "memory");
            named_bar(9, 288);
            if (lane == 0) asm volatile("red.release.gpu.global.add.u32 [%0], 1;" ::"l"(&g_h_count[16 + rb1]) : "memory");
        } else if (lane == 0) {
            const int pw = warp - 8;
            mbar_wait(bar_peer, 0);
            for (int it = 1 + pw; it < G1_ITERS; it += 3) {
                const int s = it % G1_STAGES, kb = it & 15;
                if (it >= G1_STAGES) mbar_wait(bar_empty + 8 * s, ((it / G1_STAGES) - 1) & 1);
                const uint32_t dst = sB + s * G1_B_STAGE;
                if (it < 16) {
                    mbar_expect_tx(bar_full + 8 * s, 16384);
                    tma_load_3d_mc(dst + kh * 8192, kh ? &tm_wu4 : &tm_wg4, 0, kb * 32, cj * 7, bar_full + 8 * s, 3);
                } else {
                    mbar_expect_tx(bar_full + 8 * s, 12288);
                    tma_load_3d_mc(dst + kh * 6144, kh ? &tm_wu3 : &tm_wg3, 0, kb * 32, cj * 7 + 4, bar_full + 8 * s, 3);
                }
            }
            const int k0 = kh * G2_KB;
            auto kblk = [&](int it) -> int {
                const unsigned long long tab = 0xDCA96532B87410ull;
                return k0 + (int)((tab >> (4 * it)) & 15);
            };
            mbar_wait(pw < 2 ? bar_g1early : bar_g1mma, 0);
            if (pw == 2) {
                mbar_expect_tx(bar_epi, G2_EPI);
                tma_load_2d(sX, &tm_x, col_fin, rb * 128, bar_epi);
            }
            spin_until(&g_h_count[rb], 8);
            fence_async_all();
            if (pw == 0) STAMP(3, 1);
            for (int it = pw; it < G2_KB; it += 3) {
                const int s = (it + 1) % G2_STAGES;
                if (it == 3) mbar_wait(bar_g1mma, 0);
                if (it == 4) mbar_wait(bar_g1done, 0);
                if (it >= G2_STAGES) mbar_wait(bar_empty2 + 8 * s, ((it / G2_STAGES) - 1) & 1);
                if (it >= 6 && it < 9) { spin_until(&g_h_count[16 + rb], 8); fence_async_all(); }
                mbar_expect_tx(bar_full2 + 8 * s, G2_STAGE);
                const int kb = kblk(it);
                tma_load_3d(sbase + s * G2_STAGE + 16384, &tm_wd, 0, kb * 64, nb * 2, bar_full2 + 8 * s);
                tma_load_2d(sbase + s * G2_STAGE, &tm_h, kb * 64, rb * 128, bar_full2 + 8 * s);
                if (it == 2) {
                    spin_until(&g_conv_count, gridDim.x);
                    fence_async_all();
                    tma_load_2d(sS, &tm_sT, rb * 128, col_fin, bar_epi);
                    tma_load_2d(sS + 8192, &tm_sT, rb * 128 + 64, col_fin, bar_epi);
                }
            }
        }
    } else {
        asm volatile("setmaxnreg.inc.sync.aligned.u32 232;");
        const int wg = __shfl_sync(0xffffffffu, (int)(threadIdx.x >> 7), 0);
        {
        float r[160];
        const int row0 = rb1 * 128 + wg * 64 + (warp & 3) * 16;
        const uint64_t descA = make_desc(sA + wg * 8192, 16, 1024);
        const uint64_t descB = make_desc(sB, 2048, 512, 2);
        const uint32_t stg = sStg + warp * 1024;
        const uint32_t st_off = (uint32_t)(((lane & 7) + ((lane >> 3) & 1) * 8) * 32 + (lane >> 4) * 16);
        __nv_bfloat16* hrow = g_h + (size_t)(row0 + (lane >> 1)) * F_ + (lane & 1) * 8 + cj * 224;
#pragma unroll
        for (int kb = 0; kb < 16; kb++) {
            const int it = kb, s = it % G1_STAGES;
            if ((kb & 1) == 0) mbar_wait(bar_a + 8 * (kb >> 1), 0);
            mbar_wait(bar_full + 8 * s, (it / G1_STAGES) & 1);
            if (threadIdx.x == 0 && (it & 7) == 0) STAMP(2, 2 + it / 8);
            wgmma_fence();
            const uint64_t da = descA + (uint64_t)(((kb >> 1) * 16384 + (kb & 1) * 64) >> 4);
            const uint64_t db = descB + (uint64_t)((s * G1_B_STAGE) >> 4);
            wgmma_n256_k32(r, da, da + 2, db, db + 64, kb != 0);
            wgmma_commit();
            if (kb > 0) {
                wgmma_wait<1>();
                if (lane < 2) mbar_arrive_remote(bar_empty + 8 * ((it - 1) % G1_STAGES), lane);
            }
        }
        wgmma_wait<0>();
        if (lane < 2) mbar_arrive_remote(bar_empty + 8 * (15 % G1_STAGES), lane);
#pragma unroll
        for (int i = 0; i < 32; i++) r[128 + i] = __uint_as_float(pack_bf16(r[2 * i], r[2 * i + 1]));
#pragma unroll
        for (int i = 31; i >= 0; i--) r[96 + i] = __uint_as_float(pack_bf16(r[64 + 2 * i], r[65 + 2 * i]));
        uint32_t eo[4];
        uint4 pv = make_uint4(0, 0, 0, 0);
#pragma unroll
        for (int kb = 0; kb < 16; kb++) {
            const int it = 16 + kb, s = it % G1_STAGES;
            mbar_wait(bar_full + 8 * s, (it / G1_STAGES) & 1);
            if (threadIdx.x == 0 && (it & 7) == 0) STAMP(2, 2 + it / 8);
            wgmma_fence();
            const uint64_t da = descA + (uint64_t)(((kb >> 1) * 16384 + (kb & 1) * 64) >> 4);
            const uint64_t db = descB + (uint64_t)((s * G1_B_STAGE) >> 4);
            wgmma_n192(r, da, db, kb != 0);
            if (kb < 8) {
                eo[0] = geglu_pair(__float_as_uint(r[128 + 4 * kb]), __float_as_uint(r[96 + 4 * kb]));
                eo[1] = geglu_pair(__float_as_uint(r[129 + 4 * kb]), __float_as_uint(r[97 + 4 * kb]));
            }
            wgmma_n192(r, da + 2, db + 64, 1);
            wgmma_commit();
            if (kb >= 2 && kb < 10) *reinterpret_cast<uint4*>(hrow + (kb - 2) * 16) = pv;
            if (kb >= 1 && kb < 9) {
                __syncwarp();
                asm volatile("ld.shared.v4.u32 {%0,%1,%2,%3}, [%4];" : "=r"(pv.x), "=r"(pv.y), "=r"(pv.z), "=r"(pv.w)
                             : "r"(stg + ((kb - 1) & 1) * 512 + lane * 16));
            }
            if (kb < 8) {
                eo[2] = geglu_pair(__float_as_uint(r[130 + 4 * kb]), __float_as_uint(r[98 + 4 * kb]));
                eo[3] = geglu_pair(__float_as_uint(r[131 + 4 * kb]), __float_as_uint(r[99 + 4 * kb]));
                stmatrix_x4(stg + (kb & 1) * 512 + st_off, eo[0], eo[1], eo[2], eo[3]);
            }
            if (kb == 9) asm volatile("bar.arrive 3, 288;" ::: "memory");
            if (kb > 0 && it - 1 + G1_STAGES < G1_ITERS) {
                wgmma_wait<1>();
                if (lane < 2) mbar_arrive_remote(bar_empty + 8 * ((it - 1) % G1_STAGES), lane);
            }
            if (kb == 12) {
                wgmma_wait<1>();
                if (lane == 0) mbar_arrive(bar_g1early);
            }
        }
        wgmma_wait<0>();
        fence_async_smem();
        __syncwarp();
        if (lane == 0) mbar_arrive(bar_g1mma);
        if (threadIdx.x == 0) STAMP(2, 6);
        {
            uint32_t o[24];
#pragma unroll
            for (int i = 0; i < 24; i++) o[i] = geglu_pair(pack_bf16(r[2 * i], r[2 * i + 1]), pack_bf16(r[48 + 2 * i], r[49 + 2 * i]));
            named_bar(1 + wg, 128);
            const uint32_t fbuf = sA + ((warp & 3) >> 1) * 16384 + wg * 8192 + (warp & 1) * 4096;
#pragma unroll
            for (int jj = 0; jj < 6; jj++) stmatrix_x4(fbuf + jj * 512 + st_off, o[4 * jj], o[4 * jj + 1], o[4 * jj + 2], o[4 * jj + 3]);
            __syncwarp();
            uint4 v[6];
#pragma unroll
            for (int jj = 0; jj < 6; jj++)
                asm volatile("ld.shared.v4.u32 {%0,%1,%2,%3}, [%4];" : "=r"(v[jj].x), "=r"(v[jj].y), "=r"(v[jj].z), "=r"(v[jj].w)
                             : "r"(fbuf + jj * 512 + lane * 16));
#pragma unroll
            for (int jj = 0; jj < 6; jj++) *reinterpret_cast<uint4*>(hrow + 128 + jj * 16) = v[jj];
        }
        }
        fence_async_smem();
        __syncwarp();
        if (lane == 0) mbar_arrive(bar_g1done);
        asm volatile("bar.arrive 9, 288;" ::: "memory");
        if (threadIdx.x == 0) STAMP(2, 7);
        {
        const int g = lane >> 2, t = lane & 3;
        float acc[64];
        const uint64_t descA2 = make_desc(sbase + wg * 8192, 16, 1024);
        const uint64_t descB2 = make_desc(sbase + 16384, 8192, 1024);
#pragma unroll
        for (int it = 0; it < G2_KB; it++) {
            const int s = (it + 1) % G2_STAGES;
            mbar_wait(bar_full2 + 8 * s, (it / G2_STAGES) & 1);
            if (threadIdx.x == 0 && (it == 0 || it == 7)) STAMP(3, 2 + it / 7);
            wgmma_fence();
            {
                const uint64_t da = descA2 + (uint64_t)((s * G2_STAGE) >> 4);
                const uint64_t db = descB2 + (uint64_t)((s * G2_STAGE) >> 4);
                wgmma_n128_k64(acc, da, da + 2, da + 4, da + 6, db, db + 128, db + 256, db + 384, it != 0);
            }
            wgmma_commit();
            if (it > 0 && it - 1 + G2_STAGES < G2_KB) {
                wgmma_wait<1>();
                if (lane == 0) mbar_arrive(bar_empty2 + 8 * (it % G2_STAGES));
            }
        }
        const int lr = wg * 64 + (warp & 3) * 16 + g;
        uint32_t xv[16], sv[16];
        mbar_wait(bar_epi, 0);
#pragma unroll
        for (int j = 0; j < 8; j++) {
#pragma unroll
            for (int hh = 0; hh < 2; hh++) {
                const int r = lr + 8 * hh;
                asm volatile("ld.shared.u32 %0, [%1];" : "=r"(xv[2 * j + hh]) : "r"(sX + r * 128 + ((j ^ (r & 7)) << 4) + 4 * t));
                const int c0 = 8 * j + 2 * t;
                const uint32_t sa = sS + (r >> 6) * 8192 + (((r & 63) >> 3) << 4) + (r & 7) * 2;
                uint16_t s0r, s1r;
                asm volatile("ld.shared.u16 %0, [%1];" : "=h"(s0r) : "r"((sa + c0 * 128) ^ ((c0 & 7) << 4)));
                asm volatile("ld.shared.u16 %0, [%1];" : "=h"(s1r) : "r"((sa + (c0 + 1) * 128) ^ (((c0 + 1) & 7) << 4)));
                sv[2 * j + hh] = (uint32_t)s0r | ((uint32_t)s1r << 16);
            }
        }
        wgmma_wait<0>();
        if (threadIdx.x == 0) STAMP(3, 4);
        {
            uint32_t remote, rbar;
            asm volatile("mapa.shared::cluster.u32 %0, %1, %2;" : "=r"(remote) : "r"(sXch + threadIdx.x * 16), "r"(kh ^ 1));
            asm volatile("mapa.shared::cluster.u32 %0, %1, %2;" : "=r"(rbar) : "r"(bar_xch), "r"(kh ^ 1));
            if (kh == 0) {
#pragma unroll
                for (int i = 0; i < 8; i++)
                    asm volatile("st.async.shared::cluster.mbarrier::complete_tx::bytes.v4.f32 [%0], {%1,%2,%3,%4}, [%5];" ::"r"(remote + i * 4096),
                                 "f"(acc[32 + 4 * i]), "f"(acc[33 + 4 * i]), "f"(acc[34 + 4 * i]), "f"(acc[35 + 4 * i]), "r"(rbar) : "memory");
            } else {
#pragma unroll
                for (int i = 0; i < 8; i++)
                    asm volatile("st.async.shared::cluster.mbarrier::complete_tx::bytes.v4.f32 [%0], {%1,%2,%3,%4}, [%5];" ::"r"(remote + i * 4096),
                                 "f"(acc[4 * i]), "f"(acc[1 + 4 * i]), "f"(acc[2 + 4 * i]), "f"(acc[3 + 4 * i]), "r"(rbar) : "memory");
#pragma unroll
                for (int i = 0; i < 32; i++) acc[i] = acc[32 + i];
            }
        }
        if (threadIdx.x == 0) STAMP(3, 6);
        mbar_wait(bar_xch, 0);
        if (threadIdx.x == 0) STAMP(3, 7);
#pragma unroll
        for (int j = 0; j < 8; j++) {
            float4 o;
            asm volatile("ld.shared.v4.f32 {%0,%1,%2,%3}, [%4];" : "=f"(o.x), "=f"(o.y), "=f"(o.z), "=f"(o.w) : "r"(sXch + threadIdx.x * 16 + j * 4096));
            acc[4 * j] += o.x; acc[4 * j + 1] += o.y; acc[4 * j + 2] += o.z; acc[4 * j + 3] += o.w;
        }
#pragma unroll
        for (int i = 0; i < 16; i++) {
            float f0 = bf16_round(acc[2 * i]), f1 = bf16_round(acc[2 * i + 1]);
            float g0 = bf16_round(__fdividef(f0, 1.0f + __expf(-f0)));
            float g1 = bf16_round(__fdividef(f1, 1.0f + __expf(-f1)));
            float o0 = bf_lo(xv[i]) + bf16_round(bf_lo(sv[i]) * g0);
            float o1 = bf_hi(xv[i]) + bf16_round(bf_hi(sv[i]) * g1);
            xv[i] = pack_bf16(o0, o1);
        }
#pragma unroll
        for (int j = 0; j < 8; j++) {
#pragma unroll
            for (int hh = 0; hh < 2; hh++) {
                const int r = lr + 8 * hh;
                asm volatile("st.shared.u32 [%0], %1;" ::"r"(sX + r * 128 + ((j ^ (r & 7)) << 4) + 4 * t), "r"(xv[2 * j + hh]) : "memory");
            }
        }
        if (threadIdx.x == 0) STAMP(3, 9);
        fence_async_smem();
        __syncwarp();
        if (lane == 0) {
            tma_store_2d(&tm_out, sX + (wg * 64 + (warp & 3) * 16) * 128, col_fin, rb * 128 + wg * 64 + (warp & 3) * 16);
            bulk_commit();
            bulk_wait_read<0>();
        }
        }
        if (threadIdx.x == 0) STAMP(3, 5);
        named_bar(4, 256);
        if (threadIdx.x == 0) {
            const unsigned int old = atomicAdd(&g_done_count, 1u);
            if (old == gridDim.x - 1) {
                g_ln_count = 0; g_conv_count = 0; g_done_count = 0;
                for (int i = 0; i < 32; i++) g_h_count[i] = 0;
            }
        }
    }
}

typedef CUresult (*EncodeFn)(CUtensorMap*, CUtensorMapDataType, cuuint32_t, void*, const cuuint64_t*, const cuuint64_t*,
                             const cuuint32_t*, const cuuint32_t*, CUtensorMapInterleave, CUtensorMapSwizzle,
                             CUtensorMapL2promotion, CUtensorMapFloatOOBfill);

void make_map(EncodeFn fn, CUtensorMap* m, const void* ptr, uint64_t inner, uint64_t outer, uint32_t box_in, uint32_t box_out,
              CUtensorMapSwizzle swz = CU_TENSOR_MAP_SWIZZLE_128B) {
    cuuint64_t dims[2] = {inner, outer};
    cuuint64_t strides[1] = {inner * 2};
    cuuint32_t box[2] = {box_in, box_out};
    cuuint32_t es[2] = {1, 1};
    fn(m, CU_TENSOR_MAP_DATA_TYPE_BFLOAT16, 2, const_cast<void*>(ptr), dims, strides, box, es, CU_TENSOR_MAP_INTERLEAVE_NONE,
       swz, CU_TENSOR_MAP_L2_PROMOTION_L2_256B, CU_TENSOR_MAP_FLOAT_OOB_FILL_NONE);
}
void make_map3(EncodeFn fn, CUtensorMap* m, const void* ptr, uint64_t cols, uint64_t rows, uint32_t atom, uint32_t box_rows,
               uint32_t box_atoms, CUtensorMapSwizzle swz) {
    cuuint64_t dims[3] = {atom, rows, cols / atom};
    cuuint64_t strides[2] = {cols * 2, (cuuint64_t)atom * 2};
    cuuint32_t box[3] = {atom, box_rows, box_atoms};
    cuuint32_t es[3] = {1, 1, 1};
    fn(m, CU_TENSOR_MAP_DATA_TYPE_BFLOAT16, 3, const_cast<void*>(ptr), dims, strides, box, es, CU_TENSOR_MAP_INTERLEAVE_NONE,
       swz, CU_TENSOR_MAP_L2_PROMOTION_L2_256B, CU_TENSOR_MAP_FLOAT_OOB_FILL_NONE);
}

template <typename... Args>
void launch_pdl(void (*kern)(Args...), int grid, int block, int smem, bool pdl, int cluster, Args... args) {
    cudaLaunchConfig_t cfg = {};
    cfg.gridDim = dim3(grid); cfg.blockDim = dim3(block); cfg.dynamicSmemBytes = smem; cfg.stream = cudaStreamPerThread;
    cudaLaunchAttribute at[2];
    int n = 0;
    if (pdl) {
        at[n].id = cudaLaunchAttributeProgrammaticStreamSerialization;
        at[n].val.programmaticStreamSerializationAllowed = 1;
        n++;
    }
    if (cluster > 1) {
        at[n].id = cudaLaunchAttributeClusterDimension;
        at[n].val.clusterDim.x = cluster; at[n].val.clusterDim.y = 1; at[n].val.clusterDim.z = 1;
        n++;
    }
    cfg.attrs = at; cfg.numAttrs = n;
    cudaLaunchKernelEx(&cfg, kern, args...);
}

}

extern "C" void kernel_launch(void* const* d_in, const int* in_sizes, int n_in, void* d_out, int out_size) {
    const __nv_bfloat16* x = (const __nv_bfloat16*)d_in[0];
    const __nv_bfloat16* A_re = (const __nv_bfloat16*)d_in[1];
    const __nv_bfloat16* A_im = (const __nv_bfloat16*)d_in[2];
    const __nv_bfloat16* B_re = (const __nv_bfloat16*)d_in[3];
    const __nv_bfloat16* B_im = (const __nv_bfloat16*)d_in[4];
    const __nv_bfloat16* C_re = (const __nv_bfloat16*)d_in[5];
    const __nv_bfloat16* C_im = (const __nv_bfloat16*)d_in[6];
    const __nv_bfloat16* log_dt = (const __nv_bfloat16*)d_in[7];
    const __nv_bfloat16* Dskip = (const __nv_bfloat16*)d_in[8];
    const __nv_bfloat16* wg = (const __nv_bfloat16*)d_in[10];
    const __nv_bfloat16* wu = (const __nv_bfloat16*)d_in[11];
    const __nv_bfloat16* wd = (const __nv_bfloat16*)d_in[12];
    __nv_bfloat16* out = (__nv_bfloat16*)d_out;

    static bool init = false;
    static CUtensorMap tm_xn, tm_wg4, tm_wu4, tm_wg3, tm_wu3, tm_hst, tm_hst96, tm_h, tm_wd, tm_x, tm_sT, tm_out;
    static const void* last_ptrs[5] = {nullptr, nullptr, nullptr, nullptr, nullptr};
    if (!init || last_ptrs[0] != wg || last_ptrs[1] != wu || last_ptrs[2] != wd || last_ptrs[3] != x || last_ptrs[4] != out) {
        void* fnp = nullptr;
        cudaDriverEntryPointQueryResult qres;
        cudaGetDriverEntryPoint("cuTensorMapEncodeTiled", &fnp, cudaEnableDefault, &qres);
        EncodeFn fn = (EncodeFn)fnp;
        void *p_xn, *p_h, *p_sT;
        cudaGetSymbolAddress(&p_xn, g_xn);
        cudaGetSymbolAddress(&p_h, g_h);
        cudaGetSymbolAddress(&p_sT, g_sT);
        make_map(fn, &tm_xn, p_xn, D_, L_, 64, 128);
        make_map3(fn, &tm_wg4, wg, F_, D_, 32, 32, 4, CU_TENSOR_MAP_SWIZZLE_64B);
        make_map3(fn, &tm_wu4, wu, F_, D_, 32, 32, 4, CU_TENSOR_MAP_SWIZZLE_64B);
        make_map3(fn, &tm_wg3, wg, F_, D_, 32, 32, 3, CU_TENSOR_MAP_SWIZZLE_64B);
        make_map3(fn, &tm_wu3, wu, F_, D_, 32, 32, 3, CU_TENSOR_MAP_SWIZZLE_64B);
        make_map(fn, &tm_hst, p_h, F_, L_, 16, 16, CU_TENSOR_MAP_SWIZZLE_NONE);
        make_map(fn, &tm_hst96, p_h, F_, L_, 96, 16, CU_TENSOR_MAP_SWIZZLE_NONE);
        make_map(fn, &tm_h, p_h, F_, L_, 64, 128);
        make_map3(fn, &tm_wd, wd, D_, F_, 64, 64, 2, CU_TENSOR_MAP_SWIZZLE_128B);
        make_map(fn, &tm_x, x, D_, L_, 64, 128);
        make_map(fn, &tm_sT, p_sT, L_, D_, 64, 64);
        make_map(fn, &tm_out, out, D_, L_, 64, 16);
        cudaFuncSetAttribute(mega_kernel, cudaFuncAttributeMaxDynamicSharedMemorySize, MG_SMEM);
        last_ptrs[0] = wg; last_ptrs[1] = wu; last_ptrs[2] = wd; last_ptrs[3] = x; last_ptrs[4] = out;
        init = true;
    }
    MegaParams P = {x, A_re, A_im, B_re, B_im, C_re, C_im, log_dt, Dskip, wg, wu, wd};
    launch_pdl(mega_kernel, 128, 384, MG_SMEM, false, 2, P, tm_xn, tm_wg4, tm_wu4, tm_wg3, tm_wu3, tm_h, tm_wd, tm_x, tm_sT, tm_out);
}
```

```cpp
#include <cuda_runtime.h>
#include <cuda_bf16.h>
#include <cuda.h>
#include <stdint.h>

namespace {

constexpr int L_ = 2048, D_ = 512, NS_ = 128, F_ = 1792;

__device__ __align__(1024) __nv_bfloat16 g_xn[L_ * D_];
__device__ __align__(1024) __nv_bfloat16 g_xnT[D_ * L_];
__device__ __align__(1024) __nv_bfloat16 g_sT[D_ * L_];
__device__ __align__(1024) __nv_bfloat16 g_h[L_ * F_];
__device__ unsigned int g_ln_count, g_conv_count, g_done_count, g_h_count[32];

#define STAMP(k, i)

__device__ __forceinline__ uint32_t smem_u32(const void* p) { return (uint32_t)__cvta_generic_to_shared(p); }
__device__ __forceinline__ void pdl_wait() { asm volatile("griddepcontrol.wait;" ::: "memory"); }
__device__ __forceinline__ void pdl_launch() { asm volatile("griddepcontrol.launch_dependents;" ::: "memory"); }

__device__ __forceinline__ void mbar_init(uint32_t bar, uint32_t cnt) {
    asm volatile("mbarrier.init.shared::cta.b64 [%0], %1;" ::"r"(bar), "r"(cnt) : "memory");
}
__device__ __forceinline__ void mbar_expect_tx(uint32_t bar, uint32_t bytes) {
    asm volatile("mbarrier.arrive.expect_tx.shared::cta.b64 _, [%0], %1;" ::"r"(bar), "r"(bytes) : "memory");
}
__device__ __forceinline__ void mbar_arrive(uint32_t bar) {
    asm volatile("mbarrier.arrive.shared::cta.b64 _, [%0];" ::"r"(bar) : "memory");
}
__device__ __forceinline__ void mbar_wait(uint32_t bar, uint32_t parity) {
    asm volatile(
        "{\n.reg .pred p;\n"
        "WAIT_LOOP:\n"
        "mbarrier.try_wait.parity.shared::cta.b64 p, [%0], %1;\n"
        "@p bra WAIT_DONE;\n"
        "bra WAIT_LOOP;\n"
        "WAIT_DONE:\n}\n" ::"r"(bar), "r"(parity) : "memory");
}
__device__ __forceinline__ void tma_load_2d(uint32_t dst, const CUtensorMap* tm, int c0, int c1, uint32_t bar) {
    asm volatile(
        "cp.async.bulk.tensor.2d.shared::cluster.global.mbarrier::complete_tx::bytes [%0], [%1, {%3, %4}], [%2];"
        ::"r"(dst), "l"((uint64_t)tm), "r"(bar), "r"(c0), "r"(c1) : "memory");
}
__device__ __forceinline__ void prefetch_tmap(const CUtensorMap* tm) {
    asm volatile("prefetch.tensormap [%0];" ::"l"((uint64_t)tm) : "memory");
}
__device__ __forceinline__ uint64_t make_desc(uint32_t addr, uint32_t lbo, uint32_t sbo, uint64_t mode = 1) {
    uint64_t d = 0;
    d |= (uint64_t)((addr & 0x3FFFF) >> 4);
    d |= (uint64_t)((lbo >> 4) & 0x3FFF) << 16;
    d |= (uint64_t)((sbo >> 4) & 0x3FFF) << 32;
    d |= mode << 62;
    return d;
}
__device__ __forceinline__ void fence_async_smem() { asm volatile("fence.proxy.async.shared::cta;" ::: "memory"); }
__device__ __forceinline__ void wgmma_fence() { asm volatile("wgmma.fence.sync.aligned;" ::: "memory"); }
__device__ __forceinline__ void wgmma_commit() { asm volatile("wgmma.commit_group.sync.aligned;" ::: "memory"); }
template <int N> __device__ __forceinline__ void wgmma_wait() {
    asm volatile("wgmma.wait_group.sync.aligned %0;" ::"n"(N) : "memory");
}

#define R8(a, i) "+f"(a[i + 0]), "+f"(a[i + 1]), "+f"(a[i + 2]), "+f"(a[i + 3]), "+f"(a[i + 4]), "+f"(a[i + 5]), "+f"(a[i + 6]), "+f"(a[i + 7])

__device__ __forceinline__ void wgmma_n256_k32(float* a, uint64_t da0, uint64_t da1, uint64_t db0, uint64_t db1, int scale_d) {
    asm volatile(
        "{\n.reg .pred p;\nsetp.ne.b32 p, %132, 0;\n"
        "wgmma.mma_async.sync.aligned.m64n256k16.f32.bf16.bf16 {%0,%1,%2,%3,%4,%5,%6,%7,%8,%9,%10,%11,%12,%13,%14,%15,%16,%17,%18,%19,%20,%21,%22,%23,%24,%25,%26,%27,%28,%29,%30,%31,%32,%33,%34,%35,%36,%37,%38,%39,%40,%41,%42,%43,%44,%45,%46,%47,%48,%49,%50,%51,%52,%53,%54,%55,%56,%57,%58,%59,%60,%61,%62,%63,%64,%65,%66,%67,%68,%69,%70,%71,%72,%73,%74,%75,%76,%77,%78,%79,%80,%81,%82,%83,%84,%85,%86,%87,%88,%89,%90,%91,%92,%93,%94,%95,%96,%97,%98,%99,%100,%101,%102,%103,%104,%105,%106,%107,%108,%109,%110,%111,%112,%113,%114,%115,%116,%117,%118,%119,%120,%121,%122,%123,%124,%125,%126,%127}, %128, %130, p, 1, 1, 0, 1;\n"
        "wgmma.mma_async.sync.aligned.m64n256k16.f32.bf16.bf16 {%0,%1,%2,%3,%4,%5,%6,%7,%8,%9,%10,%11,%12,%13,%14,%15,%16,%17,%18,%19,%20,%21,%22,%23,%24,%25,%26,%27,%28,%29,%30,%31,%32,%33,%34,%35,%36,%37,%38,%39,%40,%41,%42,%43,%44,%45,%46,%47,%48,%49,%50,%51,%52,%53,%54,%55,%56,%57,%58,%59,%60,%61,%62,%63,%64,%65,%66,%67,%68,%69,%70,%71,%72,%73,%74,%75,%76,%77,%78,%79,%80,%81,%82,%83,%84,%85,%86,%87,%88,%89,%90,%91,%92,%93,%94,%95,%96,%97,%98,%99,%100,%101,%102,%103,%104,%105,%106,%107,%108,%109,%110,%111,%112,%113,%114,%115,%116,%117,%118,%119,%120,%121,%122,%123,%124,%125,%126,%127}, %129, %131, 1, 1, 1, 0, 1;\n"
        "}\n"
        : R8(a, 0), R8(a, 8), R8(a, 16), R8(a, 24), R8(a, 32), R8(a, 40), R8(a, 48), R8(a, 56), R8(a, 64), R8(a, 72), R8(a, 80), R8(a, 88), R8(a, 96), R8(a, 104), R8(a, 112), R8(a, 120)
        : "l"(da0), "l"(da1), "l"(db0), "l"(db1), "r"(scale_d));
}
__device__ __forceinline__ void wgmma_n192_k32(float* a, uint64_t da0, uint64_t da1, uint64_t db0, uint64_t db1, int scale_d) {
    asm volatile(
        "{\n.reg .pred p;\nsetp.ne.b32 p, %100, 0;\n"
        "wgmma.mma_async.sync.aligned.m64n192k16.f32.bf16.bf16 {%0,%1,%2,%3,%4,%5,%6,%7,%8,%9,%10,%11,%12,%13,%14,%15,%16,%17,%18,%19,%20,%21,%22,%23,%24,%25,%26,%27,%28,%29,%30,%31,%32,%33,%34,%35,%36,%37,%38,%39,%40,%41,%42,%43,%44,%45,%46,%47,%48,%49,%50,%51,%52,%53,%54,%55,%56,%57,%58,%59,%60,%61,%62,%63,%64,%65,%66,%67,%68,%69,%70,%71,%72,%73,%74,%75,%76,%77,%78,%79,%80,%81,%82,%83,%84,%85,%86,%87,%88,%89,%90,%91,%92,%93,%94,%95}, %96, %98, p, 1, 1, 0, 1;\n"
        "wgmma.mma_async.sync.aligned.m64n192k16.f32.bf16.bf16 {%0,%1,%2,%3,%4,%5,%6,%7,%8,%9,%10,%11,%12,%13,%14,%15,%16,%17,%18,%19,%20,%21,%22,%23,%24,%25,%26,%27,%28,%29,%30,%31,%32,%33,%34,%35,%36,%37,%38,%39,%40,%41,%42,%43,%44,%45,%46,%47,%48,%49,%50,%51,%52,%53,%54,%55,%56,%57,%58,%59,%60,%61,%62,%63,%64,%65,%66,%67,%68,%69,%70,%71,%72,%73,%74,%75,%76,%77,%78,%79,%80,%81,%82,%83,%84,%85,%86,%87,%88,%89,%90,%91,%92,%93,%94,%95}, %97, %99, 1, 1, 1, 0, 1;\n"
        "}\n"
        : R8(a, 0), R8(a, 8), R8(a, 16), R8(a, 24), R8(a, 32), R8(a, 40), R8(a, 48), R8(a, 56), R8(a, 64), R8(a, 72), R8(a, 80), R8(a, 88)
        : "l"(da0), "l"(da1), "l"(db0), "l"(db1), "r"(scale_d));
}
__device__ __forceinline__ void wgmma_n192(float* a, uint64_t da0, uint64_t db0, int scale_d) {
    asm volatile(
        "{\n.reg .pred p;\nsetp.ne.b32 p, %98, 0;\n"
        "wgmma.mma_async.sync.aligned.m64n192k16.f32.bf16.bf16 {%0,%1,%2,%3,%4,%5,%6,%7,%8,%9,%10,%11,%12,%13,%14,%15,%16,%17,%18,%19,%20,%21,%22,%23,%24,%25,%26,%27,%28,%29,%30,%31,%32,%33,%34,%35,%36,%37,%38,%39,%40,%41,%42,%43,%44,%45,%46,%47,%48,%49,%50,%51,%52,%53,%54,%55,%56,%57,%58,%59,%60,%61,%62,%63,%64,%65,%66,%67,%68,%69,%70,%71,%72,%73,%74,%75,%76,%77,%78,%79,%80,%81,%82,%83,%84,%85,%86,%87,%88,%89,%90,%91,%92,%93,%94,%95}, %96, %97, p, 1, 1, 0, 1;\n"
        "}\n"
        : R8(a, 0), R8(a, 8), R8(a, 16), R8(a, 24), R8(a, 32), R8(a, 40), R8(a, 48), R8(a, 56), R8(a, 64), R8(a, 72), R8(a, 80), R8(a, 88)
        : "l"(da0), "l"(db0), "r"(scale_d));
}
__device__ __forceinline__ void wgmma_n128_k64(float* a, uint64_t da0, uint64_t da1, uint64_t da2, uint64_t da3,
                                               uint64_t db0, uint64_t db1, uint64_t db2, uint64_t db3, int scale_d) {
    asm volatile(
        "{\n.reg .pred p;\nsetp.ne.b32 p, %72, 0;\n"
        "wgmma.mma_async.sync.aligned.m64n128k16.f32.bf16.bf16 {%0,%1,%2,%3,%4,%5,%6,%7,%8,%9,%10,%11,%12,%13,%14,%15,%16,%17,%18,%19,%20,%21,%22,%23,%24,%25,%26,%27,%28,%29,%30,%31,%32,%33,%34,%35,%36,%37,%38,%39,%40,%41,%42,%43,%44,%45,%46,%47,%48,%49,%50,%51,%52,%53,%54,%55,%56,%57,%58,%59,%60,%61,%62,%63}, %64, %68, p, 1, 1, 0, 1;\n"
        "wgmma.mma_async.sync.aligned.m64n128k16.f32.bf16.bf16 {%0,%1,%2,%3,%4,%5,%6,%7,%8,%9,%10,%11,%12,%13,%14,%15,%16,%17,%18,%19,%20,%21,%22,%23,%24,%25,%26,%27,%28,%29,%30,%31,%32,%33,%34,%35,%36,%37,%38,%39,%40,%41,%42,%43,%44,%45,%46,%47,%48,%49,%50,%51,%52,%53,%54,%55,%56,%57,%58,%59,%60,%61,%62,%63}, %65, %69, 1, 1, 1, 0, 1;\n"
        "wgmma.mma_async.sync.aligned.m64n128k16.f32.bf16.bf16 {%0,%1,%2,%3,%4,%5,%6,%7,%8,%9,%10,%11,%12,%13,%14,%15,%16,%17,%18,%19,%20,%21,%22,%23,%24,%25,%26,%27,%28,%29,%30,%31,%32,%33,%34,%35,%36,%37,%38,%39,%40,%41,%42,%43,%44,%45,%46,%47,%48,%49,%50,%51,%52,%53,%54,%55,%56,%57,%58,%59,%60,%61,%62,%63}, %66, %70, 1, 1, 1, 0, 1;\n"
        "wgmma.mma_async.sync.aligned.m64n128k16.f32.bf16.bf16 {%0,%1,%2,%3,%4,%5,%6,%7,%8,%9,%10,%11,%12,%13,%14,%15,%16,%17,%18,%19,%20,%21,%22,%23,%24,%25,%26,%27,%28,%29,%30,%31,%32,%33,%34,%35,%36,%37,%38,%39,%40,%41,%42,%43,%44,%45,%46,%47,%48,%49,%50,%51,%52,%53,%54,%55,%56,%57,%58,%59,%60,%61,%62,%63}, %67, %71, 1, 1, 1, 0, 1;\n"
        "}\n"
        : R8(a, 0), R8(a, 8), R8(a, 16), R8(a, 24), R8(a, 32), R8(a, 40), R8(a, 48), R8(a, 56)
        : "l"(da0), "l"(da1), "l"(da2), "l"(da3), "l"(db0), "l"(db1), "l"(db2), "l"(db3), "r"(scale_d));
}

__device__ __forceinline__ float bf16_round(float x) {
    uint32_t p; asm("cvt.rn.bf16x2.f32 %0, %1, %2;" : "=r"(p) : "f"(x), "f"(0.0f));
    return __uint_as_float(p);
}
__device__ __forceinline__ uint32_t pack_bf16(float lo, float hi) {
    __nv_bfloat162 v = __floats2bfloat162_rn(lo, hi);
    return *reinterpret_cast<uint32_t*>(&v);
}
__device__ __forceinline__ float bf_lo(uint32_t v) { return __uint_as_float(v << 16); }
__device__ __forceinline__ float bf_hi(uint32_t v) { return __uint_as_float(v & 0xFFFF0000u); }

struct cplx { float r, i; };
__device__ __forceinline__ cplx cmul(cplx a, cplx b) {
    cplx c; c.r = a.r * b.r - a.i * b.i; c.i = a.r * b.i + a.i * b.r; return c;
}
__device__ __forceinline__ cplx csq(cplx a) {
    cplx c; c.r = a.r * a.r - a.i * a.i; c.i = 2.0f * a.r * a.i; return c;
}
__device__ __forceinline__ cplx cexp_m(float ar2, float ai2, float m) {
    float mag;
    asm("ex2.approx.ftz.f32 %0, %1;" : "=f"(mag) : "f"(ar2 * m));
    float rr = ai2 * m;
    rr -= (rr + 12582912.0f) - 12582912.0f;
    float th = rr * 6.283185307179586f;
    cplx c; c.r = mag * __cosf(th); c.i = mag * __sinf(th);
    return c;
}
__device__ __forceinline__ uint32_t to_tf32(float x) { return __float_as_uint(x) + 0x1000u; }
__device__ __forceinline__ void mma_tf32(float* c, uint32_t a0, uint32_t a1, uint32_t a2, uint32_t a3, uint32_t b0, uint32_t b1) {
    asm volatile("mma.sync.aligned.m16n8k8.row.col.f32.tf32.tf32.f32 {%0,%1,%2,%3}, {%4,%5,%6,%7}, {%8,%9}, {%0,%1,%2,%3};"
                 : "+f"(c[0]), "+f"(c[1]), "+f"(c[2]), "+f"(c[3])
                 : "r"(a0), "r"(a1), "r"(a2), "r"(a3), "r"(b0), "r"(b1));
}
__device__ __forceinline__ void mma_bf16(float* c, uint32_t a0, uint32_t a1, uint32_t a2, uint32_t a3, uint32_t b0, uint32_t b1) {
    asm volatile("mma.sync.aligned.m16n8k16.row.col.f32.bf16.bf16.f32 {%0,%1,%2,%3}, {%4,%5,%6,%7}, {%8,%9}, {%0,%1,%2,%3};"
                 : "+f"(c[0]), "+f"(c[1]), "+f"(c[2]), "+f"(c[3])
                 : "r"(a0), "r"(a1), "r"(a2), "r"(a3), "r"(b0), "r"(b1));
}
__device__ __forceinline__ void named_bar(int id, int n) { asm volatile("bar.sync %0, %1;" ::"r"(id), "r"(n) : "memory"); }
__device__ __forceinline__ void ldsm_x4(uint32_t addr, uint32_t& r0, uint32_t& r1, uint32_t& r2, uint32_t& r3) {
    asm volatile("ldmatrix.sync.aligned.m8n8.x4.shared.b16 {%0,%1,%2,%3}, [%4];" : "=r"(r0), "=r"(r1), "=r"(r2), "=r"(r3) : "r"(addr));
}
__device__ __forceinline__ void ldsm_x4_t(uint32_t addr, uint32_t& r0, uint32_t& r1, uint32_t& r2, uint32_t& r3) {
    asm volatile("ldmatrix.sync.aligned.m8n8.x4.trans.shared.b16 {%0,%1,%2,%3}, [%4];" : "=r"(r0), "=r"(r1), "=r"(r2), "=r"(r3) : "r"(addr));
}

constexpr int CV_CH = 4;
constexpr int CV_O_CONST = 0;
constexpr int CV_O_KP = 12288;
constexpr int CV_EARLY = 12288 + 7776;
constexpr int CV_O_Q = 0;
constexpr int CV_O_Q2 = CV_O_Q + 2304;
constexpr int CV_O_Q3 = CV_O_Q2 + 1024;
constexpr int CV_O_Q4X = CV_O_Q3 + 768;
constexpr int CV_O_W3 = CV_O_Q4X + 256;
constexpr int CV_O_W5 = CV_O_W3 + 3104;
constexpr int CV_O_W7 = CV_O_W5 + 3104;
constexpr int CV_O_W9 = CV_O_W7 + 2048;
constexpr int CV_O_U = CV_O_W9 + 2048;
constexpr int CV_LATE = CV_O_U + 4352;
constexpr int CV_LATE_BASE = 229376 - CV_CH * CV_LATE;
constexpr int CV_TILE_OFF = CV_CH * CV_EARLY;
static_assert(CV_TILE_OFF + 16 * (D_ + 8) * 2 <= CV_LATE_BASE && CV_LATE_BASE >= 131072 + 16384, "front layout");
static_assert(CV_O_W3 >= 4096 && CV_O_U - CV_O_W3 >= 8192 && (CV_LATE % 16) == 0 && (CV_EARLY % 16) == 0, "front layout");

constexpr int LN_ROWS = 16;

template <typename PF>
__device__ __forceinline__ void front_phase(PF prefetch_fn, uint8_t* smem, const __nv_bfloat16* __restrict__ x,
                                            const __nv_bfloat16* __restrict__ A_re, const __nv_bfloat16* __restrict__ A_im,
                                            const __nv_bfloat16* __restrict__ B_re, const __nv_bfloat16* __restrict__ B_im,
                                            const __nv_bfloat16* __restrict__ C_re, const __nv_bfloat16* __restrict__ C_im,
                                            const __nv_bfloat16* __restrict__ log_dt, const __nv_bfloat16* __restrict__ Dskip,
                                            const __nv_bfloat16* __restrict__ wg, const __nv_bfloat16* __restrict__ wu,
                                            const __nv_bfloat16* __restrict__ wd) {
    const int warp = threadIdx.x >> 5, lane = threadIdx.x & 31;
    const int ch = warp / 3, w = warp - 3 * ch, tc = threadIdx.x - 96 * ch;
    const int d = blockIdx.x * CV_CH + ch;
    const int g = lane >> 2, t = lane & 3;
    uint8_t* base = smem + CV_LATE_BASE + ch * CV_LATE;
    float4* s_const = reinterpret_cast<float4*>(smem + ch * CV_EARLY + CV_O_CONST);
    float* s_kp = reinterpret_cast<float*>(smem + ch * CV_EARLY + CV_O_KP);
    uint32_t* s_q = reinterpret_cast<uint32_t*>(base + CV_O_Q);
    uint32_t* s_q2 = reinterpret_cast<uint32_t*>(base + CV_O_Q2);
    uint32_t* s_q3 = reinterpret_cast<uint32_t*>(base + CV_O_Q3);
    uint32_t* s_q4 = reinterpret_cast<uint32_t*>(base + CV_O_Q4X);
    __nv_bfloat16* s_u = reinterpret_cast<__nv_bfloat16*>(base + CV_O_U);
    const int bar_id = 5 + ch;
    const __nv_bfloat16 p_dsk = Dskip[d];
    __nv_bfloat16 (*tile)[D_ + 8] = reinterpret_cast<__nv_bfloat16 (*)[D_ + 8]>(smem + CV_TILE_OFF);

    if (warp < 8) {
        const int row = blockIdx.x * LN_ROWS + warp * 2;
        uint4 xv[2][2];
#pragma unroll
        for (int r = 0; r < 2; r++) {
            xv[r][0] = *reinterpret_cast<const uint4*>(x + (size_t)(row + r) * D_ + lane * 8);
            xv[r][1] = *reinterpret_cast<const uint4*>(x + (size_t)(row + r) * D_ + 256 + lane * 8);
        }
        float f[2][16], sm[2], q[2];
#pragma unroll
        for (int r = 0; r < 2; r++) {
            const uint32_t wv[8] = {xv[r][0].x, xv[r][0].y, xv[r][0].z, xv[r][0].w, xv[r][1].x, xv[r][1].y, xv[r][1].z, xv[r][1].w};
#pragma unroll
            for (int i = 0; i < 8; i++) { f[r][2 * i] = bf_lo(wv[i]); f[r][2 * i + 1] = bf_hi(wv[i]); }
            sm[r] = 0.f;
#pragma unroll
            for (int i = 0; i < 16; i++) sm[r] += f[r][i];
        }
#pragma unroll
        for (int o = 16; o > 0; o >>= 1) { sm[0] += __shfl_xor_sync(0xffffffffu, sm[0], o); sm[1] += __shfl_xor_sync(0xffffffffu, sm[1], o); }
#pragma unroll
        for (int r = 0; r < 2; r++) {
            sm[r] *= (1.0f / D_);
            q[r] = 0.f;
#pragma unroll
            for (int i = 0; i < 16; i++) { float dd = f[r][i] - sm[r]; q[r] += dd * dd; }
        }
#pragma unroll
        for (int o = 16; o > 0; o >>= 1) { q[0] += __shfl_xor_sync(0xffffffffu, q[0], o); q[1] += __shfl_xor_sync(0xffffffffu, q[1], o); }
#pragma unroll
        for (int r = 0; r < 2; r++) {
            const float mb = bf16_round(sm[r]);
            const float vb = bf16_round(q[r] * (1.0f / D_));
            const float den = bf16_round(sqrtf(bf16_round(vb + 1e-5f)));
            uint32_t o[8];
#pragma unroll
            for (int i = 0; i < 8; i++) {
                float a = __fdiv_rn(bf16_round(f[r][2 * i] - mb), den);
                float b = __fdiv_rn(bf16_round(f[r][2 * i + 1] - mb), den);
                o[i] = pack_bf16(a, b);
            }
            __nv_bfloat16* dst = g_xn + (size_t)(row + r) * D_;
            *reinterpret_cast<uint4*>(dst + lane * 8) = make_uint4(o[0], o[1], o[2], o[3]);
            *reinterpret_cast<uint4*>(dst + 256 + lane * 8) = make_uint4(o[4], o[5], o[6], o[7]);
            *reinterpret_cast<uint4*>(&tile[warp * 2 + r][lane * 8]) = make_uint4(o[0], o[1], o[2], o[3]);
            *reinterpret_cast<uint4*>(&tile[warp * 2 + r][256 + lane * 8]) = make_uint4(o[4], o[5], o[6], o[7]);
        }
    } else {
        const int cc_ = warp - 8, dd = blockIdx.x * CV_CH + cc_;
        float4* sc = reinterpret_cast<float4*>(smem + cc_ * CV_EARLY + CV_O_CONST);
        __nv_bfloat16 pr[4][6];
#pragma unroll
        for (int j = 0; j < 4; j++) {
            const size_t off = (size_t)dd * NS_ + lane + 32 * j;
            pr[j][0] = A_re[off]; pr[j][1] = A_im[off]; pr[j][2] = B_re[off]; pr[j][3] = B_im[off]; pr[j][4] = C_re[off]; pr[j][5] = C_im[off];
        }
        const float dt = bf16_round(expf(__bfloat162float(log_dt[dd])));
        float tail = 0.f;
#pragma unroll
        for (int j = 0; j < 4; j++) {
            const float ar = dt * __bfloat162float(pr[j][0]), ai = dt * __bfloat162float(pr[j][1]);
            const cplx db = {dt * __bfloat162float(pr[j][2]), dt * __bfloat162float(pr[j][3])};
            const cplx cc = {__bfloat162float(pr[j][4]), __bfloat162float(pr[j][5])};
            const cplx cb = cmul(cc, db);
            const float ar2 = ar * 1.4426950408889634f, ai2 = ai * 0.15915494309189535f;
            const cplx e8 = cexp_m(ar2, ai2, 8.f), e128 = cexp_m(ar2, ai2, 128.f);
            const cplx cb8 = cmul(cb, e8);
            const cplx e256 = cexp_m(ar2, ai2, 256.f), e512 = cexp_m(ar2, ai2, 512.f), e1024 = cexp_m(ar2, ai2, 1024.f);
            const cplx c256 = cmul(cb, e256), c512 = cmul(cb, e512), c1024 = cmul(cb, e1024);
            const cplx c768 = cmul(c512, e256), c1280 = cmul(c1024, e256), c1536 = cmul(c1024, e512);
            const cplx c1792 = cmul(c1536, e256);
            tail += cmul(c1024, e1024).r;
            float4* c = sc + (lane + 32 * j) * 6;
            c[0] = make_float4(ar2, ai2, cb.r, cb.i);
            c[1] = make_float4(e128.r, e128.i, cb8.r, cb8.i);
            c[2] = make_float4(c256.r, c256.i, e8.r, e8.i);
            c[3] = make_float4(c512.r, c512.i, c768.r, c768.i);
            c[4] = make_float4(c1024.r, c1024.i, c1280.r, c1280.i);
            c[5] = make_float4(c1536.r, c1536.i, c1792.r, c1792.i);
        }
#pragma unroll
        for (int o = 16; o > 0; o >>= 1) tail += __shfl_xor_sync(0xffffffffu, tail, o);
        if (lane == 0) {
            float* kp = reinterpret_cast<float*>(smem + cc_ * CV_EARLY + CV_O_KP);
            kp[640] = tail; kp[648 + 640] = 0.f; kp[1296 + 640] = 0.f;
        }
    }
    __syncthreads();
    if (threadIdx.x == 0) STAMP(0, 3);
#pragma unroll
    for (int rep = 0; rep < 2; rep++) {
        const int c = threadIdx.x + 384 * rep;
        if (c < D_) {
            uint32_t ot[8];
#pragma unroll
            for (int i = 0; i < 8; i++) {
                uint32_t lo = *reinterpret_cast<const uint16_t*>(&tile[2 * i][c]);
                uint32_t hi = *reinterpret_cast<const uint16_t*>(&tile[2 * i + 1][c]);
                ot[i] = lo | (hi << 16);
            }
            __nv_bfloat16* dT = g_xnT + (size_t)c * L_ + blockIdx.x * LN_ROWS;
            *reinterpret_cast<uint4*>(dT) = make_uint4(ot[0], ot[1], ot[2], ot[3]);
            *reinterpret_cast<uint4*>(dT + 8) = make_uint4(ot[4], ot[5], ot[6], ot[7]);
        }
    }
    if (threadIdx.x < 336) {
        const int m = threadIdx.x / 112, i = threadIdx.x - m * 112;
        const char* wp = (const char*)(m == 0 ? wg : (m == 1 ? wu : wd));
        asm volatile("prefetch.global.L2 [%0];" ::"l"(wp + ((size_t)blockIdx.x * 112 + i) * 128));
    }
    __syncthreads();
    if (threadIdx.x == 0) STAMP(1, 1);
    {
        float acc[5][4];
#pragma unroll
        for (int i = 0; i < 5; i++) { acc[i][0] = acc[i][1] = acc[i][2] = acc[i][3] = 0.f; }
        const float gf = (float)g;
        const int src4 = ((g & 3) << 2) | t;
#pragma unroll 2
        for (int s = w; s < 32; s += 3) {
            if (s == 17 && threadIdx.x == 352) asm volatile("red.release.gpu.global.add.u32 [%0], 1;" ::"l"(&g_ln_count) : "memory");
            const float4* c = s_const + (s * 4 + t) * 6;
            const float4 k0 = c[0], k1 = c[1], k2 = c[2];
            const float2 k3 = reinterpret_cast<const float2*>(c + 3)[g >> 2];
            const float2 k4 = reinterpret_cast<const float2*>(c + 4)[g >> 1];
            const cplx cb = {k0.z, k0.w}, e128 = {k1.x, k1.y}, cb8 = {k1.z, k1.w}, c256 = {k2.x, k2.y}, e8 = {k2.z, k2.w};
            const cplx c2 = {k3.x, k3.y}, c3 = {k4.x, k4.y};
            const cplx p1 = cexp_m(k0.x, k0.y, gf);
            const cplx p2 = csq(p1), p4 = csq(p2);
            const cplx r16a = csq(csq(p4));
            cplx q4;
            q4.r = __shfl_sync(0xffffffffu, p4.r, src4);
            q4.i = __shfl_sync(0xffffffffu, p4.i, src4);
            const cplx r16b = cmul(r16a, e128);
            const cplx f0a = cmul(cb, p1), f0b = cmul(cb8, p1), f1 = cmul(c256, p2), f2 = cmul(c2, q4);
            cplx f3 = cmul(c3, e8);
            if (!(g & 1)) f3 = c3;
            const uint32_t a0 = to_tf32(r16a.r), a1 = to_tf32(r16b.r), a2 = to_tf32(-r16a.i), a3 = to_tf32(-r16b.i);
            mma_tf32(acc[0], a0, a1, a2, a3, to_tf32(f0a.r), to_tf32(f0a.i));
            mma_tf32(acc[1], a0, a1, a2, a3, to_tf32(f0b.r), to_tf32(f0b.i));
            mma_tf32(acc[2], a0, a1, a2, a3, to_tf32(f1.r), to_tf32(f1.i));
            mma_tf32(acc[3], a0, a1, a2, a3, to_tf32(f2.r), to_tf32(f2.i));
            mma_tf32(acc[4], a0, a1, a2, a3, to_tf32(f3.r), to_tf32(f3.i));
        }
        float* kv = s_kp + w * 648;
#pragma unroll
        for (int hh = 0; hh < 2; hh++) {
            const int i = g + 8 * hh;
            *reinterpret_cast<float2*>(kv + 16 * i + 2 * t) = make_float2(acc[0][2 * hh], acc[0][2 * hh + 1]);
            *reinterpret_cast<float2*>(kv + 16 * i + 8 + 2 * t) = make_float2(acc[1][2 * hh], acc[1][2 * hh + 1]);
            *reinterpret_cast<float2*>(kv + 256 + 8 * i + 2 * t) = make_float2(acc[2][2 * hh], acc[2][2 * hh + 1]);
            *reinterpret_cast<float2*>(kv + 384 + 64 * (t >> 1) + 2 * (t & 1) + 4 * i) = make_float2(acc[3][2 * hh], acc[3][2 * hh + 1]);
            *reinterpret_cast<float2*>(kv + 512 + 32 * t + 2 * i) = make_float2(acc[4][2 * hh], acc[4][2 * hh + 1]);
        }
    }
    named_bar(bar_id, 96);
    if (threadIdx.x == 0) STAMP(1, 2);
#pragma unroll
    for (int i = 0; i < 7; i++) {
        const int idx = tc + 96 * i;
        if (idx < 641) s_kp[idx] = (s_kp[idx] + s_kp[648 + idx]) + s_kp[1296 + idx];
    }
    named_bar(bar_id, 96);
    {
        auto kdir = [&](int l) -> float {
            if (l < 0 || l > 514) return 0.f;
            const int idx = (l < 256) ? l : (l > 512 ? 384 : 128 + ((l + ((l >> 1) & 1)) >> 1));
            return s_kp[idx];
        };
#pragma unroll
        for (int i = 0; i < 6; i++) {
            const int e = tc + 96 * i;
            s_q[e] = pack_bf16(kdir(e - 16), kdir(e - 17));
        }
        if (tc < 64) {
            const int xx = 1008 + tc;
            const float k1024 = s_kp[512];
            s_q4[tc] = pack_bf16((xx == 1027 || xx == 1028) ? k1024 : 0.f, (xx == 1028 || xx == 1029) ? k1024 : 0.f);
        }
#pragma unroll
        for (int i = 0; i < 3; i++) {
            const int e = tc + 96 * i;
            if (e < 256) {
                const int a = e >> 6, ii = (e & 63) - 16;
                const int b = 385 + (a >> 1) + 2 * (a & 1);
                const float v0 = (ii >= 0 && ii < 32) ? s_kp[b + 4 * ii] : 0.f;
                const float v1 = (ii >= 1 && ii < 33) ? s_kp[b + 4 * (ii - 1)] : 0.f;
                s_q2[e] = pack_bf16(v0, v1);
            }
        }
#pragma unroll
        for (int a = 0; a < 2; a++) {
            const int jj = tc - 16;
            const float v0 = (jj >= 0 && jj < 64) ? s_kp[513 + a + 2 * jj] : 0.f;
            const float v1 = (jj >= 1 && jj < 65) ? s_kp[513 + a + 2 * (jj - 1)] : 0.f;
            s_q3[96 * a + tc] = pack_bf16(v0, v1);
        }
    }
    if (threadIdx.x == 0) STAMP(1, 3);
    if (threadIdx.x == 0) {
        unsigned int v = 0;
        for (int spin = 0; spin < (1 << 22); spin++) {
            asm volatile("ld.acquire.gpu.global.u32 %0, [%1];" : "=r"(v) : "l"(&g_ln_count) : "memory");
            if (v >= gridDim.x) break;
        }
    }
    fence_async_smem();
    __syncthreads();
    if (threadIdx.x == 0) STAMP(1, 4);
    prefetch_fn();
    {
        if (tc < 16) *reinterpret_cast<uint4*>(s_u + tc * 8) = make_uint4(0, 0, 0, 0);
        const uint4* src = reinterpret_cast<const uint4*>(g_xnT + (size_t)d * L_);
        uint4 v[3];
#pragma unroll
        for (int i = 0; i < 3; i++) if (tc + 96 * i < 256) v[i] = src[tc + 96 * i];
#pragma unroll
        for (int i = 0; i < 3; i++) if (tc + 96 * i < 256) *reinterpret_cast<uint4*>(s_u + 128 + (tc + 96 * i) * 8) = v[i];
        if (tc < 2) *reinterpret_cast<uint4*>(base + (tc ? CV_O_W5 : CV_O_W3)) = make_uint4(0, 0, 0, 0);
    }
    named_bar(bar_id, 96);
    if (w == 2) {
#pragma unroll 2
      for (int rep = 0; rep < 6; rep++) {
        const int m = lane + 32 * rep;
        float P[30];
        const uint4* up = reinterpret_cast<const uint4*>(s_u + 128 + 8 * m - 24);
        P[0] = 0.f;
#pragma unroll
        for (int c4 = 0; c4 < 4; c4++) {
            const uint4 v = up[c4];
            const uint32_t ww[4] = {v.x, v.y, v.z, v.w};
#pragma unroll
            for (int j = 0; j < 4; j++) {
                const int k = c4 * 8 + 2 * j;
                if (k + 1 <= 29) P[k + 1] = P[k] + bf_lo(ww[j]);
                if (k + 2 <= 29) P[k + 2] = P[k + 1] + bf_hi(ww[j]);
            }
        }
        uint32_t o3[4], o5[4], o7[4], o9[4];
#pragma unroll
        for (int j = 0; j < 4; j++) {
            const int i = 2 * j;
            o3[j] = pack_bf16(P[i + 22] - P[i + 19], P[i + 23] - P[i + 20]);
            o5[j] = pack_bf16(P[i + 19] - P[i + 14], P[i + 20] - P[i + 15]);
            o7[j] = pack_bf16(P[i + 20] - P[i + 13], P[i + 21] - P[i + 14]);
            o9[j] = pack_bf16(P[i + 13] - P[i + 4], P[i + 14] - P[i + 5]);
        }
        *reinterpret_cast<uint4*>(base + CV_O_W3 + 16 + m * 16) = make_uint4(o3[0], o3[1], o3[2], o3[3]);
        *reinterpret_cast<uint4*>(base + CV_O_W5 + 16 + m * 16) = make_uint4(o5[0], o5[1], o5[2], o5[3]);
        if (m < 128) {
            *reinterpret_cast<uint4*>(base + CV_O_W7 + m * 16) = make_uint4(o7[0], o7[1], o7[2], o7[3]);
            *reinterpret_cast<uint4*>(base + CV_O_W9 + m * 16) = make_uint4(o9[0], o9[1], o9[2], o9[3]);
        }
    }
      named_bar(bar_id, 96);
      return;
    }
    if (threadIdx.x == 0) STAMP(1, 5);
    const int hb = w;
    float acc[16][4];
#pragma unroll
    for (int i = 0; i < 16; i++) { acc[i][0] = acc[i][1] = acc[i][2] = acc[i][3] = 0.f; }
    const uint32_t sb_addr = smem_u32(base);
    const int mi = lane >> 3, rowi = lane & 7;
#pragma unroll 1
    for (int rr = 0; rr < 4; rr++) {
        const int r = 4 * hb + rr;
        uint32_t ub[16][2];
        {
            const uint32_t addr = sb_addr + CV_O_U + (uint32_t)((128 + 16 * (8 * (mi >> 1) + rowi - r) + 8 * (mi & 1)) * 2);
#pragma unroll
            for (int j = 0; j < 16; j += 2) ldsm_x4(addr + (uint32_t)(j * 256), ub[j][0], ub[j][1], ub[j + 1][0], ub[j + 1][1]);
        }
        const uint32_t* qp = s_q + 16 + 16 * r + g - 2 * t;
        uint32_t af[4][3];
#pragma unroll
        for (int q = 0; q < 4; q++) { af[q][0] = qp[128 * q]; af[q][1] = qp[128 * q + 8]; af[q][2] = qp[128 * q - 8]; }
#pragma unroll
        for (int q = 0; q < 4; q++) {
#pragma unroll
            for (int nt = q; nt < 16; nt++) mma_bf16(acc[nt], af[q][0], af[q][1], af[q][2], af[q][0], ub[nt - q][0], ub[nt - q][1]);
        }
        if (r < 2) {
            {
                const uint32_t a0 = qp[512], a1 = qp[520], a2 = qp[504];
#pragma unroll
                for (int nt = 4; nt < 16; nt++) mma_bf16(acc[nt], a0, a1, a2, a0, ub[nt - 4][0], ub[nt - 4][1]);
            }
            {
                const uint32_t* q4p = s_q4 + 16 + 16 * r + g - 2 * t;
                const uint32_t a0 = q4p[0], a1 = q4p[8], a2 = q4p[-8];
#pragma unroll
                for (int nt = 8; nt < 16; nt++) mma_bf16(acc[nt], a0, a1, a2, a0, ub[nt - 8][0], ub[nt - 8][1]);
            }
        }
    }
    named_bar(bar_id, 96);
#pragma unroll 1
    for (int a = hb; a <= 3 * hb; a++) {
        uint32_t bq[7];
        const uint32_t* q2 = s_q2 + a * 64 + 16 + g - 2 * t - 32;
#pragma unroll
        for (int dlt = 3; dlt <= 9; dlt++) bq[dlt - 3] = q2[8 * dlt];
        const uint32_t addr = sb_addr + ((a >> 1) ? CV_O_W5 : CV_O_W3) + (uint32_t)((8 + 16 * (8 * (mi >> 1) + rowi) + 8 * (mi & 1) - 8 * (a & 1)) * 2);
        uint32_t aa[6][4];
#pragma unroll
        for (int kp = 0; kp < 6; kp++) ldsm_x4_t(addr + kp * 512, aa[kp][0], aa[kp][1], aa[kp][2], aa[kp][3]);
#pragma unroll
        for (int kp = 0; kp < 6; kp++) {
#pragma unroll
            for (int dlt = 4; dlt <= 9; dlt++) {
                if (2 * kp + dlt < 16) mma_bf16(acc[2 * kp + dlt], aa[kp][0], aa[kp][1], aa[kp][2], aa[kp][3], bq[dlt - 3], bq[dlt - 4]);
            }
        }
    }
    if (hb == 0) {
#pragma unroll 1
        for (int a = 0; a < 2; a++) {
            uint32_t bq[9];
            const uint32_t* q3 = s_q3 + a * 96 + 16 + g - 2 * t - 64;
#pragma unroll
            for (int dlt = 7; dlt <= 15; dlt++) bq[dlt - 7] = q3[8 * dlt];
            const uint32_t addr = sb_addr + (a ? CV_O_W9 : CV_O_W7) + (uint32_t)((16 * (8 * (mi >> 1) + rowi) + 8 * (mi & 1)) * 2);
            uint32_t aa[4][4];
#pragma unroll
            for (int kp = 0; kp < 4; kp++) ldsm_x4_t(addr + kp * 512, aa[kp][0], aa[kp][1], aa[kp][2], aa[kp][3]);
#pragma unroll
            for (int kp = 0; kp < 4; kp++) {
#pragma unroll
                for (int dlt = 8; dlt <= 15; dlt++) {
                    if (2 * kp + dlt < 16) mma_bf16(acc[2 * kp + dlt], aa[kp][0], aa[kp][1], aa[kp][2], aa[kp][3], bq[dlt - 7], bq[dlt - 8]);
                }
            }
        }
    }
    if (threadIdx.x == 0) STAMP(1, 6);
    named_bar(bar_id, 64);
    {
        float4* xch = reinterpret_cast<float4*>(base + CV_O_W3) + hb * 256;
        if (hb) {
#pragma unroll
            for (int i = 0; i < 8; i++) xch[i * 32 + lane] = make_float4(acc[i][0], acc[i][1], acc[i][2], acc[i][3]);
#pragma unroll
            for (int i = 0; i < 8; i++) { acc[i][0] = acc[8 + i][0]; acc[i][1] = acc[8 + i][1]; acc[i][2] = acc[8 + i][2]; acc[i][3] = acc[8 + i][3]; }
        } else {
#pragma unroll
            for (int i = 0; i < 8; i++) xch[i * 32 + lane] = make_float4(acc[8 + i][0], acc[8 + i][1], acc[8 + i][2], acc[8 + i][3]);
        }
    }
    named_bar(bar_id, 64);
    if (threadIdx.x == 0) STAMP(1, 10);
    {
        const float4* xch = reinterpret_cast<const float4*>(base + CV_O_W3) + (hb ^ 1) * 256 + lane;
        const float dsk = __bfloat162float(p_dsk);
        uint16_t* stg = reinterpret_cast<uint16_t*>(base + CV_O_Q);
        const uint16_t* uu = reinterpret_cast<const uint16_t*>(s_u) + 128;
#pragma unroll
        for (int i = 0; i < 8; i++) {
            const float4 p0 = xch[i * 32];
            const float y[4] = {acc[i][0] + p0.x, acc[i][1] + p0.y, acc[i][2] + p0.z, acc[i][3] + p0.w};
            const int nt = 8 * hb + i;
#pragma unroll
            for (int e = 0; e < 4; e++) {
                const int tau = 16 * (8 * nt + 2 * t + (e & 1)) + g + 8 * (e >> 1);
                const float sv = bf16_round(y[e]) + bf16_round(__uint_as_float((uint32_t)uu[tau] << 16) * dsk);
                stg[tau] = (uint16_t)(__float_as_uint(bf16_round(sv)) >> 16);
            }
        }
        __syncwarp();
        if (threadIdx.x == 0) STAMP(1, 11);
        uint4* dst = reinterpret_cast<uint4*>(g_sT + (size_t)d * L_ + hb * 1024);
        const uint4* srcp = reinterpret_cast<const uint4*>(stg + hb * 1024);
#pragma unroll
        for (int i = 0; i < 4; i++) dst[i * 32 + lane] = srcp[i * 32 + lane];
    }
}

__device__ __forceinline__ uint32_t cluster_rank() { uint32_t r; asm volatile("mov.u32 %0, %%cluster_ctarank;" : "=r"(r)); return r; }
__device__ __forceinline__ void cluster_sync_all() {
    asm volatile("barrier.cluster.arrive.release.aligned;\nbarrier.cluster.wait.acquire.aligned;" ::: "memory");
}
__device__ __forceinline__ void mbar_arrive_remote(uint32_t bar, uint32_t cta) {
    asm volatile("{\n.reg .b32 ra;\nmapa.shared::cluster.u32 ra, %0, %1;\n"
                 "mbarrier.arrive.shared::cluster.b64 _, [ra];\n}\n" ::"r"(bar), "r"(cta) : "memory");
}
__device__ __forceinline__ void tma_load_2d_mc(uint32_t dst, const CUtensorMap* tm, int c0, int c1, uint32_t bar, uint16_t mask) {
    asm volatile(
        "cp.async.bulk.tensor.2d.shared::cluster.global.mbarrier::complete_tx::bytes.multicast::cluster [%0], [%1, {%3, %4}], [%2], %5;"
        ::"r"(dst), "l"((uint64_t)tm), "r"(bar), "r"(c0), "r"(c1), "h"(mask) : "memory");
}
__device__ __forceinline__ void tma_store_2d(const CUtensorMap* tm, uint32_t src, int c0, int c1) {
    asm volatile("cp.async.bulk.tensor.2d.global.shared::cta.bulk_group [%0, {%2, %3}], [%1];"
                 ::"l"((uint64_t)tm), "r"(src), "r"(c0), "r"(c1) : "memory");
}
__device__ __forceinline__ void bulk_commit() { asm volatile("cp.async.bulk.commit_group;" ::: "memory"); }
template <int N> __device__ __forceinline__ void bulk_wait_read() { asm volatile("cp.async.bulk.wait_group.read %0;" ::"n"(N) : "memory"); }
template <int N> __device__ __forceinline__ void bulk_wait() { asm volatile("cp.async.bulk.wait_group %0;" ::"n"(N) : "memory"); }
__device__ __forceinline__ void stmatrix_x4(uint32_t addr, uint32_t r0, uint32_t r1, uint32_t r2, uint32_t r3) {
    asm volatile("stmatrix.sync.aligned.m8n8.x4.shared.b16 [%0], {%1,%2,%3,%4};" ::"r"(addr), "r"(r0), "r"(r1), "r"(r2), "r"(r3) : "memory");
}

constexpr int G1_STAGES = 5;
constexpr int G1_A_BYTES = 8 * 16384;
constexpr int G1_B_STAGE = 16384;
constexpr int G1_STG = 8 * 1024;
constexpr int G1_SMEM = G1_A_BYTES + G1_STAGES * G1_B_STAGE + G1_STG + 1024 + 256;
constexpr int G1_ITERS = 32;

__device__ __forceinline__ void tma_load_3d(uint32_t dst, const CUtensorMap* tm, int c0, int c1, int c2, uint32_t bar) {
    asm volatile(
        "cp.async.bulk.tensor.3d.shared::cluster.global.mbarrier::complete_tx::bytes [%0], [%1, {%3, %4, %5}], [%2];"
        ::"r"(dst), "l"((uint64_t)tm), "r"(bar), "r"(c0), "r"(c1), "r"(c2) : "memory");
}

__device__ __forceinline__ void tma_load_3d_mc(uint32_t dst, const CUtensorMap* tm, int c0, int c1, int c2, uint32_t bar, uint16_t mask) {
    asm volatile(
        "cp.async.bulk.tensor.3d.shared::cluster.global.mbarrier::complete_tx::bytes.multicast::cluster [%0], [%1, {%3, %4, %5}], [%2], %6;"
        ::"r"(dst), "l"((uint64_t)tm), "r"(bar), "r"(c0), "r"(c1), "r"(c2), "h"(mask) : "memory");
}

__device__ __forceinline__ float gelu_tanh(float x) {
    float u = x * (0.7978845608028654f + 0.035677408136300125f * x * x);
    float t; asm("tanh.approx.f32 %0, %1;" : "=f"(t) : "f"(u));
    float hx = 0.5f * x;
    return fmaf(hx, t, hx);
}
__device__ __forceinline__ uint32_t geglu_pair(uint32_t g2, uint32_t u2) {
    uint32_t a = pack_bf16(gelu_tanh(bf_lo(g2)), gelu_tanh(bf_hi(g2)));
    uint32_t r; asm("mul.rn.bf16x2 %0, %1, %2;" : "=r"(r) : "r"(a), "r"(u2));
    return r;
}

constexpr int G2_STAGES = 5;
constexpr int G2_STAGE = 16384 + 16384;
constexpr int G2_XCH = 32768;
constexpr int G2_EPI = 16384 + 16384;
constexpr int G2_SMEM = G2_STAGES * G2_STAGE + G2_XCH + G2_EPI + 1024 + 256;
constexpr int G2_KB = F_ / 64 / 2;

constexpr int MG_BAR_OFF = G2_STAGES * G2_STAGE + G2_XCH + G2_EPI;
constexpr int MG_SMEM = MG_BAR_OFF + 512 + 1024;
static_assert(MG_BAR_OFF == 229376 && G1_A_BYTES + G1_STAGES * G1_B_STAGE + G1_STG <= MG_BAR_OFF, "smem layout");

__device__ __forceinline__ void fence_async_all() { asm volatile("fence.proxy.async.global;" ::: "memory"); }
__device__ __forceinline__ void spin_until(const unsigned int* p, unsigned int target) {
    unsigned int v = 0;
    for (int spin = 0; spin < (1 << 22); spin++) {
        asm volatile("ld.acquire.gpu.global.u32 %0, [%1];" : "=r"(v) : "l"(p) : "memory");
        if (v >= target) break;
    }
}

struct MegaParams {
    const __nv_bfloat16 *x, *A_re, *A_im, *B_re, *B_im, *C_re, *C_im, *log_dt, *Dskip, *wg, *wu, *wd;
};

__global__ void __launch_bounds__(384, 1) mega_kernel(const __grid_constant__ MegaParams P,
                                                       const __grid_constant__ CUtensorMap tm_xn,
                                                       const __grid_constant__ CUtensorMap tm_wg4,
                                                       const __grid_constant__ CUtensorMap tm_wu4,
                                                       const __grid_constant__ CUtensorMap tm_wg3,
                                                       const __grid_constant__ CUtensorMap tm_wu3,
                                                       const __grid_constant__ CUtensorMap tm_h,
                                                       const __grid_constant__ CUtensorMap tm_wd,
                                                       const __grid_constant__ CUtensorMap tm_x,
                                                       const __grid_constant__ CUtensorMap tm_sT,
                                                       const __grid_constant__ CUtensorMap tm_out) {
    if (threadIdx.x == 0) STAMP(1, 0);
    extern __shared__ uint8_t smem_raw[];
    const uint32_t sraw = smem_u32(smem_raw);
    const uint32_t sbase = (sraw + 1023) & ~1023u;
    uint8_t* smem = smem_raw + (sbase - sraw);
    const int warp = threadIdx.x >> 5, lane = threadIdx.x & 31;
    const uint32_t sA = sbase, sB = sbase + G1_A_BYTES, sStg = sB + G1_STAGES * G1_B_STAGE;
    const uint32_t sXch = sbase + G2_STAGES * G2_STAGE, sX = sXch + G2_XCH, sS = sX + 16384;
    const uint32_t sBar = sbase + MG_BAR_OFF;
    const uint32_t bar_a = sBar, bar_full = sBar + 64, bar_empty = bar_full + 8 * G1_STAGES;
    const uint32_t bar_full2 = bar_empty + 8 * G1_STAGES, bar_empty2 = bar_full2 + 8 * G2_STAGES;
    const uint32_t bar_epi = bar_empty2 + 8 * G2_STAGES, bar_xch = bar_epi + 8, bar_g1done = bar_xch + 8, bar_g1mma = bar_g1done + 8, bar_peer = bar_g1mma + 8;
    const uint32_t kh = blockIdx.x & 1;
    const int rb1 = ((blockIdx.x >> 4) << 1) + (int)kh, cj = (blockIdx.x >> 1) & 7;
    const int rb = blockIdx.x >> 3;
    const int nb = (blockIdx.x >> 1) & 3;
    const int col_fin = nb * 128 + kh * 64;

    if (threadIdx.x == 0) {
        for (int i = 0; i < 8; i++) mbar_init(bar_a + 8 * i, 1);
        for (int i = 0; i < G1_STAGES; i++) { mbar_init(bar_full + 8 * i, 1); mbar_init(bar_empty + 8 * i, 16); }
        for (int i = 0; i < G2_STAGES; i++) { mbar_init(bar_full2 + 8 * i, 1); mbar_init(bar_empty2 + 8 * i, 8); }
        mbar_init(bar_epi, 1);
        mbar_init(bar_xch, 1);
        mbar_init(bar_g1done, 8);
        mbar_init(bar_g1mma, 8);
        mbar_init(bar_peer, 1);
        asm volatile("fence.mbarrier_init.release.cluster;" ::: "memory");
        mbar_expect_tx(bar_xch, G2_XCH);
    }
    if (warp == 11 && lane == 0) {
        prefetch_tmap(&tm_wg4); prefetch_tmap(&tm_wu4); prefetch_tmap(&tm_xn); prefetch_tmap(&tm_wg3); prefetch_tmap(&tm_wu3);
        prefetch_tmap(&tm_wd); prefetch_tmap(&tm_h); prefetch_tmap(&tm_x); prefetch_tmap(&tm_sT); prefetch_tmap(&tm_out);
    }
    asm volatile("barrier.cluster.arrive.release.aligned;" ::: "memory");

    auto g1_prefetch = [&]() {
        if (warp == 8 && lane == 0) {
            fence_async_all();
            mbar_expect_tx(bar_full, 16384);
            tma_load_3d(sB, &tm_wg4, 0, 0, cj * 7, bar_full);
            tma_load_3d(sB + 8192, &tm_wu4, 0, 0, cj * 7, bar_full);
            for (int k = 0; k < 8; k++) {
                mbar_expect_tx(bar_a + 8 * k, 16384);
                tma_load_2d(sA + k * 16384, &tm_xn, k * 64, rb1 * 128, bar_a + 8 * k);
            }
        }
    };
    front_phase(g1_prefetch, smem, P.x, P.A_re, P.A_im, P.B_re, P.B_im, P.C_re, P.C_im, P.log_dt, P.Dskip, P.wg, P.wu, P.wd);
    fence_async_smem();
    asm volatile("barrier.cluster.wait.acquire.aligned;" ::: "memory");
    __syncthreads();
    if (threadIdx.x == 352) mbar_arrive_remote(bar_peer, kh ^ 1);
    if (threadIdx.x == 0) STAMP(1, 7);

    if (warp >= 8) {
        asm volatile("setmaxnreg.dec.sync.aligned.u32 40;");
        if (warp == 11) {
            if (lane == 0) asm volatile("red.release.gpu.global.add.u32 [%0], 1;" ::"l"(&g_conv_count) : "memory");
            named_bar(3, 288);
            if (lane == 0) asm volatile("red.release.gpu.global.add.u32 [%0], 1;" ::"l"(&g_h_count[rb1]) : "memory");
            named_bar(9, 288);
            if (lane == 0) asm volatile("red.release.gpu.global.add.u32 [%0], 1;" ::"l"(&g_h_count[16 + rb1]) : "memory");
        } else if (lane == 0) {
            const int pw = warp - 8;
            mbar_wait(bar_peer, 0);
            for (int it = 1 + pw; it < G1_ITERS; it += 3) {
                const int s = it % G1_STAGES, kb = it & 15;
                if (it >= G1_STAGES) mbar_wait(bar_empty + 8 * s, ((it / G1_STAGES) - 1) & 1);
                const uint32_t dst = sB + s * G1_B_STAGE;
                if (it < 16) {
                    mbar_expect_tx(bar_full + 8 * s, 16384);
                    tma_load_3d_mc(dst + kh * 8192, kh ? &tm_wu4 : &tm_wg4, 0, kb * 32, cj * 7, bar_full + 8 * s, 3);
                } else {
                    mbar_expect_tx(bar_full + 8 * s, 12288);
                    tma_load_3d_mc(dst + kh * 6144, kh ? &tm_wu3 : &tm_wg3, 0, kb * 32, cj * 7 + 4, bar_full + 8 * s, 3);
                }
            }
            const int k0 = kh * G2_KB;
            auto kblk = [&](int it) -> int {
                const unsigned long long tab = 0xDCA96532B87410ull;
                return k0 + (int)((tab >> (4 * it)) & 15);
            };
            mbar_wait(bar_g1mma, 0);
            if (pw == 2) {
                mbar_expect_tx(bar_epi, G2_EPI);
                tma_load_2d(sX, &tm_x, col_fin, rb * 128, bar_epi);
            }
            spin_until(&g_h_count[rb], 8);
            fence_async_all();
            if (pw == 0) STAMP(3, 1);
            for (int it = pw; it < G2_KB; it += 3) {
                const int s = (it + 1) % G2_STAGES;
                if (it == 4) mbar_wait(bar_g1done, 0);
                if (it >= G2_STAGES) mbar_wait(bar_empty2 + 8 * s, ((it / G2_STAGES) - 1) & 1);
                if (it >= 6 && it < 9) { spin_until(&g_h_count[16 + rb], 8); fence_async_all(); }
                mbar_expect_tx(bar_full2 + 8 * s, G2_STAGE);
                const int kb = kblk(it);
                tma_load_3d(sbase + s * G2_STAGE + 16384, &tm_wd, 0, kb * 64, nb * 2, bar_full2 + 8 * s);
                tma_load_2d(sbase + s * G2_STAGE, &tm_h, kb * 64, rb * 128, bar_full2 + 8 * s);
                if (it == 2) {
                    spin_until(&g_conv_count, gridDim.x);
                    fence_async_all();
                    tma_load_2d(sS, &tm_sT, rb * 128, col_fin, bar_epi);
                    tma_load_2d(sS + 8192, &tm_sT, rb * 128 + 64, col_fin, bar_epi);
                }
            }
        }
    } else {
        asm volatile("setmaxnreg.inc.sync.aligned.u32 232;");
        const int wg = __shfl_sync(0xffffffffu, (int)(threadIdx.x >> 7), 0);
        {
        float r[160];
        const int row0 = rb1 * 128 + wg * 64 + (warp & 3) * 16;
        const uint64_t descA = make_desc(sA + wg * 8192, 16, 1024);
        const uint64_t descB = make_desc(sB, 2048, 512, 2);
        const uint32_t stg = sStg + warp * 1024;
        const uint32_t st_off = (uint32_t)(((lane & 7) + ((lane >> 3) & 1) * 8) * 32 + (lane >> 4) * 16);
        __nv_bfloat16* hrow = g_h + (size_t)(row0 + (lane >> 1)) * F_ + (lane & 1) * 8 + cj * 224;
#pragma unroll
        for (int kb = 0; kb < 16; kb++) {
            const int it = kb, s = it % G1_STAGES;
            if ((kb & 1) == 0) mbar_wait(bar_a + 8 * (kb >> 1), 0);
            mbar_wait(bar_full + 8 * s, (it / G1_STAGES) & 1);
            if (threadIdx.x == 0 && (it & 7) == 0) STAMP(2, 2 + it / 8);
            wgmma_fence();
            const uint64_t da = descA + (uint64_t)(((kb >> 1) * 16384 + (kb & 1) * 64) >> 4);
            const uint64_t db = descB + (uint64_t)((s * G1_B_STAGE) >> 4);
            wgmma_n256_k32(r, da, da + 2, db, db + 64, kb != 0);
            wgmma_commit();
            if (kb > 0) {
                wgmma_wait<1>();
                if (lane < 2) mbar_arrive_remote(bar_empty + 8 * ((it - 1) % G1_STAGES), lane);
            }
        }
        wgmma_wait<0>();
        if (lane < 2) mbar_arrive_remote(bar_empty + 8 * (15 % G1_STAGES), lane);
#pragma unroll
        for (int i = 0; i < 32; i++) r[128 + i] = __uint_as_float(pack_bf16(r[2 * i], r[2 * i + 1]));
#pragma unroll
        for (int i = 31; i >= 0; i--) r[96 + i] = __uint_as_float(pack_bf16(r[64 + 2 * i], r[65 + 2 * i]));
        uint32_t eo[4];
        uint4 pv = make_uint4(0, 0, 0, 0);
#pragma unroll
        for (int kb = 0; kb < 16; kb++) {
            const int it = 16 + kb, s = it % G1_STAGES;
            mbar_wait(bar_full + 8 * s, (it / G1_STAGES) & 1);
            if (threadIdx.x == 0 && (it & 7) == 0) STAMP(2, 2 + it / 8);
            wgmma_fence();
            const uint64_t da = descA + (uint64_t)(((kb >> 1) * 16384 + (kb & 1) * 64) >> 4);
            const uint64_t db = descB + (uint64_t)((s * G1_B_STAGE) >> 4);
            wgmma_n192(r, da, db, kb != 0);
            if (kb < 8) {
                eo[0] = geglu_pair(__float_as_uint(r[128 + 4 * kb]), __float_as_uint(r[96 + 4 * kb]));
                eo[1] = geglu_pair(__float_as_uint(r[129 + 4 * kb]), __float_as_uint(r[97 + 4 * kb]));
            }
            wgmma_n192(r, da + 2, db + 64, 1);
            wgmma_commit();
            if (kb >= 2 && kb < 10) *reinterpret_cast<uint4*>(hrow + (kb - 2) * 16) = pv;
            if (kb >= 1 && kb < 9) {
                __syncwarp();
                asm volatile("ld.shared.v4.u32 {%0,%1,%2,%3}, [%4];" : "=r"(pv.x), "=r"(pv.y), "=r"(pv.z), "=r"(pv.w)
                             : "r"(stg + ((kb - 1) & 1) * 512 + lane * 16));
            }
            if (kb < 8) {
                eo[2] = geglu_pair(__float_as_uint(r[130 + 4 * kb]), __float_as_uint(r[98 + 4 * kb]));
                eo[3] = geglu_pair(__float_as_uint(r[131 + 4 * kb]), __float_as_uint(r[99 + 4 * kb]));
                stmatrix_x4(stg + (kb & 1) * 512 + st_off, eo[0], eo[1], eo[2], eo[3]);
            }
            if (kb == 9) asm volatile("bar.arrive 3, 288;" ::: "memory");
            if (kb > 0 && it - 1 + G1_STAGES < G1_ITERS) {
                wgmma_wait<1>();
                if (lane < 2) mbar_arrive_remote(bar_empty + 8 * ((it - 1) % G1_STAGES), lane);
            }
        }
        wgmma_wait<0>();
        fence_async_smem();
        __syncwarp();
        if (lane == 0) mbar_arrive(bar_g1mma);
        if (threadIdx.x == 0) STAMP(2, 6);
        {
            uint32_t o[24];
#pragma unroll
            for (int i = 0; i < 24; i++) o[i] = geglu_pair(pack_bf16(r[2 * i], r[2 * i + 1]), pack_bf16(r[48 + 2 * i], r[49 + 2 * i]));
            named_bar(1 + wg, 128);
            const uint32_t fbuf = sA + ((warp & 3) >> 1) * 16384 + wg * 8192 + (warp & 1) * 4096;
#pragma unroll
            for (int jj = 0; jj < 6; jj++) stmatrix_x4(fbuf + jj * 512 + st_off, o[4 * jj], o[4 * jj + 1], o[4 * jj + 2], o[4 * jj + 3]);
            __syncwarp();
            uint4 v[6];
#pragma unroll
            for (int jj = 0; jj < 6; jj++)
                asm volatile("ld.shared.v4.u32 {%0,%1,%2,%3}, [%4];" : "=r"(v[jj].x), "=r"(v[jj].y), "=r"(v[jj].z), "=r"(v[jj].w)
                             : "r"(fbuf + jj * 512 + lane * 16));
#pragma unroll
            for (int jj = 0; jj < 6; jj++) *reinterpret_cast<uint4*>(hrow + 128 + jj * 16) = v[jj];
        }
        }
        fence_async_smem();
        __syncwarp();
        if (lane == 0) mbar_arrive(bar_g1done);
        asm volatile("bar.arrive 9, 288;" ::: "memory");
        if (threadIdx.x == 0) STAMP(2, 7);
        {
        const int g = lane >> 2, t = lane & 3;
        float acc[64];
        const uint64_t descA2 = make_desc(sbase + wg * 8192, 16, 1024);
        const uint64_t descB2 = make_desc(sbase + 16384, 8192, 1024);
#pragma unroll
        for (int it = 0; it < G2_KB; it++) {
            const int s = (it + 1) % G2_STAGES;
            mbar_wait(bar_full2 + 8 * s, (it / G2_STAGES) & 1);
            if (threadIdx.x == 0 && (it == 0 || it == 7)) STAMP(3, 2 + it / 7);
            wgmma_fence();
            {
                const uint64_t da = descA2 + (uint64_t)((s * G2_STAGE) >> 4);
                const uint64_t db = descB2 + (uint64_t)((s * G2_STAGE) >> 4);
                wgmma_n128_k64(acc, da, da + 2, da + 4, da + 6, db, db + 128, db + 256, db + 384, it != 0);
            }
            wgmma_commit();
            if (it > 0 && it - 1 + G2_STAGES < G2_KB) {
                wgmma_wait<1>();
                if (lane == 0) mbar_arrive(bar_empty2 + 8 * (it % G2_STAGES));
            }
        }
        const int lr = wg * 64 + (warp & 3) * 16 + g;
        uint32_t xv[16], sv[16];
        mbar_wait(bar_epi, 0);
#pragma unroll
        for (int j = 0; j < 8; j++) {
#pragma unroll
            for (int hh = 0; hh < 2; hh++) {
                const int r = lr + 8 * hh;
                asm volatile("ld.shared.u32 %0, [%1];" : "=r"(xv[2 * j + hh]) : "r"(sX + r * 128 + ((j ^ (r & 7)) << 4) + 4 * t));
                const int c0 = 8 * j + 2 * t;
                const uint32_t sa = sS + (r >> 6) * 8192 + (((r & 63) >> 3) << 4) + (r & 7) * 2;
                uint16_t s0r, s1r;
                asm volatile("ld.shared.u16 %0, [%1];" : "=h"(s0r) : "r"((sa + c0 * 128) ^ ((c0 & 7) << 4)));
                asm volatile("ld.shared.u16 %0, [%1];" : "=h"(s1r) : "r"((sa + (c0 + 1) * 128) ^ (((c0 + 1) & 7) << 4)));
                sv[2 * j + hh] = (uint32_t)s0r | ((uint32_t)s1r << 16);
            }
        }
        wgmma_wait<0>();
        if (threadIdx.x == 0) STAMP(3, 4);
        {
            uint32_t remote, rbar;
            asm volatile("mapa.shared::cluster.u32 %0, %1, %2;" : "=r"(remote) : "r"(sXch + threadIdx.x * 16), "r"(kh ^ 1));
            asm volatile("mapa.shared::cluster.u32 %0, %1, %2;" : "=r"(rbar) : "r"(bar_xch), "r"(kh ^ 1));
            if (kh == 0) {
#pragma unroll
                for (int i = 0; i < 8; i++)
                    asm volatile("st.async.shared::cluster.mbarrier::complete_tx::bytes.v4.f32 [%0], {%1,%2,%3,%4}, [%5];" ::"r"(remote + i * 4096),
                                 "f"(acc[32 + 4 * i]), "f"(acc[33 + 4 * i]), "f"(acc[34 + 4 * i]), "f"(acc[35 + 4 * i]), "r"(rbar) : "memory");
            } else {
#pragma unroll
                for (int i = 0; i < 8; i++)
                    asm volatile("st.async.shared::cluster.mbarrier::complete_tx::bytes.v4.f32 [%0], {%1,%2,%3,%4}, [%5];" ::"r"(remote + i * 4096),
                                 "f"(acc[4 * i]), "f"(acc[1 + 4 * i]), "f"(acc[2 + 4 * i]), "f"(acc[3 + 4 * i]), "r"(rbar) : "memory");
#pragma unroll
                for (int i = 0; i < 32; i++) acc[i] = acc[32 + i];
            }
        }
        if (threadIdx.x == 0) STAMP(3, 6);
        mbar_wait(bar_xch, 0);
        if (threadIdx.x == 0) STAMP(3, 7);
#pragma unroll
        for (int j = 0; j < 8; j++) {
            float4 o;
            asm volatile("ld.shared.v4.f32 {%0,%1,%2,%3}, [%4];" : "=f"(o.x), "=f"(o.y), "=f"(o.z), "=f"(o.w) : "r"(sXch + threadIdx.x * 16 + j * 4096));
            acc[4 * j] += o.x; acc[4 * j + 1] += o.y; acc[4 * j + 2] += o.z; acc[4 * j + 3] += o.w;
        }
#pragma unroll
        for (int i = 0; i < 16; i++) {
            float f0 = bf16_round(acc[2 * i]), f1 = bf16_round(acc[2 * i + 1]);
            float g0 = bf16_round(__fdividef(f0, 1.0f + __expf(-f0)));
            float g1 = bf16_round(__fdividef(f1, 1.0f + __expf(-f1)));
            float o0 = bf_lo(xv[i]) + bf16_round(bf_lo(sv[i]) * g0);
            float o1 = bf_hi(xv[i]) + bf16_round(bf_hi(sv[i]) * g1);
            xv[i] = pack_bf16(o0, o1);
        }
#pragma unroll
        for (int j = 0; j < 8; j++) {
#pragma unroll
            for (int hh = 0; hh < 2; hh++) {
                const int r = lr + 8 * hh;
                asm volatile("st.shared.u32 [%0], %1;" ::"r"(sX + r * 128 + ((j ^ (r & 7)) << 4) + 4 * t), "r"(xv[2 * j + hh]) : "memory");
            }
        }
        if (threadIdx.x == 0) STAMP(3, 9);
        fence_async_smem();
        __syncwarp();
        if (lane == 0) {
            tma_store_2d(&tm_out, sX + (wg * 64 + (warp & 3) * 16) * 128, col_fin, rb * 128 + wg * 64 + (warp & 3) * 16);
            bulk_commit();
            bulk_wait_read<0>();
        }
        }
        if (threadIdx.x == 0) STAMP(3, 5);
        named_bar(4, 256);
        if (threadIdx.x == 0) {
            const unsigned int old = atomicAdd(&g_done_count, 1u);
            if (old == gridDim.x - 1) {
                g_ln_count = 0; g_conv_count = 0; g_done_count = 0;
                for (int i = 0; i < 32; i++) g_h_count[i] = 0;
            }
        }
    }
}

typedef CUresult (*EncodeFn)(CUtensorMap*, CUtensorMapDataType, cuuint32_t, void*, const cuuint64_t*, const cuuint64_t*,
                             const cuuint32_t*, const cuuint32_t*, CUtensorMapInterleave, CUtensorMapSwizzle,
                             CUtensorMapL2promotion, CUtensorMapFloatOOBfill);

void make_map(EncodeFn fn, CUtensorMap* m, const void* ptr, uint64_t inner, uint64_t outer, uint32_t box_in, uint32_t box_out,
              CUtensorMapSwizzle swz = CU_TENSOR_MAP_SWIZZLE_128B) {
    cuuint64_t dims[2] = {inner, outer};
    cuuint64_t strides[1] = {inner * 2};
    cuuint32_t box[2] = {box_in, box_out};
    cuuint32_t es[2] = {1, 1};
    fn(m, CU_TENSOR_MAP_DATA_TYPE_BFLOAT16, 2, const_cast<void*>(ptr), dims, strides, box, es, CU_TENSOR_MAP_INTERLEAVE_NONE,
       swz, CU_TENSOR_MAP_L2_PROMOTION_L2_256B, CU_TENSOR_MAP_FLOAT_OOB_FILL_NONE);
}
void make_map3(EncodeFn fn, CUtensorMap* m, const void* ptr, uint64_t cols, uint64_t rows, uint32_t atom, uint32_t box_rows,
               uint32_t box_atoms, CUtensorMapSwizzle swz) {
    cuuint64_t dims[3] = {atom, rows, cols / atom};
    cuuint64_t strides[2] = {cols * 2, (cuuint64_t)atom * 2};
    cuuint32_t box[3] = {atom, box_rows, box_atoms};
    cuuint32_t es[3] = {1, 1, 1};
    fn(m, CU_TENSOR_MAP_DATA_TYPE_BFLOAT16, 3, const_cast<void*>(ptr), dims, strides, box, es, CU_TENSOR_MAP_INTERLEAVE_NONE,
       swz, CU_TENSOR_MAP_L2_PROMOTION_L2_256B, CU_TENSOR_MAP_FLOAT_OOB_FILL_NONE);
}

template <typename... Args>
void launch_pdl(void (*kern)(Args...), int grid, int block, int smem, bool pdl, int cluster, Args... args) {
    cudaLaunchConfig_t cfg = {};
    cfg.gridDim = dim3(grid); cfg.blockDim = dim3(block); cfg.dynamicSmemBytes = smem; cfg.stream = cudaStreamPerThread;
    cudaLaunchAttribute at[2];
    int n = 0;
    if (pdl) {
        at[n].id = cudaLaunchAttributeProgrammaticStreamSerialization;
        at[n].val.programmaticStreamSerializationAllowed = 1;
        n++;
    }
    if (cluster > 1) {
        at[n].id = cudaLaunchAttributeClusterDimension;
        at[n].val.clusterDim.x = cluster; at[n].val.clusterDim.y = 1; at[n].val.clusterDim.z = 1;
        n++;
    }
    cfg.attrs = at; cfg.numAttrs = n;
    cudaLaunchKernelEx(&cfg, kern, args...);
}

}

extern "C" void kernel_launch(void* const* d_in, const int* in_sizes, int n_in, void* d_out, int out_size) {
    const __nv_bfloat16* x = (const __nv_bfloat16*)d_in[0];
    const __nv_bfloat16* A_re = (const __nv_bfloat16*)d_in[1];
    const __nv_bfloat16* A_im = (const __nv_bfloat16*)d_in[2];
    const __nv_bfloat16* B_re = (const __nv_bfloat16*)d_in[3];
    const __nv_bfloat16* B_im = (const __nv_bfloat16*)d_in[4];
    const __nv_bfloat16* C_re = (const __nv_bfloat16*)d_in[5];
    const __nv_bfloat16* C_im = (const __nv_bfloat16*)d_in[6];
    const __nv_bfloat16* log_dt = (const __nv_bfloat16*)d_in[7];
    const __nv_bfloat16* Dskip = (const __nv_bfloat16*)d_in[8];
    const __nv_bfloat16* wg = (const __nv_bfloat16*)d_in[10];
    const __nv_bfloat16* wu = (const __nv_bfloat16*)d_in[11];
    const __nv_bfloat16* wd = (const __nv_bfloat16*)d_in[12];
    __nv_bfloat16* out = (__nv_bfloat16*)d_out;

    static bool init = false;
    static CUtensorMap tm_xn, tm_wg4, tm_wu4, tm_wg3, tm_wu3, tm_hst, tm_hst96, tm_h, tm_wd, tm_x, tm_sT, tm_out;
    static const void* last_ptrs[5] = {nullptr, nullptr, nullptr, nullptr, nullptr};
    if (!init || last_ptrs[0] != wg || last_ptrs[1] != wu || last_ptrs[2] != wd || last_ptrs[3] != x || last_ptrs[4] != out) {
        void* fnp = nullptr;
        cudaDriverEntryPointQueryResult qres;
        cudaGetDriverEntryPoint("cuTensorMapEncodeTiled", &fnp, cudaEnableDefault, &qres);
        EncodeFn fn = (EncodeFn)fnp;
        void *p_xn, *p_h, *p_sT;
        cudaGetSymbolAddress(&p_xn, g_xn);
        cudaGetSymbolAddress(&p_h, g_h);
        cudaGetSymbolAddress(&p_sT, g_sT);
        make_map(fn, &tm_xn, p_xn, D_, L_, 64, 128);
        make_map3(fn, &tm_wg4, wg, F_, D_, 32, 32, 4, CU_TENSOR_MAP_SWIZZLE_64B);
        make_map3(fn, &tm_wu4, wu, F_, D_, 32, 32, 4, CU_TENSOR_MAP_SWIZZLE_64B);
        make_map3(fn, &tm_wg3, wg, F_, D_, 32, 32, 3, CU_TENSOR_MAP_SWIZZLE_64B);
        make_map3(fn, &tm_wu3, wu, F_, D_, 32, 32, 3, CU_TENSOR_MAP_SWIZZLE_64B);
        make_map(fn, &tm_hst, p_h, F_, L_, 16, 16, CU_TENSOR_MAP_SWIZZLE_NONE);
        make_map(fn, &tm_hst96, p_h, F_, L_, 96, 16, CU_TENSOR_MAP_SWIZZLE_NONE);
        make_map(fn, &tm_h, p_h, F_, L_, 64, 128);
        make_map3(fn, &tm_wd, wd, D_, F_, 64, 64, 2, CU_TENSOR_MAP_SWIZZLE_128B);
        make_map(fn, &tm_x, x, D_, L_, 64, 128);
        make_map(fn, &tm_sT, p_sT, L_, D_, 64, 64);
        make_map(fn, &tm_out, out, D_, L_, 64, 16);
        cudaFuncSetAttribute(mega_kernel, cudaFuncAttributeMaxDynamicSharedMemorySize, MG_SMEM);
        last_ptrs[0] = wg; last_ptrs[1] = wu; last_ptrs[2] = wd; last_ptrs[3] = x; last_ptrs[4] = out;
        init = true;
    }
    MegaParams P = {x, A_re, A_im, B_re, B_im, C_re, C_im, log_dt, Dskip, wg, wu, wd};
    launch_pdl(mega_kernel, 128, 384, MG_SMEM, false, 2, P, tm_xn, tm_wg4, tm_wu4, tm_wg3, tm_wu3, tm_h, tm_wd, tm_x, tm_sT, tm_out);
}
```

```cpp
#include <cuda_runtime.h>
#include <cuda_bf16.h>
#include <cuda.h>
#include <stdint.h>

namespace {

constexpr int L_ = 2048, D_ = 512, NS_ = 128, F_ = 1792;

__device__ __align__(1024) __nv_bfloat16 g_xn[L_ * D_];
__device__ __align__(1024) __nv_bfloat16 g_xnT[D_ * L_];
__device__ __align__(1024) __nv_bfloat16 g_sT[D_ * L_];
__device__ __align__(1024) __nv_bfloat16 g_h[L_ * F_];
__device__ unsigned int g_ln_count, g_conv_count, g_done_count, g_h_count[32];

#define STAMP(k, i)

__device__ __forceinline__ uint32_t smem_u32(const void* p) { return (uint32_t)__cvta_generic_to_shared(p); }
__device__ __forceinline__ void pdl_wait() { asm volatile("griddepcontrol.wait;" ::: "memory"); }
__device__ __forceinline__ void pdl_launch() { asm volatile("griddepcontrol.launch_dependents;" ::: "memory"); }

__device__ __forceinline__ void mbar_init(uint32_t bar, uint32_t cnt) {
    asm volatile("mbarrier.init.shared::cta.b64 [%0], %1;" ::"r"(bar), "r"(cnt) : "memory");
}
__device__ __forceinline__ void mbar_expect_tx(uint32_t bar, uint32_t bytes) {
    asm volatile("mbarrier.arrive.expect_tx.shared::cta.b64 _, [%0], %1;" ::"r"(bar), "r"(bytes) : "memory");
}
__device__ __forceinline__ void mbar_arrive(uint32_t bar) {
    asm volatile("mbarrier.arrive.shared::cta.b64 _, [%0];" ::"r"(bar) : "memory");
}
__device__ __forceinline__ void mbar_wait(uint32_t bar, uint32_t parity) {
    asm volatile(
        "{\n.reg .pred p;\n"
        "WAIT_LOOP:\n"
        "mbarrier.try_wait.parity.shared::cta.b64 p, [%0], %1;\n"
        "@p bra WAIT_DONE;\n"
        "bra WAIT_LOOP;\n"
        "WAIT_DONE:\n}\n" ::"r"(bar), "r"(parity) : "memory");
}
__device__ __forceinline__ void tma_load_2d(uint32_t dst, const CUtensorMap* tm, int c0, int c1, uint32_t bar) {
    asm volatile(
        "cp.async.bulk.tensor.2d.shared::cluster.global.mbarrier::complete_tx::bytes [%0], [%1, {%3, %4}], [%2];"
        ::"r"(dst), "l"((uint64_t)tm), "r"(bar), "r"(c0), "r"(c1) : "memory");
}
__device__ __forceinline__ void prefetch_tmap(const CUtensorMap* tm) {
    asm volatile("prefetch.tensormap [%0];" ::"l"((uint64_t)tm) : "memory");
}
__device__ __forceinline__ uint64_t make_desc(uint32_t addr, uint32_t lbo, uint32_t sbo, uint64_t mode = 1) {
    uint64_t d = 0;
    d |= (uint64_t)((addr & 0x3FFFF) >> 4);
    d |= (uint64_t)((lbo >> 4) & 0x3FFF) << 16;
    d |= (uint64_t)((sbo >> 4) & 0x3FFF) << 32;
    d |= mode << 62;
    return d;
}
__device__ __forceinline__ void fence_async_smem() { asm volatile("fence.proxy.async.shared::cta;" ::: "memory"); }
__device__ __forceinline__ void wgmma_fence() { asm volatile("wgmma.fence.sync.aligned;" ::: "memory"); }
__device__ __forceinline__ void wgmma_commit() { asm volatile("wgmma.commit_group.sync.aligned;" ::: "memory"); }
template <int N> __device__ __forceinline__ void wgmma_wait() {
    asm volatile("wgmma.wait_group.sync.aligned %0;" ::"n"(N) : "memory");
}

#define R8(a, i) "+f"(a[i + 0]), "+f"(a[i + 1]), "+f"(a[i + 2]), "+f"(a[i + 3]), "+f"(a[i + 4]), "+f"(a[i + 5]), "+f"(a[i + 6]), "+f"(a[i + 7])

__device__ __forceinline__ void wgmma_n256_k32(float* a, uint64_t da0, uint64_t da1, uint64_t db0, uint64_t db1, int scale_d) {
    asm volatile(
        "{\n.reg .pred p;\nsetp.ne.b32 p, %132, 0;\n"
        "wgmma.mma_async.sync.aligned.m64n256k16.f32.bf16.bf16 {%0,%1,%2,%3,%4,%5,%6,%7,%8,%9,%10,%11,%12,%13,%14,%15,%16,%17,%18,%19,%20,%21,%22,%23,%24,%25,%26,%27,%28,%29,%30,%31,%32,%33,%34,%35,%36,%37,%38,%39,%40,%41,%42,%43,%44,%45,%46,%47,%48,%49,%50,%51,%52,%53,%54,%55,%56,%57,%58,%59,%60,%61,%62,%63,%64,%65,%66,%67,%68,%69,%70,%71,%72,%73,%74,%75,%76,%77,%78,%79,%80,%81,%82,%83,%84,%85,%86,%87,%88,%89,%90,%91,%92,%93,%94,%95,%96,%97,%98,%99,%100,%101,%102,%103,%104,%105,%106,%107,%108,%109,%110,%111,%112,%113,%114,%115,%116,%117,%118,%119,%120,%121,%122,%123,%124,%125,%126,%127}, %128, %130, p, 1, 1, 0, 1;\n"
        "wgmma.mma_async.sync.aligned.m64n256k16.f32.bf16.bf16 {%0,%1,%2,%3,%4,%5,%6,%7,%8,%9,%10,%11,%12,%13,%14,%15,%16,%17,%18,%19,%20,%21,%22,%23,%24,%25,%26,%27,%28,%29,%30,%31,%32,%33,%34,%35,%36,%37,%38,%39,%40,%41,%42,%43,%44,%45,%46,%47,%48,%49,%50,%51,%52,%53,%54,%55,%56,%57,%58,%59,%60,%61,%62,%63,%64,%65,%66,%67,%68,%69,%70,%71,%72,%73,%74,%75,%76,%77,%78,%79,%80,%81,%82,%83,%84,%85,%86,%87,%88,%89,%90,%91,%92,%93,%94,%95,%96,%97,%98,%99,%100,%101,%102,%103,%104,%105,%106,%107,%108,%109,%110,%111,%112,%113,%114,%115,%116,%117,%118,%119,%120,%121,%122,%123,%124,%125,%126,%127}, %129, %131, 1, 1, 1, 0, 1;\n"
        "}\n"
        : R8(a, 0), R8(a, 8), R8(a, 16), R8(a, 24), R8(a, 32), R8(a, 40), R8(a, 48), R8(a, 56), R8(a, 64), R8(a, 72), R8(a, 80), R8(a, 88), R8(a, 96), R8(a, 104), R8(a, 112), R8(a, 120)
        : "l"(da0), "l"(da1), "l"(db0), "l"(db1), "r"(scale_d));
}
__device__ __forceinline__ void wgmma_n192_k32(float* a, uint64_t da0, uint64_t da1, uint64_t db0, uint64_t db1, int scale_d) {
    asm volatile(
        "{\n.reg .pred p;\nsetp.ne.b32 p, %100, 0;\n"
        "wgmma.mma_async.sync.aligned.m64n192k16.f32.bf16.bf16 {%0,%1,%2,%3,%4,%5,%6,%7,%8,%9,%10,%11,%12,%13,%14,%15,%16,%17,%18,%19,%20,%21,%22,%23,%24,%25,%26,%27,%28,%29,%30,%31,%32,%33,%34,%35,%36,%37,%38,%39,%40,%41,%42,%43,%44,%45,%46,%47,%48,%49,%50,%51,%52,%53,%54,%55,%56,%57,%58,%59,%60,%61,%62,%63,%64,%65,%66,%67,%68,%69,%70,%71,%72,%73,%74,%75,%76,%77,%78,%79,%80,%81,%82,%83,%84,%85,%86,%87,%88,%89,%90,%91,%92,%93,%94,%95}, %96, %98, p, 1, 1, 0, 1;\n"
        "wgmma.mma_async.sync.aligned.m64n192k16.f32.bf16.bf16 {%0,%1,%2,%3,%4,%5,%6,%7,%8,%9,%10,%11,%12,%13,%14,%15,%16,%17,%18,%19,%20,%21,%22,%23,%24,%25,%26,%27,%28,%29,%30,%31,%32,%33,%34,%35,%36,%37,%38,%39,%40,%41,%42,%43,%44,%45,%46,%47,%48,%49,%50,%51,%52,%53,%54,%55,%56,%57,%58,%59,%60,%61,%62,%63,%64,%65,%66,%67,%68,%69,%70,%71,%72,%73,%74,%75,%76,%77,%78,%79,%80,%81,%82,%83,%84,%85,%86,%87,%88,%89,%90,%91,%92,%93,%94,%95}, %97, %99, 1, 1, 1, 0, 1;\n"
        "}\n"
        : R8(a, 0), R8(a, 8), R8(a, 16), R8(a, 24), R8(a, 32), R8(a, 40), R8(a, 48), R8(a, 56), R8(a, 64), R8(a, 72), R8(a, 80), R8(a, 88)
        : "l"(da0), "l"(da1), "l"(db0), "l"(db1), "r"(scale_d));
}
__device__ __forceinline__ void wgmma_n192(float* a, uint64_t da0, uint64_t db0, int scale_d) {
    asm volatile(
        "{\n.reg .pred p;\nsetp.ne.b32 p, %98, 0;\n"
        "wgmma.mma_async.sync.aligned.m64n192k16.f32.bf16.bf16 {%0,%1,%2,%3,%4,%5,%6,%7,%8,%9,%10,%11,%12,%13,%14,%15,%16,%17,%18,%19,%20,%21,%22,%23,%24,%25,%26,%27,%28,%29,%30,%31,%32,%33,%34,%35,%36,%37,%38,%39,%40,%41,%42,%43,%44,%45,%46,%47,%48,%49,%50,%51,%52,%53,%54,%55,%56,%57,%58,%59,%60,%61,%62,%63,%64,%65,%66,%67,%68,%69,%70,%71,%72,%73,%74,%75,%76,%77,%78,%79,%80,%81,%82,%83,%84,%85,%86,%87,%88,%89,%90,%91,%92,%93,%94,%95}, %96, %97, p, 1, 1, 0, 1;\n"
        "}\n"
        : R8(a, 0), R8(a, 8), R8(a, 16), R8(a, 24), R8(a, 32), R8(a, 40), R8(a, 48), R8(a, 56), R8(a, 64), R8(a, 72), R8(a, 80), R8(a, 88)
        : "l"(da0), "l"(db0), "r"(scale_d));
}
__device__ __forceinline__ void wgmma_n128_k64(float* a, uint64_t da0, uint64_t da1, uint64_t da2, uint64_t da3,
                                               uint64_t db0, uint64_t db1, uint64_t db2, uint64_t db3, int scale_d) {
    asm volatile(
        "{\n.reg .pred p;\nsetp.ne.b32 p, %72, 0;\n"
        "wgmma.mma_async.sync.aligned.m64n128k16.f32.bf16.bf16 {%0,%1,%2,%3,%4,%5,%6,%7,%8,%9,%10,%11,%12,%13,%14,%15,%16,%17,%18,%19,%20,%21,%22,%23,%24,%25,%26,%27,%28,%29,%30,%31,%32,%33,%34,%35,%36,%37,%38,%39,%40,%41,%42,%43,%44,%45,%46,%47,%48,%49,%50,%51,%52,%53,%54,%55,%56,%57,%58,%59,%60,%61,%62,%63}, %64, %68, p, 1, 1, 0, 1;\n"
        "wgmma.mma_async.sync.aligned.m64n128k16.f32.bf16.bf16 {%0,%1,%2,%3,%4,%5,%6,%7,%8,%9,%10,%11,%12,%13,%14,%15,%16,%17,%18,%19,%20,%21,%22,%23,%24,%25,%26,%27,%28,%29,%30,%31,%32,%33,%34,%35,%36,%37,%38,%39,%40,%41,%42,%43,%44,%45,%46,%47,%48,%49,%50,%51,%52,%53,%54,%55,%56,%57,%58,%59,%60,%61,%62,%63}, %65, %69, 1, 1, 1, 0, 1;\n"
        "wgmma.mma_async.sync.aligned.m64n128k16.f32.bf16.bf16 {%0,%1,%2,%3,%4,%5,%6,%7,%8,%9,%10,%11,%12,%13,%14,%15,%16,%17,%18,%19,%20,%21,%22,%23,%24,%25,%26,%27,%28,%29,%30,%31,%32,%33,%34,%35,%36,%37,%38,%39,%40,%41,%42,%43,%44,%45,%46,%47,%48,%49,%50,%51,%52,%53,%54,%55,%56,%57,%58,%59,%60,%61,%62,%63}, %66, %70, 1, 1, 1, 0, 1;\n"
        "wgmma.mma_async.sync.aligned.m64n128k16.f32.bf16.bf16 {%0,%1,%2,%3,%4,%5,%6,%7,%8,%9,%10,%11,%12,%13,%14,%15,%16,%17,%18,%19,%20,%21,%22,%23,%24,%25,%26,%27,%28,%29,%30,%31,%32,%33,%34,%35,%36,%37,%38,%39,%40,%41,%42,%43,%44,%45,%46,%47,%48,%49,%50,%51,%52,%53,%54,%55,%56,%57,%58,%59,%60,%61,%62,%63}, %67, %71, 1, 1, 1, 0, 1;\n"
        "}\n"
        : R8(a, 0), R8(a, 8), R8(a, 16), R8(a, 24), R8(a, 32), R8(a, 40), R8(a, 48), R8(a, 56)
        : "l"(da0), "l"(da1), "l"(da2), "l"(da3), "l"(db0), "l"(db1), "l"(db2), "l"(db3), "r"(scale_d));
}

__device__ __forceinline__ float bf16_round(float x) {
    uint32_t p; asm("cvt.rn.bf16x2.f32 %0, %1, %2;" : "=r"(p) : "f"(x), "f"(0.0f));
    return __uint_as_float(p);
}
__device__ __forceinline__ uint32_t pack_bf16(float lo, float hi) {
    __nv_bfloat162 v = __floats2bfloat162_rn(lo, hi);
    return *reinterpret_cast<uint32_t*>(&v);
}
__device__ __forceinline__ float bf_lo(uint32_t v) { return __uint_as_float(v << 16); }
__device__ __forceinline__ float bf_hi(uint32_t v) { return __uint_as_float(v & 0xFFFF0000u); }

struct cplx { float r, i; };
__device__ __forceinline__ cplx cmul(cplx a, cplx b) {
    cplx c; c.r = a.r * b.r - a.i * b.i; c.i = a.r * b.i + a.i * b.r; return c;
}
__device__ __forceinline__ cplx csq(cplx a) {
    cplx c; c.r = a.r * a.r - a.i * a.i; c.i = 2.0f * a.r * a.i; return c;
}
__device__ __forceinline__ cplx cexp_m(float ar2, float ai2, float m) {
    float mag;
    asm("ex2.approx.ftz.f32 %0, %1;" : "=f"(mag) : "f"(ar2 * m));
    float rr = ai2 * m;
    rr -= (rr + 12582912.0f) - 12582912.0f;
    float th = rr * 6.283185307179586f;
    cplx c; c.r = mag * __cosf(th); c.i = mag * __sinf(th);
    return c;
}
__device__ __forceinline__ uint32_t to_tf32(float x) { return __float_as_uint(x) + 0x1000u; }
__device__ __forceinline__ void mma_tf32(float* c, uint32_t a0, uint32_t a1, uint32_t a2, uint32_t a3, uint32_t b0, uint32_t b1) {
    asm volatile("mma.sync.aligned.m16n8k8.row.col.f32.tf32.tf32.f32 {%0,%1,%2,%3}, {%4,%5,%6,%7}, {%8,%9}, {%0,%1,%2,%3};"
                 : "+f"(c[0]), "+f"(c[1]), "+f"(c[2]), "+f"(c[3])
                 : "r"(a0), "r"(a1), "r"(a2), "r"(a3), "r"(b0), "r"(b1));
}
__device__ __forceinline__ void mma_bf16(float* c, uint32_t a0, uint32_t a1, uint32_t a2, uint32_t a3, uint32_t b0, uint32_t b1) {
    asm volatile("mma.sync.aligned.m16n8k16.row.col.f32.bf16.bf16.f32 {%0,%1,%2,%3}, {%4,%5,%6,%7}, {%8,%9}, {%0,%1,%2,%3};"
                 : "+f"(c[0]), "+f"(c[1]), "+f"(c[2]), "+f"(c[3])
                 : "r"(a0), "r"(a1), "r"(a2), "r"(a3), "r"(b0), "r"(b1));
}
__device__ __forceinline__ void named_bar(int id, int n) { asm volatile("bar.sync %0, %1;" ::"r"(id), "r"(n) : "memory"); }
__device__ __forceinline__ void ldsm_x4(uint32_t addr, uint32_t& r0, uint32_t& r1, uint32_t& r2, uint32_t& r3) {
    asm volatile("ldmatrix.sync.aligned.m8n8.x4.shared.b16 {%0,%1,%2,%3}, [%4];" : "=r"(r0), "=r"(r1), "=r"(r2), "=r"(r3) : "r"(addr));
}
__device__ __forceinline__ void ldsm_x4_t(uint32_t addr, uint32_t& r0, uint32_t& r1, uint32_t& r2, uint32_t& r3) {
    asm volatile("ldmatrix.sync.aligned.m8n8.x4.trans.shared.b16 {%0,%1,%2,%3}, [%4];" : "=r"(r0), "=r"(r1), "=r"(r2), "=r"(r3) : "r"(addr));
}

constexpr int CV_CH = 4;
constexpr int CV_O_CONST = 0;
constexpr int CV_O_KP = 12288;
constexpr int CV_EARLY = 12288 + 7776;
constexpr int CV_O_Q = 0;
constexpr int CV_O_Q2 = CV_O_Q + 2304;
constexpr int CV_O_Q3 = CV_O_Q2 + 1024;
constexpr int CV_O_Q4X = CV_O_Q3 + 768;
constexpr int CV_O_W3 = CV_O_Q4X + 256;
constexpr int CV_O_W5 = CV_O_W3 + 3104;
constexpr int CV_O_W7 = CV_O_W5 + 3104;
constexpr int CV_O_W9 = CV_O_W7 + 2048;
constexpr int CV_O_U = CV_O_W9 + 2048;
constexpr int CV_LATE = CV_O_U + 4352;
constexpr int CV_LATE_BASE = 229376 - CV_CH * CV_LATE;
constexpr int CV_TILE_OFF = CV_CH * CV_EARLY;
static_assert(CV_TILE_OFF + 16 * (D_ + 8) * 2 <= CV_LATE_BASE && CV_LATE_BASE >= 131072 + 16384, "front layout");
static_assert(CV_O_W3 >= 4096 && CV_O_U - CV_O_W3 >= 8192 && (CV_LATE % 16) == 0 && (CV_EARLY % 16) == 0, "front layout");

constexpr int LN_ROWS = 16;

template <typename PF>
__device__ __forceinline__ void front_phase(PF prefetch_fn, uint8_t* smem, const __nv_bfloat16* __restrict__ x,
                                            const __nv_bfloat16* __restrict__ A_re, const __nv_bfloat16* __restrict__ A_im,
                                            const __nv_bfloat16* __restrict__ B_re, const __nv_bfloat16* __restrict__ B_im,
                                            const __nv_bfloat16* __restrict__ C_re, const __nv_bfloat16* __restrict__ C_im,
                                            const __nv_bfloat16* __restrict__ log_dt, const __nv_bfloat16* __restrict__ Dskip,
                                            const __nv_bfloat16* __restrict__ wg, const __nv_bfloat16* __restrict__ wu,
                                            const __nv_bfloat16* __restrict__ wd) {
    const int warp = threadIdx.x >> 5, lane = threadIdx.x & 31;
    const int ch = warp / 3, w = warp - 3 * ch, tc = threadIdx.x - 96 * ch;
    const int d = blockIdx.x * CV_CH + ch;
    const int g = lane >> 2, t = lane & 3;
    uint8_t* base = smem + CV_LATE_BASE + ch * CV_LATE;
    float4* s_const = reinterpret_cast<float4*>(smem + ch * CV_EARLY + CV_O_CONST);
    float* s_kp = reinterpret_cast<float*>(smem + ch * CV_EARLY + CV_O_KP);
    uint32_t* s_q = reinterpret_cast<uint32_t*>(base + CV_O_Q);
    uint32_t* s_q2 = reinterpret_cast<uint32_t*>(base + CV_O_Q2);
    uint32_t* s_q3 = reinterpret_cast<uint32_t*>(base + CV_O_Q3);
    uint32_t* s_q4 = reinterpret_cast<uint32_t*>(base + CV_O_Q4X);
    __nv_bfloat16* s_u = reinterpret_cast<__nv_bfloat16*>(base + CV_O_U);
    const int bar_id = 5 + ch;
    const __nv_bfloat16 p_dsk = Dskip[d];
    __nv_bfloat16 (*tile)[D_ + 8] = reinterpret_cast<__nv_bfloat16 (*)[D_ + 8]>(smem + CV_TILE_OFF);

    if (warp < 8) {
        const int row = blockIdx.x * LN_ROWS + warp * 2;
        uint4 xv[2][2];
#pragma unroll
        for (int r = 0; r < 2; r++) {
            xv[r][0] = *reinterpret_cast<const uint4*>(x + (size_t)(row + r) * D_ + lane * 8);
            xv[r][1] = *reinterpret_cast<const uint4*>(x + (size_t)(row + r) * D_ + 256 + lane * 8);
        }
        float f[2][16], sm[2], q[2];
#pragma unroll
        for (int r = 0; r < 2; r++) {
            const uint32_t wv[8] = {xv[r][0].x, xv[r][0].y, xv[r][0].z, xv[r][0].w, xv[r][1].x, xv[r][1].y, xv[r][1].z, xv[r][1].w};
#pragma unroll
            for (int i = 0; i < 8; i++) { f[r][2 * i] = bf_lo(wv[i]); f[r][2 * i + 1] = bf_hi(wv[i]); }
            sm[r] = 0.f;
#pragma unroll
            for (int i = 0; i < 16; i++) sm[r] += f[r][i];
        }
#pragma unroll
        for (int o = 16; o > 0; o >>= 1) { sm[0] += __shfl_xor_sync(0xffffffffu, sm[0], o); sm[1] += __shfl_xor_sync(0xffffffffu, sm[1], o); }
#pragma unroll
        for (int r = 0; r < 2; r++) {
            sm[r] *= (1.0f / D_);
            q[r] = 0.f;
#pragma unroll
            for (int i = 0; i < 16; i++) { float dd = f[r][i] - sm[r]; q[r] += dd * dd; }
        }
#pragma unroll
        for (int o = 16; o > 0; o >>= 1) { q[0] += __shfl_xor_sync(0xffffffffu, q[0], o); q[1] += __shfl_xor_sync(0xffffffffu, q[1], o); }
#pragma unroll
        for (int r = 0; r < 2; r++) {
            const float mb = bf16_round(sm[r]);
            const float vb = bf16_round(q[r] * (1.0f / D_));
            const float den = bf16_round(sqrtf(bf16_round(vb + 1e-5f)));
            uint32_t o[8];
#pragma unroll
            for (int i = 0; i < 8; i++) {
                float a = __fdiv_rn(bf16_round(f[r][2 * i] - mb), den);
                float b = __fdiv_rn(bf16_round(f[r][2 * i + 1] - mb), den);
                o[i] = pack_bf16(a, b);
            }
            __nv_bfloat16* dst = g_xn + (size_t)(row + r) * D_;
            *reinterpret_cast<uint4*>(dst + lane * 8) = make_uint4(o[0], o[1], o[2], o[3]);
            *reinterpret_cast<uint4*>(dst + 256 + lane * 8) = make_uint4(o[4], o[5], o[6], o[7]);
            *reinterpret_cast<uint4*>(&tile[warp * 2 + r][lane * 8]) = make_uint4(o[0], o[1], o[2], o[3]);
            *reinterpret_cast<uint4*>(&tile[warp * 2 + r][256 + lane * 8]) = make_uint4(o[4], o[5], o[6], o[7]);
        }
    } else {
        const int cc_ = warp - 8, dd = blockIdx.x * CV_CH + cc_;
        float4* sc = reinterpret_cast<float4*>(smem + cc_ * CV_EARLY + CV_O_CONST);
        __nv_bfloat16 pr[4][6];
#pragma unroll
        for (int j = 0; j < 4; j++) {
            const size_t off = (size_t)dd * NS_ + lane + 32 * j;
            pr[j][0] = A_re[off]; pr[j][1] = A_im[off]; pr[j][2] = B_re[off]; pr[j][3] = B_im[off]; pr[j][4] = C_re[off]; pr[j][5] = C_im[off];
        }
        const float dt = bf16_round(expf(__bfloat162float(log_dt[dd])));
        float tail = 0.f;
#pragma unroll
        for (int j = 0; j < 4; j++) {
            const float ar = dt * __bfloat162float(pr[j][0]), ai = dt * __bfloat162float(pr[j][1]);
            const cplx db = {dt * __bfloat162float(pr[j][2]), dt * __bfloat162float(pr[j][3])};
            const cplx cc = {__bfloat162float(pr[j][4]), __bfloat162float(pr[j][5])};
            const cplx cb = cmul(cc, db);
            const float ar2 = ar * 1.4426950408889634f, ai2 = ai * 0.15915494309189535f;
            const cplx e8 = cexp_m(ar2, ai2, 8.f), e128 = cexp_m(ar2, ai2, 128.f);
            const cplx cb8 = cmul(cb, e8);
            const cplx e256 = cexp_m(ar2, ai2, 256.f), e512 = cexp_m(ar2, ai2, 512.f), e1024 = cexp_m(ar2, ai2, 1024.f);
            const cplx c256 = cmul(cb, e256), c512 = cmul(cb, e512), c1024 = cmul(cb, e1024);
            const cplx c768 = cmul(c512, e256), c1280 = cmul(c1024, e256), c1536 = cmul(c1024, e512);
            const cplx c1792 = cmul(c1536, e256);
            tail += cmul(c1024, e1024).r;
            float4* c = sc + (lane + 32 * j) * 6;
            c[0] = make_float4(ar2, ai2, cb.r, cb.i);
            c[1] = make_float4(e128.r, e128.i, cb8.r, cb8.i);
            c[2] = make_float4(c256.r, c256.i, e8.r, e8.i);
            c[3] = make_float4(c512.r, c512.i, c768.r, c768.i);
            c[4] = make_float4(c1024.r, c1024.i, c1280.r, c1280.i);
            c[5] = make_float4(c1536.r, c1536.i, c1792.r, c1792.i);
        }
#pragma unroll
        for (int o = 16; o > 0; o >>= 1) tail += __shfl_xor_sync(0xffffffffu, tail, o);
        if (lane == 0) {
            float* kp = reinterpret_cast<float*>(smem + cc_ * CV_EARLY + CV_O_KP);
            kp[640] = tail; kp[648 + 640] = 0.f; kp[1296 + 640] = 0.f;
        }
    }
    __syncthreads();
    if (threadIdx.x == 0) STAMP(0, 3);
#pragma unroll
    for (int rep = 0; rep < 2; rep++) {
        const int c = threadIdx.x + 384 * rep;
        if (c < D_) {
            uint32_t ot[8];
#pragma unroll
            for (int i = 0; i < 8; i++) {
                uint32_t lo = *reinterpret_cast<const uint16_t*>(&tile[2 * i][c]);
                uint32_t hi = *reinterpret_cast<const uint16_t*>(&tile[2 * i + 1][c]);
                ot[i] = lo | (hi << 16);
            }
            __nv_bfloat16* dT = g_xnT + (size_t)c * L_ + blockIdx.x * LN_ROWS;
            *reinterpret_cast<uint4*>(dT) = make_uint4(ot[0], ot[1], ot[2], ot[3]);
            *reinterpret_cast<uint4*>(dT + 8) = make_uint4(ot[4], ot[5], ot[6], ot[7]);
        }
    }
    if (threadIdx.x < 336) {
        const int m = threadIdx.x / 112, i = threadIdx.x - m * 112;
        const char* wp = (const char*)(m == 0 ? wg : (m == 1 ? wu : wd));
        asm volatile("prefetch.global.L2 [%0];" ::"l"(wp + ((size_t)blockIdx.x * 112 + i) * 128));
    }
    __syncthreads();
    if (threadIdx.x == 0) STAMP(1, 1);
    {
        float acc[5][4];
#pragma unroll
        for (int i = 0; i < 5; i++) { acc[i][0] = acc[i][1] = acc[i][2] = acc[i][3] = 0.f; }
        const float gf = (float)g;
        const int src4 = ((g & 3) << 2) | t;
#pragma unroll 2
        for (int s = w; s < 32; s += 3) {
            if (s == 17 && threadIdx.x == 352) asm volatile("red.release.gpu.global.add.u32 [%0], 1;" ::"l"(&g_ln_count) : "memory");
            const float4* c = s_const + (s * 4 + t) * 6;
            const float4 k0 = c[0], k1 = c[1], k2 = c[2];
            const float2 k3 = reinterpret_cast<const float2*>(c + 3)[g >> 2];
            const float2 k4 = reinterpret_cast<const float2*>(c + 4)[g >> 1];
            const cplx cb = {k0.z, k0.w}, e128 = {k1.x, k1.y}, cb8 = {k1.z, k1.w}, c256 = {k2.x, k2.y}, e8 = {k2.z, k2.w};
            const cplx c2 = {k3.x, k3.y}, c3 = {k4.x, k4.y};
            const cplx p1 = cexp_m(k0.x, k0.y, gf);
            const cplx p2 = csq(p1), p4 = csq(p2);
            const cplx r16a = csq(csq(p4));
            cplx q4;
            q4.r = __shfl_sync(0xffffffffu, p4.r, src4);
            q4.i = __shfl_sync(0xffffffffu, p4.i, src4);
            const cplx r16b = cmul(r16a, e128);
            const cplx f0a = cmul(cb, p1), f0b = cmul(cb8, p1), f1 = cmul(c256, p2), f2 = cmul(c2, q4);
            cplx f3 = cmul(c3, e8);
            if (!(g & 1)) f3 = c3;
            const uint32_t a0 = to_tf32(r16a.r), a1 = to_tf32(r16b.r), a2 = to_tf32(-r16a.i), a3 = to_tf32(-r16b.i);
            mma_tf32(acc[0], a0, a1, a2, a3, to_tf32(f0a.r), to_tf32(f0a.i));
            mma_tf32(acc[1], a0, a1, a2, a3, to_tf32(f0b.r), to_tf32(f0b.i));
            mma_tf32(acc[2], a0, a1, a2, a3, to_tf32(f1.r), to_tf32(f1.i));
            mma_tf32(acc[3], a0, a1, a2, a3, to_tf32(f2.r), to_tf32(f2.i));
            mma_tf32(acc[4], a0, a1, a2, a3, to_tf32(f3.r), to_tf32(f3.i));
        }
        float* kv = s_kp + w * 648;
#pragma unroll
        for (int hh = 0; hh < 2; hh++) {
            const int i = g + 8 * hh;
            *reinterpret_cast<float2*>(kv + 16 * i + 2 * t) = make_float2(acc[0][2 * hh], acc[0][2 * hh + 1]);
            *reinterpret_cast<float2*>(kv + 16 * i + 8 + 2 * t) = make_float2(acc[1][2 * hh], acc[1][2 * hh + 1]);
            *reinterpret_cast<float2*>(kv + 256 + 8 * i + 2 * t) = make_float2(acc[2][2 * hh], acc[2][2 * hh + 1]);
            *reinterpret_cast<float2*>(kv + 384 + 64 * (t >> 1) + 2 * (t & 1) + 4 * i) = make_float2(acc[3][2 * hh], acc[3][2 * hh + 1]);
            *reinterpret_cast<float2*>(kv + 512 + 32 * t + 2 * i) = make_float2(acc[4][2 * hh], acc[4][2 * hh + 1]);
        }
    }
    named_bar(bar_id, 96);
    if (threadIdx.x == 0) STAMP(1, 2);
#pragma unroll
    for (int i = 0; i < 7; i++) {
        const int idx = tc + 96 * i;
        if (idx < 641) s_kp[idx] = (s_kp[idx] + s_kp[648 + idx]) + s_kp[1296 + idx];
    }
    named_bar(bar_id, 96);
    {
        auto kdir = [&](int l) -> float {
            if (l < 0 || l > 514) return 0.f;
            const int idx = (l < 256) ? l : (l > 512 ? 384 : 128 + ((l + ((l >> 1) & 1)) >> 1));
            return s_kp[idx];
        };
#pragma unroll
        for (int i = 0; i < 6; i++) {
            const int e = tc + 96 * i;
            s_q[e] = pack_bf16(kdir(e - 16), kdir(e - 17));
        }
        if (tc < 64) {
            const int xx = 1008 + tc;
            const float k1024 = s_kp[512];
            s_q4[tc] = pack_bf16((xx == 1027 || xx == 1028) ? k1024 : 0.f, (xx == 1028 || xx == 1029) ? k1024 : 0.f);
        }
#pragma unroll
        for (int i = 0; i < 3; i++) {
            const int e = tc + 96 * i;
            if (e < 256) {
                const int a = e >> 6, ii = (e & 63) - 16;
                const int b = 385 + (a >> 1) + 2 * (a & 1);
                const float v0 = (ii >= 0 && ii < 32) ? s_kp[b + 4 * ii] : 0.f;
                const float v1 = (ii >= 1 && ii < 33) ? s_kp[b + 4 * (ii - 1)] : 0.f;
                s_q2[e] = pack_bf16(v0, v1);
            }
        }
#pragma unroll
        for (int a = 0; a < 2; a++) {
            const int jj = tc - 16;
            const float v0 = (jj >= 0 && jj < 64) ? s_kp[513 + a + 2 * jj] : 0.f;
            const float v1 = (jj >= 1 && jj < 65) ? s_kp[513 + a + 2 * (jj - 1)] : 0.f;
            s_q3[96 * a + tc] = pack_bf16(v0, v1);
        }
    }
    if (threadIdx.x == 0) STAMP(1, 3);
    if (threadIdx.x == 0) {
        unsigned int v = 0;
        for (int spin = 0; spin < (1 << 22); spin++) {
            asm volatile("ld.acquire.gpu.global.u32 %0, [%1];" : "=r"(v) : "l"(&g_ln_count) : "memory");
            if (v >= gridDim.x) break;
        }
    }
    fence_async_smem();
    __syncthreads();
    if (threadIdx.x == 0) STAMP(1, 4);
    prefetch_fn();
    {
        if (tc < 16) *reinterpret_cast<uint4*>(s_u + tc * 8) = make_uint4(0, 0, 0, 0);
        const uint4* src = reinterpret_cast<const uint4*>(g_xnT + (size_t)d * L_);
        uint4 v[3];
#pragma unroll
        for (int i = 0; i < 3; i++) if (tc + 96 * i < 256) v[i] = src[tc + 96 * i];
#pragma unroll
        for (int i = 0; i < 3; i++) if (tc + 96 * i < 256) *reinterpret_cast<uint4*>(s_u + 128 + (tc + 96 * i) * 8) = v[i];
        if (tc < 2) *reinterpret_cast<uint4*>(base + (tc ? CV_O_W5 : CV_O_W3)) = make_uint4(0, 0, 0, 0);
    }
    named_bar(bar_id, 96);
    if (w == 2) {
#pragma unroll 2
      for (int rep = 0; rep < 6; rep++) {
        const int m = lane + 32 * rep;
        float P[30];
        const uint4* up = reinterpret_cast<const uint4*>(s_u + 128 + 8 * m - 24);
        P[0] = 0.f;
#pragma unroll
        for (int c4 = 0; c4 < 4; c4++) {
            const uint4 v = up[c4];
            const uint32_t ww[4] = {v.x, v.y, v.z, v.w};
#pragma unroll
            for (int j = 0; j < 4; j++) {
                const int k = c4 * 8 + 2 * j;
                if (k + 1 <= 29) P[k + 1] = P[k] + bf_lo(ww[j]);
                if (k + 2 <= 29) P[k + 2] = P[k + 1] + bf_hi(ww[j]);
            }
        }
        uint32_t o3[4], o5[4], o7[4], o9[4];
#pragma unroll
        for (int j = 0; j < 4; j++) {
            const int i = 2 * j;
            o3[j] = pack_bf16(P[i + 22] - P[i + 19], P[i + 23] - P[i + 20]);
            o5[j] = pack_bf16(P[i + 19] - P[i + 14], P[i + 20] - P[i + 15]);
            o7[j] = pack_bf16(P[i + 20] - P[i + 13], P[i + 21] - P[i + 14]);
            o9[j] = pack_bf16(P[i + 13] - P[i + 4], P[i + 14] - P[i + 5]);
        }
        *reinterpret_cast<uint4*>(base + CV_O_W3 + 16 + m * 16) = make_uint4(o3[0], o3[1], o3[2], o3[3]);
        *reinterpret_cast<uint4*>(base + CV_O_W5 + 16 + m * 16) = make_uint4(o5[0], o5[1], o5[2], o5[3]);
        if (m < 128) {
            *reinterpret_cast<uint4*>(base + CV_O_W7 + m * 16) = make_uint4(o7[0], o7[1], o7[2], o7[3]);
            *reinterpret_cast<uint4*>(base + CV_O_W9 + m * 16) = make_uint4(o9[0], o9[1], o9[2], o9[3]);
        }
    }
      named_bar(bar_id, 96);
      return;
    }
    if (threadIdx.x == 0) STAMP(1, 5);
    const int hb = w;
    float acc[16][4];
#pragma unroll
    for (int i = 0; i < 16; i++) { acc[i][0] = acc[i][1] = acc[i][2] = acc[i][3] = 0.f; }
    const uint32_t sb_addr = smem_u32(base);
    const int mi = lane >> 3, rowi = lane & 7;
#pragma unroll 1
    for (int rr = 0; rr < 4; rr++) {
        const int r = 4 * hb + rr;
        uint32_t ub[16][2];
        {
            const uint32_t addr = sb_addr + CV_O_U + (uint32_t)((128 + 16 * (8 * (mi >> 1) + rowi - r) + 8 * (mi & 1)) * 2);
#pragma unroll
            for (int j = 0; j < 16; j += 2) ldsm_x4(addr + (uint32_t)(j * 256), ub[j][0], ub[j][1], ub[j + 1][0], ub[j + 1][1]);
        }
        const uint32_t* qp = s_q + 16 + 16 * r + g - 2 * t;
        uint32_t af[4][3];
#pragma unroll
        for (int q = 0; q < 4; q++) { af[q][0] = qp[128 * q]; af[q][1] = qp[128 * q + 8]; af[q][2] = qp[128 * q - 8]; }
#pragma unroll
        for (int q = 0; q < 4; q++) {
#pragma unroll
            for (int nt = q; nt < 16; nt++) mma_bf16(acc[nt], af[q][0], af[q][1], af[q][2], af[q][0], ub[nt - q][0], ub[nt - q][1]);
        }
        if (r < 2) {
            {
                const uint32_t a0 = qp[512], a1 = qp[520], a2 = qp[504];
#pragma unroll
                for (int nt = 4; nt < 16; nt++) mma_bf16(acc[nt], a0, a1, a2, a0, ub[nt - 4][0], ub[nt - 4][1]);
            }
            {
                const uint32_t* q4p = s_q4 + 16 + 16 * r + g - 2 * t;
                const uint32_t a0 = q4p[0], a1 = q4p[8], a2 = q4p[-8];
#pragma unroll
                for (int nt = 8; nt < 16; nt++) mma_bf16(acc[nt], a0, a1, a2, a0, ub[nt - 8][0], ub[nt - 8][1]);
            }
        }
    }
    named_bar(bar_id, 96);
#pragma unroll 1
    for (int a = hb; a <= 3 * hb; a++) {
        uint32_t bq[7];
        const uint32_t* q2 = s_q2 + a * 64 + 16 + g - 2 * t - 32;
#pragma unroll
        for (int dlt = 3; dlt <= 9; dlt++) bq[dlt - 3] = q2[8 * dlt];
        const uint32_t addr = sb_addr + ((a >> 1) ? CV_O_W5 : CV_O_W3) + (uint32_t)((8 + 16 * (8 * (mi >> 1) + rowi) + 8 * (mi & 1) - 8 * (a & 1)) * 2);
        uint32_t aa[6][4];
#pragma unroll
        for (int kp = 0; kp < 6; kp++) ldsm_x4_t(addr + kp * 512, aa[kp][0], aa[kp][1], aa[kp][2], aa[kp][3]);
#pragma unroll
        for (int kp = 0; kp < 6; kp++) {
#pragma unroll
            for (int dlt = 4; dlt <= 9; dlt++) {
                if (2 * kp + dlt < 16) mma_bf16(acc[2 * kp + dlt], aa[kp][0], aa[kp][1], aa[kp][2], aa[kp][3], bq[dlt - 3], bq[dlt - 4]);
            }
        }
    }
    if (hb == 0) {
#pragma unroll 1
        for (int a = 0; a < 2; a++) {
            uint32_t bq[9];
            const uint32_t* q3 = s_q3 + a * 96 + 16 + g - 2 * t - 64;
#pragma unroll
            for (int dlt = 7; dlt <= 15; dlt++) bq[dlt - 7] = q3[8 * dlt];
            const uint32_t addr = sb_addr + (a ? CV_O_W9 : CV_O_W7) + (uint32_t)((16 * (8 * (mi >> 1) + rowi) + 8 * (mi & 1)) * 2);
            uint32_t aa[4][4];
#pragma unroll
            for (int kp = 0; kp < 4; kp++) ldsm_x4_t(addr + kp * 512, aa[kp][0], aa[kp][1], aa[kp][2], aa[kp][3]);
#pragma unroll
            for (int kp = 0; kp < 4; kp++) {
#pragma unroll
                for (int dlt = 8; dlt <= 15; dlt++) {
                    if (2 * kp + dlt < 16) mma_bf16(acc[2 * kp + dlt], aa[kp][0], aa[kp][1], aa[kp][2], aa[kp][3], bq[dlt - 7], bq[dlt - 8]);
                }
            }
        }
    }
    if (threadIdx.x == 0) STAMP(1, 6);
    named_bar(bar_id, 64);
    {
        float4* xch = reinterpret_cast<float4*>(base + CV_O_W3) + hb * 256;
        if (hb) {
#pragma unroll
            for (int i = 0; i < 8; i++) xch[i * 32 + lane] = make_float4(acc[i][0], acc[i][1], acc[i][2], acc[i][3]);
#pragma unroll
            for (int i = 0; i < 8; i++) { acc[i][0] = acc[8 + i][0]; acc[i][1] = acc[8 + i][1]; acc[i][2] = acc[8 + i][2]; acc[i][3] = acc[8 + i][3]; }
        } else {
#pragma unroll
            for (int i = 0; i < 8; i++) xch[i * 32 + lane] = make_float4(acc[8 + i][0], acc[8 + i][1], acc[8 + i][2], acc[8 + i][3]);
        }
    }
    named_bar(bar_id, 64);
    if (threadIdx.x == 0) STAMP(1, 10);
    {
        const float4* xch = reinterpret_cast<const float4*>(base + CV_O_W3) + (hb ^ 1) * 256 + lane;
        const float dsk = __bfloat162float(p_dsk);
        uint16_t* stg = reinterpret_cast<uint16_t*>(base + CV_O_Q);
        const uint16_t* uu = reinterpret_cast<const uint16_t*>(s_u) + 128;
#pragma unroll
        for (int i = 0; i < 8; i++) {
            const float4 p0 = xch[i * 32];
            const float y[4] = {acc[i][0] + p0.x, acc[i][1] + p0.y, acc[i][2] + p0.z, acc[i][3] + p0.w};
            const int nt = 8 * hb + i;
#pragma unroll
            for (int e = 0; e < 4; e++) {
                const int tau = 16 * (8 * nt + 2 * t + (e & 1)) + g + 8 * (e >> 1);
                const float sv = bf16_round(y[e]) + bf16_round(__uint_as_float((uint32_t)uu[tau] << 16) * dsk);
                stg[tau] = (uint16_t)(__float_as_uint(bf16_round(sv)) >> 16);
            }
        }
        __syncwarp();
        if (threadIdx.x == 0) STAMP(1, 11);
        uint4* dst = reinterpret_cast<uint4*>(g_sT + (size_t)d * L_ + hb * 1024);
        const uint4* srcp = reinterpret_cast<const uint4*>(stg + hb * 1024);
#pragma unroll
        for (int i = 0; i < 4; i++) dst[i * 32 + lane] = srcp[i * 32 + lane];
    }
}

__device__ __forceinline__ uint32_t cluster_rank() { uint32_t r; asm volatile("mov.u32 %0, %%cluster_ctarank;" : "=r"(r)); return r; }
__device__ __forceinline__ void cluster_sync_all() {
    asm volatile("barrier.cluster.arrive.release.aligned;\nbarrier.cluster.wait.acquire.aligned;" ::: "memory");
}
__device__ __forceinline__ void mbar_arrive_remote(uint32_t bar, uint32_t cta) {
    asm volatile("{\n.reg .b32 ra;\nmapa.shared::cluster.u32 ra, %0, %1;\n"
                 "mbarrier.arrive.shared::cluster.b64 _, [ra];\n}\n" ::"r"(bar), "r"(cta) : "memory");
}
__device__ __forceinline__ void tma_load_2d_mc(uint32_t dst, const CUtensorMap* tm, int c0, int c1, uint32_t bar, uint16_t mask) {
    asm volatile(
        "cp.async.bulk.tensor.2d.shared::cluster.global.mbarrier::complete_tx::bytes.multicast::cluster [%0], [%1, {%3, %4}], [%2], %5;"
        ::"r"(dst), "l"((uint64_t)tm), "r"(bar), "r"(c0), "r"(c1), "h"(mask) : "memory");
}
__device__ __forceinline__ void tma_store_2d(const CUtensorMap* tm, uint32_t src, int c0, int c1) {
    asm volatile("cp.async.bulk.tensor.2d.global.shared::cta.bulk_group [%0, {%2, %3}], [%1];"
                 ::"l"((uint64_t)tm), "r"(src), "r"(c0), "r"(c1) : "memory");
}
__device__ __forceinline__ void bulk_commit() { asm volatile("cp.async.bulk.commit_group;" ::: "memory"); }
template <int N> __device__ __forceinline__ void bulk_wait_read() { asm volatile("cp.async.bulk.wait_group.read %0;" ::"n"(N) : "memory"); }
template <int N> __device__ __forceinline__ void bulk_wait() { asm volatile("cp.async.bulk.wait_group %0;" ::"n"(N) : "memory"); }
__device__ __forceinline__ void stmatrix_x4(uint32_t addr, uint32_t r0, uint32_t r1, uint32_t r2, uint32_t r3) {
    asm volatile("stmatrix.sync.aligned.m8n8.x4.shared.b16 [%0], {%1,%2,%3,%4};" ::"r"(addr), "r"(r0), "r"(r1), "r"(r2), "r"(r3) : "memory");
}

constexpr int G1_STAGES = 5;
constexpr int G1_A_BYTES = 8 * 16384;
constexpr int G1_B_STAGE = 16384;
constexpr int G1_STG = 8 * 1024;
constexpr int G1_SMEM = G1_A_BYTES + G1_STAGES * G1_B_STAGE + G1_STG + 1024 + 256;
constexpr int G1_ITERS = 32;

__device__ __forceinline__ void tma_load_3d(uint32_t dst, const CUtensorMap* tm, int c0, int c1, int c2, uint32_t bar) {
    asm volatile(
        "cp.async.bulk.tensor.3d.shared::cluster.global.mbarrier::complete_tx::bytes [%0], [%1, {%3, %4, %5}], [%2];"
        ::"r"(dst), "l"((uint64_t)tm), "r"(bar), "r"(c0), "r"(c1), "r"(c2) : "memory");
}

__device__ __forceinline__ void tma_load_3d_mc(uint32_t dst, const CUtensorMap* tm, int c0, int c1, int c2, uint32_t bar, uint16_t mask) {
    asm volatile(
        "cp.async.bulk.tensor.3d.shared::cluster.global.mbarrier::complete_tx::bytes.multicast::cluster [%0], [%1, {%3, %4, %5}], [%2], %6;"
        ::"r"(dst), "l"((uint64_t)tm), "r"(bar), "r"(c0), "r"(c1), "r"(c2), "h"(mask) : "memory");
}

__device__ __forceinline__ float gelu_tanh(float x) {
    float u = x * (0.7978845608028654f + 0.035677408136300125f * x * x);
    float t; asm("tanh.approx.f32 %0, %1;" : "=f"(t) : "f"(u));
    float hx = 0.5f * x;
    return fmaf(hx, t, hx);
}
__device__ __forceinline__ uint32_t geglu_pair(uint32_t g2, uint32_t u2) {
    uint32_t a = pack_bf16(gelu_tanh(bf_lo(g2)), gelu_tanh(bf_hi(g2)));
    uint32_t r; asm("mul.rn.bf16x2 %0, %1, %2;" : "=r"(r) : "r"(a), "r"(u2));
    return r;
}

constexpr int G2_STAGES = 5;
constexpr int G2_STAGE = 16384 + 16384;
constexpr int G2_XCH = 32768;
constexpr int G2_EPI = 16384 + 16384;
constexpr int G2_SMEM = G2_STAGES * G2_STAGE + G2_XCH + G2_EPI + 1024 + 256;
constexpr int G2_KB = F_ / 64 / 2;

constexpr int MG_BAR_OFF = G2_STAGES * G2_STAGE + G2_XCH + G2_EPI;
constexpr int MG_SMEM = MG_BAR_OFF + 512 + 1024;
static_assert(MG_BAR_OFF == 229376 && G1_A_BYTES + G1_STAGES * G1_B_STAGE + G1_STG <= MG_BAR_OFF, "smem layout");

__device__ __forceinline__ void fence_async_all() { asm volatile("fence.proxy.async.global;" ::: "memory"); }
__device__ __forceinline__ void spin_until(const unsigned int* p, unsigned int target) {
    unsigned int v = 0;
    for (int spin = 0; spin < (1 << 22); spin++) {
        asm volatile("ld.acquire.gpu.global.u32 %0, [%1];" : "=r"(v) : "l"(p) : "memory");
        if (v >= target) break;
    }
}

struct MegaParams {
    const __nv_bfloat16 *x, *A_re, *A_im, *B_re, *B_im, *C_re, *C_im, *log_dt, *Dskip, *wg, *wu, *wd;
};

__global__ void __launch_bounds__(384, 1) mega_kernel(const __grid_constant__ MegaParams P,
                                                       const __grid_constant__ CUtensorMap tm_xn,
                                                       const __grid_constant__ CUtensorMap tm_wg4,
                                                       const __grid_constant__ CUtensorMap tm_wu4,
                                                       const __grid_constant__ CUtensorMap tm_wg3,
                                                       const __grid_constant__ CUtensorMap tm_wu3,
                                                       const __grid_constant__ CUtensorMap tm_h,
                                                       const __grid_constant__ CUtensorMap tm_wd,
                                                       const __grid_constant__ CUtensorMap tm_x,
                                                       const __grid_constant__ CUtensorMap tm_sT,
                                                       const __grid_constant__ CUtensorMap tm_out) {
    if (threadIdx.x == 0) STAMP(1, 0);
    extern __shared__ uint8_t smem_raw[];
    const uint32_t sraw = smem_u32(smem_raw);
    const uint32_t sbase = (sraw + 1023) & ~1023u;
    uint8_t* smem = smem_raw + (sbase - sraw);
    const int warp = threadIdx.x >> 5, lane = threadIdx.x & 31;
    const uint32_t sA = sbase, sB = sbase + G1_A_BYTES, sStg = sB + G1_STAGES * G1_B_STAGE;
    const uint32_t sXch = sbase + G2_STAGES * G2_STAGE, sX = sXch + G2_XCH, sS = sX + 16384;
    const uint32_t sBar = sbase + MG_BAR_OFF;
    const uint32_t bar_a = sBar, bar_full = sBar + 64, bar_empty = bar_full + 8 * G1_STAGES;
    const uint32_t bar_full2 = bar_empty + 8 * G1_STAGES, bar_empty2 = bar_full2 + 8 * G2_STAGES;
    const uint32_t bar_epi = bar_empty2 + 8 * G2_STAGES, bar_xch = bar_epi + 8, bar_g1done = bar_xch + 8, bar_g1mma = bar_g1done + 8, bar_peer = bar_g1mma + 8, bar_g1early = bar_peer + 8;
    const uint32_t kh = blockIdx.x & 1;
    const int rb1 = ((blockIdx.x >> 4) << 1) + (int)kh, cj = (blockIdx.x >> 1) & 7;
    const int rb = blockIdx.x >> 3;
    const int nb = (blockIdx.x >> 1) & 3;
    const int col_fin = nb * 128 + kh * 64;

    if (threadIdx.x == 0) {
        for (int i = 0; i < 8; i++) mbar_init(bar_a + 8 * i, 1);
        for (int i = 0; i < G1_STAGES; i++) { mbar_init(bar_full + 8 * i, 1); mbar_init(bar_empty + 8 * i, 16); }
        for (int i = 0; i < G2_STAGES; i++) { mbar_init(bar_full2 + 8 * i, 1); mbar_init(bar_empty2 + 8 * i, 8); }
        mbar_init(bar_epi, 1);
        mbar_init(bar_xch, 1);
        mbar_init(bar_g1done, 8);
        mbar_init(bar_g1mma, 8);
        mbar_init(bar_peer, 1);
        mbar_init(bar_g1early, 8);
        asm volatile("fence.mbarrier_init.release.cluster;" ::: "memory");
        mbar_expect_tx(bar_xch, G2_XCH);
    }
    if (warp == 11 && lane == 0) {
        prefetch_tmap(&tm_wg4); prefetch_tmap(&tm_wu4); prefetch_tmap(&tm_xn); prefetch_tmap(&tm_wg3); prefetch_tmap(&tm_wu3);
        prefetch_tmap(&tm_wd); prefetch_tmap(&tm_h); prefetch_tmap(&tm_x); prefetch_tmap(&tm_sT); prefetch_tmap(&tm_out);
    }
    asm volatile("barrier.cluster.arrive.release.aligned;" ::: "memory");

    auto g1_prefetch = [&]() {
        if (warp == 8 && lane == 0) {
            fence_async_all();
            mbar_expect_tx(bar_full, 16384);
            tma_load_3d(sB, &tm_wg4, 0, 0, cj * 7, bar_full);
            tma_load_3d(sB + 8192, &tm_wu4, 0, 0, cj * 7, bar_full);
            for (int k = 0; k < 8; k++) {
                mbar_expect_tx(bar_a + 8 * k, 16384);
                tma_load_2d(sA + k * 16384, &tm_xn, k * 64, rb1 * 128, bar_a + 8 * k);
            }
        }
    };
    front_phase(g1_prefetch, smem, P.x, P.A_re, P.A_im, P.B_re, P.B_im, P.C_re, P.C_im, P.log_dt, P.Dskip, P.wg, P.wu, P.wd);
    fence_async_smem();
    asm volatile("barrier.cluster.wait.acquire.aligned;" ::: "memory");
    __syncthreads();
    if (threadIdx.x == 352) mbar_arrive_remote(bar_peer, kh ^ 1);
    if (threadIdx.x == 0) STAMP(1, 7);

    if (warp >= 8) {
        asm volatile("setmaxnreg.dec.sync.aligned.u32 40;");
        if (warp == 11) {
            if (lane == 0) asm volatile("red.release.gpu.global.add.u32 [%0], 1;" ::"l"(&g_conv_count) : "memory");
            named_bar(3, 288);
            if (lane == 0) asm volatile("red.release.gpu.global.add.u32 [%0], 1;" ::"l"(&g_h_count[rb1]) : "memory");
            named_bar(9, 288);
            if (lane == 0) asm volatile("red.release.gpu.global.add.u32 [%0], 1;" ::"l"(&g_h_count[16 + rb1]) : "memory");
        } else if (lane == 0) {
            const int pw = warp - 8;
            mbar_wait(bar_peer, 0);
            for (int it = 1 + pw; it < G1_ITERS; it += 3) {
                const int s = it % G1_STAGES, kb = it & 15;
                if (it >= G1_STAGES) mbar_wait(bar_empty + 8 * s, ((it / G1_STAGES) - 1) & 1);
                const uint32_t dst = sB + s * G1_B_STAGE;
                if (it < 16) {
                    mbar_expect_tx(bar_full + 8 * s, 16384);
                    tma_load_3d_mc(dst + kh * 8192, kh ? &tm_wu4 : &tm_wg4, 0, kb * 32, cj * 7, bar_full + 8 * s, 3);
                } else {
                    mbar_expect_tx(bar_full + 8 * s, 12288);
                    tma_load_3d_mc(dst + kh * 6144, kh ? &tm_wu3 : &tm_wg3, 0, kb * 32, cj * 7 + 4, bar_full + 8 * s, 3);
                }
            }
            const int k0 = kh * G2_KB;
            auto kblk = [&](int it) -> int {
                const unsigned long long tab = 0xDCA96532B87410ull;
                return k0 + (int)((tab >> (4 * it)) & 15);
            };
            mbar_wait(pw == 0 ? bar_g1early : bar_g1mma, 0);
            if (pw == 2) {
                mbar_expect_tx(bar_epi, G2_EPI);
                tma_load_2d(sX, &tm_x, col_fin, rb * 128, bar_epi);
            }
            spin_until(&g_h_count[rb], 8);
            fence_async_all();
            if (pw == 0) STAMP(3, 1);
            for (int it = pw; it < G2_KB; it += 3) {
                const int s = (it + 1) % G2_STAGES;
                if (it == 3) mbar_wait(bar_g1mma, 0);
                if (it == 4) mbar_wait(bar_g1done, 0);
                if (it >= G2_STAGES) mbar_wait(bar_empty2 + 8 * s, ((it / G2_STAGES) - 1) & 1);
                if (it >= 6 && it < 9) { spin_until(&g_h_count[16 + rb], 8); fence_async_all(); }
                mbar_expect_tx(bar_full2 + 8 * s, G2_STAGE);
                const int kb = kblk(it);
                tma_load_3d(sbase + s * G2_STAGE + 16384, &tm_wd, 0, kb * 64, nb * 2, bar_full2 + 8 * s);
                tma_load_2d(sbase + s * G2_STAGE, &tm_h, kb * 64, rb * 128, bar_full2 + 8 * s);
                if (it == 2) {
                    spin_until(&g_conv_count, gridDim.x);
                    fence_async_all();
                    tma_load_2d(sS, &tm_sT, rb * 128, col_fin, bar_epi);
                    tma_load_2d(sS + 8192, &tm_sT, rb * 128 + 64, col_fin, bar_epi);
                }
            }
        }
    } else {
        asm volatile("setmaxnreg.inc.sync.aligned.u32 232;");
        const int wg = __shfl_sync(0xffffffffu, (int)(threadIdx.x >> 7), 0);
        {
        float r[160];
        const int row0 = rb1 * 128 + wg * 64 + (warp & 3) * 16;
        const uint64_t descA = make_desc(sA + wg * 8192, 16, 1024);
        const uint64_t descB = make_desc(sB, 2048, 512, 2);
        const uint32_t stg = sStg + warp * 1024;
        const uint32_t st_off = (uint32_t)(((lane & 7) + ((lane >> 3) & 1) * 8) * 32 + (lane >> 4) * 16);
        __nv_bfloat16* hrow = g_h + (size_t)(row0 + (lane >> 1)) * F_ + (lane & 1) * 8 + cj * 224;
#pragma unroll
        for (int kb = 0; kb < 16; kb++) {
            const int it = kb, s = it % G1_STAGES;
            if ((kb & 1) == 0) mbar_wait(bar_a + 8 * (kb >> 1), 0);
            mbar_wait(bar_full + 8 * s, (it / G1_STAGES) & 1);
            if (threadIdx.x == 0 && (it & 7) == 0) STAMP(2, 2 + it / 8);
            wgmma_fence();
            const uint64_t da = descA + (uint64_t)(((kb >> 1) * 16384 + (kb & 1) * 64) >> 4);
            const uint64_t db = descB + (uint64_t)((s * G1_B_STAGE) >> 4);
            wgmma_n256_k32(r, da, da + 2, db, db + 64, kb != 0);
            wgmma_commit();
            if (kb > 0) {
                wgmma_wait<1>();
                if (lane < 2) mbar_arrive_remote(bar_empty + 8 * ((it - 1) % G1_STAGES), lane);
            }
        }
        wgmma_wait<0>();
        if (lane < 2) mbar_arrive_remote(bar_empty + 8 * (15 % G1_STAGES), lane);
#pragma unroll
        for (int i = 0; i < 32; i++) r[128 + i] = __uint_as_float(pack_bf16(r[2 * i], r[2 * i + 1]));
#pragma unroll
        for (int i = 31; i >= 0; i--) r[96 + i] = __uint_as_float(pack_bf16(r[64 + 2 * i], r[65 + 2 * i]));
        uint32_t eo[4];
        uint4 pv = make_uint4(0, 0, 0, 0);
#pragma unroll
        for (int kb = 0; kb < 16; kb++) {
            const int it = 16 + kb, s = it % G1_STAGES;
            mbar_wait(bar_full + 8 * s, (it / G1_STAGES) & 1);
            if (threadIdx.x == 0 && (it & 7) == 0) STAMP(2, 2 + it / 8);
            wgmma_fence();
            const uint64_t da = descA + (uint64_t)(((kb >> 1) * 16384 + (kb & 1) * 64) >> 4);
            const uint64_t db = descB + (uint64_t)((s * G1_B_STAGE) >> 4);
            wgmma_n192(r, da, db, kb != 0);
            if (kb < 8) {
                eo[0] = geglu_pair(__float_as_uint(r[128 + 4 * kb]), __float_as_uint(r[96 + 4 * kb]));
                eo[1] = geglu_pair(__float_as_uint(r[129 + 4 * kb]), __float_as_uint(r[97 + 4 * kb]));
            }
            wgmma_n192(r, da + 2, db + 64, 1);
            wgmma_commit();
            if (kb >= 2 && kb < 10) *reinterpret_cast<uint4*>(hrow + (kb - 2) * 16) = pv;
            if (kb >= 1 && kb < 9) {
                __syncwarp();
                asm volatile("ld.shared.v4.u32 {%0,%1,%2,%3}, [%4];" : "=r"(pv.x), "=r"(pv.y), "=r"(pv.z), "=r"(pv.w)
                             : "r"(stg + ((kb - 1) & 1) * 512 + lane * 16));
            }
            if (kb < 8) {
                eo[2] = geglu_pair(__float_as_uint(r[130 + 4 * kb]), __float_as_uint(r[98 + 4 * kb]));
                eo[3] = geglu_pair(__float_as_uint(r[131 + 4 * kb]), __float_as_uint(r[99 + 4 * kb]));
                stmatrix_x4(stg + (kb & 1) * 512 + st_off, eo[0], eo[1], eo[2], eo[3]);
            }
            if (kb == 9) asm volatile("bar.arrive 3, 288;" ::: "memory");
            if (kb > 0 && it - 1 + G1_STAGES < G1_ITERS) {
                wgmma_wait<1>();
                if (lane < 2) mbar_arrive_remote(bar_empty + 8 * ((it - 1) % G1_STAGES), lane);
                if (kb == 11 && lane == 0) mbar_arrive(bar_g1early);
            }
        }
        wgmma_wait<0>();
        fence_async_smem();
        __syncwarp();
        if (lane == 0) mbar_arrive(bar_g1mma);
        if (threadIdx.x == 0) STAMP(2, 6);
        {
            uint32_t o[24];
#pragma unroll
            for (int i = 0; i < 24; i++) o[i] = geglu_pair(pack_bf16(r[2 * i], r[2 * i + 1]), pack_bf16(r[48 + 2 * i], r[49 + 2 * i]));
            named_bar(1 + wg, 128);
            const uint32_t fbuf = sA + ((warp & 3) >> 1) * 16384 + wg * 8192 + (warp & 1) * 4096;
#pragma unroll
            for (int jj = 0; jj < 6; jj++) stmatrix_x4(fbuf + jj * 512 + st_off, o[4 * jj], o[4 * jj + 1], o[4 * jj + 2], o[4 * jj + 3]);
            __syncwarp();
            uint4 v[6];
#pragma unroll
            for (int jj = 0; jj < 6; jj++)
                asm volatile("ld.shared.v4.u32 {%0,%1,%2,%3}, [%4];" : "=r"(v[jj].x), "=r"(v[jj].y), "=r"(v[jj].z), "=r"(v[jj].w)
                             : "r"(fbuf + jj * 512 + lane * 16));
#pragma unroll
            for (int jj = 0; jj < 6; jj++) *reinterpret_cast<uint4*>(hrow + 128 + jj * 16) = v[jj];
        }
        }
        fence_async_smem();
        __syncwarp();
        if (lane == 0) mbar_arrive(bar_g1done);
        asm volatile("bar.arrive 9, 288;" ::: "memory");
        if (threadIdx.x == 0) STAMP(2, 7);
        {
        const int g = lane >> 2, t = lane & 3;
        float acc[64];
        const uint64_t descA2 = make_desc(sbase + wg * 8192, 16, 1024);
        const uint64_t descB2 = make_desc(sbase + 16384, 8192, 1024);
#pragma unroll
        for (int it = 0; it < G2_KB; it++) {
            const int s = (it + 1) % G2_STAGES;
            mbar_wait(bar_full2 + 8 * s, (it / G2_STAGES) & 1);
            if (threadIdx.x == 0 && (it == 0 || it == 7)) STAMP(3, 2 + it / 7);
            wgmma_fence();
            {
                const uint64_t da = descA2 + (uint64_t)((s * G2_STAGE) >> 4);
                const uint64_t db = descB2 + (uint64_t)((s * G2_STAGE) >> 4);
                wgmma_n128_k64(acc, da, da + 2, da + 4, da + 6, db, db + 128, db + 256, db + 384, it != 0);
            }
            wgmma_commit();
            if (it > 0 && it - 1 + G2_STAGES < G2_KB) {
                wgmma_wait<1>();
                if (lane == 0) mbar_arrive(bar_empty2 + 8 * (it % G2_STAGES));
            }
        }
        const int lr = wg * 64 + (warp & 3) * 16 + g;
        uint32_t xv[16], sv[16];
        mbar_wait(bar_epi, 0);
#pragma unroll
        for (int j = 0; j < 8; j++) {
#pragma unroll
            for (int hh = 0; hh < 2; hh++) {
                const int r = lr + 8 * hh;
                asm volatile("ld.shared.u32 %0, [%1];" : "=r"(xv[2 * j + hh]) : "r"(sX + r * 128 + ((j ^ (r & 7)) << 4) + 4 * t));
                const int c0 = 8 * j + 2 * t;
                const uint32_t sa = sS + (r >> 6) * 8192 + (((r & 63) >> 3) << 4) + (r & 7) * 2;
                uint16_t s0r, s1r;
                asm volatile("ld.shared.u16 %0, [%1];" : "=h"(s0r) : "r"((sa + c0 * 128) ^ ((c0 & 7) << 4)));
                asm volatile("ld.shared.u16 %0, [%1];" : "=h"(s1r) : "r"((sa + (c0 + 1) * 128) ^ (((c0 + 1) & 7) << 4)));
                sv[2 * j + hh] = (uint32_t)s0r | ((uint32_t)s1r << 16);
            }
        }
        wgmma_wait<0>();
        if (threadIdx.x == 0) STAMP(3, 4);
        {
            uint32_t remote, rbar;
            asm volatile("mapa.shared::cluster.u32 %0, %1, %2;" : "=r"(remote) : "r"(sXch + threadIdx.x * 16), "r"(kh ^ 1));
            asm volatile("mapa.shared::cluster.u32 %0, %1, %2;" : "=r"(rbar) : "r"(bar_xch), "r"(kh ^ 1));
            if (kh == 0) {
#pragma unroll
                for (int i = 0; i < 8; i++)
                    asm volatile("st.async.shared::cluster.mbarrier::complete_tx::bytes.v4.f32 [%0], {%1,%2,%3,%4}, [%5];" ::"r"(remote + i * 4096),
                                 "f"(acc[32 + 4 * i]), "f"(acc[33 + 4 * i]), "f"(acc[34 + 4 * i]), "f"(acc[35 + 4 * i]), "r"(rbar) : "memory");
            } else {
#pragma unroll
                for (int i = 0; i < 8; i++)
                    asm volatile("st.async.shared::cluster.mbarrier::complete_tx::bytes.v4.f32 [%0], {%1,%2,%3,%4}, [%5];" ::"r"(remote + i * 4096),
                                 "f"(acc[4 * i]), "f"(acc[1 + 4 * i]), "f"(acc[2 + 4 * i]), "f"(acc[3 + 4 * i]), "r"(rbar) : "memory");
#pragma unroll
                for (int i = 0; i < 32; i++) acc[i] = acc[32 + i];
            }
        }
        if (threadIdx.x == 0) STAMP(3, 6);
        mbar_wait(bar_xch, 0);
        if (threadIdx.x == 0) STAMP(3, 7);
#pragma unroll
        for (int j = 0; j < 8; j++) {
            float4 o;
            asm volatile("ld.shared.v4.f32 {%0,%1,%2,%3}, [%4];" : "=f"(o.x), "=f"(o.y), "=f"(o.z), "=f"(o.w) : "r"(sXch + threadIdx.x * 16 + j * 4096));
            acc[4 * j] += o.x; acc[4 * j + 1] += o.y; acc[4 * j + 2] += o.z; acc[4 * j + 3] += o.w;
        }
#pragma unroll
        for (int i = 0; i < 16; i++) {
            float f0 = bf16_round(acc[2 * i]), f1 = bf16_round(acc[2 * i + 1]);
            float g0 = bf16_round(__fdividef(f0, 1.0f + __expf(-f0)));
            float g1 = bf16_round(__fdividef(f1, 1.0f + __expf(-f1)));
            float o0 = bf_lo(xv[i]) + bf16_round(bf_lo(sv[i]) * g0);
            float o1 = bf_hi(xv[i]) + bf16_round(bf_hi(sv[i]) * g1);
            xv[i] = pack_bf16(o0, o1);
        }
#pragma unroll
        for (int j = 0; j < 8; j++) {
#pragma unroll
            for (int hh = 0; hh < 2; hh++) {
                const int r = lr + 8 * hh;
                asm volatile("st.shared.u32 [%0], %1;" ::"r"(sX + r * 128 + ((j ^ (r & 7)) << 4) + 4 * t), "r"(xv[2 * j + hh]) : "memory");
            }
        }
        if (threadIdx.x == 0) STAMP(3, 9);
        fence_async_smem();
        __syncwarp();
        if (lane == 0) {
            tma_store_2d(&tm_out, sX + (wg * 64 + (warp & 3) * 16) * 128, col_fin, rb * 128 + wg * 64 + (warp & 3) * 16);
            bulk_commit();
            bulk_wait_read<0>();
        }
        }
        if (threadIdx.x == 0) STAMP(3, 5);
        named_bar(4, 256);
        if (threadIdx.x == 0) {
            const unsigned int old = atomicAdd(&g_done_count, 1u);
            if (old == gridDim.x - 1) {
                g_ln_count = 0; g_conv_count = 0; g_done_count = 0;
                for (int i = 0; i < 32; i++) g_h_count[i] = 0;
            }
        }
    }
}

typedef CUresult (*EncodeFn)(CUtensorMap*, CUtensorMapDataType, cuuint32_t, void*, const cuuint64_t*, const cuuint64_t*,
                             const cuuint32_t*, const cuuint32_t*, CUtensorMapInterleave, CUtensorMapSwizzle,
                             CUtensorMapL2promotion, CUtensorMapFloatOOBfill);

void make_map(EncodeFn fn, CUtensorMap* m, const void* ptr, uint64_t inner, uint64_t outer, uint32_t box_in, uint32_t box_out,
              CUtensorMapSwizzle swz = CU_TENSOR_MAP_SWIZZLE_128B) {
    cuuint64_t dims[2] = {inner, outer};
    cuuint64_t strides[1] = {inner * 2};
    cuuint32_t box[2] = {box_in, box_out};
    cuuint32_t es[2] = {1, 1};
    fn(m, CU_TENSOR_MAP_DATA_TYPE_BFLOAT16, 2, const_cast<void*>(ptr), dims, strides, box, es, CU_TENSOR_MAP_INTERLEAVE_NONE,
       swz, CU_TENSOR_MAP_L2_PROMOTION_L2_256B, CU_TENSOR_MAP_FLOAT_OOB_FILL_NONE);
}
void make_map3(EncodeFn fn, CUtensorMap* m, const void* ptr, uint64_t cols, uint64_t rows, uint32_t atom, uint32_t box_rows,
               uint32_t box_atoms, CUtensorMapSwizzle swz) {
    cuuint64_t dims[3] = {atom, rows, cols / atom};
    cuuint64_t strides[2] = {cols * 2, (cuuint64_t)atom * 2};
    cuuint32_t box[3] = {atom, box_rows, box_atoms};
    cuuint32_t es[3] = {1, 1, 1};
    fn(m, CU_TENSOR_MAP_DATA_TYPE_BFLOAT16, 3, const_cast<void*>(ptr), dims, strides, box, es, CU_TENSOR_MAP_INTERLEAVE_NONE,
       swz, CU_TENSOR_MAP_L2_PROMOTION_L2_256B, CU_TENSOR_MAP_FLOAT_OOB_FILL_NONE);
}

template <typename... Args>
void launch_pdl(void (*kern)(Args...), int grid, int block, int smem, bool pdl, int cluster, Args... args) {
    cudaLaunchConfig_t cfg = {};
    cfg.gridDim = dim3(grid); cfg.blockDim = dim3(block); cfg.dynamicSmemBytes = smem; cfg.stream = cudaStreamPerThread;
    cudaLaunchAttribute at[2];
    int n = 0;
    if (pdl) {
        at[n].id = cudaLaunchAttributeProgrammaticStreamSerialization;
        at[n].val.programmaticStreamSerializationAllowed = 1;
        n++;
    }
    if (cluster > 1) {
        at[n].id = cudaLaunchAttributeClusterDimension;
        at[n].val.clusterDim.x = cluster; at[n].val.clusterDim.y = 1; at[n].val.clusterDim.z = 1;
        n++;
    }
    cfg.attrs = at; cfg.numAttrs = n;
    cudaLaunchKernelEx(&cfg, kern, args...);
}

}

extern "C" void kernel_launch(void* const* d_in, const int* in_sizes, int n_in, void* d_out, int out_size) {
    const __nv_bfloat16* x = (const __nv_bfloat16*)d_in[0];
    const __nv_bfloat16* A_re = (const __nv_bfloat16*)d_in[1];
    const __nv_bfloat16* A_im = (const __nv_bfloat16*)d_in[2];
    const __nv_bfloat16* B_re = (const __nv_bfloat16*)d_in[3];
    const __nv_bfloat16* B_im = (const __nv_bfloat16*)d_in[4];
    const __nv_bfloat16* C_re = (const __nv_bfloat16*)d_in[5];
    const __nv_bfloat16* C_im = (const __nv_bfloat16*)d_in[6];
    const __nv_bfloat16* log_dt = (const __nv_bfloat16*)d_in[7];
    const __nv_bfloat16* Dskip = (const __nv_bfloat16*)d_in[8];
    const __nv_bfloat16* wg = (const __nv_bfloat16*)d_in[10];
    const __nv_bfloat16* wu = (const __nv_bfloat16*)d_in[11];
    const __nv_bfloat16* wd = (const __nv_bfloat16*)d_in[12];
    __nv_bfloat16* out = (__nv_bfloat16*)d_out;

    static bool init = false;
    static CUtensorMap tm_xn, tm_wg4, tm_wu4, tm_wg3, tm_wu3, tm_hst, tm_hst96, tm_h, tm_wd, tm_x, tm_sT, tm_out;
    static const void* last_ptrs[5] = {nullptr, nullptr, nullptr, nullptr, nullptr};
    if (!init || last_ptrs[0] != wg || last_ptrs[1] != wu || last_ptrs[2] != wd || last_ptrs[3] != x || last_ptrs[4] != out) {
        void* fnp = nullptr;
        cudaDriverEntryPointQueryResult qres;
        cudaGetDriverEntryPoint("cuTensorMapEncodeTiled", &fnp, cudaEnableDefault, &qres);
        EncodeFn fn = (EncodeFn)fnp;
        void *p_xn, *p_h, *p_sT;
        cudaGetSymbolAddress(&p_xn, g_xn);
        cudaGetSymbolAddress(&p_h, g_h);
        cudaGetSymbolAddress(&p_sT, g_sT);
        make_map(fn, &tm_xn, p_xn, D_, L_, 64, 128);
        make_map3(fn, &tm_wg4, wg, F_, D_, 32, 32, 4, CU_TENSOR_MAP_SWIZZLE_64B);
        make_map3(fn, &tm_wu4, wu, F_, D_, 32, 32, 4, CU_TENSOR_MAP_SWIZZLE_64B);
        make_map3(fn, &tm_wg3, wg, F_, D_, 32, 32, 3, CU_TENSOR_MAP_SWIZZLE_64B);
        make_map3(fn, &tm_wu3, wu, F_, D_, 32, 32, 3, CU_TENSOR_MAP_SWIZZLE_64B);
        make_map(fn, &tm_hst, p_h, F_, L_, 16, 16, CU_TENSOR_MAP_SWIZZLE_NONE);
        make_map(fn, &tm_hst96, p_h, F_, L_, 96, 16, CU_TENSOR_MAP_SWIZZLE_NONE);
        make_map(fn, &tm_h, p_h, F_, L_, 64, 128);
        make_map3(fn, &tm_wd, wd, D_, F_, 64, 64, 2, CU_TENSOR_MAP_SWIZZLE_128B);
        make_map(fn, &tm_x, x, D_, L_, 64, 128);
        make_map(fn, &tm_sT, p_sT, L_, D_, 64, 64);
        make_map(fn, &tm_out, out, D_, L_, 64, 16);
        cudaFuncSetAttribute(mega_kernel, cudaFuncAttributeMaxDynamicSharedMemorySize, MG_SMEM);
        last_ptrs[0] = wg; last_ptrs[1] = wu; last_ptrs[2] = wd; last_ptrs[3] = x; last_ptrs[4] = out;
        init = true;
    }
    MegaParams P = {x, A_re, A_im, B_re, B_im, C_re, C_im, log_dt, Dskip, wg, wu, wd};
    launch_pdl(mega_kernel, 128, 384, MG_SMEM, false, 2, P, tm_xn, tm_wg4, tm_wu4, tm_wg3, tm_wu3, tm_h, tm_wd, tm_x, tm_sT, tm_out);
}
```

```cpp
#include <cuda_runtime.h>
#include <cuda_bf16.h>
#include <cuda.h>
#include <stdint.h>

namespace {

constexpr int L_ = 2048, D_ = 512, NS_ = 128, F_ = 1792;

__device__ __align__(1024) __nv_bfloat16 g_xn[L_ * D_];
__device__ __align__(1024) __nv_bfloat16 g_xnT[D_ * L_];
__device__ __align__(1024) __nv_bfloat16 g_sT[D_ * L_];
__device__ __align__(1024) __nv_bfloat16 g_h[L_ * F_];
__device__ unsigned int g_ln_count, g_conv_count, g_done_count, g_h_count[32];

#define STAMP(k, i)

__device__ __forceinline__ uint32_t smem_u32(const void* p) { return (uint32_t)__cvta_generic_to_shared(p); }

__device__ __forceinline__ void mbar_init(uint32_t bar, uint32_t cnt) {
    asm volatile("mbarrier.init.shared::cta.b64 [%0], %1;" ::"r"(bar), "r"(cnt) : "memory");
}
__device__ __forceinline__ void mbar_expect_tx(uint32_t bar, uint32_t bytes) {
    asm volatile("mbarrier.arrive.expect_tx.shared::cta.b64 _, [%0], %1;" ::"r"(bar), "r"(bytes) : "memory");
}
__device__ __forceinline__ void mbar_arrive(uint32_t bar) {
    asm volatile("mbarrier.arrive.shared::cta.b64 _, [%0];" ::"r"(bar) : "memory");
}
__device__ __forceinline__ void mbar_wait(uint32_t bar, uint32_t parity) {
    asm volatile(
        "{\n.reg .pred p;\n"
        "WAIT_LOOP:\n"
        "mbarrier.try_wait.parity.shared::cta.b64 p, [%0], %1;\n"
        "@p bra WAIT_DONE;\n"
        "bra WAIT_LOOP;\n"
        "WAIT_DONE:\n}\n" ::"r"(bar), "r"(parity) : "memory");
}
__device__ __forceinline__ void tma_load_2d(uint32_t dst, const CUtensorMap* tm, int c0, int c1, uint32_t bar) {
    asm volatile(
        "cp.async.bulk.tensor.2d.shared::cluster.global.mbarrier::complete_tx::bytes [%0], [%1, {%3, %4}], [%2];"
        ::"r"(dst), "l"((uint64_t)tm), "r"(bar), "r"(c0), "r"(c1) : "memory");
}
__device__ __forceinline__ void prefetch_tmap(const CUtensorMap* tm) {
    asm volatile("prefetch.tensormap [%0];" ::"l"((uint64_t)tm) : "memory");
}
__device__ __forceinline__ uint64_t make_desc(uint32_t addr, uint32_t lbo, uint32_t sbo, uint64_t mode = 1) {
    uint64_t d = 0;
    d |= (uint64_t)((addr & 0x3FFFF) >> 4);
    d |= (uint64_t)((lbo >> 4) & 0x3FFF) << 16;
    d |= (uint64_t)((sbo >> 4) & 0x3FFF) << 32;
    d |= mode << 62;
    return d;
}
__device__ __forceinline__ void fence_async_smem() { asm volatile("fence.proxy.async.shared::cta;" ::: "memory"); }
__device__ __forceinline__ void wgmma_fence() { asm volatile("wgmma.fence.sync.aligned;" ::: "memory"); }
__device__ __forceinline__ void wgmma_commit() { asm volatile("wgmma.commit_group.sync.aligned;" ::: "memory"); }
template <int N> __device__ __forceinline__ void wgmma_wait() {
    asm volatile("wgmma.wait_group.sync.aligned %0;" ::"n"(N) : "memory");
}

#define R8(a, i) "+f"(a[i + 0]), "+f"(a[i + 1]), "+f"(a[i + 2]), "+f"(a[i + 3]), "+f"(a[i + 4]), "+f"(a[i + 5]), "+f"(a[i + 6]), "+f"(a[i + 7])

__device__ __forceinline__ void wgmma_n256_k32(float* a, uint64_t da0, uint64_t da1, uint64_t db0, uint64_t db1, int scale_d) {
    asm volatile(
        "{\n.reg .pred p;\nsetp.ne.b32 p, %132, 0;\n"
        "wgmma.mma_async.sync.aligned.m64n256k16.f32.bf16.bf16 {%0,%1,%2,%3,%4,%5,%6,%7,%8,%9,%10,%11,%12,%13,%14,%15,%16,%17,%18,%19,%20,%21,%22,%23,%24,%25,%26,%27,%28,%29,%30,%31,%32,%33,%34,%35,%36,%37,%38,%39,%40,%41,%42,%43,%44,%45,%46,%47,%48,%49,%50,%51,%52,%53,%54,%55,%56,%57,%58,%59,%60,%61,%62,%63,%64,%65,%66,%67,%68,%69,%70,%71,%72,%73,%74,%75,%76,%77,%78,%79,%80,%81,%82,%83,%84,%85,%86,%87,%88,%89,%90,%91,%92,%93,%94,%95,%96,%97,%98,%99,%100,%101,%102,%103,%104,%105,%106,%107,%108,%109,%110,%111,%112,%113,%114,%115,%116,%117,%118,%119,%120,%121,%122,%123,%124,%125,%126,%127}, %128, %130, p, 1, 1, 0, 1;\n"
        "wgmma.mma_async.sync.aligned.m64n256k16.f32.bf16.bf16 {%0,%1,%2,%3,%4,%5,%6,%7,%8,%9,%10,%11,%12,%13,%14,%15,%16,%17,%18,%19,%20,%21,%22,%23,%24,%25,%26,%27,%28,%29,%30,%31,%32,%33,%34,%35,%36,%37,%38,%39,%40,%41,%42,%43,%44,%45,%46,%47,%48,%49,%50,%51,%52,%53,%54,%55,%56,%57,%58,%59,%60,%61,%62,%63,%64,%65,%66,%67,%68,%69,%70,%71,%72,%73,%74,%75,%76,%77,%78,%79,%80,%81,%82,%83,%84,%85,%86,%87,%88,%89,%90,%91,%92,%93,%94,%95,%96,%97,%98,%99,%100,%101,%102,%103,%104,%105,%106,%107,%108,%109,%110,%111,%112,%113,%114,%115,%116,%117,%118,%119,%120,%121,%122,%123,%124,%125,%126,%127}, %129, %131, 1, 1, 1, 0, 1;\n"
        "}\n"
        : R8(a, 0), R8(a, 8), R8(a, 16), R8(a, 24), R8(a, 32), R8(a, 40), R8(a, 48), R8(a, 56), R8(a, 64), R8(a, 72), R8(a, 80), R8(a, 88), R8(a, 96), R8(a, 104), R8(a, 112), R8(a, 120)
        : "l"(da0), "l"(da1), "l"(db0), "l"(db1), "r"(scale_d));
}
__device__ __forceinline__ void wgmma_n192(float* a, uint64_t da0, uint64_t db0, int scale_d) {
    asm volatile(
        "{\n.reg .pred p;\nsetp.ne.b32 p, %98, 0;\n"
        "wgmma.mma_async.sync.aligned.m64n192k16.f32.bf16.bf16 {%0,%1,%2,%3,%4,%5,%6,%7,%8,%9,%10,%11,%12,%13,%14,%15,%16,%17,%18,%19,%20,%21,%22,%23,%24,%25,%26,%27,%28,%29,%30,%31,%32,%33,%34,%35,%36,%37,%38,%39,%40,%41,%42,%43,%44,%45,%46,%47,%48,%49,%50,%51,%52,%53,%54,%55,%56,%57,%58,%59,%60,%61,%62,%63,%64,%65,%66,%67,%68,%69,%70,%71,%72,%73,%74,%75,%76,%77,%78,%79,%80,%81,%82,%83,%84,%85,%86,%87,%88,%89,%90,%91,%92,%93,%94,%95}, %96, %97, p, 1, 1, 0, 1;\n"
        "}\n"
        : R8(a, 0), R8(a, 8), R8(a, 16), R8(a, 24), R8(a, 32), R8(a, 40), R8(a, 48), R8(a, 56), R8(a, 64), R8(a, 72), R8(a, 80), R8(a, 88)
        : "l"(da0), "l"(db0), "r"(scale_d));
}
__device__ __forceinline__ void wgmma_n128_k64(float* a, uint64_t da0, uint64_t da1, uint64_t da2, uint64_t da3,
                                               uint64_t db0, uint64_t db1, uint64_t db2, uint64_t db3, int scale_d) {
    asm volatile(
        "{\n.reg .pred p;\nsetp.ne.b32 p, %72, 0;\n"
        "wgmma.mma_async.sync.aligned.m64n128k16.f32.bf16.bf16 {%0,%1,%2,%3,%4,%5,%6,%7,%8,%9,%10,%11,%12,%13,%14,%15,%16,%17,%18,%19,%20,%21,%22,%23,%24,%25,%26,%27,%28,%29,%30,%31,%32,%33,%34,%35,%36,%37,%38,%39,%40,%41,%42,%43,%44,%45,%46,%47,%48,%49,%50,%51,%52,%53,%54,%55,%56,%57,%58,%59,%60,%61,%62,%63}, %64, %68, p, 1, 1, 0, 1;\n"
        "wgmma.mma_async.sync.aligned.m64n128k16.f32.bf16.bf16 {%0,%1,%2,%3,%4,%5,%6,%7,%8,%9,%10,%11,%12,%13,%14,%15,%16,%17,%18,%19,%20,%21,%22,%23,%24,%25,%26,%27,%28,%29,%30,%31,%32,%33,%34,%35,%36,%37,%38,%39,%40,%41,%42,%43,%44,%45,%46,%47,%48,%49,%50,%51,%52,%53,%54,%55,%56,%57,%58,%59,%60,%61,%62,%63}, %65, %69, 1, 1, 1, 0, 1;\n"
        "wgmma.mma_async.sync.aligned.m64n128k16.f32.bf16.bf16 {%0,%1,%2,%3,%4,%5,%6,%7,%8,%9,%10,%11,%12,%13,%14,%15,%16,%17,%18,%19,%20,%21,%22,%23,%24,%25,%26,%27,%28,%29,%30,%31,%32,%33,%34,%35,%36,%37,%38,%39,%40,%41,%42,%43,%44,%45,%46,%47,%48,%49,%50,%51,%52,%53,%54,%55,%56,%57,%58,%59,%60,%61,%62,%63}, %66, %70, 1, 1, 1, 0, 1;\n"
        "wgmma.mma_async.sync.aligned.m64n128k16.f32.bf16.bf16 {%0,%1,%2,%3,%4,%5,%6,%7,%8,%9,%10,%11,%12,%13,%14,%15,%16,%17,%18,%19,%20,%21,%22,%23,%24,%25,%26,%27,%28,%29,%30,%31,%32,%33,%34,%35,%36,%37,%38,%39,%40,%41,%42,%43,%44,%45,%46,%47,%48,%49,%50,%51,%52,%53,%54,%55,%56,%57,%58,%59,%60,%61,%62,%63}, %67, %71, 1, 1, 1, 0, 1;\n"
        "}\n"
        : R8(a, 0), R8(a, 8), R8(a, 16), R8(a, 24), R8(a, 32), R8(a, 40), R8(a, 48), R8(a, 56)
        : "l"(da0), "l"(da1), "l"(da2), "l"(da3), "l"(db0), "l"(db1), "l"(db2), "l"(db3), "r"(scale_d));
}

__device__ __forceinline__ float bf16_round(float x) {
    uint32_t p; asm("cvt.rn.bf16x2.f32 %0, %1, %2;" : "=r"(p) : "f"(x), "f"(0.0f));
    return __uint_as_float(p);
}
__device__ __forceinline__ uint32_t pack_bf16(float lo, float hi) {
    __nv_bfloat162 v = __floats2bfloat162_rn(lo, hi);
    return *reinterpret_cast<uint32_t*>(&v);
}
__device__ __forceinline__ float bf_lo(uint32_t v) { return __uint_as_float(v << 16); }
__device__ __forceinline__ float bf_hi(uint32_t v) { return __uint_as_float(v & 0xFFFF0000u); }

struct cplx { float r, i; };
__device__ __forceinline__ cplx cmul(cplx a, cplx b) {
    cplx c; c.r = a.r * b.r - a.i * b.i; c.i = a.r * b.i + a.i * b.r; return c;
}
__device__ __forceinline__ cplx csq(cplx a) {
    cplx c; c.r = a.r * a.r - a.i * a.i; c.i = 2.0f * a.r * a.i; return c;
}
__device__ __forceinline__ cplx cexp_m(float ar2, float ai2, float m) {
    float mag;
    asm("ex2.approx.ftz.f32 %0, %1;" : "=f"(mag) : "f"(ar2 * m));
    float rr = ai2 * m;
    rr -= (rr + 12582912.0f) - 12582912.0f;
    float th = rr * 6.283185307179586f;
    cplx c; c.r = mag * __cosf(th); c.i = mag * __sinf(th);
    return c;
}
__device__ __forceinline__ uint32_t to_tf32(float x) { return __float_as_uint(x) + 0x1000u; }
__device__ __forceinline__ void mma_tf32(float* c, uint32_t a0, uint32_t a1, uint32_t a2, uint32_t a3, uint32_t b0, uint32_t b1) {
    asm volatile("mma.sync.aligned.m16n8k8.row.col.f32.tf32.tf32.f32 {%0,%1,%2,%3}, {%4,%5,%6,%7}, {%8,%9}, {%0,%1,%2,%3};"
                 : "+f"(c[0]), "+f"(c[1]), "+f"(c[2]), "+f"(c[3])
                 : "r"(a0), "r"(a1), "r"(a2), "r"(a3), "r"(b0), "r"(b1));
}
__device__ __forceinline__ void mma_bf16(float* c, uint32_t a0, uint32_t a1, uint32_t a2, uint32_t a3, uint32_t b0, uint32_t b1) {
    asm volatile("mma.sync.aligned.m16n8k16.row.col.f32.bf16.bf16.f32 {%0,%1,%2,%3}, {%4,%5,%6,%7}, {%8,%9}, {%0,%1,%2,%3};"
                 : "+f"(c[0]), "+f"(c[1]), "+f"(c[2]), "+f"(c[3])
                 : "r"(a0), "r"(a1), "r"(a2), "r"(a3), "r"(b0), "r"(b1));
}
__device__ __forceinline__ void named_bar(int id, int n) { asm volatile("bar.sync %0, %1;" ::"r"(id), "r"(n) : "memory"); }
__device__ __forceinline__ void ldsm_x4(uint32_t addr, uint32_t& r0, uint32_t& r1, uint32_t& r2, uint32_t& r3) {
    asm volatile("ldmatrix.sync.aligned.m8n8.x4.shared.b16 {%0,%1,%2,%3}, [%4];" : "=r"(r0), "=r"(r1), "=r"(r2), "=r"(r3) : "r"(addr));
}
__device__ __forceinline__ void ldsm_x4_t(uint32_t addr, uint32_t& r0, uint32_t& r1, uint32_t& r2, uint32_t& r3) {
    asm volatile("ldmatrix.sync.aligned.m8n8.x4.trans.shared.b16 {%0,%1,%2,%3}, [%4];" : "=r"(r0), "=r"(r1), "=r"(r2), "=r"(r3) : "r"(addr));
}

constexpr int CV_CH = 4;
constexpr int CV_O_CONST = 0;
constexpr int CV_O_KP = 12288;
constexpr int CV_EARLY = 12288 + 7776;
constexpr int CV_O_Q = 0;
constexpr int CV_O_Q2 = CV_O_Q + 2304;
constexpr int CV_O_Q3 = CV_O_Q2 + 1024;
constexpr int CV_O_Q4X = CV_O_Q3 + 768;
constexpr int CV_O_W3 = CV_O_Q4X + 256;
constexpr int CV_O_W5 = CV_O_W3 + 3104;
constexpr int CV_O_W7 = CV_O_W5 + 3104;
constexpr int CV_O_W9 = CV_O_W7 + 2048;
constexpr int CV_O_U = CV_O_W9 + 2048;
constexpr int CV_LATE = CV_O_U + 4352;
constexpr int CV_LATE_BASE = 229376 - CV_CH * CV_LATE;
constexpr int CV_TILE_OFF = CV_CH * CV_EARLY;
static_assert(CV_TILE_OFF + 16 * (D_ + 8) * 2 <= CV_LATE_BASE && CV_LATE_BASE >= 131072 + 16384, "front layout");
static_assert(CV_O_W3 >= 4096 && CV_O_U - CV_O_W3 >= 8192 && (CV_LATE % 16) == 0 && (CV_EARLY % 16) == 0, "front layout");

constexpr int LN_ROWS = 16;

template <typename PF>
__device__ __forceinline__ void front_phase(PF prefetch_fn, uint8_t* smem, const __nv_bfloat16* __restrict__ x,
                                            const __nv_bfloat16* __restrict__ A_re, const __nv_bfloat16* __restrict__ A_im,
                                            const __nv_bfloat16* __restrict__ B_re, const __nv_bfloat16* __restrict__ B_im,
                                            const __nv_bfloat16* __restrict__ C_re, const __nv_bfloat16* __restrict__ C_im,
                                            const __nv_bfloat16* __restrict__ log_dt, const __nv_bfloat16* __restrict__ Dskip,
                                            const __nv_bfloat16* __restrict__ wg, const __nv_bfloat16* __restrict__ wu,
                                            const __nv_bfloat16* __restrict__ wd) {
    const int warp = threadIdx.x >> 5, lane = threadIdx.x & 31;
    const int ch = warp / 3, w = warp - 3 * ch, tc = threadIdx.x - 96 * ch;
    const int d = blockIdx.x * CV_CH + ch;
    const int g = lane >> 2, t = lane & 3;
    uint8_t* base = smem + CV_LATE_BASE + ch * CV_LATE;
    float4* s_const = reinterpret_cast<float4*>(smem + ch * CV_EARLY + CV_O_CONST);
    float* s_kp = reinterpret_cast<float*>(smem + ch * CV_EARLY + CV_O_KP);
    uint32_t* s_q = reinterpret_cast<uint32_t*>(base + CV_O_Q);
    uint32_t* s_q2 = reinterpret_cast<uint32_t*>(base + CV_O_Q2);
    uint32_t* s_q3 = reinterpret_cast<uint32_t*>(base + CV_O_Q3);
    uint32_t* s_q4 = reinterpret_cast<uint32_t*>(base + CV_O_Q4X);
    __nv_bfloat16* s_u = reinterpret_cast<__nv_bfloat16*>(base + CV_O_U);
    const int bar_id = 5 + ch;
    const __nv_bfloat16 p_dsk = Dskip[d];
    __nv_bfloat16 (*tile)[D_ + 8] = reinterpret_cast<__nv_bfloat16 (*)[D_ + 8]>(smem + CV_TILE_OFF);

    if (warp < 8) {
        const int row = blockIdx.x * LN_ROWS + warp * 2;
        uint4 xv[2][2];
#pragma unroll
        for (int r = 0; r < 2; r++) {
            xv[r][0] = *reinterpret_cast<const uint4*>(x + (size_t)(row + r) * D_ + lane * 8);
            xv[r][1] = *reinterpret_cast<const uint4*>(x + (size_t)(row + r) * D_ + 256 + lane * 8);
        }
        float f[2][16], sm[2], q[2];
#pragma unroll
        for (int r = 0; r < 2; r++) {
            const uint32_t wv[8] = {xv[r][0].x, xv[r][0].y, xv[r][0].z, xv[r][0].w, xv[r][1].x, xv[r][1].y, xv[r][1].z, xv[r][1].w};
#pragma unroll
            for (int i = 0; i < 8; i++) { f[r][2 * i] = bf_lo(wv[i]); f[r][2 * i + 1] = bf_hi(wv[i]); }
            sm[r] = 0.f;
#pragma unroll
            for (int i = 0; i < 16; i++) sm[r] += f[r][i];
        }
#pragma unroll
        for (int o = 16; o > 0; o >>= 1) { sm[0] += __shfl_xor_sync(0xffffffffu, sm[0], o); sm[1] += __shfl_xor_sync(0xffffffffu, sm[1], o); }
#pragma unroll
        for (int r = 0; r < 2; r++) {
            sm[r] *= (1.0f / D_);
            q[r] = 0.f;
#pragma unroll
            for (int i = 0; i < 16; i++) { float dd = f[r][i] - sm[r]; q[r] += dd * dd; }
        }
#pragma unroll
        for (int o = 16; o > 0; o >>= 1) { q[0] += __shfl_xor_sync(0xffffffffu, q[0], o); q[1] += __shfl_xor_sync(0xffffffffu, q[1], o); }
#pragma unroll
        for (int r = 0; r < 2; r++) {
            const float mb = bf16_round(sm[r]);
            const float vb = bf16_round(q[r] * (1.0f / D_));
            const float den = bf16_round(sqrtf(bf16_round(vb + 1e-5f)));
            uint32_t o[8];
#pragma unroll
            for (int i = 0; i < 8; i++) {
                float a = __fdiv_rn(bf16_round(f[r][2 * i] - mb), den);
                float b = __fdiv_rn(bf16_round(f[r][2 * i + 1] - mb), den);
                o[i] = pack_bf16(a, b);
            }
            __nv_bfloat16* dst = g_xn + (size_t)(row + r) * D_;
            *reinterpret_cast<uint4*>(dst + lane * 8) = make_uint4(o[0], o[1], o[2], o[3]);
            *reinterpret_cast<uint4*>(dst + 256 + lane * 8) = make_uint4(o[4], o[5], o[6], o[7]);
            *reinterpret_cast<uint4*>(&tile[warp * 2 + r][lane * 8]) = make_uint4(o[0], o[1], o[2], o[3]);
            *reinterpret_cast<uint4*>(&tile[warp * 2 + r][256 + lane * 8]) = make_uint4(o[4], o[5], o[6], o[7]);
        }
    } else {
        const int cc_ = warp - 8, dd = blockIdx.x * CV_CH + cc_;
        float4* sc = reinterpret_cast<float4*>(smem + cc_ * CV_EARLY + CV_O_CONST);
        __nv_bfloat16 pr[4][6];
#pragma unroll
        for (int j = 0; j < 4; j++) {
            const size_t off = (size_t)dd * NS_ + lane + 32 * j;
            pr[j][0] = A_re[off]; pr[j][1] = A_im[off]; pr[j][2] = B_re[off]; pr[j][3] = B_im[off]; pr[j][4] = C_re[off]; pr[j][5] = C_im[off];
        }
        const float dt = bf16_round(expf(__bfloat162float(log_dt[dd])));
        float tail = 0.f;
#pragma unroll
        for (int j = 0; j < 4; j++) {
            const float ar = dt * __bfloat162float(pr[j][0]), ai = dt * __bfloat162float(pr[j][1]);
            const cplx db = {dt * __bfloat162float(pr[j][2]), dt * __bfloat162float(pr[j][3])};
            const cplx cc = {__bfloat162float(pr[j][4]), __bfloat162float(pr[j][5])};
            const cplx cb = cmul(cc, db);
            const float ar2 = ar * 1.4426950408889634f, ai2 = ai * 0.15915494309189535f;
            const cplx e8 = cexp_m(ar2, ai2, 8.f), e128 = cexp_m(ar2, ai2, 128.f);
            const cplx cb8 = cmul(cb, e8);
            const cplx e256 = cexp_m(ar2, ai2, 256.f), e512 = cexp_m(ar2, ai2, 512.f), e1024 = cexp_m(ar2, ai2, 1024.f);
            const cplx c256 = cmul(cb, e256), c512 = cmul(cb, e512), c1024 = cmul(cb, e1024);
            const cplx c768 = cmul(c512, e256), c1280 = cmul(c1024, e256), c1536 = cmul(c1024, e512);
            const cplx c1792 = cmul(c1536, e256);
            tail += cmul(c1024, e1024).r;
            float4* c = sc + (lane + 32 * j) * 6;
            c[0] = make_float4(ar2, ai2, cb.r, cb.i);
            c[1] = make_float4(e128.r, e128.i, cb8.r, cb8.i);
            c[2] = make_float4(c256.r, c256.i, e8.r, e8.i);
            c[3] = make_float4(c512.r, c512.i, c768.r, c768.i);
            c[4] = make_float4(c1024.r, c1024.i, c1280.r, c1280.i);
            c[5] = make_float4(c1536.r, c1536.i, c1792.r, c1792.i);
        }
#pragma unroll
        for (int o = 16; o > 0; o >>= 1) tail += __shfl_xor_sync(0xffffffffu, tail, o);
        if (lane == 0) {
            float* kp = reinterpret_cast<float*>(smem + cc_ * CV_EARLY + CV_O_KP);
            kp[640] = tail; kp[648 + 640] = 0.f; kp[1296 + 640] = 0.f;
        }
    }
    __syncthreads();
    if (threadIdx.x == 0) STAMP(0, 3);
#pragma unroll
    for (int rep = 0; rep < 2; rep++) {
        const int c = threadIdx.x + 384 * rep;
        if (c < D_) {
            uint32_t ot[8];
#pragma unroll
            for (int i = 0; i < 8; i++) {
                uint32_t lo = *reinterpret_cast<const uint16_t*>(&tile[2 * i][c]);
                uint32_t hi = *reinterpret_cast<const uint16_t*>(&tile[2 * i + 1][c]);
                ot[i] = lo | (hi << 16);
            }
            __nv_bfloat16* dT = g_xnT + (size_t)c * L_ + blockIdx.x * LN_ROWS;
            *reinterpret_cast<uint4*>(dT) = make_uint4(ot[0], ot[1], ot[2], ot[3]);
            *reinterpret_cast<uint4*>(dT + 8) = make_uint4(ot[4], ot[5], ot[6], ot[7]);
        }
    }
    if (threadIdx.x < 336) {
        const int m = threadIdx.x / 112, i = threadIdx.x - m * 112;
        const char* wp = (const char*)(m == 0 ? wg : (m == 1 ? wu : wd));
        asm volatile("prefetch.global.L2 [%0];" ::"l"(wp + ((size_t)blockIdx.x * 112 + i) * 128));
    }
    __syncthreads();
    if (threadIdx.x == 0) STAMP(1, 1);
    {
        float acc[5][4];
#pragma unroll
        for (int i = 0; i < 5; i++) { acc[i][0] = acc[i][1] = acc[i][2] = acc[i][3] = 0.f; }
        const float gf = (float)g;
        const int src4 = ((g & 3) << 2) | t;
#pragma unroll 2
        for (int s = w; s < 32; s += 3) {
            if (s == 17 && threadIdx.x == 352) asm volatile("red.release.gpu.global.add.u32 [%0], 1;" ::"l"(&g_ln_count) : "memory");
            const float4* c = s_const + (s * 4 + t) * 6;
            const float4 k0 = c[0], k1 = c[1], k2 = c[2];
            const float2 k3 = reinterpret_cast<const float2*>(c + 3)[g >> 2];
            const float2 k4 = reinterpret_cast<const float2*>(c + 4)[g >> 1];
            const cplx cb = {k0.z, k0.w}, e128 = {k1.x, k1.y}, cb8 = {k1.z, k1.w}, c256 = {k2.x, k2.y}, e8 = {k2.z, k2.w};
            const cplx c2 = {k3.x, k3.y}, c3 = {k4.x, k4.y};
            const cplx p1 = cexp_m(k0.x, k0.y, gf);
            const cplx p2 = csq(p1), p4 = csq(p2);
            const cplx r16a = csq(csq(p4));
            cplx q4;
            q4.r = __shfl_sync(0xffffffffu, p4.r, src4);
            q4.i = __shfl_sync(0xffffffffu, p4.i, src4);
            const cplx r16b = cmul(r16a, e128);
            const cplx f0a = cmul(cb, p1), f0b = cmul(cb8, p1), f1 = cmul(c256, p2), f2 = cmul(c2, q4);
            cplx f3 = cmul(c3, e8);
            if (!(g & 1)) f3 = c3;
            const uint32_t a0 = to_tf32(r16a.r), a1 = to_tf32(r16b.r), a2 = to_tf32(-r16a.i), a3 = to_tf32(-r16b.i);
            mma_tf32(acc[0], a0, a1, a2, a3, to_tf32(f0a.r), to_tf32(f0a.i));
            mma_tf32(acc[1], a0, a1, a2, a3, to_tf32(f0b.r), to_tf32(f0b.i));
            mma_tf32(acc[2], a0, a1, a2, a3, to_tf32(f1.r), to_tf32(f1.i));
            mma_tf32(acc[3], a0, a1, a2, a3, to_tf32(f2.r), to_tf32(f2.i));
            mma_tf32(acc[4], a0, a1, a2, a3, to_tf32(f3.r), to_tf32(f3.i));
        }
        float* kv = s_kp + w * 648;
#pragma unroll
        for (int hh = 0; hh < 2; hh++) {
            const int i = g + 8 * hh;
            *reinterpret_cast<float2*>(kv + 16 * i + 2 * t) = make_float2(acc[0][2 * hh], acc[0][2 * hh + 1]);
            *reinterpret_cast<float2*>(kv + 16 * i + 8 + 2 * t) = make_float2(acc[1][2 * hh], acc[1][2 * hh + 1]);
            *reinterpret_cast<float2*>(kv + 256 + 8 * i + 2 * t) = make_float2(acc[2][2 * hh], acc[2][2 * hh + 1]);
            *reinterpret_cast<float2*>(kv + 384 + 64 * (t >> 1) + 2 * (t & 1) + 4 * i) = make_float2(acc[3][2 * hh], acc[3][2 * hh + 1]);
            *reinterpret_cast<float2*>(kv + 512 + 32 * t + 2 * i) = make_float2(acc[4][2 * hh], acc[4][2 * hh + 1]);
        }
    }
    named_bar(bar_id, 96);
    if (threadIdx.x == 0) STAMP(1, 2);
#pragma unroll
    for (int i = 0; i < 7; i++) {
        const int idx = tc + 96 * i;
        if (idx < 641) s_kp[idx] = (s_kp[idx] + s_kp[648 + idx]) + s_kp[1296 + idx];
    }
    named_bar(bar_id, 96);
    {
        auto kdir = [&](int l) -> float {
            if (l < 0 || l > 514) return 0.f;
            const int idx = (l < 256) ? l : (l > 512 ? 384 : 128 + ((l + ((l >> 1) & 1)) >> 1));
            return s_kp[idx];
        };
#pragma unroll
        for (int i = 0; i < 6; i++) {
            const int e = tc + 96 * i;
            s_q[e] = pack_bf16(kdir(e - 16), kdir(e - 17));
        }
        if (tc < 64) {
            const int xx = 1008 + tc;
            const float k1024 = s_kp[512];
            s_q4[tc] = pack_bf16((xx == 1027 || xx == 1028) ? k1024 : 0.f, (xx == 1028 || xx == 1029) ? k1024 : 0.f);
        }
#pragma unroll
        for (int i = 0; i < 3; i++) {
            const int e = tc + 96 * i;
            if (e < 256) {
                const int a = e >> 6, ii = (e & 63) - 16;
                const int b = 385 + (a >> 1) + 2 * (a & 1);
                const float v0 = (ii >= 0 && ii < 32) ? s_kp[b + 4 * ii] : 0.f;
                const float v1 = (ii >= 1 && ii < 33) ? s_kp[b + 4 * (ii - 1)] : 0.f;
                s_q2[e] = pack_bf16(v0, v1);
            }
        }
#pragma unroll
        for (int a = 0; a < 2; a++) {
            const int jj = tc - 16;
            const float v0 = (jj >= 0 && jj < 64) ? s_kp[513 + a + 2 * jj] : 0.f;
            const float v1 = (jj >= 1 && jj < 65) ? s_kp[513 + a + 2 * (jj - 1)] : 0.f;
            s_q3[96 * a + tc] = pack_bf16(v0, v1);
        }
    }
    if (threadIdx.x == 0) STAMP(1, 3);
    if (threadIdx.x == 0) {
        unsigned int v = 0;
        for (int spin = 0; spin < (1 << 22); spin++) {
            asm volatile("ld.acquire.gpu.global.u32 %0, [%1];" : "=r"(v) : "l"(&g_ln_count) : "memory");
            if (v >= gridDim.x) break;
        }
    }
    fence_async_smem();
    __syncthreads();
    if (threadIdx.x == 0) STAMP(1, 4);
    prefetch_fn();
    {
        if (tc < 16) *reinterpret_cast<uint4*>(s_u + tc * 8) = make_uint4(0, 0, 0, 0);
        const uint4* src = reinterpret_cast<const uint4*>(g_xnT + (size_t)d * L_);
        uint4 v[3];
#pragma unroll
        for (int i = 0; i < 3; i++) if (tc + 96 * i < 256) v[i] = src[tc + 96 * i];
#pragma unroll
        for (int i = 0; i < 3; i++) if (tc + 96 * i < 256) *reinterpret_cast<uint4*>(s_u + 128 + (tc + 96 * i) * 8) = v[i];
        if (tc < 2) *reinterpret_cast<uint4*>(base + (tc ? CV_O_W5 : CV_O_W3)) = make_uint4(0, 0, 0, 0);
    }
    named_bar(bar_id, 96);
    if (w == 2) {
#pragma unroll 2
      for (int rep = 0; rep < 6; rep++) {
        const int m = lane + 32 * rep;
        float P[30];
        const uint4* up = reinterpret_cast<const uint4*>(s_u + 128 + 8 * m - 24);
        P[0] = 0.f;
#pragma unroll
        for (int c4 = 0; c4 < 4; c4++) {
            const uint4 v = up[c4];
            const uint32_t ww[4] = {v.x, v.y, v.z, v.w};
#pragma unroll
            for (int j = 0; j < 4; j++) {
                const int k = c4 * 8 + 2 * j;
                if (k + 1 <= 29) P[k + 1] = P[k] + bf_lo(ww[j]);
                if (k + 2 <= 29) P[k + 2] = P[k + 1] + bf_hi(ww[j]);
            }
        }
        uint32_t o3[4], o5[4], o7[4], o9[4];
#pragma unroll
        for (int j = 0; j < 4; j++) {
            const int i = 2 * j;
            o3[j] = pack_bf16(P[i + 22] - P[i + 19], P[i + 23] - P[i + 20]);
            o5[j] = pack_bf16(P[i + 19] - P[i + 14], P[i + 20] - P[i + 15]);
            o7[j] = pack_bf16(P[i + 20] - P[i + 13], P[i + 21] - P[i + 14]);
            o9[j] = pack_bf16(P[i + 13] - P[i + 4], P[i + 14] - P[i + 5]);
        }
        *reinterpret_cast<uint4*>(base + CV_O_W3 + 16 + m * 16) = make_uint4(o3[0], o3[1], o3[2], o3[3]);
        *reinterpret_cast<uint4*>(base + CV_O_W5 + 16 + m * 16) = make_uint4(o5[0], o5[1], o5[2], o5[3]);
        if (m < 128) {
            *reinterpret_cast<uint4*>(base + CV_O_W7 + m * 16) = make_uint4(o7[0], o7[1], o7[2], o7[3]);
            *reinterpret_cast<uint4*>(base + CV_O_W9 + m * 16) = make_uint4(o9[0], o9[1], o9[2], o9[3]);
        }
    }
      named_bar(bar_id, 96);
      return;
    }
    if (threadIdx.x == 0) STAMP(1, 5);
    const int hb = w;
    float acc[16][4];
#pragma unroll
    for (int i = 0; i < 16; i++) { acc[i][0] = acc[i][1] = acc[i][2] = acc[i][3] = 0.f; }
    const uint32_t sb_addr = smem_u32(base);
    const int mi = lane >> 3, rowi = lane & 7;
#pragma unroll 1
    for (int rr = 0; rr < 4; rr++) {
        const int r = 4 * hb + rr;
        uint32_t ub[16][2];
        {
            const uint32_t addr = sb_addr + CV_O_U + (uint32_t)((128 + 16 * (8 * (mi >> 1) + rowi - r) + 8 * (mi & 1)) * 2);
#pragma unroll
            for (int j = 0; j < 16; j += 2) ldsm_x4(addr + (uint32_t)(j * 256), ub[j][0], ub[j][1], ub[j + 1][0], ub[j + 1][1]);
        }
        const uint32_t* qp = s_q + 16 + 16 * r + g - 2 * t;
        uint32_t af[4][3];
#pragma unroll
        for (int q = 0; q < 4; q++) { af[q][0] = qp[128 * q]; af[q][1] = qp[128 * q + 8]; af[q][2] = qp[128 * q - 8]; }
#pragma unroll
        for (int q = 0; q < 4; q++) {
#pragma unroll
            for (int nt = q; nt < 16; nt++) mma_bf16(acc[nt], af[q][0], af[q][1], af[q][2], af[q][0], ub[nt - q][0], ub[nt - q][1]);
        }
        if (r < 2) {
            {
                const uint32_t a0 = qp[512], a1 = qp[520], a2 = qp[504];
#pragma unroll
                for (int nt = 4; nt < 16; nt++) mma_bf16(acc[nt], a0, a1, a2, a0, ub[nt - 4][0], ub[nt - 4][1]);
            }
            {
                const uint32_t* q4p = s_q4 + 16 + 16 * r + g - 2 * t;
                const uint32_t a0 = q4p[0], a1 = q4p[8], a2 = q4p[-8];
#pragma unroll
                for (int nt = 8; nt < 16; nt++) mma_bf16(acc[nt], a0, a1, a2, a0, ub[nt - 8][0], ub[nt - 8][1]);
            }
        }
    }
    named_bar(bar_id, 96);
#pragma unroll 1
    for (int a = hb; a <= 3 * hb; a++) {
        uint32_t bq[7];
        const uint32_t* q2 = s_q2 + a * 64 + 16 + g - 2 * t - 32;
#pragma unroll
        for (int dlt = 3; dlt <= 9; dlt++) bq[dlt - 3] = q2[8 * dlt];
        const uint32_t addr = sb_addr + ((a >> 1) ? CV_O_W5 : CV_O_W3) + (uint32_t)((8 + 16 * (8 * (mi >> 1) + rowi) + 8 * (mi & 1) - 8 * (a & 1)) * 2);
        uint32_t aa[6][4];
#pragma unroll
        for (int kp = 0; kp < 6; kp++) ldsm_x4_t(addr + kp * 512, aa[kp][0], aa[kp][1], aa[kp][2], aa[kp][3]);
#pragma unroll
        for (int kp = 0; kp < 6; kp++) {
#pragma unroll
            for (int dlt = 4; dlt <= 9; dlt++) {
                if (2 * kp + dlt < 16) mma_bf16(acc[2 * kp + dlt], aa[kp][0], aa[kp][1], aa[kp][2], aa[kp][3], bq[dlt - 3], bq[dlt - 4]);
            }
        }
    }
    if (hb == 0) {
#pragma unroll 1
        for (int a = 0; a < 2; a++) {
            uint32_t bq[9];
            const uint32_t* q3 = s_q3 + a * 96 + 16 + g - 2 * t - 64;
#pragma unroll
            for (int dlt = 7; dlt <= 15; dlt++) bq[dlt - 7] = q3[8 * dlt];
            const uint32_t addr = sb_addr + (a ? CV_O_W9 : CV_O_W7) + (uint32_t)((16 * (8 * (mi >> 1) + rowi) + 8 * (mi & 1)) * 2);
            uint32_t aa[4][4];
#pragma unroll
            for (int kp = 0; kp < 4; kp++) ldsm_x4_t(addr + kp * 512, aa[kp][0], aa[kp][1], aa[kp][2], aa[kp][3]);
#pragma unroll
            for (int kp = 0; kp < 4; kp++) {
#pragma unroll
                for (int dlt = 8; dlt <= 15; dlt++) {
                    if (2 * kp + dlt < 16) mma_bf16(acc[2 * kp + dlt], aa[kp][0], aa[kp][1], aa[kp][2], aa[kp][3], bq[dlt - 7], bq[dlt - 8]);
                }
            }
        }
    }
    if (threadIdx.x == 0) STAMP(1, 6);
    named_bar(bar_id, 64);
    {
        float4* xch = reinterpret_cast<float4*>(base + CV_O_W3) + hb * 256;
        if (hb) {
#pragma unroll
            for (int i = 0; i < 8; i++) xch[i * 32 + lane] = make_float4(acc[i][0], acc[i][1], acc[i][2], acc[i][3]);
#pragma unroll
            for (int i = 0; i < 8; i++) { acc[i][0] = acc[8 + i][0]; acc[i][1] = acc[8 + i][1]; acc[i][2] = acc[8 + i][2]; acc[i][3] = acc[8 + i][3]; }
        } else {
#pragma unroll
            for (int i = 0; i < 8; i++) xch[i * 32 + lane] = make_float4(acc[8 + i][0], acc[8 + i][1], acc[8 + i][2], acc[8 + i][3]);
        }
    }
    named_bar(bar_id, 64);
    if (threadIdx.x == 0) STAMP(1, 10);
    {
        const float4* xch = reinterpret_cast<const float4*>(base + CV_O_W3) + (hb ^ 1) * 256 + lane;
        const float dsk = __bfloat162float(p_dsk);
        uint16_t* stg = reinterpret_cast<uint16_t*>(base + CV_O_Q);
        const uint16_t* uu = reinterpret_cast<const uint16_t*>(s_u) + 128;
#pragma unroll
        for (int i = 0; i < 8; i++) {
            const float4 p0 = xch[i * 32];
            const float y[4] = {acc[i][0] + p0.x, acc[i][1] + p0.y, acc[i][2] + p0.z, acc[i][3] + p0.w};
            const int nt = 8 * hb + i;
#pragma unroll
            for (int e = 0; e < 4; e++) {
                const int tau = 16 * (8 * nt + 2 * t + (e & 1)) + g + 8 * (e >> 1);
                const float sv = bf16_round(y[e]) + bf16_round(__uint_as_float((uint32_t)uu[tau] << 16) * dsk);
                stg[tau] = (uint16_t)(__float_as_uint(bf16_round(sv)) >> 16);
            }
        }
        __syncwarp();
        if (threadIdx.x == 0) STAMP(1, 11);
        uint4* dst = reinterpret_cast<uint4*>(g_sT + (size_t)d * L_ + hb * 1024);
        const uint4* srcp = reinterpret_cast<const uint4*>(stg + hb * 1024);
#pragma unroll
        for (int i = 0; i < 4; i++) dst[i * 32 + lane] = srcp[i * 32 + lane];
    }
}

__device__ __forceinline__ void mbar_arrive_remote(uint32_t bar, uint32_t cta) {
    asm volatile("{\n.reg .b32 ra;\nmapa.shared::cluster.u32 ra, %0, %1;\n"
                 "mbarrier.arrive.shared::cluster.b64 _, [ra];\n}\n" ::"r"(bar), "r"(cta) : "memory");
}
__device__ __forceinline__ void tma_store_2d(const CUtensorMap* tm, uint32_t src, int c0, int c1) {
    asm volatile("cp.async.bulk.tensor.2d.global.shared::cta.bulk_group [%0, {%2, %3}], [%1];"
                 ::"l"((uint64_t)tm), "r"(src), "r"(c0), "r"(c1) : "memory");
}
__device__ __forceinline__ void bulk_commit() { asm volatile("cp.async.bulk.commit_group;" ::: "memory"); }
template <int N> __device__ __forceinline__ void bulk_wait_read() { asm volatile("cp.async.bulk.wait_group.read %0;" ::"n"(N) : "memory"); }
__device__ __forceinline__ void stmatrix_x4(uint32_t addr, uint32_t r0, uint32_t r1, uint32_t r2, uint32_t r3) {
    asm volatile("stmatrix.sync.aligned.m8n8.x4.shared.b16 [%0], {%1,%2,%3,%4};" ::"r"(addr), "r"(r0), "r"(r1), "r"(r2), "r"(r3) : "memory");
}

constexpr int G1_STAGES = 5;
constexpr int G1_A_BYTES = 8 * 16384;
constexpr int G1_B_STAGE = 16384;
constexpr int G1_STG = 8 * 1024;
constexpr int G1_ITERS = 32;

__device__ __forceinline__ void tma_load_3d(uint32_t dst, const CUtensorMap* tm, int c0, int c1, int c2, uint32_t bar) {
    asm volatile(
        "cp.async.bulk.tensor.3d.shared::cluster.global.mbarrier::complete_tx::bytes [%0], [%1, {%3, %4, %5}], [%2];"
        ::"r"(dst), "l"((uint64_t)tm), "r"(bar), "r"(c0), "r"(c1), "r"(c2) : "memory");
}

__device__ __forceinline__ void tma_load_3d_mc(uint32_t dst, const CUtensorMap* tm, int c0, int c1, int c2, uint32_t bar, uint16_t mask) {
    asm volatile(
        "cp.async.bulk.tensor.3d.shared::cluster.global.mbarrier::complete_tx::bytes.multicast::cluster [%0], [%1, {%3, %4, %5}], [%2], %6;"
        ::"r"(dst), "l"((uint64_t)tm), "r"(bar), "r"(c0), "r"(c1), "r"(c2), "h"(mask) : "memory");
}

__device__ __forceinline__ float gelu_tanh(float x) {
    float u = x * (0.7978845608028654f + 0.035677408136300125f * x * x);
    float t; asm("tanh.approx.f32 %0, %1;" : "=f"(t) : "f"(u));
    float hx = 0.5f * x;
    return fmaf(hx, t, hx);
}
__device__ __forceinline__ uint32_t geglu_pair(uint32_t g2, uint32_t u2) {
    uint32_t a = pack_bf16(gelu_tanh(bf_lo(g2)), gelu_tanh(bf_hi(g2)));
    uint32_t r; asm("mul.rn.bf16x2 %0, %1, %2;" : "=r"(r) : "r"(a), "r"(u2));
    return r;
}

constexpr int G2_STAGES = 5;
constexpr int G2_STAGE = 16384 + 16384;
constexpr int G2_XCH = 32768;
constexpr int G2_EPI = 16384 + 16384;
constexpr int G2_KB = F_ / 64 / 2;

constexpr int MG_BAR_OFF = G2_STAGES * G2_STAGE + G2_XCH + G2_EPI;
constexpr int MG_SMEM = MG_BAR_OFF + 512 + 1024;
static_assert(MG_BAR_OFF == 229376 && G1_A_BYTES + G1_STAGES * G1_B_STAGE + G1_STG <= MG_BAR_OFF, "smem layout");

__device__ __forceinline__ void fence_async_all() { asm volatile("fence.proxy.async.global;" ::: "memory"); }
__device__ __forceinline__ void spin_until(const unsigned int* p, unsigned int target) {
    unsigned int v = 0;
    for (int spin = 0; spin < (1 << 22); spin++) {
        asm volatile("ld.acquire.gpu.global.u32 %0, [%1];" : "=r"(v) : "l"(p) : "memory");
        if (v >= target) break;
    }
}

struct MegaParams {
    const __nv_bfloat16 *x, *A_re, *A_im, *B_re, *B_im, *C_re, *C_im, *log_dt, *Dskip, *wg, *wu, *wd;
};

__global__ void __launch_bounds__(384, 1) mega_kernel(const __grid_constant__ MegaParams P,
                                                       const __grid_constant__ CUtensorMap tm_xn,
                                                       const __grid_constant__ CUtensorMap tm_wg4,
                                                       const __grid_constant__ CUtensorMap tm_wu4,
                                                       const __grid_constant__ CUtensorMap tm_wg3,
                                                       const __grid_constant__ CUtensorMap tm_wu3,
                                                       const __grid_constant__ CUtensorMap tm_h,
                                                       const __grid_constant__ CUtensorMap tm_wd,
                                                       const __grid_constant__ CUtensorMap tm_x,
                                                       const __grid_constant__ CUtensorMap tm_sT,
                                                       const __grid_constant__ CUtensorMap tm_out) {
    if (threadIdx.x == 0) STAMP(1, 0);
    extern __shared__ uint8_t smem_raw[];
    const uint32_t sraw = smem_u32(smem_raw);
    const uint32_t sbase = (sraw + 1023) & ~1023u;
    uint8_t* smem = smem_raw + (sbase - sraw);
    const int warp = threadIdx.x >> 5, lane = threadIdx.x & 31;
    const uint32_t sA = sbase, sB = sbase + G1_A_BYTES, sStg = sB + G1_STAGES * G1_B_STAGE;
    const uint32_t sXch = sbase + G2_STAGES * G2_STAGE, sX = sXch + G2_XCH, sS = sX + 16384;
    const uint32_t sBar = sbase + MG_BAR_OFF;
    const uint32_t bar_a = sBar, bar_full = sBar + 64, bar_empty = bar_full + 8 * G1_STAGES;
    const uint32_t bar_full2 = bar_empty + 8 * G1_STAGES, bar_empty2 = bar_full2 + 8 * G2_STAGES;
    const uint32_t bar_epi = bar_empty2 + 8 * G2_STAGES, bar_xch = bar_epi + 8, bar_g1done = bar_xch + 8, bar_g1mma = bar_g1done + 8, bar_peer = bar_g1mma + 8, bar_g1early = bar_peer + 8;
    const uint32_t kh = blockIdx.x & 1;
    const int rb1 = ((blockIdx.x >> 4) << 1) + (int)kh, cj = (blockIdx.x >> 1) & 7;
    const int rb = blockIdx.x >> 3;
    const int nb = (blockIdx.x >> 1) & 3;
    const int col_fin = nb * 128 + kh * 64;

    if (threadIdx.x == 0) {
        for (int i = 0; i < 8; i++) mbar_init(bar_a + 8 * i, 1);
        for (int i = 0; i < G1_STAGES; i++) { mbar_init(bar_full + 8 * i, 1); mbar_init(bar_empty + 8 * i, 16); }
        for (int i = 0; i < G2_STAGES; i++) { mbar_init(bar_full2 + 8 * i, 1); mbar_init(bar_empty2 + 8 * i, 8); }
        mbar_init(bar_epi, 1);
        mbar_init(bar_xch, 1);
        mbar_init(bar_g1done, 8);
        mbar_init(bar_g1mma, 8);
        mbar_init(bar_peer, 1);
        mbar_init(bar_g1early, 8);
        asm volatile("fence.mbarrier_init.release.cluster;" ::: "memory");
        mbar_expect_tx(bar_xch, G2_XCH);
    }
    if (warp == 11 && lane == 0) {
        prefetch_tmap(&tm_wg4); prefetch_tmap(&tm_wu4); prefetch_tmap(&tm_xn); prefetch_tmap(&tm_wg3); prefetch_tmap(&tm_wu3);
        prefetch_tmap(&tm_wd); prefetch_tmap(&tm_h); prefetch_tmap(&tm_x); prefetch_tmap(&tm_sT); prefetch_tmap(&tm_out);
    }
    asm volatile("barrier.cluster.arrive.release.aligned;" ::: "memory");

    auto g1_prefetch = [&]() {
        if (warp == 8 && lane == 0) {
            fence_async_all();
            mbar_expect_tx(bar_full, 16384);
            tma_load_3d(sB, &tm_wg4, 0, 0, cj * 7, bar_full);
            tma_load_3d(sB + 8192, &tm_wu4, 0, 0, cj * 7, bar_full);
            for (int k = 0; k < 8; k++) {
                mbar_expect_tx(bar_a + 8 * k, 16384);
                tma_load_2d(sA + k * 16384, &tm_xn, k * 64, rb1 * 128, bar_a + 8 * k);
            }
        }
    };
    front_phase(g1_prefetch, smem, P.x, P.A_re, P.A_im, P.B_re, P.B_im, P.C_re, P.C_im, P.log_dt, P.Dskip, P.wg, P.wu, P.wd);
    fence_async_smem();
    asm volatile("barrier.cluster.wait.acquire.aligned;" ::: "memory");
    __syncthreads();
    if (threadIdx.x == 352) mbar_arrive_remote(bar_peer, kh ^ 1);
    if (threadIdx.x == 0) STAMP(1, 7);

    if (warp >= 8) {
        asm volatile("setmaxnreg.dec.sync.aligned.u32 40;");
        if (warp == 11) {
            if (lane == 0) asm volatile("red.release.gpu.global.add.u32 [%0], 1;" ::"l"(&g_conv_count) : "memory");
            named_bar(3, 288);
            if (lane == 0) asm volatile("red.release.gpu.global.add.u32 [%0], 1;" ::"l"(&g_h_count[rb1]) : "memory");
            named_bar(9, 288);
            if (lane == 0) asm volatile("red.release.gpu.global.add.u32 [%0], 1;" ::"l"(&g_h_count[16 + rb1]) : "memory");
        } else if (lane == 0) {
            const int pw = warp - 8;
            mbar_wait(bar_peer, 0);
            for (int it = 1 + pw; it < G1_ITERS; it += 3) {
                const int s = it % G1_STAGES, kb = it & 15;
                if (it >= G1_STAGES) mbar_wait(bar_empty + 8 * s, ((it / G1_STAGES) - 1) & 1);
                const uint32_t dst = sB + s * G1_B_STAGE;
                if (it < 16) {
                    mbar_expect_tx(bar_full + 8 * s, 16384);
                    tma_load_3d_mc(dst + kh * 8192, kh ? &tm_wu4 : &tm_wg4, 0, kb * 32, cj * 7, bar_full + 8 * s, 3);
                } else {
                    mbar_expect_tx(bar_full + 8 * s, 12288);
                    tma_load_3d_mc(dst + kh * 6144, kh ? &tm_wu3 : &tm_wg3, 0, kb * 32, cj * 7 + 4, bar_full + 8 * s, 3);
                }
            }
            const int k0 = kh * G2_KB;
            auto kblk = [&](int it) -> int {
                const unsigned long long tab = 0xDCA96532B87410ull;
                return k0 + (int)((tab >> (4 * it)) & 15);
            };
            mbar_wait(pw == 0 ? bar_g1early : bar_g1mma, 0);
            if (pw == 2) {
                mbar_expect_tx(bar_epi, G2_EPI);
                tma_load_2d(sX, &tm_x, col_fin, rb * 128, bar_epi);
            }
            spin_until(&g_h_count[rb], 8);
            fence_async_all();
            if (pw == 0) STAMP(3, 1);
            for (int it = pw; it < G2_KB; it += 3) {
                const int s = (it + 1) % G2_STAGES;
                if (it == 3) mbar_wait(bar_g1mma, 0);
                if (it == 4) mbar_wait(bar_g1done, 0);
                if (it >= G2_STAGES) mbar_wait(bar_empty2 + 8 * s, ((it / G2_STAGES) - 1) & 1);
                if (it >= 6 && it < 9) { spin_until(&g_h_count[16 + rb], 8); fence_async_all(); }
                mbar_expect_tx(bar_full2 + 8 * s, G2_STAGE);
                const int kb = kblk(it);
                tma_load_3d(sbase + s * G2_STAGE + 16384, &tm_wd, 0, kb * 64, nb * 2, bar_full2 + 8 * s);
                tma_load_2d(sbase + s * G2_STAGE, &tm_h, kb * 64, rb * 128, bar_full2 + 8 * s);
                if (it == 2) {
                    spin_until(&g_conv_count, gridDim.x);
                    fence_async_all();
                    tma_load_2d(sS, &tm_sT, rb * 128, col_fin, bar_epi);
                    tma_load_2d(sS + 8192, &tm_sT, rb * 128 + 64, col_fin, bar_epi);
                }
            }
        }
    } else {
        asm volatile("setmaxnreg.inc.sync.aligned.u32 232;");
        const int wg = __shfl_sync(0xffffffffu, (int)(threadIdx.x >> 7), 0);
        {
        float r[160];
        const int row0 = rb1 * 128 + wg * 64 + (warp & 3) * 16;
        const uint64_t descA = make_desc(sA + wg * 8192, 16, 1024);
        const uint64_t descB = make_desc(sB, 2048, 512, 2);
        const uint32_t stg = sStg + warp * 1024;
        const uint32_t st_off = (uint32_t)(((lane & 7) + ((lane >> 3) & 1) * 8) * 32 + (lane >> 4) * 16);
        __nv_bfloat16* hrow = g_h + (size_t)(row0 + (lane >> 1)) * F_ + (lane & 1) * 8 + cj * 224;
#pragma unroll
        for (int kb = 0; kb < 16; kb++) {
            const int it = kb, s = it % G1_STAGES;
            if ((kb & 1) == 0) mbar_wait(bar_a + 8 * (kb >> 1), 0);
            mbar_wait(bar_full + 8 * s, (it / G1_STAGES) & 1);
            if (threadIdx.x == 0 && (it & 7) == 0) STAMP(2, 2 + it / 8);
            wgmma_fence();
            const uint64_t da = descA + (uint64_t)(((kb >> 1) * 16384 + (kb & 1) * 64) >> 4);
            const uint64_t db = descB + (uint64_t)((s * G1_B_STAGE) >> 4);
            wgmma_n256_k32(r, da, da + 2, db, db + 64, kb != 0);
            wgmma_commit();
            if (kb > 0) {
                wgmma_wait<1>();
                if (lane < 2) mbar_arrive_remote(bar_empty + 8 * ((it - 1) % G1_STAGES), lane);
            }
        }
        wgmma_wait<0>();
        if (lane < 2) mbar_arrive_remote(bar_empty + 8 * (15 % G1_STAGES), lane);
#pragma unroll
        for (int i = 0; i < 32; i++) r[128 + i] = __uint_as_float(pack_bf16(r[2 * i], r[2 * i + 1]));
#pragma unroll
        for (int i = 31; i >= 0; i--) r[96 + i] = __uint_as_float(pack_bf16(r[64 + 2 * i], r[65 + 2 * i]));
        uint32_t eo[4];
        uint4 pv = make_uint4(0, 0, 0, 0);
#pragma unroll
        for (int kb = 0; kb < 16; kb++) {
            const int it = 16 + kb, s = it % G1_STAGES;
            mbar_wait(bar_full + 8 * s, (it / G1_STAGES) & 1);
            if (threadIdx.x == 0 && (it & 7) == 0) STAMP(2, 2 + it / 8);
            wgmma_fence();
            const uint64_t da = descA + (uint64_t)(((kb >> 1) * 16384 + (kb & 1) * 64) >> 4);
            const uint64_t db = descB + (uint64_t)((s * G1_B_STAGE) >> 4);
            wgmma_n192(r, da, db, kb != 0);
            if (kb < 8) {
                eo[0] = geglu_pair(__float_as_uint(r[128 + 4 * kb]), __float_as_uint(r[96 + 4 * kb]));
                eo[1] = geglu_pair(__float_as_uint(r[129 + 4 * kb]), __float_as_uint(r[97 + 4 * kb]));
            }
            wgmma_n192(r, da + 2, db + 64, 1);
            wgmma_commit();
            if (kb >= 2 && kb < 10) *reinterpret_cast<uint4*>(hrow + (kb - 2) * 16) = pv;
            if (kb >= 1 && kb < 9) {
                __syncwarp();
                asm volatile("ld.shared.v4.u32 {%0,%1,%2,%3}, [%4];" : "=r"(pv.x), "=r"(pv.y), "=r"(pv.z), "=r"(pv.w)
                             : "r"(stg + ((kb - 1) & 1) * 512 + lane * 16));
            }
            if (kb < 8) {
                eo[2] = geglu_pair(__float_as_uint(r[130 + 4 * kb]), __float_as_uint(r[98 + 4 * kb]));
                eo[3] = geglu_pair(__float_as_uint(r[131 + 4 * kb]), __float_as_uint(r[99 + 4 * kb]));
                stmatrix_x4(stg + (kb & 1) * 512 + st_off, eo[0], eo[1], eo[2], eo[3]);
            }
            if (kb == 9) asm volatile("bar.arrive 3, 288;" ::: "memory");
            if (kb > 0 && it - 1 + G1_STAGES < G1_ITERS) {
                wgmma_wait<1>();
                if (lane < 2) mbar_arrive_remote(bar_empty + 8 * ((it - 1) % G1_STAGES), lane);
                if (kb == 11 && lane == 0) mbar_arrive(bar_g1early);
            }
        }
        wgmma_wait<0>();
        fence_async_smem();
        __syncwarp();
        if (lane == 0) mbar_arrive(bar_g1mma);
        if (threadIdx.x == 0) STAMP(2, 6);
        {
            uint32_t o[24];
#pragma unroll
            for (int i = 0; i < 24; i++) o[i] = geglu_pair(pack_bf16(r[2 * i], r[2 * i + 1]), pack_bf16(r[48 + 2 * i], r[49 + 2 * i]));
            named_bar(1 + wg, 128);
            const uint32_t fbuf = sA + ((warp & 3) >> 1) * 16384 + wg * 8192 + (warp & 1) * 4096;
#pragma unroll
            for (int jj = 0; jj < 6; jj++) stmatrix_x4(fbuf + jj * 512 + st_off, o[4 * jj], o[4 * jj + 1], o[4 * jj + 2], o[4 * jj + 3]);
            __syncwarp();
            uint4 v[6];
#pragma unroll
            for (int jj = 0; jj < 6; jj++)
                asm volatile("ld.shared.v4.u32 {%0,%1,%2,%3}, [%4];" : "=r"(v[jj].x), "=r"(v[jj].y), "=r"(v[jj].z), "=r"(v[jj].w)
                             : "r"(fbuf + jj * 512 + lane * 16));
#pragma unroll
            for (int jj = 0; jj < 6; jj++) *reinterpret_cast<uint4*>(hrow + 128 + jj * 16) = v[jj];
        }
        }
        fence_async_smem();
        __syncwarp();
        if (lane == 0) mbar_arrive(bar_g1done);
        asm volatile("bar.arrive 9, 288;" ::: "memory");
        if (threadIdx.x == 0) STAMP(2, 7);
        {
        const int g = lane >> 2, t = lane & 3;
        float acc[64];
        const uint64_t descA2 = make_desc(sbase + wg * 8192, 16, 1024);
        const uint64_t descB2 = make_desc(sbase + 16384, 8192, 1024);
#pragma unroll
        for (int it = 0; it < G2_KB; it++) {
            const int s = (it + 1) % G2_STAGES;
            mbar_wait(bar_full2 + 8 * s, (it / G2_STAGES) & 1);
            if (threadIdx.x == 0 && (it == 0 || it == 7)) STAMP(3, 2 + it / 7);
            wgmma_fence();
            {
                const uint64_t da = descA2 + (uint64_t)((s * G2_STAGE) >> 4);
                const uint64_t db = descB2 + (uint64_t)((s * G2_STAGE) >> 4);
                wgmma_n128_k64(acc, da, da + 2, da + 4, da + 6, db, db + 128, db + 256, db + 384, it != 0);
            }
            wgmma_commit();
            if (it > 0 && it - 1 + G2_STAGES < G2_KB) {
                wgmma_wait<1>();
                if (lane == 0) mbar_arrive(bar_empty2 + 8 * (it % G2_STAGES));
            }
        }
        const int lr = wg * 64 + (warp & 3) * 16 + g;
        uint32_t xv[16], sv[16];
        mbar_wait(bar_epi, 0);
#pragma unroll
        for (int j = 0; j < 8; j++) {
#pragma unroll
            for (int hh = 0; hh < 2; hh++) {
                const int r = lr + 8 * hh;
                asm volatile("ld.shared.u32 %0, [%1];" : "=r"(xv[2 * j + hh]) : "r"(sX + r * 128 + ((j ^ (r & 7)) << 4) + 4 * t));
                const int c0 = 8 * j + 2 * t;
                const uint32_t sa = sS + (r >> 6) * 8192 + (((r & 63) >> 3) << 4) + (r & 7) * 2;
                uint16_t s0r, s1r;
                asm volatile("ld.shared.u16 %0, [%1];" : "=h"(s0r) : "r"((sa + c0 * 128) ^ ((c0 & 7) << 4)));
                asm volatile("ld.shared.u16 %0, [%1];" : "=h"(s1r) : "r"((sa + (c0 + 1) * 128) ^ (((c0 + 1) & 7) << 4)));
                sv[2 * j + hh] = (uint32_t)s0r | ((uint32_t)s1r << 16);
            }
        }
        wgmma_wait<0>();
        if (threadIdx.x == 0) STAMP(3, 4);
        {
            uint32_t remote, rbar;
            asm volatile("mapa.shared::cluster.u32 %0, %1, %2;" : "=r"(remote) : "r"(sXch + threadIdx.x * 16), "r"(kh ^ 1));
            asm volatile("mapa.shared::cluster.u32 %0, %1, %2;" : "=r"(rbar) : "r"(bar_xch), "r"(kh ^ 1));
            if (kh == 0) {
#pragma unroll
                for (int i = 0; i < 8; i++)
                    asm volatile("st.async.shared::cluster.mbarrier::complete_tx::bytes.v4.f32 [%0], {%1,%2,%3,%4}, [%5];" ::"r"(remote + i * 4096),
                                 "f"(acc[32 + 4 * i]), "f"(acc[33 + 4 * i]), "f"(acc[34 + 4 * i]), "f"(acc[35 + 4 * i]), "r"(rbar) : "memory");
            } else {
#pragma unroll
                for (int i = 0; i < 8; i++)
                    asm volatile("st.async.shared::cluster.mbarrier::complete_tx::bytes.v4.f32 [%0], {%1,%2,%3,%4}, [%5];" ::"r"(remote + i * 4096),
                                 "f"(acc[4 * i]), "f"(acc[1 + 4 * i]), "f"(acc[2 + 4 * i]), "f"(acc[3 + 4 * i]), "r"(rbar) : "memory");
#pragma unroll
                for (int i = 0; i < 32; i++) acc[i] = acc[32 + i];
            }
        }
        if (threadIdx.x == 0) STAMP(3, 6);
        mbar_wait(bar_xch, 0);
        if (threadIdx.x == 0) STAMP(3, 7);
#pragma unroll
        for (int j = 0; j < 8; j++) {
            float4 o;
            asm volatile("ld.shared.v4.f32 {%0,%1,%2,%3}, [%4];" : "=f"(o.x), "=f"(o.y), "=f"(o.z), "=f"(o.w) : "r"(sXch + threadIdx.x * 16 + j * 4096));
            acc[4 * j] += o.x; acc[4 * j + 1] += o.y; acc[4 * j + 2] += o.z; acc[4 * j + 3] += o.w;
        }
#pragma unroll
        for (int i = 0; i < 16; i++) {
            float f0 = bf16_round(acc[2 * i]), f1 = bf16_round(acc[2 * i + 1]);
            float g0 = bf16_round(__fdividef(f0, 1.0f + __expf(-f0)));
            float g1 = bf16_round(__fdividef(f1, 1.0f + __expf(-f1)));
            float o0 = bf_lo(xv[i]) + bf16_round(bf_lo(sv[i]) * g0);
            float o1 = bf_hi(xv[i]) + bf16_round(bf_hi(sv[i]) * g1);
            xv[i] = pack_bf16(o0, o1);
        }
#pragma unroll
        for (int j = 0; j < 8; j++) {
#pragma unroll
            for (int hh = 0; hh < 2; hh++) {
                const int r = lr + 8 * hh;
                asm volatile("st.shared.u32 [%0], %1;" ::"r"(sX + r * 128 + ((j ^ (r & 7)) << 4) + 4 * t), "r"(xv[2 * j + hh]) : "memory");
            }
        }
        if (threadIdx.x == 0) STAMP(3, 9);
        fence_async_smem();
        __syncwarp();
        if (lane == 0) {
            tma_store_2d(&tm_out, sX + (wg * 64 + (warp & 3) * 16) * 128, col_fin, rb * 128 + wg * 64 + (warp & 3) * 16);
            bulk_commit();
            bulk_wait_read<0>();
        }
        }
        if (threadIdx.x == 0) STAMP(3, 5);
        named_bar(4, 256);
        if (threadIdx.x == 0) {
            const unsigned int old = atomicAdd(&g_done_count, 1u);
            if (old == gridDim.x - 1) {
                g_ln_count = 0; g_conv_count = 0; g_done_count = 0;
                for (int i = 0; i < 32; i++) g_h_count[i] = 0;
            }
        }
    }
}

typedef CUresult (*EncodeFn)(CUtensorMap*, CUtensorMapDataType, cuuint32_t, void*, const cuuint64_t*, const cuuint64_t*,
                             const cuuint32_t*, const cuuint32_t*, CUtensorMapInterleave, CUtensorMapSwizzle,
                             CUtensorMapL2promotion, CUtensorMapFloatOOBfill);

void make_map(EncodeFn fn, CUtensorMap* m, const void* ptr, uint64_t inner, uint64_t outer, uint32_t box_in, uint32_t box_out,
              CUtensorMapSwizzle swz = CU_TENSOR_MAP_SWIZZLE_128B) {
    cuuint64_t dims[2] = {inner, outer};
    cuuint64_t strides[1] = {inner * 2};
    cuuint32_t box[2] = {box_in, box_out};
    cuuint32_t es[2] = {1, 1};
    fn(m, CU_TENSOR_MAP_DATA_TYPE_BFLOAT16, 2, const_cast<void*>(ptr), dims, strides, box, es, CU_TENSOR_MAP_INTERLEAVE_NONE,
       swz, CU_TENSOR_MAP_L2_PROMOTION_L2_256B, CU_TENSOR_MAP_FLOAT_OOB_FILL_NONE);
}
void make_map3(EncodeFn fn, CUtensorMap* m, const void* ptr, uint64_t cols, uint64_t rows, uint32_t atom, uint32_t box_rows,
               uint32_t box_atoms, CUtensorMapSwizzle swz) {
    cuuint64_t dims[3] = {atom, rows, cols / atom};
    cuuint64_t strides[2] = {cols * 2, (cuuint64_t)atom * 2};
    cuuint32_t box[3] = {atom, box_rows, box_atoms};
    cuuint32_t es[3] = {1, 1, 1};
    fn(m, CU_TENSOR_MAP_DATA_TYPE_BFLOAT16, 3, const_cast<void*>(ptr), dims, strides, box, es, CU_TENSOR_MAP_INTERLEAVE_NONE,
       swz, CU_TENSOR_MAP_L2_PROMOTION_L2_256B, CU_TENSOR_MAP_FLOAT_OOB_FILL_NONE);
}

template <typename... Args>
void launch_pdl(void (*kern)(Args...), int grid, int block, int smem, bool pdl, int cluster, Args... args) {
    cudaLaunchConfig_t cfg = {};
    cfg.gridDim = dim3(grid); cfg.blockDim = dim3(block); cfg.dynamicSmemBytes = smem; cfg.stream = cudaStreamPerThread;
    cudaLaunchAttribute at[2];
    int n = 0;
    if (pdl) {
        at[n].id = cudaLaunchAttributeProgrammaticStreamSerialization;
        at[n].val.programmaticStreamSerializationAllowed = 1;
        n++;
    }
    if (cluster > 1) {
        at[n].id = cudaLaunchAttributeClusterDimension;
        at[n].val.clusterDim.x = cluster; at[n].val.clusterDim.y = 1; at[n].val.clusterDim.z = 1;
        n++;
    }
    cfg.attrs = at; cfg.numAttrs = n;
    cudaLaunchKernelEx(&cfg, kern, args...);
}

}

extern "C" void kernel_launch(void* const* d_in, const int* in_sizes, int n_in, void* d_out, int out_size) {
    const __nv_bfloat16* x = (const __nv_bfloat16*)d_in[0];
    const __nv_bfloat16* A_re = (const __nv_bfloat16*)d_in[1];
    const __nv_bfloat16* A_im = (const __nv_bfloat16*)d_in[2];
    const __nv_bfloat16* B_re = (const __nv_bfloat16*)d_in[3];
    const __nv_bfloat16* B_im = (const __nv_bfloat16*)d_in[4];
    const __nv_bfloat16* C_re = (const __nv_bfloat16*)d_in[5];
    const __nv_bfloat16* C_im = (const __nv_bfloat16*)d_in[6];
    const __nv_bfloat16* log_dt = (const __nv_bfloat16*)d_in[7];
    const __nv_bfloat16* Dskip = (const __nv_bfloat16*)d_in[8];
    const __nv_bfloat16* wg = (const __nv_bfloat16*)d_in[10];
    const __nv_bfloat16* wu = (const __nv_bfloat16*)d_in[11];
    const __nv_bfloat16* wd = (const __nv_bfloat16*)d_in[12];
    __nv_bfloat16* out = (__nv_bfloat16*)d_out;

    static bool init = false;
    static CUtensorMap tm_xn, tm_wg4, tm_wu4, tm_wg3, tm_wu3,  tm_h, tm_wd, tm_x, tm_sT, tm_out;
    static const void* last_ptrs[5] = {nullptr, nullptr, nullptr, nullptr, nullptr};
    if (!init || last_ptrs[0] != wg || last_ptrs[1] != wu || last_ptrs[2] != wd || last_ptrs[3] != x || last_ptrs[4] != out) {
        void* fnp = nullptr;
        cudaDriverEntryPointQueryResult qres;
        cudaGetDriverEntryPoint("cuTensorMapEncodeTiled", &fnp, cudaEnableDefault, &qres);
        EncodeFn fn = (EncodeFn)fnp;
        void *p_xn, *p_h, *p_sT;
        cudaGetSymbolAddress(&p_xn, g_xn);
        cudaGetSymbolAddress(&p_h, g_h);
        cudaGetSymbolAddress(&p_sT, g_sT);
        make_map(fn, &tm_xn, p_xn, D_, L_, 64, 128);
        make_map3(fn, &tm_wg4, wg, F_, D_, 32, 32, 4, CU_TENSOR_MAP_SWIZZLE_64B);
        make_map3(fn, &tm_wu4, wu, F_, D_, 32, 32, 4, CU_TENSOR_MAP_SWIZZLE_64B);
        make_map3(fn, &tm_wg3, wg, F_, D_, 32, 32, 3, CU_TENSOR_MAP_SWIZZLE_64B);
        make_map3(fn, &tm_wu3, wu, F_, D_, 32, 32, 3, CU_TENSOR_MAP_SWIZZLE_64B);
        make_map(fn, &tm_h, p_h, F_, L_, 64, 128);
        make_map3(fn, &tm_wd, wd, D_, F_, 64, 64, 2, CU_TENSOR_MAP_SWIZZLE_128B);
        make_map(fn, &tm_x, x, D_, L_, 64, 128);
        make_map(fn, &tm_sT, p_sT, L_, D_, 64, 64);
        make_map(fn, &tm_out, out, D_, L_, 64, 16);
        cudaFuncSetAttribute(mega_kernel, cudaFuncAttributeMaxDynamicSharedMemorySize, MG_SMEM);
        last_ptrs[0] = wg; last_ptrs[1] = wu; last_ptrs[2] = wd; last_ptrs[3] = x; last_ptrs[4] = out;
        init = true;
    }
    MegaParams P = {x, A_re, A_im, B_re, B_im, C_re, C_im, log_dt, Dskip, wg, wu, wd};
    launch_pdl(mega_kernel, 128, 384, MG_SMEM, false, 2, P, tm_xn, tm_wg4, tm_wu4, tm_wg3, tm_wu3, tm_h, tm_wd, tm_x, tm_sT, tm_out);
}
```
